```python
import torch

def _softmax(x, axis=-1):
    return torch.softmax(x, dim=axis)

def _gelu(x):
    return torch.nn.functional.gelu(x, approximate='tanh')

def _silu(x):
    return torch.nn.functional.silu(x)

def _sigmoid(x):
    return torch.sigmoid(x)

def _layernorm(x, axis=-1, eps=1e-05):
    m = x.mean(dim=axis, keepdim=True)
    v = x.var(dim=axis, keepdim=True, unbiased=False)
    return (x - m) / torch.sqrt(v + eps)

def _scatter_add(tgt, idx, src, axis=0):
    return tgt.clone().index_add_(axis, idx, src)

def _segment_sum(src, seg, n):
    out = torch.zeros((n,) + src.shape[1:], dtype=src.dtype)
    return out.index_add_(0, seg, src)

def _pad(x, pw):
    flat = tuple((v for pair in reversed(pw) for v in pair))
    return torch.nn.functional.pad(x, flat)
kernel_name = 'gated_mix__memory_aug_recurrent_mem_tr__ssm_conv_s4d__prompt'

def setup_inputs():

    _w = lambda a: (lambda t: t.to(torch.bfloat16) if t.is_floating_point() else t)(torch.as_tensor(a))

    def _A_setup():
        B, S, Dm = (1, 2048, 576)
        H, Dh = (32, 128)
        M, seg = (8, 32)
        seg = min(seg, S)
        S = S // seg * seg
        return {'x': _w((lambda *s: torch.randn(*s, dtype=torch.bfloat16) * 0.05)(B, S, Dm)), 'mem0': _w((lambda *s: torch.randn(*s, dtype=torch.bfloat16) * 0.4)(B, M, Dm)), 'Wq': _w((lambda *s: torch.randn(*s, dtype=torch.bfloat16) * 6.4)(Dm, H, Dh) * Dm ** (-0.5)), 'Wk': _w((lambda *s: torch.randn(*s, dtype=torch.bfloat16) * 6.4)(Dm, H, Dh) * Dm ** (-0.5)), 'Wv': _w((lambda *s: torch.randn(*s, dtype=torch.bfloat16) * 0.4)(Dm, H, Dh) * Dm ** (-0.5)), 'Wo': _w((lambda *s: torch.randn(*s, dtype=torch.bfloat16) * 0.4)(H, Dh, Dm) * (H * Dh) ** (-0.5)), 'seg_len': seg}
    _A_in = _A_setup()

    def _B_setup():
        Bsz, L, D, N = (1, 2048, 576, 128)
        return {'u': _w((lambda *s: torch.randn(*s, dtype=torch.bfloat16) * 0.05)(Bsz, L, D)), 'log_A_real': _w((lambda *s: torch.randn(*s, dtype=torch.bfloat16) * 6.4)(D, N) * 0.5), 'A_imag': _w((lambda *s: torch.randn(*s, dtype=torch.bfloat16) * 0.05)(D, N) * 3.14), 'C_real': _w((lambda *s: torch.randn(*s, dtype=torch.bfloat16) * 0.2)(D, N) / N ** 0.5), 'C_imag': _w((lambda *s: torch.randn(*s, dtype=torch.bfloat16) * 0.2)(D, N) / N ** 0.5), 'log_dt': _w((lambda *s: torch.randn(*s, dtype=torch.bfloat16) * 0.05)(D) * 0.5 - 4.0), 'D_skip': _w((lambda *s: torch.randn(*s, dtype=torch.bfloat16) * 0.05)(D))}
    _B_in = _B_setup()
    return {'A_x': _A_in['x'], 'A_mem0': _A_in['mem0'], 'A_Wq': _A_in['Wq'], 'A_Wk': _A_in['Wk'], 'A_Wv': _A_in['Wv'], 'A_Wo': _A_in['Wo'], 'A_seg_len': _A_in['seg_len'], 'B_u': _B_in['u'], 'B_log_A_real': _B_in['log_A_real'], 'B_A_imag': _B_in['A_imag'], 'B_C_real': _B_in['C_real'], 'B_C_imag': _B_in['C_imag'], 'B_log_dt': _B_in['log_dt'], 'B_D_skip': _B_in['D_skip'], 'gate_w': _w((lambda *s: torch.randn(*s, dtype=torch.bfloat16) * 0.05)(576) * 16.0)}

def reference(A_x, A_mem0, A_Wq, A_Wk, A_Wv, A_Wo, A_seg_len, B_u, B_log_A_real, B_A_imag, B_C_real, B_C_imag, B_log_dt, B_D_skip, gate_w):

    def _A_ref(x, mem0, Wq, Wk, Wv, Wo, seg_len):
        B, S, Dm = x.shape
        H, Dh = (Wq.shape[1], Wq.shape[2])
        M = mem0.shape[1]
        scale = Dh ** (-0.5)
        n_seg = S // seg_len
        L = M + seg_len
        idx = torch.arange(L)
        mask = (idx[:, None] < M) | (idx[:, None] >= idx[None, :])
        mem = mem0
        outs = []
        for s in range(n_seg):
            xs = x[:, s * seg_len:(s + 1) * seg_len, :].clone()
            h = torch.concatenate([mem, xs], axis=1)
            q = torch.einsum('btd,dhe->bhte', h, Wq)
            k = torch.einsum('btd,dhe->bhte', h, Wk)
            v = torch.einsum('btd,dhe->bhte', h, Wv)
            scores = torch.einsum('bhqe,bhke->bhqk', q, k) * scale
            scores = torch.where(mask[None, None], scores, -1000000000.0)
            p = _softmax(scores, axis=-1)
            o = torch.einsum('bhqk,bhke->bhqe', p, v)
            o = torch.einsum('bhte,hed->btd', o, Wo)
            mem = o[:, :M, :].clone()
            outs.append(o[:, M:, :])
        return torch.concatenate(outs, axis=1)

    def _B_ref(u, log_A_real, A_imag, C_real, C_imag, log_dt, D_skip):
        L = u.shape[1]
        dt = torch.exp(log_dt)
        A = -torch.exp(log_A_real) + 1j * A_imag
        C = (C_real + 1j * C_imag) * dt[:, None]
        pos = (lambda x, dt: x.to(dt))(torch.arange(L), log_dt.dtype)
        P = torch.exp((A * dt[:, None])[:, :, None] * pos[None, None, :])
        K = 2.0 * torch.einsum('dn,dnl->dl', C, P).real
        L2 = 2 * L
        u_t = (lambda x, *d: x.permute(*d))(u, 0, 2, 1)
        Kf = (lambda x, *a, **k: torch.fft.rfft(x.float(), *a, **k))(K, L2)
        Uf = (lambda x, *a, **k: torch.fft.rfft(x.float(), *a, **k))(u_t, L2)
        y = (lambda x, *a, **k: torch.fft.irfft(x, *a, **k).to(torch.bfloat16))(Uf * Kf[None, :, :], L2)[:, :, :L]
        y = (lambda x, *d: x.permute(*d))(y, 0, 2, 1)
        return y + u * D_skip[None, None, :]
    x = A_x
    g = _sigmoid((x * gate_w).sum(-1, keepdims=True))
    a = _A_ref(x, A_mem0, A_Wq, A_Wk, A_Wv, A_Wo, A_seg_len)
    b = _B_ref(x, B_log_A_real, B_A_imag, B_C_real, B_C_imag, B_log_dt, B_D_skip)
    return g * a + (1 - g) * b
```

```cpp
#include <cuda_runtime.h>
#include <cuda.h>
#include <cuda_bf16.h>
#include <stdint.h>

#define S_LEN 2048
#define DM 576
#define NH 32
#define DH 128
#define NMEM 8
#define SEG 32
#define NSEG 64
#define LQ 40
#define NS 128

typedef __nv_bfloat16 bf16;

__device__ __forceinline__ float bf(bf16 v) { return __bfloat162float(v); }
__device__ __forceinline__ bf16 tobf(float v) { return __float2bfloat16_rn(v); }
__device__ __forceinline__ float rbf(float v) { return __bfloat162float(__float2bfloat16_rn(v)); }

#define CH_THREADS 384
#define SPIN_LIMIT (1 << 17)
#define SM_X     0
#define XBUF     36864
#define SM_TOK   73728
#define TOKBUF   24576
#define SM_FB    131072
#define SM_STASH 139264
#define SM_TS    (SM_STASH + 3072)
#define SM_WO    147456
#define SM_MEM   196608
#define SM_EX    205824
#define EXBUF    6144
#define SM_P     218112
#define SM_FLAG  (SM_P + 640)
#define SM_OST   219136
#define SM_O     223232
#define SM_BAR   228352
#define SM_IL    (SM_BAR + 128)
#define SM_SG    (SM_IL + 64)
#define SM_TOTAL (SM_IL + 128)

#define ACC_X    36864
#define ACC_FULL 0x0020u
#define SLOT_OFF(sl) ((((sl) & 1) << 7) | (((sl) & 2) << 8))
__device__ __align__(65536) unsigned char g_acc[65536];
__device__ __align__(1024) uint4 g_fb[3][32][384];
__device__ unsigned int g_fbf[3][32];
__device__ unsigned int g_init[96];
__device__ unsigned int g_epoch = 1;
__device__ __align__(128) unsigned int g_ts[128];
__device__ __align__(1024) bf16 g_otok[S_LEN * NH * DH];
__device__ __align__(1024) unsigned char g_tokx[96][8192];
__device__ unsigned int g_flag[NSEG][96];
#define STAMP(i)
#define STAMPV(i, v)
#define GT(b, i)
#define STAMPB(i)

__device__ __forceinline__ uint32_t smem_u32(const void* p) { return (uint32_t)__cvta_generic_to_shared(p); }
__device__ __forceinline__ void ldsm_x4(uint32_t (&r)[4], uint32_t addr) {
    asm volatile("ldmatrix.sync.aligned.m8n8.x4.shared.b16 {%0,%1,%2,%3}, [%4];" : "=r"(r[0]), "=r"(r[1]), "=r"(r[2]), "=r"(r[3]) : "r"(addr) : "memory");
}
__device__ __forceinline__ void ldsm_x4_p(uint32_t (&r)[4], uint32_t addr, uint32_t skip) {
    asm volatile("{\n.reg .pred p;\nsetp.eq.u32 p, %5, 0;\n@p ldmatrix.sync.aligned.m8n8.x4.shared.b16 {%0,%1,%2,%3}, [%4];\n}\n" : "+r"(r[0]), "+r"(r[1]), "+r"(r[2]), "+r"(r[3]) : "r"(addr), "r"(skip) : "memory");
}
__device__ __forceinline__ void ldsm_x4_t(uint32_t (&r)[4], uint32_t addr) {
    asm volatile("ldmatrix.sync.aligned.m8n8.x4.trans.shared.b16 {%0,%1,%2,%3}, [%4];" : "=r"(r[0]), "=r"(r[1]), "=r"(r[2]), "=r"(r[3]) : "r"(addr) : "memory");
}
__device__ __forceinline__ uint32_t ldsm_x1_t(uint32_t addr) {
    uint32_t r; asm volatile("ldmatrix.sync.aligned.m8n8.x1.trans.shared.b16 {%0}, [%1];" : "=r"(r) : "r"(addr) : "memory"); return r;
}
__device__ __forceinline__ void ldsm_x2_t(uint32_t& r0, uint32_t& r1, uint32_t addr) {
    asm volatile("ldmatrix.sync.aligned.m8n8.x2.trans.shared.b16 {%0,%1}, [%2];" : "=r"(r0), "=r"(r1) : "r"(addr) : "memory");
}
__device__ __forceinline__ void stsm_x4(uint32_t addr, uint32_t r0, uint32_t r1, uint32_t r2, uint32_t r3) {
    asm volatile("stmatrix.sync.aligned.m8n8.x4.shared.b16 [%0], {%1,%2,%3,%4};" :: "r"(addr), "r"(r0), "r"(r1), "r"(r2), "r"(r3) : "memory");
}
__device__ __forceinline__ void stsm_x4_t(uint32_t addr, uint32_t r0, uint32_t r1, uint32_t r2, uint32_t r3) {
    asm volatile("stmatrix.sync.aligned.m8n8.x4.trans.shared.b16 [%0], {%1,%2,%3,%4};" :: "r"(addr), "r"(r0), "r"(r1), "r"(r2), "r"(r3) : "memory");
}
__device__ __forceinline__ void mma16816(float (&c)[4], const uint32_t (&a)[4], uint32_t b0, uint32_t b1) {
    asm("mma.sync.aligned.m16n8k16.row.col.f32.bf16.bf16.f32 {%0,%1,%2,%3}, {%4,%5,%6,%7}, {%8,%9}, {%0,%1,%2,%3};"
        : "+f"(c[0]), "+f"(c[1]), "+f"(c[2]), "+f"(c[3]) : "r"(a[0]), "r"(a[1]), "r"(a[2]), "r"(a[3]), "r"(b0), "r"(b1));
}
__device__ __forceinline__ void mma16816r(float (&c)[4], uint32_t a0, uint32_t a1, uint32_t a2, uint32_t a3, uint32_t b0, uint32_t b1) {
    asm("mma.sync.aligned.m16n8k16.row.col.f32.bf16.bf16.f32 {%0,%1,%2,%3}, {%4,%5,%6,%7}, {%8,%9}, {%0,%1,%2,%3};"
        : "+f"(c[0]), "+f"(c[1]), "+f"(c[2]), "+f"(c[3]) : "r"(a0), "r"(a1), "r"(a2), "r"(a3), "r"(b0), "r"(b1));
}
__device__ __forceinline__ void mma1688(float (&c)[4], uint32_t a0, uint32_t a1, uint32_t b0) {
    asm("mma.sync.aligned.m16n8k8.row.col.f32.bf16.bf16.f32 {%0,%1,%2,%3}, {%4,%5}, {%6}, {%0,%1,%2,%3};"
        : "+f"(c[0]), "+f"(c[1]), "+f"(c[2]), "+f"(c[3]) : "r"(a0), "r"(a1), "r"(b0));
}
__device__ __forceinline__ uint32_t pack_bf16(float lo, float hi) {
    uint32_t r; asm("cvt.rn.bf16x2.f32 %0, %1, %2;" : "=r"(r) : "f"(hi), "f"(lo)); return r;
}
__device__ __forceinline__ float bf_lo(uint32_t v) { return __uint_as_float(v << 16); }
__device__ __forceinline__ float bf_hi(uint32_t v) { return __uint_as_float(v & 0xffff0000u); }
__device__ __forceinline__ uint32_t max_bf2(uint32_t a, uint32_t b) { uint32_t r; asm("max.bf16x2 %0, %1, %2;" : "=r"(r) : "r"(a), "r"(b)); return r; }
__device__ __forceinline__ uint32_t maxabs_bf2(uint32_t a, uint32_t b) { uint32_t r; asm("max.NaN.xorsign.abs.bf16x2 %0, %1, %2;" : "=r"(r) : "r"(a), "r"(b)); return r; }
__device__ __forceinline__ float ex2(float x) { float r; asm("ex2.approx.ftz.f32 %0, %1;" : "=f"(r) : "f"(x)); return r; }
__device__ __forceinline__ void ld_relaxed128_p(uint4& v, const uint4* p, uint32_t pred) {
    asm volatile("{\n.reg .pred p;\nsetp.ne.u32 p, %5, 0;\n@p ld.relaxed.gpu.global.v4.u32 {%0,%1,%2,%3}, [%4];\n}\n" : "+r"(v.x), "+r"(v.y), "+r"(v.z), "+r"(v.w) : "l"(p), "r"(pred) : "memory");
}
__device__ __forceinline__ uint4 ld_relaxed128(const uint4* p) { uint4 v; asm volatile("ld.relaxed.gpu.global.v4.u32 {%0,%1,%2,%3}, [%4];" : "=r"(v.x), "=r"(v.y), "=r"(v.z), "=r"(v.w) : "l"(p) : "memory"); return v; }
__device__ __forceinline__ uint32_t ld_relaxed32(const uint32_t* p) { uint32_t v; asm volatile("ld.relaxed.gpu.global.u32 %0, [%1];" : "=r"(v) : "l"(p) : "memory"); return v; }
__device__ __forceinline__ void st_relaxed128(uint4* p, uint4 v) { asm volatile("st.relaxed.gpu.global.v4.u32 [%0], {%1,%2,%3,%4};" :: "l"(p), "r"(v.x), "r"(v.y), "r"(v.z), "r"(v.w) : "memory"); }
__device__ __forceinline__ void st_relaxed32(uint32_t* p, uint32_t v) { asm volatile("st.relaxed.gpu.global.u32 [%0], %1;" :: "l"(p), "r"(v) : "memory"); }
__device__ __forceinline__ void st_relaxed128_p(uint4* p, uint4 v, uint32_t skip) {
    asm volatile("{\n.reg .pred p;\nsetp.eq.u32 p, %5, 0;\n@p st.relaxed.gpu.global.v4.u32 [%0], {%1,%2,%3,%4};\n}\n" :: "l"(p), "r"(v.x), "r"(v.y), "r"(v.z), "r"(v.w), "r"(skip) : "memory");
}
__device__ __forceinline__ void st_relaxed64_p(void* p, uint32_t x, uint32_t y, uint32_t skip) {
    asm volatile("{\n.reg .pred p;\n.reg .b64 v;\nsetp.eq.u32 p, %3, 0;\nmov.b64 v, {%1,%2};\n@p st.relaxed.gpu.global.b64 [%0], v;\n}\n" :: "l"(p), "r"(x), "r"(y), "r"(skip) : "memory");
}
__device__ __forceinline__ void ld_relaxed64_p(uint2& v, const void* p, uint32_t pred) {
    asm volatile("{\n.reg .pred p;\n.reg .b64 v;\nsetp.ne.u32 p, %3, 0;\nmov.b64 v, {%0,%1};\n@p ld.relaxed.gpu.global.b64 v, [%2];\nmov.b64 {%0,%1}, v;\n}\n" : "+r"(v.x), "+r"(v.y) : "l"(p), "r"(pred) : "memory");
}
__device__ __forceinline__ uint2 ld_relaxed64(const void* p) {
    uint2 v; asm volatile("{\n.reg .b64 v;\nld.relaxed.gpu.global.b64 v, [%2];\nmov.b64 {%0,%1}, v;\n}\n" : "=r"(v.x), "=r"(v.y) : "l"(p) : "memory"); return v;
}
__device__ __forceinline__ void st_relaxed32_p(void* p, uint32_t v, uint32_t skip) {
    asm volatile("{\n.reg .pred p;\nsetp.eq.u32 p, %2, 0;\n@p st.relaxed.gpu.global.u32 [%0], %1;\n}\n" :: "l"(p), "r"(v), "r"(skip) : "memory");
}
__device__ __forceinline__ void bar_arrive_p(int id, int n, uint32_t skip) {
    asm volatile("{\n.reg .pred p;\nsetp.eq.u32 p, %2, 0;\n@p bar.arrive %0, %1;\n}\n" :: "r"(id), "r"(n), "r"(skip) : "memory");
}
__device__ __forceinline__ void bar_sync_p(int id, int n, uint32_t skip) {
    asm volatile("{\n.reg .pred p;\nsetp.eq.u32 p, %2, 0;\n@p bar.sync %0, %1;\n}\n" :: "r"(id), "r"(n), "r"(skip) : "memory");
}
__device__ __forceinline__ uint32_t movm(uint32_t x) { uint32_t r; asm volatile("movmatrix.sync.aligned.m8n8.trans.b16 %0, %1;" : "=r"(r) : "r"(x)); return r; }
__device__ __forceinline__ void sts32_p(uint32_t a, uint32_t v, uint32_t doit) {
    asm volatile("{\n.reg .pred p;\nsetp.ne.u32 p, %2, 0;\n@p st.shared.u32 [%0], %1;\n}\n" :: "r"(a), "r"(v), "r"(doit) : "memory");
}
__device__ __forceinline__ uint32_t pin(uint32_t x) { return __shfl_sync(0xffffffffu, x, threadIdx.x & 31); }
__device__ __forceinline__ void ldsm16_t(uint32_t (&b)[4][4], uint32_t a) {
    asm volatile("ldmatrix.sync.aligned.m8n8.x4.trans.shared.b16 {%0,%1,%2,%3}, [%16];\n"
                 "ldmatrix.sync.aligned.m8n8.x4.trans.shared.b16 {%4,%5,%6,%7}, [%16+512];\n"
                 "ldmatrix.sync.aligned.m8n8.x4.trans.shared.b16 {%8,%9,%10,%11}, [%16+1024];\n"
                 "ldmatrix.sync.aligned.m8n8.x4.trans.shared.b16 {%12,%13,%14,%15}, [%16+1536];\n"
        : "=r"(b[0][0]), "=r"(b[0][1]), "=r"(b[0][2]), "=r"(b[0][3]), "=r"(b[1][0]), "=r"(b[1][1]), "=r"(b[1][2]), "=r"(b[1][3]),
          "=r"(b[2][0]), "=r"(b[2][1]), "=r"(b[2][2]), "=r"(b[2][3]), "=r"(b[3][0]), "=r"(b[3][1]), "=r"(b[3][2]), "=r"(b[3][3]) : "r"(a) : "memory");
}
template<int ID> __device__ __forceinline__ void sched_fence(uint32_t never) { while (never == 0x7fffff00u + ID) { asm volatile("nanosleep.u32 64;" ::: "memory"); } }
__device__ __forceinline__ uint32_t opaque_u() { uint32_t v; asm volatile("mov.u32 %0, %%nsmid;" : "=r"(v)); return v; }
__device__ __forceinline__ uint32_t bar_red_or(int id, int n, uint32_t v) {
    uint32_t r; asm volatile("{\n.reg .pred p, q;\nsetp.ne.u32 p, %3, 0;\nbar.red.or.pred q, %1, %2, p;\nselp.u32 %0, 1, 0, q;\n}\n" : "=r"(r) : "r"(id), "r"(n), "r"(v) : "memory"); return r;
}
template<class T> __device__ __forceinline__ T* launder_p(T* p) { asm volatile("" : "+l"(p)); return p; }
__device__ __forceinline__ uint32_t mapa_u32(uint32_t addr, uint32_t rank) { uint32_t d; asm("mapa.shared::cluster.u32 %0, %1, %2;" : "=r"(d) : "r"(addr), "r"(rank)); return d; }
__device__ __forceinline__ uint32_t mapa_v(uint32_t addr, uint32_t rank) { uint32_t d; asm volatile("mapa.shared::cluster.u32 %0, %1, %2;" : "=r"(d) : "r"(addr), "r"(rank)); return d; }
__device__ __forceinline__ void st_async32(uint32_t addr, uint32_t v, uint32_t mbar) { asm volatile("st.async.shared::cluster.mbarrier::complete_tx::bytes.u32 [%0], %1, [%2];" :: "r"(addr), "r"(v), "r"(mbar) : "memory"); }
__device__ __forceinline__ void cluster_arrive() { asm volatile("barrier.cluster.arrive.release.aligned;" ::: "memory"); }
__device__ __forceinline__ void cluster_wait() { asm volatile("barrier.cluster.wait.acquire.aligned;" ::: "memory"); }
__device__ __forceinline__ void cp_async16(uint32_t dst, const void* src) { asm volatile("cp.async.cg.shared.global [%0], [%1], 16;" :: "r"(dst), "l"(src) : "memory"); }
__device__ __forceinline__ void cp_async_commit() { asm volatile("cp.async.commit_group;" ::: "memory"); }
template<int N> __device__ __forceinline__ void cp_async_wait() { asm volatile("cp.async.wait_group %0;" :: "n"(N) : "memory"); }
__device__ __forceinline__ void cp_async_wait0() { asm volatile("cp.async.wait_group 0;" ::: "memory"); }
__device__ __forceinline__ void mbar_init(uint32_t a, uint32_t cnt) { asm volatile("mbarrier.init.shared.b64 [%0], %1;" :: "r"(a), "r"(cnt) : "memory"); }
__device__ __forceinline__ void mbar_expect_tx(uint32_t a, uint32_t bytes) { asm volatile("mbarrier.arrive.expect_tx.shared.b64 _, [%0], %1;" :: "r"(a), "r"(bytes) : "memory"); }
__device__ __forceinline__ bool mbar_try(uint32_t a, uint32_t parity) {
    uint32_t ok; asm volatile("{\n.reg .pred p;\nmbarrier.try_wait.parity.shared::cta.b64 p, [%1], %2;\nselp.u32 %0, 1, 0, p;\n}\n" : "=r"(ok) : "r"(a), "r"(parity) : "memory"); return ok;
}
__device__ __forceinline__ void mbar_wait(uint32_t a, uint32_t parity) { int it = 0; while (!mbar_try(a, parity) && ++it < SPIN_LIMIT) {} }
__device__ __forceinline__ void bar_sync(int id, int n) { asm volatile("bar.sync %0, %1;" :: "r"(id), "r"(n) : "memory"); }
__device__ __forceinline__ void bar_arrive(int id, int n) { asm volatile("bar.arrive %0, %1;" :: "r"(id), "r"(n) : "memory"); }
__device__ __forceinline__ void fence_async_smem() { asm volatile("fence.proxy.async.shared::cta;" ::: "memory"); }
__device__ __forceinline__ void sts32(uint32_t a, uint32_t v) { asm volatile("st.shared.u32 [%0], %1;" :: "r"(a), "r"(v) : "memory"); }
__device__ __forceinline__ void sts128(uint32_t a, uint4 v) { asm volatile("st.shared.v4.u32 [%0], {%1,%2,%3,%4};" :: "r"(a), "r"(v.x), "r"(v.y), "r"(v.z), "r"(v.w) : "memory"); }
__device__ __forceinline__ uint4 lds128(uint32_t a) { uint4 v; asm volatile("ld.shared.v4.u32 {%0,%1,%2,%3}, [%4];" : "=r"(v.x), "=r"(v.y), "=r"(v.z), "=r"(v.w) : "r"(a) : "memory"); return v; }
__device__ __forceinline__ uint32_t lds32(uint32_t a) { uint32_t v; asm volatile("ld.shared.u32 %0, [%1];" : "=r"(v) : "r"(a) : "memory"); return v; }
__device__ __forceinline__ uint32_t gtime_lo() { uint32_t t; asm volatile("mov.u32 %0, %globaltimer_lo;" : "=r"(t)); return t; }
__device__ __forceinline__ void wait_gtime(uint32_t tg) {
    asm volatile("{\n.reg .pred p, q;\n.reg .b64 t;\n.reg .b32 lo, hi, d, n;\nmov.b32 n, 300;\n"
                 "WG_%=:\nmov.u64 t, %%globaltimer;\nmov.b64 {lo, hi}, t;\nsub.s32 d, lo, %0;\nsub.s32 n, n, 1;\n"
                 "setp.gt.s32 q, n, 0;\nsetp.lt.and.s32 p, d, 0, q;\n@p bra.uni WG_%=;\n}\n" :: "r"(tg) : "memory");
}
__device__ __forceinline__ void delay_clk(int d) { uint32_t t0 = clock(); while ((int)(clock() - t0) < d) {} }

__device__ __forceinline__ uint64_t desc128(uint32_t addr) {
    return (uint64_t)((addr & 0x3FFFF) >> 4) | ((uint64_t)1 << 16) | ((uint64_t)64 << 32) | ((uint64_t)1 << 62);
}
template<int accum> __device__ __forceinline__ void wgmma_n32(float (&d)[16], const uint32_t (&a)[4], uint64_t desc) {
    if (accum) {
        asm volatile("{\n.reg .pred p;\nsetp.ne.b32 p, 1, 0;\n"
            "wgmma.mma_async.sync.aligned.m64n32k16.f32.bf16.bf16 {%0,%1,%2,%3,%4,%5,%6,%7,%8,%9,%10,%11,%12,%13,%14,%15}, {%16,%17,%18,%19}, %20, p, 1, 1, 0;\n}\n"
            : "+f"(d[0]), "+f"(d[1]), "+f"(d[2]), "+f"(d[3]), "+f"(d[4]), "+f"(d[5]), "+f"(d[6]), "+f"(d[7]),
              "+f"(d[8]), "+f"(d[9]), "+f"(d[10]), "+f"(d[11]), "+f"(d[12]), "+f"(d[13]), "+f"(d[14]), "+f"(d[15])
            : "r"(a[0]), "r"(a[1]), "r"(a[2]), "r"(a[3]), "l"(desc));
    } else {
        asm volatile("{\n.reg .pred p;\nsetp.ne.b32 p, 0, 0;\n"
            "wgmma.mma_async.sync.aligned.m64n32k16.f32.bf16.bf16 {%0,%1,%2,%3,%4,%5,%6,%7,%8,%9,%10,%11,%12,%13,%14,%15}, {%16,%17,%18,%19}, %20, p, 1, 1, 0;\n}\n"
            : "=f"(d[0]), "=f"(d[1]), "=f"(d[2]), "=f"(d[3]), "=f"(d[4]), "=f"(d[5]), "=f"(d[6]), "=f"(d[7]),
              "=f"(d[8]), "=f"(d[9]), "=f"(d[10]), "=f"(d[11]), "=f"(d[12]), "=f"(d[13]), "=f"(d[14]), "=f"(d[15])
            : "r"(a[0]), "r"(a[1]), "r"(a[2]), "r"(a[3]), "l"(desc));
    }
}
__device__ __forceinline__ float rcp_approx(float x) { float r; asm("rcp.approx.ftz.f32 %0, %1;" : "=f"(r) : "f"(x)); return r; }
__device__ __forceinline__ void wg_fence() { asm volatile("wgmma.fence.sync.aligned;" ::: "memory"); }
__device__ __forceinline__ void wg_commit() { asm volatile("wgmma.commit_group.sync.aligned;" ::: "memory"); }
__device__ __forceinline__ void wg_wait0() { asm volatile("wgmma.wait_group.sync.aligned 0;" ::: "memory"); }

#define SCALE_HI 0x3db53db5u
#define SCALE_LO 0x371e371eu
#define LOG2E 1.4426950408889634f
#define NEG_BIG2 0xce6ece6eu
__device__ __forceinline__ uint32_t scale_bf2(uint32_t x) {
    uint32_t t, r;
    asm("mul.rn.bf16x2 %0, %1, %2;" : "=r"(t) : "r"(x), "r"(SCALE_LO));
    asm("fma.rn.bf16x2 %0, %1, %2, %3;" : "=r"(r) : "r"(x), "r"(SCALE_HI), "r"(t));
    return r;
}
__device__ __forceinline__ void cluster_arrive_rx() { asm volatile("barrier.cluster.arrive.relaxed.aligned;" ::: "memory"); }
__device__ __forceinline__ uint32_t launder(uint32_t x) { asm volatile("" : "+r"(x)); return x; }
__device__ __forceinline__ void mbar_arrive(uint32_t a) { asm volatile("mbarrier.arrive.shared.b64 _, [%0];" :: "r"(a) : "memory"); }
__device__ __forceinline__ void mbar_wait_cl(uint32_t a, uint32_t parity) {
    int it = 0; uint32_t ok;
    do { asm volatile("{\n.reg .pred p;\nmbarrier.try_wait.parity.acquire.cluster.shared::cta.b64 p, [%1], %2;\nselp.u32 %0, 1, 0, p;\n}\n" : "=r"(ok) : "r"(a), "r"(parity) : "memory"); } while (!ok && ++it < SPIN_LIMIT);
}
__device__ __forceinline__ uint64_t desc_from(uint32_t lo) { return (uint64_t)lo | ((uint64_t)0x40000040u << 32); }
#define SB_OFF 1024u
#define DESC_LO(off) ((((SB_OFF + (uint32_t)(off)) & 0x3FFFFu) >> 4) | 0x10000u)
template<int N> struct ic { static constexpr int value = N; };
__device__ __forceinline__ uint32_t uni(uint32_t x) { return __shfl_sync(0xffffffffu, x, 0); }

__device__ __forceinline__ uint32_t pack_f16(float lo, float hi) { uint32_t r; asm("cvt.rn.f16x2.f32 %0, %1, %2;" : "=r"(r) : "f"(hi), "f"(lo)); return r; }
__device__ __forceinline__ uint32_t maxabs_h2(uint32_t a, uint32_t b) { uint32_t r; asm("max.NaN.xorsign.abs.f16x2 %0, %1, %2;" : "=r"(r) : "r"(a), "r"(b)); return r; }
__device__ __forceinline__ uint32_t h2_to_bf2(uint32_t v) {
    uint32_t r; asm("{\n.reg .b16 l, h;\n.reg .f32 a, b;\nmov.b32 {l, h}, %1;\ncvt.f32.f16 a, l;\ncvt.f32.f16 b, h;\ncvt.rn.bf16x2.f32 %0, b, a;\n}\n" : "=r"(r) : "r"(v)); return r;
}
__device__ __forceinline__ void sts16(uint32_t a, uint16_t v) { asm volatile("st.shared.u16 [%0], %1;" :: "r"(a), "h"(v) : "memory"); }
__device__ __forceinline__ void sts64(uint32_t a, uint32_t x, uint32_t y) { asm volatile("st.shared.v2.u32 [%0], {%1,%2};" :: "r"(a), "r"(x), "r"(y) : "memory"); }
__device__ __forceinline__ void ld_relaxed32_p(uint32_t& v, const void* p, uint32_t pred) {
    asm volatile("{\n.reg .pred p;\nsetp.ne.u32 p, %2, 0;\n@p ld.relaxed.gpu.global.u32 %0, [%1];\n}\n" : "+r"(v) : "l"(p), "r"(pred) : "memory");
}
__device__ __forceinline__ uint2 lds64(uint32_t a) { uint2 v; asm volatile("ld.shared.v2.u32 {%0,%1}, [%2];" : "=r"(v.x), "=r"(v.y) : "r"(a) : "memory"); return v; }
__device__ __forceinline__ uint32_t h1_to_bf(uint32_t v) {
    uint32_t r; asm("{\n.reg .b16 l, h;\n.reg .f32 a;\nmov.b32 {l, h}, %1;\ncvt.f32.f16 a, l;\ncvt.rn.bf16x2.f32 %0, a, a;\n}\n" : "=r"(r) : "r"(v)); return r;
}
#define T_V 0
#define BLK_Q(p) (((p) < 3 ? (p) : 8) * 2048)
#define BLK_K(p) (((p) < 3 ? 4 + (p) : 9) * 2048)
#define BLK_V(p) (((p) < 2 ? 3 + 4 * (p) : 8 + (p)) * 2048)
template<int MT>
__device__ __forceinline__ void tok_part1(uint32_t tok, int lane, uint32_t (&q)[8][4], float (&e)[5][4], uint32_t& mt, float (&st)[2]) {
    constexpr int NK = MT ? 5 : 3;
    const int g = lane >> 2, t = lane & 3, mi = lane >> 3, r8 = lane & 7;
    #pragma unroll
    for (int nt = 1; nt < NK; nt++) { e[nt][0] = e[nt][1] = e[nt][2] = e[nt][3] = 0.f; }
    const uint32_t qa = tok + (16 * MT + (mi & 1) * 8 + r8) * 64 + (((mi >> 1) ^ (r8 >> 1)) << 4);
    const uint32_t ka = tok + r8 * 64 + ((mi ^ (r8 >> 1)) << 4);
    #pragma unroll
    for (int k2 = 0; k2 < 4; k2++) {
        uint32_t b[NK][4];
        ldsm_x4(q[2 * k2], qa + BLK_Q(k2));
        ldsm_x4(q[2 * k2 + 1], (qa ^ 32) + BLK_Q(k2));
        #pragma unroll
        for (int nt = 1; nt < NK; nt++) ldsm_x4(b[nt], ka + BLK_K(k2) + (nt - 1) * 512);
        #pragma unroll
        for (int nt = 1; nt < NK; nt++) mma16816(e[nt], q[2 * k2], b[nt][0], b[nt][1]);
        #pragma unroll
        for (int nt = 1; nt < NK; nt++) mma16816(e[nt], q[2 * k2 + 1], b[nt][2], b[nt][3]);
    }
    uint32_t sp[NK][2];
    #pragma unroll
    for (int nt = 1; nt < NK; nt++) { sp[nt][0] = scale_bf2(pack_bf16(e[nt][0], e[nt][1])); sp[nt][1] = scale_bf2(pack_bf16(e[nt][2], e[nt][3])); }
    const uint32_t keep = (2 * t <= g ? 0x0000ffffu : 0u) | (2 * t + 1 <= g ? 0xffff0000u : 0u);
    sp[NK - 2][0] = (sp[NK - 2][0] & keep) | (NEG_BIG2 & ~keep);
    sp[NK - 1][1] = (sp[NK - 1][1] & keep) | (NEG_BIG2 & ~keep);
    uint32_t m0 = sp[1][0], m1 = sp[1][1];
    #pragma unroll
    for (int nt = 2; nt < NK; nt++) { if (nt < NK - 1) m0 = max_bf2(m0, sp[nt][0]); m1 = max_bf2(m1, sp[nt][1]); }
    mt = max_bf2(__byte_perm(m0, m1, 0x5410), __byte_perm(m0, m1, 0x7632));
    mt = max_bf2(mt, __shfl_xor_sync(0xffffffffu, mt, 1));
    mt = max_bf2(mt, __shfl_xor_sync(0xffffffffu, mt, 2));
    const float nm0 = -bf_lo(mt) * LOG2E, nm1 = -bf_hi(mt) * LOG2E;
    st[0] = st[1] = 0.f;
    #pragma unroll
    for (int nt = 1; nt < NK; nt++) {
        if (nt < NK - 1) {
            e[nt][0] = ex2(fmaf(bf_lo(sp[nt][0]), LOG2E, nm0)); e[nt][1] = ex2(fmaf(bf_hi(sp[nt][0]), LOG2E, nm0));
            st[0] += e[nt][0] + e[nt][1];
        }
        e[nt][2] = ex2(fmaf(bf_lo(sp[nt][1]), LOG2E, nm1)); e[nt][3] = ex2(fmaf(bf_hi(sp[nt][1]), LOG2E, nm1));
        st[1] += e[nt][2] + e[nt][3];
    }
}
template<int MT, class F>
__device__ __forceinline__ void tok_part2(uint32_t tok, uint32_t exl, uint32_t ost, int eh, int lane, const uint32_t (&q)[8][4], float (&e)[5][4], uint32_t mt, const float (&st)[2], bool vb, F&& wait_v) {
    constexpr int NK = MT ? 5 : 3;
    const int mi = lane >> 3, r8 = lane & 7;
    uint32_t sm0, sm1;
    {
        uint32_t b[4][4];
        float s1[4] = {0.f, 0.f, 0.f, 0.f}, s2[4] = {0.f, 0.f, 0.f, 0.f};
        ldsm16_t(b, exl + 2048);
        #pragma unroll
        for (int k2 = 0; k2 < 4; k2++) { mma16816(s1, q[2 * k2], b[k2][0], b[k2][1]); mma16816(s2, q[2 * k2 + 1], b[k2][2], b[k2][3]); }
        sm0 = scale_bf2(pack_bf16(s1[0] + s2[0], s1[1] + s2[1])); sm1 = scale_bf2(pack_bf16(s1[2] + s2[2], s1[3] + s2[3]));
    }
    asm volatile("" : "+r"(sm0), "+r"(sm1));
    if (T_V == 0 && vb) bar_arrive(12, 384);
    wait_v();
    constexpr int NQ = MT ? 2 : 4;
    uint32_t bm[NQ][4], bv[8][4];
    uint32_t mm = max_bf2(__byte_perm(sm0, sm1, 0x5410), __byte_perm(sm0, sm1, 0x7632));
    mm = max_bf2(mm, __shfl_xor_sync(0xffffffffu, mm, 1));
    mm = max_bf2(mm, __shfl_xor_sync(0xffffffffu, mm, 2));
    {
        const uint32_t va = MT ? tok + lane * 64 + ((r8 >> 1) << 4) : tok + (lane & 15) * 64 + (((lane >> 4) ^ (r8 >> 1)) << 4);
        const uint32_t o0 = eh ? BLK_V(2) : BLK_V(0), o1 = eh ? BLK_V(3) : BLK_V(1);
        #pragma unroll
        for (int n = 0; n < 8; n++) { if (MT) ldsm_x4_t(bv[n], (va ^ ((n & 3) << 4)) + (n < 4 ? o0 : o1)); else ldsm_x4_t(bv[n], (va ^ ((n & 1) << 5)) + BLK_V(n >> 1)); }
    }
    mm = max_bf2(mm, mt);
    asm volatile("" : "+r"(mm));
    const float nm0 = -bf_lo(mm) * LOG2E, nm1 = -bf_hi(mm) * LOG2E;
    const float f0 = ex2(fmaf(bf_lo(mt), LOG2E, nm0)), f1 = ex2(fmaf(bf_hi(mt), LOG2E, nm1));
    e[0][0] = ex2(fmaf(bf_lo(sm0), LOG2E, nm0)); e[0][1] = ex2(fmaf(bf_hi(sm0), LOG2E, nm0));
    e[0][2] = ex2(fmaf(bf_lo(sm1), LOG2E, nm1)); e[0][3] = ex2(fmaf(bf_hi(sm1), LOG2E, nm1));
    float s0 = fmaf(st[0], f0, e[0][0] + e[0][1]), s1 = fmaf(st[1], f1, e[0][2] + e[0][3]);
    s0 += __shfl_xor_sync(0xffffffffu, s0, 1); s1 += __shfl_xor_sync(0xffffffffu, s1, 1);
    s0 += __shfl_xor_sync(0xffffffffu, s0, 2); s1 += __shfl_xor_sync(0xffffffffu, s1, 2);
    {
        const uint32_t vm = exl + 4096 + (MT ? eh * 1024 : 0);
        #pragma unroll
        for (int j = 0; j < NQ; j++) ldsm_x4(bm[j], vm + 512 * j);
    }
    const float i0 = rcp_approx(s0), i1 = rcp_approx(s1), j0 = i0 * f0, j1 = i1 * f1;
    uint32_t pa[NK][2];
    pa[0][0] = pack_bf16(e[0][0] * i0, e[0][1] * i0); pa[0][1] = pack_bf16(e[0][2] * i1, e[0][3] * i1);
    #pragma unroll
    for (int nt = 1; nt < NK; nt++) { pa[nt][0] = nt < NK - 1 ? pack_bf16(e[nt][0] * j0, e[nt][1] * j0) : 0u; pa[nt][1] = pack_bf16(e[nt][2] * j1, e[nt][3] * j1); }
    const uint32_t oa = ost + ((mi & 1) * 8 + r8) * 128 + (((mi >> 1) ^ r8) << 4);
    #pragma unroll
    for (int j = 0; j < NQ; j++) {
        float o[4][4];
        #pragma unroll
        for (int n = 0; n < 4; n++) {
            o[n][0] = o[n][1] = o[n][2] = o[n][3] = 0.f;
            if (MT) mma16816r(o[n], pa[1][0], pa[1][1], pa[2][0], pa[2][1], bv[4 * j + n][0], bv[4 * j + n][1]);
            else mma16816r(o[n], pa[1][0], pa[1][1], pa[2][0], pa[2][1], bv[2 * j + (n >> 1)][2 * (n & 1)], bv[2 * j + (n >> 1)][2 * (n & 1) + 1]);
        }
        if (MT) {
            #pragma unroll
            for (int n = 0; n < 4; n++) mma16816r(o[n], pa[3 % NK][0], pa[3 % NK][1], pa[4 % NK][0], pa[4 % NK][1], bv[4 * j + n][2], bv[4 * j + n][3]);
        }
        #pragma unroll
        for (int n = 0; n < 4; n++) mma1688(o[n], pa[0][0], pa[0][1], bm[j][n]);
        stsm_x4((oa ^ ((j & 1) << 6)) + (j >> 1) * 2048, pack_bf16(o[0][0], o[0][1]), pack_bf16(o[0][2], o[0][3]), pack_bf16(o[1][0], o[1][1]), pack_bf16(o[1][2], o[1][3]));
        stsm_x4((oa ^ (((j & 1) << 6) | 32)) + (j >> 1) * 2048, pack_bf16(o[2][0], o[2][1]), pack_bf16(o[2][2], o[2][3]), pack_bf16(o[3][0], o[3][1]), pack_bf16(o[3][2], o[3][3]));
    }
}

struct SendAddr { const unsigned char* a; const unsigned char* b; uint32_t other; };
__device__ __forceinline__ SendAddr send_addr(uint32_t tile, uint32_t so, uint32_t l16) {
    SendAddr d;
    d.a = launder_p(g_acc + ((l16 & 0x100u) + ((l16 & 0xf0u) >> 1) + (tile * 1024 + so)));
    d.b = launder_p(g_acc + (((l16 >> 4) & 28u) + (ACC_X + (tile >> 1) * 1024 + (tile & 1) * 256 + so)));
    d.other = launder((l16 ^ (tile << 4)) & 0x30u);
    return d;
}
template<int OA, int OB, int OT>
__device__ __forceinline__ void send_tile(float c0, float c1, float c2, float c3, const SendAddr& d, uint32_t fb) {
    const uint32_t w0 = pack_f16(c0, c1), w1 = pack_f16(c2, c3);
    asm volatile("{\n.reg .pred q;\n.reg .b32 a, b;\nsetp.eq.u32 q, %4, %5;\n"
                 "prmt.b32 b, %3, 1, 0x5432;\nprmt.b32 a, %3, 1, 0x5410;\nselp.b32 a, a, %3, q;\n"
                 "red.relaxed.gpu.global.add.noftz.v2.f16x2 [%0], {%2, a};\n@q red.relaxed.gpu.global.add.noftz.f16x2 [%1], b;\n}\n"
        :: "l"(d.a + OA), "l"(d.b + OB), "r"(w0), "r"(w1), "r"(d.other), "n"(OT) : "memory");
    sts128(fb, make_uint4(__float_as_uint(c0), __float_as_uint(c1), __float_as_uint(c2), __float_as_uint(c3)));
}
template<int FENCE, bool OWN>
__device__ __forceinline__ void stage_w(const uint32_t (&wo)[8][4], uint32_t ol, uint32_t tile, uint32_t so, uint32_t l16, uint32_t fb, uint32_t ph, uint32_t nv, uint32_t ila, float il, float ih) {
    uint32_t b[4][4];
    ldsm16_t(b, ol);
    if (FENCE) sched_fence<0>(nv);
    float c[2][4];
    #pragma unroll
    for (int i = 0; i < 2; i++) c[i][0] = c[i][1] = c[i][2] = c[i][3] = 0.f;
    #pragma unroll
    for (int j = 0; j < 2; j++) { mma16816(c[0], wo[2 * j], b[j][0], b[j][1]); mma16816(c[1], wo[2 * j + 1], b[j][2], b[j][3]); }
    if (!OWN) asm volatile("ld.volatile.shared.v2.f32 {%0,%1}, [%2];" : "=f"(il), "=f"(ih) : "r"(ila) : "memory");
    #pragma unroll
    for (int j = 2; j < 4; j++) { mma16816(c[0], wo[2 * j], b[j][0], b[j][1]); mma16816(c[1], wo[2 * j + 1], b[j][2], b[j][3]); }
    const SendAddr d = send_addr(tile, so, l16);
    if (!OWN) {
        int it = 0;
        while (__builtin_expect(__any_sync(0xffffffffu, (__float_as_uint(il) ^ ph) & 1u), 0) && ++it < SPIN_LIMIT)
            asm volatile("ld.volatile.shared.v2.f32 {%0,%1}, [%2];" : "=f"(il), "=f"(ih) : "r"(ila) : "memory");
    }
    send_tile<0, 0, 0>((c[0][0] + c[1][0]) * il, (c[0][1] + c[1][1]) * ih, (c[0][2] + c[1][2]) * il, (c[0][3] + c[1][3]) * ih, d, fb);
}

#define BAR_PRO 1
#define BAR_MEM 2
#define BAR_P   3
#define BAR_PRJ 4
#define BAR_VGO 7
#define BAR_X0  7
#define BAR_S   9
#define BAR_P2  10
#define BAR_O   11
#define BAR_O2  14
#define BAR_TP  15
#define BAR_V   12
#define BAR_G   13
#define VGO_AT 9
#define TP_N 36
#define TP_N1 24
#define REG_P 200
#define W_FENCE 1
#define WO_PRE 2
#define WO_MID 6
#define TP_DELAY 0
#define PRE_W 4
#ifndef M_RES
#define M_RES 6
#endif
#define K_PRE 6
#define CV_FENCE 0x1f
#define G1_0 64
#define G1_NS 1312
#define SIG_LO     (127 - 3)
#define SIG_HI     (127 + 5)
#define SIG_LOW    0x3c00u
#define SIG_LIM    56

__global__ void __cluster_dims__(3, 1, 1) __launch_bounds__(CH_THREADS, 1)
chain_kernel(const __grid_constant__ CUtensorMap tmx, const __grid_constant__ CUtensorMap tmq, const __grid_constant__ CUtensorMap tmk,
             const __grid_constant__ CUtensorMap tmv, const __grid_constant__ CUtensorMap tmo, const bf16* __restrict__ mem0, const uint32_t nv) {
    extern __shared__ __align__(1024) unsigned char smem[];
    const uint32_t sb = smem_u32(smem);
    const int tid = threadIdx.x, lane = tid & 31;
    const int warp = __shfl_sync(0xffffffffu, tid >> 5, 0);
    const int h = blockIdx.x / 3, r = blockIdx.x % 3;
    const int mi = lane >> 3, r8 = lane & 7;
    const uint32_t bX = sb + SM_BAR, bTOK = bX + 16, bEX = bX + 40, bW = bX + 64, bEV = bX + 104, bFREE = bX + 32;
    const int nqk = r < 2 ? 6 : 4;
    if ((sb & 0xFFFFFFu) != SB_OFF) __trap();
    asm volatile("griddepcontrol.launch_dependents;");
    if (tid == 0 && blockIdx.x == 0) GT(40, 0);

    auto load_w = [&](int lo, int hi) {
        #pragma unroll 1
        for (int i = lo; i < hi; i++) {
            const int blk = i >> 2, j = i & 3;
            if (i < 48) {
                const int m = r < 2 ? (j < 3 ? r : 2) : (j < 2 ? j : 2), p = r < 2 ? (j < 3 ? j : r) : (j < 2 ? 3 : j);
                asm volatile("cp.async.bulk.tensor.2d.shared::cluster.global.mbarrier::complete_tx::bytes [%0], [%1, {%3, %4}], [%2];"
                    :: "r"(sb + i * 3072), "l"(m == 0 ? &tmq : (m == 1 ? &tmk : &tmv)), "r"(bW + (blk < 3 ? 0 : (blk < 6 ? 8 : (blk < 10 ? 16 : 24)))), "r"(h * DH + p * 32), "r"(blk * 48) : "memory");
            } else asm volatile("cp.async.bulk.tensor.2d.shared::cluster.global.mbarrier::complete_tx::bytes [%0], [%1, {%3, %4}], [%2];"
                :: "r"(sb + SM_WO + (i - 48) * 8192), "l"(&tmo), "r"(bW + 32), "r"(192 * r + 32 * (i - 48)), "r"(h * DH) : "memory");
        }
    };
    if (tid == 352) {
        #pragma unroll
        for (int i = 0; i < 15; i++) mbar_init(bX + 8 * i, (i == 5 || i == 6) ? 1 + nqk : (i >= 13 ? 9 - nqk : 1));
        asm volatile("fence.mbarrier_init.release.cluster;" ::: "memory");
        mbar_expect_tx(bW, 36864); mbar_expect_tx(bW + 8, 36864); mbar_expect_tx(bW + 16, 49152); mbar_expect_tx(bW + 24, 24576); mbar_expect_tx(bW + 32, 49152);
        load_w(0, 2 * PRE_W);
    }
    const unsigned epoch = ld_relaxed32(&g_epoch);
    __syncthreads();
    const uint32_t pw0 = ((mi >> 1) * 8 + r8) * 64 + (((2 * (warp & 1) + (mi & 1)) ^ (r8 >> 1)) << 4);
    auto tok_publish = [&](int tb, int k) {
        const uint32_t src = sb + SM_TOK + tb * TOKBUF + r * 8192, bar = bTOK + 8 * tb;
        if (k == 1) asm volatile("{\n.reg .pred p;\nelect.sync _|p, 0xffffffff;\n@p mbarrier.arrive.expect_tx.shared.b64 _, [%0], 16384;\n}\n" :: "r"(bar) : "memory");
        asm volatile("{\n.reg .pred p;\nelect.sync _|p, 0xffffffff;\n"
                     "@p cp.async.bulk.shared::cluster.shared::cta.mbarrier::complete_tx::bytes [%0], [%1], 8192, [%2];\n}\n"
            :: "r"(mapa_u32(src, (r + k) % 3)), "r"(src), "r"(mapa_u32(bar, (r + k) % 3)) : "memory");
    };
    auto issue_x = [&](int sg) {
        const uint32_t bar = bX + 8 * (sg & 1), dst = sb + SM_X + (sg & 1) * XBUF + 3 * r * 4096;
        asm volatile("{\n.reg .pred p;\nelect.sync _|p, 0xffffffff;\n"
                     "@p mbarrier.arrive.expect_tx.shared.b64 _, [%2], 36864;\n"
                     "@p cp.async.bulk.tensor.2d.shared::cluster.global.mbarrier::complete_tx::bytes.multicast::cluster [%0], [%1, {%3, %4}], [%2], %5;\n"
                     "@p cp.async.bulk.tensor.2d.shared::cluster.global.mbarrier::complete_tx::bytes.multicast::cluster [%6], [%1, {%7, %4}], [%2], %5;\n"
                     "@p cp.async.bulk.tensor.2d.shared::cluster.global.mbarrier::complete_tx::bytes.multicast::cluster [%8], [%1, {%9, %4}], [%2], %5;\n}\n"
            :: "r"(dst), "l"(&tmx), "r"(bar), "r"(192 * r), "r"(sg * SEG), "h"((unsigned short)7), "r"(dst + 4096), "r"(192 * r + 64), "r"(dst + 8192), "r"(192 * r + 128) : "memory");
    };

    if (warp < 8) {
        asm volatile("setmaxnreg.inc.sync.aligned.u32 %0;" :: "n"(REG_P));
        uint32_t wf[36][4];
        const uint32_t wl = sb + (warp >> 1) * 3072 + pw0;
        float ta0[16], ta1[16];
        auto tp_part = [&](auto lo, auto hi) {
            wg_fence();
            #pragma unroll
            for (int i = lo.value; i < hi.value; i++) {
                if (i == 0) wgmma_n32<0>(ta0, wf[0], desc_from(DESC_LO(SM_X))); else wgmma_n32<1>(ta0, wf[i], desc_from(DESC_LO(SM_X) + (i >> 2) * 256 + (i & 3) * 2));
            }
            #pragma unroll
            for (int i = lo.value; i < hi.value; i++) {
                if (i == 0) wgmma_n32<0>(ta1, wf[0], desc_from(DESC_LO(SM_X + XBUF))); else wgmma_n32<1>(ta1, wf[i], desc_from(DESC_LO(SM_X + XBUF) + (i >> 2) * 256 + (i & 3) * 2));
            }
            wg_commit();
        };
        if (tid == 32) load_w(2 * PRE_W, 40);
        if (tid == 0) GT(41 + blockIdx.x % 3, 7);
        mbar_wait(bW, 0);
        #pragma unroll
        for (int i = 0; i < 9; i++) ldsm_x4_t(wf[i], wl + (i / 3) * 12288 + (i % 3) * 1024);
        fence_async_smem(); bar_arrive(BAR_X0, 288);
        mbar_wait(bW + 8, 0);
        #pragma unroll
        for (int i = 9; i < 18; i++) ldsm_x4_t(wf[i], wl + (i / 3) * 12288 + (i % 3) * 1024);
        fence_async_smem(); bar_arrive(BAR_X0 + 1, 288);
        mbar_wait(bX, 0); mbar_wait(bX + 8, 0);
        tp_part(ic<0>(), ic<18>());
        wg_wait0();
        sts128(sb + SM_OST + tid * 16, make_uint4(wf[0][0], wf[0][1], wf[0][2], wf[0][3]));
        mbar_wait(bW + 16, 0);
        #pragma unroll
        for (int i = 18; i < 30; i++) ldsm_x4_t(wf[i], wl + (i / 3) * 12288 + (i % 3) * 1024);
        tp_part(ic<18>(), ic<30>());
        mbar_wait(bW + 24, 0);
        if (tid == 0) GT(41 + blockIdx.x % 3, 0);
        wg_wait0();
        #pragma unroll
        for (int i = 30; i < 36; i++) ldsm_x4_t(wf[i], wl + (i / 3) * 12288 + (i % 3) * 1024);
        fence_async_smem();
        cluster_arrive_rx();
        tp_part(ic<30>(), ic<36>());
        if (tid == 0) GT(41 + blockIdx.x % 3, 2);
        const uint32_t pw = pin(pw0);
        auto tp_store = [&](const float (&acc)[16], uint32_t off) {
            const uint32_t ta = pw + launder(sb + off + (warp >> 1) * 2048);
            stsm_x4_t(ta, pack_bf16(acc[0], acc[1]), pack_bf16(acc[2], acc[3]), pack_bf16(acc[4], acc[5]), pack_bf16(acc[6], acc[7]));
            stsm_x4_t(ta + 1024, pack_bf16(acc[8], acc[9]), pack_bf16(acc[10], acc[11]), pack_bf16(acc[12], acc[13]), pack_bf16(acc[14], acc[15]));
            fence_async_smem();
        };
        cluster_wait();
        wg_wait0();
        tp_store(ta0, SM_TOK + r * 8192);
        if (warp == 0) { bar_sync(BAR_PRJ, 256); tok_publish(0, 1); tok_publish(0, 2); } else bar_arrive(BAR_PRJ, 256);
        tp_store(ta1, SM_TOK + TOKBUF + r * 8192);
        bar_arrive(BAR_TP, 288);
        { const uint4 v = lds128(sb + SM_OST + tid * 16); wf[0][0] = v.x; wf[0][1] = v.y; wf[0][2] = v.z; wf[0][3] = v.w; }
        if (tid == 0) GT(41 + blockIdx.x % 3, 4);
        const uint32_t l16 = pin(lane * 16), sbl = sb + l16, l4w = pin(sb + warp * 256 + lane * 4);
        uint32_t wo[8][4];
        const int exo = r < 2 ? (warp < 6 ? r * 2048 : 4096 + (2 * r - 6) * 256) : (warp < 2 ? 6 * 256 : (warp < 4 ? 2048 + 4 * 256 : 4096));
        const bool isqk = warp < nqk;
        const uint32_t exbar = isqk ? bEX : bEV;
        for (int s = 0; s < NSEG; s++) {
            const int par = s & 1;
            const uint32_t va = pw + launder(sb + SM_TOK + par * TOKBUF + BLK_V(warp >> 1)), wa = pw + launder(sb + SM_WO + (warp >> 1) * 8192);
            const uint32_t exu = launder(SM_EX + par * EXBUF), ph = launder(par ^ 1);
            uint32_t vf[2][4];
            if (s == 0) mbar_wait(bTOK, 0);
            ldsm_x4_t(vf[0], va); ldsm_x4_t(vf[1], va + 1024);
            const float unsc = __uint_as_float((254u - lds32(sb + SM_SG + 12 + par * 16)) << 23);
            if (!isqk) { bar_arrive(BAR_MEM, 352); bar_sync(BAR_VGO, 256); } else bar_sync(BAR_MEM, 352);
            if (warp == 0) STAMPB(0);
            {
                float acc[4][4];
                #pragma unroll
                for (int i = 0; i < 4; i++) { acc[i][0] = acc[i][1] = acc[i][2] = acc[i][3] = 0.f; }
                #pragma unroll
                for (int i2 = 0; i2 < 18; i2++) {
                    uint32_t b[4];
                    ldsm_x4_t(b, sbl + SM_MEM + i2 * 512);
                    if (i2 == VGO_AT) bar_arrive_p(BAR_VGO, 256, !isqk);
                    mma16816(acc[(2 * i2) & 3], wf[2 * i2], b[0], b[1]);
                    mma16816(acc[(2 * i2 + 1) & 3], wf[2 * i2 + 1], b[2], b[3]);
                }
                float q[4];
                #pragma unroll
                for (int i = 0; i < 4; i++) q[i] = fmaf(acc[2][i] + acc[3][i], unsc, (acc[0][i] + acc[1][i]) * unsc);
                const uint32_t lo = pack_bf16(q[0], q[1]), hi = pack_bf16(q[2], q[3]);
                const uint32_t exl = l4w + launder(exu + exo), bar = exbar + par * 8;
                #pragma unroll
                for (int k = 1; k < 3; k++) {
                    const uint32_t exd = mapa_u32(exl, (r + k) % 3), exb = mapa_u32(bar, (r + k) % 3);
                    st_async32(exd, lo, exb); st_async32(exd + 128, hi, exb);
                }
                sts32(exl, lo); sts32(exl + 128, hi);
                __syncwarp();
                asm volatile("{\n.reg .pred p;\nelect.sync _|p, 0xffffffff;\n@p mbarrier.arrive.shared.b64 _, [%0];\n}\n" :: "r"(bar) : "memory");
            }
            if (warp == 0) STAMP(1);
            if (s == 0) mbar_wait(bW + 32, 0);
            if (s == NSEG - 1) break;
            {
                bar_sync_p(BAR_PRO, 32 * nqk, !isqk);
                #pragma unroll
                for (int i = 0; i < WO_PRE; i++) ldsm_x4_t(wo[i], wa + i * 1024);
                if (warp == 1) {
                    mbar_wait(bEX + 8 * par, (s >> 1) & 1);
                    asm volatile("{\n.reg .pred p;\nelect.sync _|p, 0xffffffff;\n"
                                 "@p mbarrier.arrive.expect_tx.shared.b64 _, [%2], 384;\n"
                                 "@p cp.async.bulk.shared::cluster.global.mbarrier::complete_tx::bytes [%0], [%1], 384, [%2];\n}\n"
                        :: "r"(sb + SM_TS), "l"(g_ts), "r"(bFREE) : "memory");
                    if (s == 0) issue_x(2);
                    if (s + 3 < NSEG) issue_x(s + 3);
                }
                mbar_wait(bEV + 8 * par, (s >> 1) & 1);
                if (warp == 0) STAMP(2);
                const uint32_t vm0 = lds32(l4w + exu + 4096), vm1 = lds32(l4w + exu + 4096 + 128);
                #pragma unroll
                for (int i = WO_PRE; i < WO_MID; i++) ldsm_x4_t(wo[i], wa + i * 1024);
                bar_sync(BAR_P, 352);
                if (warp == 0) STAMPB(3);
                uint32_t pb[4]; ldsm_x4_t(pb, sbl + SM_P);
                uint32_t pm, big; ldsm_x2_t(pm, big, sbl + SM_P + 512);
                float o0[4] = {0.f, 0.f, 0.f, 0.f}, o1[4] = {0.f, 0.f, 0.f, 0.f};
                sched_fence<1>(nv);
                #pragma unroll
                for (int i = WO_MID; i < 8; i++) ldsm_x4_t(wo[i], wa + i * 1024);
                if (WO_MID < 8) sched_fence<12>(nv);
                mma16816(o0, vf[0], pb[0], pb[1]);
                mma16816(o1, vf[1], pb[2], pb[3]);
                mma1688(o0, vm0, vm1, pm);
                if (__builtin_expect(__any_sync(0xffffffffu, big), 0)) {
                    bar_arrive(BAR_S, 352);
                    bar_sync(BAR_P2, 352);
                    ldsm_x4_t(pb, sbl + SM_P); pm = ldsm_x1_t(sbl + SM_P + 512);
                    #pragma unroll
                    for (int i = 0; i < 4; i++) o0[i] = o1[i] = 0.f;
                    ldsm_x4_t(vf[0], va); mma16816(o0, vf[0], pb[0], pb[1]);
                    ldsm_x4_t(vf[0], va + 1024); mma16816(o0, vf[0], pb[2], pb[3]);
                    mma1688(o0, lds32(l4w + exu + 4096), lds32(l4w + exu + 4096 + 128), pm);
                }
                sts32(l4w + SM_O, pack_bf16(o0[0] + o1[0], o0[1] + o1[1]));
                sts32(l4w + SM_O + 128, pack_bf16(o0[2] + o1[2], o0[3] + o1[3]));
            }
            {
                bar_arrive(BAR_O2, 320);
                bar_sync(BAR_O, 288);
                if (warp == 0) STAMPB(16);
                const uint32_t ll = launder(l16);
                stage_w<W_FENCE, false>(wo, sbl + SM_O, 12 * r + warp, SLOT_OFF(s + 1), ll, ll + (sb + SM_FB + warp * 512), ph, nv, sb + SM_IL + (ll & 0x30u), 0.f, 0.f);
            }
            if (warp == 7) STAMP(9);
            if (warp == 0) STAMP(4);
            bar_sync(BAR_V, 384);
            if (TP_DELAY) delay_clk(TP_DELAY);
            if (s + 2 < NSEG) {
                float acc[16];
                const uint32_t xd = uni(DESC_LO(SM_X) + par * (XBUF >> 4));
                if (s == 0) mbar_wait(bX, 1);
                wg_fence();
                #pragma unroll
                for (int i = 0; i < TP_N; i++) {
                    if (i == TP_N1) {
                        wg_commit();
                        if (s + 3 < NSEG) mbar_wait(bX + 8 * (par ^ 1), (((s + 1) >> 1) & 1) ^ 1);
                        bar_sync(BAR_G, 288);
                    }
                    if (i == 0) wgmma_n32<0>(acc, wf[0], desc_from(xd));
                    else wgmma_n32<1>(acc, wf[i], desc_from(xd + (i >> 2) * 256 + (i & 3) * 2));
                }
                wg_commit();
                if (TP_N1 >= TP_N) { if (s + 3 < NSEG) mbar_wait(bX + 8 * (par ^ 1), (((s + 1) >> 1) & 1) ^ 1); bar_sync(BAR_G, 288); }
                mbar_wait(bTOK + 8 * (par ^ 1), ((s + 1) >> 1) & 1);
                wg_wait0();
                if (warp == 0) STAMP(5);
                tp_store(acc, SM_TOK + par * TOKBUF + r * 8192);
                bar_arrive(BAR_TP, 288);
            } else { bar_sync(BAR_G, 288); mbar_wait(bTOK + 8 * (par ^ 1), ((s + 1) >> 1) & 1); }
            if (warp == 0) STAMP(6);
        }
        cluster_arrive(); cluster_wait();
    } else {
        asm volatile("setmaxnreg.dec.sync.aligned.u32 %0;" :: "n"(504 - 2 * REG_P));
        const int a = warp - 8;
        const uint32_t sbl = sb + lane * 16;
        if (a < 3) {
            const uint32_t zs = 3 * blockIdx.x + (r8 >> 1);
            const uint32_t zoff = (r8 < 6 ? (zs >> 3) * 1024 + ((zs >> 2) & 1) * 256 + (zs & 3) * 32 : ACC_X + (blockIdx.x >> 1) * 1024 + (blockIdx.x & 1) * 256) + (lane & 1) * 16;
            const uint32_t zskip = r8 >= 6 && blockIdx.x >= 36;
            if (a == 1) {
                st_relaxed128_p((uint4*)(g_acc + zoff + SLOT_OFF(mi)), make_uint4(0, 0, 0, 0), zskip);
                __threadfence();
                __syncwarp();
                if (lane == 0) st_relaxed32(&g_init[blockIdx.x], epoch);
            }
            {
                uint32_t mx = 0;
                #pragma unroll
                for (int i = 0; i < 6; i++) {
                    const int c = tid - 256 + 96 * i;
                    const unsigned short* m = (const unsigned short*)mem0 + c;
                    uint4 v;
                    v.x = m[0] | ((uint32_t)m[DM] << 16); v.y = m[2 * DM] | ((uint32_t)m[3 * DM] << 16);
                    v.z = m[4 * DM] | ((uint32_t)m[5 * DM] << 16); v.w = m[6 * DM] | ((uint32_t)m[7 * DM] << 16);
                    sts128(sb + SM_MEM + c * 16, v);
                    mx = maxabs_bf2(maxabs_bf2(mx, v.x), maxabs_bf2(maxabs_bf2(v.y, v.z), v.w));
                }
                mx = __reduce_max_sync(0xffffffffu, max((mx >> 7) & 0xffu, (mx >> 23) & 0xffu));
                sts32(sb + SM_SG + a * 4, max(mx, 1u)); sts32(sb + SM_SG + 12, 127u);
            }
            sts32(sb + SM_FLAG + lane * 4, 0u); if (lane < 16) sts32(sb + SM_IL + lane * 4, 0u);
            asm volatile("barrier.cluster.arrive.release.aligned;" ::: "memory");
            { int it = 0; while (__any_sync(0xffffffffu, ld_relaxed32(&g_init[a * 32 + lane]) != epoch) && ++it < SPIN_LIMIT) {} }
            __threadfence();
            const uint32_t kl0 = (a < 2 ? SM_TOK + (16 * a + (mi & 1) * 8 + r8) * 64 + (((mi >> 1) ^ (r8 >> 1)) << 4) : SM_EX + 2048 + ((((mi & 1) << 1) | (mi >> 1)) * 8 + r8) * 16);
            const uint32_t l16 = pin(lane * 16);
            uint32_t kf[8][4], wo[8][4];
            auto load_k = [&](int tb, uint32_t kl, auto lo, auto hi) {
                const uint32_t ka = kl + launder(sb + tb * TOKBUF);
                if (a < 2) {
                    #pragma unroll
                    for (int kk = lo.value; kk < hi.value; kk++) ldsm_x4(kf[kk], (ka ^ ((kk & 1) << 5)) + BLK_K(kk >> 1));
                }
            };
            cluster_wait();
            if (a == 0 && lane == 0) { mbar_expect_tx(bEX, 4096 - 256 * nqk); mbar_expect_tx(bEV, 256 * nqk); }
            bar_arrive(BAR_MEM, 352);
            mbar_wait(bW + 32, 0);
            #pragma unroll
            for (int i = 0; i < 8; i++) ldsm_x4_t(wo[i], pw0 + sb + SM_WO + (warp >> 1) * 8192 + i * 1024);
            sts128(sbl + SM_STASH + a * 1024 + 512, make_uint4(kl0, (pw0 ^ 32) + sb + SM_WO + 5 * 8192, zoff | ((zskip || lane >= 8) << 31), epoch << 6));
            sts128(sbl + SM_STASH + a * 1024, make_uint4(a * 12288 + (lane >> 4) * 1024 + (mi & 1) * 256 + r8 * 16, ACC_X + a * 6144 + (lane >> 4) * 1024 + (mi & 1) * 256 + r8 * 4,
                                                         sb + SM_MEM + a * 3072 + (lane >> 4) * 256 + (lane & 15) * 8, sb + SM_MEM + a * 3072 + mi * 260 + r8 * 16 + 130));
            const uint32_t stash = l16 + uni(sb + SM_STASH + a * 1024);
            #pragma unroll
            for (int i = 0; i < 8; i++) ldsm_x4_t(kf[i], (pw0 ^ 32) + sb + SM_WO + 5 * 8192 + i * 1024);
            mbar_wait(bTOK, 0); load_k(0, kl0, ic<0>(), ic<8>());
            if (a == 2) st_relaxed32_p(&g_ts[blockIdx.x], gtime_lo(), l16);
            __syncwarp();
            #pragma unroll 1
            for (int s = 0; s < NSEG - 1; s++) {
                const int par = s & 1;
                const uint32_t exu = launder(sb + par * EXBUF);
                const uint32_t exl = l16 + exu + SM_EX;
                if (a == 1) {
                    const uint32_t z = lds32(stash + 520);
                    st_relaxed128_p((uint4*)(g_acc + (z + SLOT_OFF(s + 3))), make_uint4(0, 0, 0, 0), z >> 31);
                }
                auto first_half = [&](auto role) {
                constexpr bool M = role.value;
                uint32_t sl, sh, kl = 0, w2 = 0;
                float sig = 0.f;
                if (M) kl = lds32(stash + 512);
                else {
                    const uint4 sg = lds128(sb + SM_SG + par * 16);
                    const int e = max(max(sg.x, sg.y), sg.z), d = e - (sg.w >> 9 ? SIG_HI : SIG_LO);
                    const bool moving = d > 2 || d < -2 || s == 0;
                    uint32_t se = sg.w & 255u;
                    if (e) se = min(max((int)se + (moving ? SIG_HI : SIG_LO) - e, 127 - SIG_LIM), 127 + SIG_LIM) | (moving << 9);
                    sts32(sb + SM_SG + 12 + (par ^ 1) * 16, se);
                    sig = __uint_as_float(se << 23);
                }
                const uint32_t pst = (launder(l16) >> 2) + launder(sb + SM_P + a * 256);
                mbar_wait(bEX + 8 * par, (s >> 1) & 1);
                if (a == 0) STAMP(8);
                if (!M) {
                    uint32_t b[4][4];
                    ldsm16_t(b, exl);
                    float c[4][4];
                    #pragma unroll
                    for (int j = 0; j < 4; j++) { c[j][0] = c[j][1] = c[j][2] = c[j][3] = 0.f; }
                    #pragma unroll
                    for (int j = 0; j < 4; j++) { mma16816(c[(2 * j) & 3], kf[2 * j], b[j][0], b[j][1]); mma16816(c[(2 * j + 1) & 3], kf[2 * j + 1], b[j][2], b[j][3]); }
                    sl = scale_bf2(pack_bf16((c[0][0] + c[1][0]) + (c[2][0] + c[3][0]), (c[0][1] + c[1][1]) + (c[2][1] + c[3][1])));
                    sh = scale_bf2(pack_bf16((c[0][2] + c[1][2]) + (c[2][2] + c[3][2]), (c[0][3] + c[1][3]) + (c[2][3] + c[3][3])));
                } else {
                    float c[4][4];
                    #pragma unroll
                    for (int j = 0; j < 4; j++) { c[j][0] = c[j][1] = c[j][2] = c[j][3] = 0.f; }
                    uint32_t k[4][4], b[4][4];
                    #pragma unroll
                    for (int j = 0; j < 4; j++) { ldsm_x4_t(k[j], kl + exu + 512 * j); ldsm_x4_t(b[j], exl + 512 * j); }
                    sched_fence<9>(nv);
                    #pragma unroll
                    for (int j = 0; j < 4; j++) { mma16816(c[2 * (j & 1)], k[j], b[j][0], b[j][1]); mma16816(c[2 * (j & 1) + 1], k[j], b[j][2], b[j][3]); }
                    sched_fence<14>(nv);
                    w2 = lds32(stash + 516);
                    sh = sl = scale_bf2(pack_bf16((c[0][0] + c[1][2]) + (c[2][0] + c[3][2]), (c[0][1] + c[1][3]) + (c[2][1] + c[3][3])));
                }
                sts32(pst, pack_bf16(ex2(bf_lo(sl) * LOG2E), ex2(bf_hi(sl) * LOG2E)));
                if (!M) sts32(pst + 128, pack_bf16(ex2(bf_lo(sh) * LOG2E), ex2(bf_hi(sh) * LOG2E)));
                sts32_p(sb + SM_FLAG, 1u, ((maxabs_bf2(sl, sh) & 0x7fff7fffu) + 0x3ddf3ddfu) & 0x80008000u);
                if (M) {
                    #pragma unroll
                    for (int i = M_RES; i < 8; i++) ldsm_x4_t(kf[i], w2 + i * 1024);
                }
                bar_sync(BAR_P, 352);
                if (a == 0) STAMP(10);
                uint32_t big;
                float l0[4], l1[4], l2[4];
                auto denom = [&] {
                    uint32_t pb[4], pm; ldsm_x4_t(pb, l16 + sb + SM_P); ldsm_x2_t(pm, big, l16 + sb + SM_P + 512);
                    const uint32_t ONE = 0x3F803F80u;
                    #pragma unroll
                    for (int i = 0; i < 4; i++) l0[i] = l1[i] = l2[i] = 0.f;
                    mma16816r(l0, ONE, ONE, ONE, ONE, pb[0], pb[1]);
                    mma16816r(l1, ONE, ONE, ONE, ONE, pb[2], pb[3]);
                    mma1688(l2, ONE, ONE, pm);
                };
                if (M) big = lds32(sb + SM_FLAG); else denom();
                if (__builtin_expect(__any_sync(0xffffffffu, big), 0)) {
                    uint32_t m2 = max_bf2(sl, sh);
                    m2 = max_bf2(m2, __shfl_xor_sync(0xffffffffu, m2, 4));
                    m2 = max_bf2(m2, __shfl_xor_sync(0xffffffffu, m2, 8));
                    m2 = max_bf2(m2, __shfl_xor_sync(0xffffffffu, m2, 16));
                    const uint32_t lq = pin(l16);
                    if (lq < 64) sts32(lq + sb + SM_P + 768 + a * 4, m2);
                    bar_sync(BAR_S, 352);
                    const uint4 m = lds128(sb + SM_P + 768 + (lq & 0x30));
                    m2 = max_bf2(max_bf2(m.x, m.y), m.z);
                    const float ml = -bf_lo(m2) * LOG2E, mh = -bf_hi(m2) * LOG2E;
                    sts32(pst, pack_bf16(ex2(fmaf(bf_lo(sl), LOG2E, ml)), ex2(fmaf(bf_hi(sl), LOG2E, mh))));
                    if (!M) sts32(pst + 128, pack_bf16(ex2(fmaf(bf_lo(sh), LOG2E, ml)), ex2(fmaf(bf_hi(sh), LOG2E, mh))));
                    sts32(sb + SM_FLAG, 0u);
                    bar_sync(BAR_P2, 352);
                    if (!M) denom();
                }
                const uint32_t ph = launder(par ^ 1), ll = launder(l16), ila = sb + SM_IL + (ll & 0x30), so = SLOT_OFF(launder(s) + 1);
                if (!M) {
                    const float sil = __uint_as_float((__float_as_uint(rcp_approx((l0[0] + l1[0]) + l2[0]) * sig) & ~1u) | ph), sih = rcp_approx((l0[1] + l1[1]) + l2[1]) * sig;
                    asm volatile("st.volatile.shared.v2.f32 [%0], {%1,%2};" :: "r"(ila), "f"(sil), "f"(sih) : "memory");
                    bar_sync(BAR_O2, 320);
                    stage_w<0, true>(wo, l16 + sb + SM_O, 12 * r + warp, so, ll, ll + (sb + SM_FB + warp * 512), ph, nv, 0u, sil, sih);
                } else {
                    bar_sync(BAR_O, 288);
                    float c[4][4], il, ih;
                    #pragma unroll
                    for (int i = 0; i < 4; i++) c[i][0] = c[i][1] = c[i][2] = c[i][3] = 0.f;
                    uint32_t b[4][4];
                    #pragma unroll
                    for (int j = 0; j < 4; j++) ldsm_x4_t(b[j], l16 + sb + SM_O + 512 * (3 - j));
                    sched_fence<11>(nv);
                    #pragma unroll
                    for (int j = 0; j < 4; j++) {
                        if (j == 2) { sched_fence<10>(nv); asm volatile("ld.volatile.shared.v2.f32 {%0,%1}, [%2];" : "=f"(il), "=f"(ih) : "r"(ila) : "memory"); }
                        mma16816(c[0], wo[6 - 2 * j], b[j][0], b[j][1]); mma16816(c[2], kf[6 - 2 * j], b[j][0], b[j][1]);
                        mma16816(c[1], wo[7 - 2 * j], b[j][2], b[j][3]); mma16816(c[3], kf[7 - 2 * j], b[j][2], b[j][3]);
                    }
                    const SendAddr d = send_addr(12 * r + 10, so, ll);
                    int it = 0;
                    while (__builtin_expect(__any_sync(0xffffffffu, (__float_as_uint(il) ^ ph) & 1u), 0) && ++it < SPIN_LIMIT)
                        asm volatile("ld.volatile.shared.v2.f32 {%0,%1}, [%2];" : "=f"(il), "=f"(ih) : "r"(ila) : "memory");
                    send_tile<0, 0, 0>((c[0][0] + c[1][0]) * il, (c[0][1] + c[1][1]) * ih, (c[0][2] + c[1][2]) * il, (c[0][3] + c[1][3]) * ih, d, ll + (sb + SM_FB + 10 * 512));
                    send_tile<1024, 256, 16>((c[2][0] + c[3][0]) * il, (c[2][1] + c[3][1]) * ih, (c[2][2] + c[3][2]) * il, (c[2][3] + c[3][3]) * ih, d, ll + (sb + SM_FB + 11 * 512));
                    #pragma unroll
                    for (int kk = M_RES; kk < 8; kk++) kf[kk][0] = kf[kk][1] = kf[kk][2] = kf[kk][3] = 0u;
                }
                if (!M) {
                    #pragma unroll
                    for (int kk = 0; kk < 8; kk++) kf[kk][0] = kf[kk][1] = kf[kk][2] = kf[kk][3] = 0u;
                }
                };
                if (a < 2) first_half(ic<0>()); else first_half(ic<1>());
                bar_sync(BAR_V, 384);
                if (a == 0 && lane == 0) { mbar_expect_tx(bEX + 8 * (par ^ 1), 4096 - 256 * nqk); mbar_expect_tx(bEV + 8 * (par ^ 1), 256 * nqk); }
                uint32_t tg;
                {
                    mbar_wait(bFREE, par);
                    const uint4 ts = lds128(sb + SM_TS + min(launder(l16), 368u));
                    const uint32_t now = gtime_lo();
                    const int d0 = ts.x - now, d1 = ts.y - now, d2 = ts.z - now, d3 = ts.w - now;
                    int mx = __reduce_max_sync(0xffffffffu, max(max(d0, d1), max(d2, d3)));
                    const int mn = __reduce_min_sync(0xffffffffu, min(min(d0, d1), min(d2, d3)));
                    if (mn < -2000) mx = max(mx, -650);
                    tg = now + (G1_0 && s == 0 ? G1_0 : min(mx, -300) + G1_NS) + (l16 >> 16);
                }
                {
                    const uint2 as = lds64(stash);
                    const uint32_t so = SLOT_OFF(launder(s) + 1);
                    const unsigned char* pm = launder_p(g_acc + (as.x + so));
                    const unsigned char* px = launder_p(g_acc + (as.y + so));
                    sts32(sb + SM_SG + (par ^ 1) * 16 + a * 4, 0u);
                    mbar_wait(bTOK + 8 * (par ^ 1), ((s + 1) >> 1) & 1);
                    load_k(par ^ 1, lds32(stash + 512), ic<0>(), ic<K_PRE>());
                    uint4 v[6]; uint32_t x[3];
                    const uint2 ad = lds64(stash + 8);
                    const bool up = l16 & 256, odd = l16 & 16;
                    wait_gtime(tg);
                    #pragma unroll
                    for (int j = 0; j < 3; j++) x[j] = ld_relaxed32((const uint32_t*)(px + 2048 * j));
                    #pragma unroll
                    for (int j = 0; j < 6; j++) v[j] = ld_relaxed128((const uint4*)(pm + 2048 * j));
                    sched_fence<16>(nv);
                    if (a == 0) STAMP(13);
                    uint32_t any[2] = {0u, 0u}, cnt[2] = {~0u, ~0u};
                    uint32_t ax = x[0] | x[1] | x[2], cx = x[0] & x[1] & x[2];
                    const uint32_t xw0 = h2_to_bf2(__byte_perm(x[0], x[1], 0x5410)), xw1 = h1_to_bf(x[2]);
                    auto group = [&](auto jj) {
                        constexpr int j = jj.value;
                        sts64(ad.x + 512 * j, h2_to_bf2(v[j].x), h2_to_bf2(v[j].z));
                        sts64(ad.x + 512 * j + 128, h2_to_bf2(v[j].y), h2_to_bf2(v[j].w));
                        any[j & 1] = (any[j & 1] | v[j].x | v[j].y) | v[j].z | v[j].w;
                        cnt[j & 1] &= up ? v[j].w : v[j].y;
                        if (CV_FENCE & (1 << j)) { sts32_p(cnt[j & 1], any[j & 1], nv); sched_fence<17 + j>(nv); }
                    };
                    group(ic<0>()); group(ic<1>()); group(ic<2>()); group(ic<3>()); group(ic<4>()); group(ic<5>());
                    sts16(ad.y, (uint16_t)xw0); sts16(ad.y + 1024, (uint16_t)(xw0 >> 16)); sts16(ad.y + 2048, (uint16_t)xw1);
                    uint32_t c = odd ? cnt[1] : cnt[0];
                    ax |= any[0] | any[1];
                    const uint32_t bad = __any_sync(0xffffffffu, (((ax & 0x40004000u) | (~(c & cx) & (ACC_FULL << 16))) != 0u) | ((ax & 0x20002000u) == 0u));
                    bar_sync_p(BAR_MEM, 352, bad);
                    if (__builtin_expect(bad, 0)) {
                        const uint32_t lq = pin(l16);
                        int it = 0;
                        while (__any_sync(0xffffffffu, !(c & cx & (ACC_FULL << 16))) && ++it < SPIN_LIMIT) {
                            const uint4 ad = lds128(stash);
                            const uint32_t so = SLOT_OFF(launder(s) + 1), o = __shfl_xor_sync(0xffffffffu, c, 1);
                            const uint32_t again[2] = {~(odd ? o : c) & (ACC_FULL << 16), ~(odd ? c : o) & (ACC_FULL << 16)};
                            #pragma unroll
                            for (int j = 0; j < 3; j++) x[j] = ld_relaxed32((const uint32_t*)(g_acc + (ad.y + so + 2048 * j)));
                            uint4 u[6];
                            #pragma unroll
                            for (int j = 0; j < 6; j++) { u[j] = make_uint4(0u, 0u, 0u, 0u); ld_relaxed128_p(u[j], (const uint4*)(g_acc + (ad.x + so + 2048 * j)), again[j & 1]); }
                            #pragma unroll
                            for (int p = 0; p < 2; p++) if (again[p]) {
                                any[p] = 0u;
                                #pragma unroll
                                for (int j = p; j < 6; j += 2) {
                                    sts64(ad.z + 512 * j, h2_to_bf2(u[j].x), h2_to_bf2(u[j].z)); sts64(ad.z + 512 * j + 128, h2_to_bf2(u[j].y), h2_to_bf2(u[j].w));
                                    any[p] |= u[j].x | u[j].y | u[j].z | u[j].w;
                                }
                                const uint32_t cw = launder(u[p].w & u[p + 2].w & u[p + 4].w), cy = launder(u[p].y & u[p + 2].y & u[p + 4].y);
                                if (odd == p) c = up ? cw : cy;
                            }
                            __syncwarp();
                            #pragma unroll
                            for (int j = 0; j < 3; j++) sts16(ad.w + 1024 * j, (uint16_t)h1_to_bf(x[j]));
                            cx = x[0] & x[1] & x[2]; ax = x[0] | x[1] | x[2] | any[0] | any[1];
                        }
                        if (__any_sync(0xffffffffu, ((ax & 0x40004000u) != 0u) | ((ax & 0x20002000u) == 0u))) {
                            uint32_t m = 0;
                            #pragma unroll
                            for (int j = 0; j < 6; j++) { const uint4 u = lds128(lq + sb + SM_MEM + a * 3072 + 512 * j); m = maxabs_bf2(maxabs_bf2(m, maxabs_bf2(u.x, u.y)), maxabs_bf2(u.z, u.w)); }
                            uint32_t res = __reduce_max_sync(0xffffffffu, max(m & 0x7fffu, (m >> 16) & 0x7fffu));
                            if (res - SIG_LOW >= 0x7f80u - SIG_LOW) {
                                const uint32_t tag = lds32(stash + 524) + s;
                                if (a == r) {
                                    #pragma unroll 1
                                    for (int i = 0; i < 12; i++) st_relaxed128(&g_fb[a][h][i * 32 + (lq >> 4)], lds128(lq + sb + SM_FB + i * 512));
                                    __threadfence();
                                    __syncwarp();
                                    st_relaxed32_p(&g_fbf[a][h], tag, lq);
                                }
                                it = 0;
                                while (__any_sync(0xffffffffu, ld_relaxed32(&g_fbf[a][lq >> 4]) != tag) && ++it < SPIN_LIMIT) {}
                                __threadfence();
                                m = 0;
                                #pragma unroll 1
                                for (int i = 0; i < 12; i++) {
                                    float c0 = 0.f, c1 = 0.f, c2 = 0.f, c3 = 0.f;
                                    #pragma unroll 4
                                    for (int hh = 0; hh < 32; hh++) {
                                        const uint4 u = ld_relaxed128(&g_fb[a][hh][i * 32 + (lq >> 4)]);
                                        c0 += __uint_as_float(u.x); c1 += __uint_as_float(u.y); c2 += __uint_as_float(u.z); c3 += __uint_as_float(u.w);
                                    }
                                    const uint32_t w0 = pack_bf16(c0, c1), w1 = pack_bf16(c2, c3), d = sb + SM_MEM + a * 3072 + i * 256 + (lq >> 2);
                                    sts32(d, w0); sts32(d + 128, w1);
                                    m = maxabs_bf2(m, maxabs_bf2(w0, w1));
                                }
                                res = __reduce_max_sync(0xffffffffu, max(m & 0x7fffu, (m >> 16) & 0x7fffu));
                            }
                            sts32(sb + SM_SG + (par ^ 1) * 16 + a * 4, max(res >> 7, 1u));
                        }
                        bar_sync(BAR_MEM, 352);
                    }
                    if (a == 2) st_relaxed32_p(&g_ts[blockIdx.x], gtime_lo(), l16);
                    load_k(par ^ 1, lds32(stash + 512), ic<K_PRE>(), ic<8>());
                }
                if (a == 0) STAMP(14);
            }
        } else {
            cluster_arrive_rx();
            const uint32_t l16 = pin(lane * 16);
            bf16* dst = g_otok + h * 4096 + (r ? 1024 : 0) + (r == 2 ? 2048 : 0);
            {
                #pragma unroll
                for (int sg = 0; sg < 2; sg++) {
                    bar_sync(BAR_X0 + sg, 288);
                    if (lane == 0) {
                        mbar_expect_tx(bX + 8 * sg, XBUF);
                        #pragma unroll
                        for (int c = 0; c < 9; c++)
                            asm volatile("cp.async.bulk.tensor.2d.shared::cluster.global.mbarrier::complete_tx::bytes [%0], [%1, {%3, %4}], [%2];"
                                :: "r"(sb + SM_X + sg * XBUF + c * 4096), "l"(&tmx), "r"(bX + 8 * sg), "r"(c * 64), "r"(sg * SEG) : "memory");
                    }
                    __syncwarp();
                }
                if (lane == 0) load_w(40, 54);
                __syncwarp();
                cluster_wait();
            }
            uint32_t q[8][4], mt; float e[5][4], st[2];
            __syncwarp();
            #pragma unroll 1
            for (int s = 0; s < NSEG; s++) {
                const int par = s & 1;
                mbar_wait(bTOK + 8 * par, (s >> 1) & 1);
                const uint32_t tok = launder(sb + SM_TOK + par * TOKBUF), exl = l16 + launder(sb + SM_EX + par * EXBUF);
                const int ln = launder(l16) >> 4;
                if (r == 0) tok_part1<0>(tok, ln, q, e, mt, st); else tok_part1<1>(tok, ln, q, e, mt, st);
                STAMP(11);
                if (s + 1 < NSEG) bar_sync(BAR_TP, 288);
                if (s > 0) {
                    if (lane == 0) {
                        asm volatile("cp.async.bulk.wait_group 0;" ::: "memory");
                        st_relaxed32(&g_flag[s - 1][blockIdx.x], epoch);
                    }
                    __syncwarp();
                    if (lane == 0 && blockIdx.x == 0) GT(40, s);
                }
                if (s + 1 < NSEG)
                    asm volatile("{\n.reg .pred p;\nelect.sync _|p, 0xffffffff;\n"
                                 "@p cp.async.bulk.global.shared::cta.bulk_group [%0], [%1], 8192;\n"
                                 "@p cp.async.bulk.commit_group;\n}\n"
                        :: "l"(g_tokx[blockIdx.x]), "r"(sb + SM_TOK + (par ^ 1) * TOKBUF + r * 8192) : "memory");
                mbar_wait(bEX + 8 * par, (s >> 1) & 1);
                auto wait_v = [&] {
                    if (s < NSEG - 1)
                        asm volatile("{\n.reg .pred p;\nelect.sync _|p, 0xffffffff;\n"
                                     "@p cp.async.bulk.wait_group 0;\n"
                                     "@p mbarrier.arrive.expect_tx.shared.b64 _, [%2], 16384;\n"
                                     "@p cp.async.bulk.shared::cluster.global.mbarrier::complete_tx::bytes.multicast::cluster [%0], [%1], 8192, [%2], %3;\n}\n"
                            :: "r"(sb + SM_TOK + (~s & 1) * TOKBUF + r * 8192), "l"(g_tokx[blockIdx.x]), "r"(bTOK + 8 * (~s & 1)), "h"((unsigned short)(7 ^ (1 << r))) : "memory");
                    mbar_wait(bEV + 8 * par, (s >> 1) & 1);
                };
                if (r == 0) tok_part2<0>(tok, exl, sb + SM_OST, 0, launder(l16) >> 4, q, e, mt, st, s < NSEG - 1, wait_v); else tok_part2<1>(tok, exl, sb + SM_OST, r - 1, launder(l16) >> 4, q, e, mt, st, s < NSEG - 1, wait_v);
                STAMP(7);
                if (s < NSEG - 1) { if (T_V) bar_arrive(BAR_V, 384); bar_arrive(BAR_G, 288); }
                fence_async_smem();
                __syncwarp();
                if (lane == 0) {
                    asm volatile("cp.async.bulk.global.shared::cta.bulk_group [%0], [%1], 2048;" :: "l"(dst), "r"(sb + SM_OST) : "memory");
                    if (r == 0) asm volatile("cp.async.bulk.global.shared::cta.bulk_group [%0], [%1], 2048;" :: "l"(dst + 2048), "r"(sb + SM_OST + 2048) : "memory");
                    asm volatile("cp.async.bulk.commit_group;" ::: "memory");
                }
                __syncwarp();
                dst += SEG * NH * DH;
                STAMP(15);
            }
            if (lane == 0) {
                asm volatile("cp.async.bulk.wait_group 0;" ::: "memory");
                st_relaxed32(&g_flag[NSEG - 1][blockIdx.x], epoch);
                if (blockIdx.x == 0) GT(40, NSEG);
            }
            __syncwarp();
        }
        cluster_arrive(); cluster_wait();
    }
}
#define SD_THREADS 384
#define SD_CTAS  36
#define BT_RS    4624
#define SD_BT    0
#define SD_STG   74752
#define SD_EF    (SD_STG + 57344)
#define SD_BC    (SD_STG)
#define KSLOTS   5
#define BC_BYTES 10240
#define BC_LBO   1280
#define SD_KP    (SD_STG + 90112)
#define SD_Q0    205824
#define SD_Q1    (SD_STG + 111616)
#define SD_OST   222720
#define SD_XCH   (SD_Q0 + 8192)
#define SD_BAR   224256
#define SD_TOTAL 224768
#define SD_SPIN  (1 << 22)
#define PART_SLOTS 8
#define SD_GO 0
#define SD_REG 200
#define SD_WAIT 6000
#define SD_P2 150
#define SD_P3 300
#define SD_GAP 0
#define SD_RUSH 44
#define SD_P1 300

__device__ uint4 g_part[SD_CTAS][PART_SLOTS][4][8][32];
__device__ __align__(16) unsigned int g_gate[S_LEN];

struct cplx { float r, i; };
__device__ __forceinline__ cplx cmul(cplx a, cplx b) { cplx c; c.r = fmaf(a.r, b.r, -a.i * b.i); c.i = fmaf(a.r, b.i, a.i * b.r); return c; }
__device__ __forceinline__ cplx cexp_(float xr, float xi) {
    const float m = ex2(xr * 1.4426950408889634f);
    const float k = rintf(xi * 0.15915494309189535f);
    const float r = fmaf(k, 1.7484555314695172e-7f, fmaf(k, -6.2831854820251465f, xi));
    cplx o; o.r = m * __cosf(r); o.i = m * __sinf(r); return o;
}
__device__ __forceinline__ void mma_f16(float (&c)[4], const uint32_t (&a)[4], uint32_t b0, uint32_t b1) {
    asm("mma.sync.aligned.m16n8k16.row.col.f32.f16.f16.f32 {%0,%1,%2,%3}, {%4,%5,%6,%7}, {%8,%9}, {%0,%1,%2,%3};"
        : "+f"(c[0]), "+f"(c[1]), "+f"(c[2]), "+f"(c[3]) : "r"(a[0]), "r"(a[1]), "r"(a[2]), "r"(a[3]), "r"(b0), "r"(b1));
}
__device__ __forceinline__ uint32_t mul_bf2(uint32_t a, uint32_t b) { uint32_t r; asm("mul.rn.bf16x2 %0, %1, %2;" : "=r"(r) : "r"(a), "r"(b)); return r; }
__device__ __forceinline__ void mbar_wait_long(uint32_t a, uint32_t parity) { int it = 0; while (!mbar_try(a, parity) && ++it < SD_SPIN) {} }
__device__ __forceinline__ uint16_t lds16(uint32_t a) { uint16_t v; asm volatile("ld.shared.u16 %0, [%1];" : "=h"(v) : "r"(a) : "memory"); return v; }
__device__ __forceinline__ void wg_wait1() { asm volatile("wgmma.wait_group.sync.aligned 1;" ::: "memory"); }
__device__ __forceinline__ void tma2d(uint32_t dst, const CUtensorMap* tm, uint32_t bar, int c0, int c1) {
    asm volatile("cp.async.bulk.tensor.2d.shared::cluster.global.mbarrier::complete_tx::bytes [%0], [%1, {%3, %4}], [%2];"
        :: "r"(dst), "l"(tm), "r"(bar), "r"(c0), "r"(c1) : "memory");
}
__device__ __forceinline__ void wgmma_conv(float (&d)[32], uint32_t a0, uint32_t a1, uint32_t a2, uint32_t a3, uint64_t desc) {
    asm volatile("{\n.reg .pred p;\nsetp.ne.b32 p, 1, 0;\n"
        "wgmma.mma_async.sync.aligned.m64n64k16.f32.bf16.bf16 {%0,%1,%2,%3,%4,%5,%6,%7,%8,%9,%10,%11,%12,%13,%14,%15,%16,%17,%18,%19,%20,%21,%22,%23,%24,%25,%26,%27,%28,%29,%30,%31}, {%32,%33,%34,%35}, %36, p, 1, 1, 0;\n}\n"
        : "+f"(d[0]), "+f"(d[1]), "+f"(d[2]), "+f"(d[3]), "+f"(d[4]), "+f"(d[5]), "+f"(d[6]), "+f"(d[7]), "+f"(d[8]), "+f"(d[9]), "+f"(d[10]), "+f"(d[11]), "+f"(d[12]), "+f"(d[13]), "+f"(d[14]), "+f"(d[15]), "+f"(d[16]), "+f"(d[17]), "+f"(d[18]), "+f"(d[19]), "+f"(d[20]), "+f"(d[21]), "+f"(d[22]), "+f"(d[23]), "+f"(d[24]), "+f"(d[25]), "+f"(d[26]), "+f"(d[27]), "+f"(d[28]), "+f"(d[29]), "+f"(d[30]), "+f"(d[31])
        : "r"(a0), "r"(a1), "r"(a2), "r"(a3), "l"(desc));
}
__device__ __forceinline__ void wgmma_conv(float (&d)[24], uint32_t a0, uint32_t a1, uint32_t a2, uint32_t a3, uint64_t desc) {
    asm volatile("{\n.reg .pred p;\nsetp.ne.b32 p, 1, 0;\n"
        "wgmma.mma_async.sync.aligned.m64n48k16.f32.bf16.bf16 {%0,%1,%2,%3,%4,%5,%6,%7,%8,%9,%10,%11,%12,%13,%14,%15,%16,%17,%18,%19,%20,%21,%22,%23}, {%24,%25,%26,%27}, %28, p, 1, 1, 0;\n}\n"
        : "+f"(d[0]), "+f"(d[1]), "+f"(d[2]), "+f"(d[3]), "+f"(d[4]), "+f"(d[5]), "+f"(d[6]), "+f"(d[7]), "+f"(d[8]), "+f"(d[9]), "+f"(d[10]), "+f"(d[11]), "+f"(d[12]), "+f"(d[13]), "+f"(d[14]), "+f"(d[15]), "+f"(d[16]), "+f"(d[17]), "+f"(d[18]), "+f"(d[19]), "+f"(d[20]), "+f"(d[21]), "+f"(d[22]), "+f"(d[23])
        : "r"(a0), "r"(a1), "r"(a2), "r"(a3), "l"(desc));
}
__device__ __forceinline__ void wgmma_conv(float (&d)[16], uint32_t a0, uint32_t a1, uint32_t a2, uint32_t a3, uint64_t desc) {
    asm volatile("{\n.reg .pred p;\nsetp.ne.b32 p, 1, 0;\n"
        "wgmma.mma_async.sync.aligned.m64n32k16.f32.bf16.bf16 {%0,%1,%2,%3,%4,%5,%6,%7,%8,%9,%10,%11,%12,%13,%14,%15}, {%16,%17,%18,%19}, %20, p, 1, 1, 0;\n}\n"
        : "+f"(d[0]), "+f"(d[1]), "+f"(d[2]), "+f"(d[3]), "+f"(d[4]), "+f"(d[5]), "+f"(d[6]), "+f"(d[7]), "+f"(d[8]), "+f"(d[9]), "+f"(d[10]), "+f"(d[11]), "+f"(d[12]), "+f"(d[13]), "+f"(d[14]), "+f"(d[15])
        : "r"(a0), "r"(a1), "r"(a2), "r"(a3), "l"(desc));
}
__device__ __forceinline__ void wgmma_conv(float (&d)[8], uint32_t a0, uint32_t a1, uint32_t a2, uint32_t a3, uint64_t desc) {
    asm volatile("{\n.reg .pred p;\nsetp.ne.b32 p, 1, 0;\n"
        "wgmma.mma_async.sync.aligned.m64n16k16.f32.bf16.bf16 {%0,%1,%2,%3,%4,%5,%6,%7}, {%8,%9,%10,%11}, %12, p, 1, 1, 0;\n}\n"
        : "+f"(d[0]), "+f"(d[1]), "+f"(d[2]), "+f"(d[3]), "+f"(d[4]), "+f"(d[5]), "+f"(d[6]), "+f"(d[7])
        : "r"(a0), "r"(a1), "r"(a2), "r"(a3), "l"(desc));
}
template<int NR> __device__ __forceinline__ void conv_mma(float (&acc)[NR], const uint32_t (&R)[16], uint32_t dlo) {
    #pragma unroll
    for (int q = 0; q < 4; q++)
        wgmma_conv(acc, R[4 * q], R[4 * q + 1], R[4 * q + 2], R[4 * q + 3], (uint64_t)(dlo + (2 * (3 - q)) * (BC_LBO >> 4)) | ((uint64_t)8 << 32));
}
__device__ __forceinline__ void conv_ld(uint32_t (&R)[16], uint32_t a) {
    #pragma unroll
    for (int q = 0; q < 4; q++) { const uint2 u = lds64(a + 64 * (2 * q + 1)); R[4 * q] = u.x; R[4 * q + 1] = u.y; }
}
__device__ __forceinline__ void conv_fix(uint32_t (&R)[16], uint32_t& carry) {
    #pragma unroll
    for (int q = 0; q < 4; q++) {
        asm volatile("mov.b32 %0, %1;" : "=r"(R[4 * q + 2]) : "r"(q ? R[4 * q - 3] : carry));
        asm volatile("mov.b32 %0, %1;" : "=r"(R[4 * q + 3]) : "r"(R[4 * q]));
    }
    asm volatile("mov.b32 %0, %1;" : "=r"(carry) : "r"(R[13]));
}
template<int A> __device__ __forceinline__ void conv_group(float (&acc)[32 - 8 * A], uint32_t (&R)[4][16], uint32_t& carry, uint32_t pb, uint32_t dlo) {
    #pragma unroll
    for (int e = 0; e < 8; e += 2) {
        const int dl = 8 * A + e;
        conv_fix(R[dl & 3], carry); conv_fix(R[(dl + 1) & 3], carry);
        wg_fence(); conv_mma(acc, R[dl & 3], dlo + 16 - 2 * e); conv_mma(acc, R[(dl + 1) & 3], dlo + 14 - 2 * e); wg_commit();
        wg_wait1();
        if (dl + 2 < 32) { conv_ld(R[(dl + 2) & 3], pb + (dl + 2) * 512); conv_ld(R[(dl + 3) & 3], pb + (dl + 3) * 512); }
    }
}

__global__ void __launch_bounds__(SD_THREADS, 1)
side_kernel(const __grid_constant__ CUtensorMap tmw, const bf16* __restrict__ x,
            const bf16* __restrict__ log_A_real, const bf16* __restrict__ A_imag, const bf16* __restrict__ C_real, const bf16* __restrict__ C_imag,
            const bf16* __restrict__ log_dt, const bf16* __restrict__ D_skip, const bf16* __restrict__ gate_w, bf16* __restrict__ out) {
    extern __shared__ __align__(1024) unsigned char smem[];
    const uint32_t sb = smem_u32(smem);
    const int tid = threadIdx.x, lane = tid & 31;
    const int warp = __shfl_sync(0xffffffffu, tid >> 5, 0);
    const int g = lane >> 2, t = lane & 3, mi = lane >> 3, r8 = lane & 7;
    const bool sh = blockIdx.x < 32;
    const int d0 = blockIdx.x * 16;
    const uint32_t b0_ = sb + SD_BAR, bKF = b0_ + 384, bKE = bKF + 8 * KSLOTS, bWO = b0_ + 48, bFULL = b0_ + 56, bEMPTY = b0_ + 88, bEPI = b0_ + 120, bPRT = b0_ + 152, bGO = b0_ + 184, bCH = b0_ + 256;
    const unsigned epoch = ld_relaxed32(&g_epoch);
    if (tid == 0) GT(blockIdx.x, 0);
    if (tid == 0) {
        for (int i = 0; i < 2 * KSLOTS; i++) mbar_init(bKF + 8 * i, 128);
        mbar_init(bWO, 1);
        for (int i = 0; i < 16; i++) mbar_init(bCH + 8 * i, 1);
        for (int i = 0; i < 4; i++) { mbar_init(bFULL + 8 * i, 1); mbar_init(bEMPTY + 8 * i, sh ? 256 : 128); mbar_init(bEPI + 8 * i, 4); mbar_init(bPRT + 8 * i, 8); mbar_init(bGO + 8 * i, 1); }
        asm volatile("fence.mbarrier_init.release.cluster;" ::: "memory");
    }
    for (int i = tid; i < KSLOTS * 8 * 16; i += SD_THREADS) sts128(sb + SD_BC + (i >> 4) * BC_LBO + (i & 15) * 16, make_uint4(0, 0, 0, 0));
    if (tid < 128) sts64(sb + ((tid & 64) ? SD_Q1 : SD_Q0) + (tid & 63) * 8, 0u, 0u);
    fence_async_smem();
    __syncthreads();

    if (warp < 8) {
        asm volatile("setmaxnreg.inc.sync.aligned.u32 %0;" :: "n"(SD_REG));
        const int wg = warp >> 2, w = warp & 3, t128 = tid & 127;
        if (SD_WAIT) __nanosleep(SD_WAIT);
        {
            #pragma unroll 1
            for (int i = 0; i < 4; i++) {
                const int tp = tid + 256 * i;
                const bf16* xp = x + (size_t)(2 * tp) * DM + d0;
                const uint4 v0 = __ldg((const uint4*)xp), v1 = __ldg((const uint4*)(xp + 8)), v2 = __ldg((const uint4*)(xp + DM)), v3 = __ldg((const uint4*)(xp + DM + 8));
                const uint32_t a = sb + SD_BT + (tp >> 5) * 144 + (tp & 31) * 4;
                const uint32_t lo[8] = {v0.x, v0.y, v0.z, v0.w, v1.x, v1.y, v1.z, v1.w};
                const uint32_t hi[8] = {v2.x, v2.y, v2.z, v2.w, v3.x, v3.y, v3.z, v3.w};
                #pragma unroll
                for (int j = 0; j < 8; j++) { sts32(a + (2 * j) * BT_RS, __byte_perm(lo[j], hi[j], 0x5410)); sts32(a + (2 * j + 1) * BT_RS, __byte_perm(lo[j], hi[j], 0x7632)); }
                if (SD_GAP) __nanosleep(SD_GAP);
            }
        }
        bar_sync(1, 256);
        if (tid == 0) GT(blockIdx.x, 65);
        const uint32_t pa = sb + (wg ? SD_Q1 : SD_Q0);
        const uint32_t pb = pa + (72 + 16 * w - 56 + g - 2 * t) * 8;
        for (int c = wg; c < 16; c += 2) {
            const uint32_t bt = sb + SD_BT + c * BT_RS;
            bar_sync(2 + wg, 128);
            #pragma unroll
            for (int it = 0; it < 9; it++) {
                const int k = it < 8 ? t128 + 128 * it : t128 - 4;
                if (it < 8 || t128 < 4) {
                    auto word = [&](int j) { return j >= 0 ? lds32(bt + (j >> 5) * 144 + (j & 31) * 4) : 0u; };
                    const uint32_t c0 = word(k), p0 = word(k - 1), c1 = word(k + 4), p1 = word(k + 3);
                    sts128(pa + (72 + 2 * k) * 8, make_uint4(__byte_perm(c0, p0, 0x7610), __byte_perm(c1, p1, 0x7610), __byte_perm(c0, c0, 0x1032), __byte_perm(c1, c1, 0x1032)));
                }
            }
            bar_sync(2 + wg, 128);
            const int slot = c % KSLOTS;
            float acc[32];
            #pragma unroll
            for (int i = 0; i < 32; i++) acc[i] = 0.f;
            uint32_t R[4][16];
            uint32_t carry = lds32(pb);
            conv_ld(R[0], pb); conv_ld(R[1], pb + 512);
            const uint32_t dlo = (((sb + SD_BC + slot * BC_BYTES) & 0x3FFFF) >> 4) | ((BC_LBO >> 4) << 16);
            mbar_wait_long(bKF + 8 * slot, (c / KSLOTS) & 1);
            const float ds = bf(D_skip[d0 + c]);
            auto fin = [&](const float* a8, int q0) {
                #pragma unroll
                for (int q = 0; q < 2; q++)
                    #pragma unroll
                    for (int hh = 0; hh < 2; hh++) {
                        const uint32_t a = bt + (4 * (q0 + q) + t) * 144 + (16 * w + g + 8 * hh) * 2;
                        const float u = __uint_as_float((uint32_t)lds16(a) << 16);
                        const float y = rbf(a8[4 * q + 2 * hh] + a8[4 * q + 2 * hh + 1]);
                        sts16(a, (uint16_t)(pack_bf16(y + rbf(u * ds), 0.f) & 0xffff));
                    }
            };
            float a1[24], a2[16], a3[8];
            conv_group<0>(acc, R, carry, pb, dlo);
            wg_wait0();
            #pragma unroll
            for (int i = 0; i < 24; i++) asm volatile("mov.b32 %0, %1;" : "=f"(a1[i]) : "f"(acc[8 + i]));
            fin(acc, 0);
            conv_group<1>(a1, R, carry, pb, dlo);
            wg_wait0();
            #pragma unroll
            for (int i = 0; i < 16; i++) asm volatile("mov.b32 %0, %1;" : "=f"(a2[i]) : "f"(a1[8 + i]));
            fin(a1, 2);
            conv_group<2>(a2, R, carry, pb, dlo);
            wg_wait0();
            #pragma unroll
            for (int i = 0; i < 8; i++) asm volatile("mov.b32 %0, %1;" : "=f"(a3[i]) : "f"(a2[8 + i]));
            fin(a2, 4);
            conv_group<3>(a3, R, carry, pb, dlo);
            wg_wait0();
            mbar_arrive(bKE + 8 * slot);
            fin(a3, 6);
        }
        fence_async_smem();
        __syncthreads();
        const uint32_t stg = sb + SD_STG + wg * 65536;
        uint32_t wf[32][4];
        if (tid == 0) GT(blockIdx.x, 66);
        mbar_wait_long(bWO, 0);
        #pragma unroll
        for (int i = 0; i < 32; i++)
            ldsm_x4_t(wf[i], stg + (i * 16 + (mi >> 1) * 8 + r8) * 128 + (((2 * w + (mi & 1)) ^ r8) << 4));
        mbar_arrive(bEMPTY + 16 * wg); mbar_arrive(bEMPTY + 16 * wg + 8);
        if (sh) { mbar_arrive(bEMPTY + 16 * (wg ^ 1)); mbar_arrive(bEMPTY + 16 * (wg ^ 1) + 8); }
        uint4* dst = sh ? &g_part[(blockIdx.x & ~7) + 4 * wg + w][0][0][blockIdx.x & 7][lane] : &g_part[32 + w][0][0][2 * (blockIdx.x - 32) + wg][lane];
        const uint32_t dl0 = (((sb + SD_STG) & 0x3FFFF) >> 4) | 0x10000u;
        for (int s = 0; s < NSEG; s++) {
            const int bi = sh ? s & 3 : 2 * wg + (s & 1), bp = (sh ? s >> 2 : s >> 1) & 1;
            const uint32_t xd = dl0 + bi * 2048;
            float acc[16];
            #pragma unroll
            for (int i = 0; i < 32; i++) {
                if ((i & 7) == 0) { mbar_wait_long(bCH + 32 * bi + i, bp); wg_fence(); }
                if (i == 0) wgmma_n32<0>(acc, wf[i], desc_from(xd));
                else wgmma_n32<1>(acc, wf[i], desc_from(xd + (i >> 2) * 256 + (i & 3) * 2));
            }
            wg_commit();
            if (s >= PART_SLOTS / 2) mbar_wait_long(bEPI + 8 * (s & 3), ((s - 4) >> 2) & 1);
            wg_wait0();
            mbar_arrive(bEMPTY + 8 * bi);
            const uint32_t ph = ((s / PART_SLOTS) & 1) ^ 1;
            uint4* p = dst + (s % PART_SLOTS) * (4 * 8 * 32);
            if (SD_GO && s + 1 < NSEG) mbar_wait_long(bGO + 8 * (s & 3), (s >> 2) & 1);
            #pragma unroll
            for (int j = 0; j < 4; j++) {
                uint4 v;
                v.x = (__float_as_uint(acc[4 * j]) & ~1u) | ph; v.y = (__float_as_uint(acc[4 * j + 1]) & ~1u) | ph;
                v.z = (__float_as_uint(acc[4 * j + 2]) & ~1u) | ph; v.w = (__float_as_uint(acc[4 * j + 3]) & ~1u) | ph;
                st_relaxed128(p + 256 * j, v);
            }
            if (tid == 0 && s == NSEG - 1) GT(blockIdx.x, 71);
            __syncwarp();
            if (lane == 0) mbar_arrive(bPRT + 8 * (s & 3));
        }
    } else {
        asm volatile("setmaxnreg.dec.sync.aligned.u32 %0;" :: "n"(504 - 2 * SD_REG));
        const int w = warp - 8, n = tid - 256;
        bf16 p_la = log_A_real[d0 * NS + n], p_ai = A_imag[d0 * NS + n], p_cr = C_real[d0 * NS + n], p_ci = C_imag[d0 * NS + n], p_dt = log_dt[d0];
        const uint32_t ef = sb + SD_EF + w * 8192;
        const uint32_t efl = ef + lane * 4;
        uint32_t goff[8];
        #pragma unroll
        for (int i = 0; i < 16; i++) {
            const int l = 64 * lane + 8 * (w + 4 * (i >> 3)) + (i & 7);
            const int p = (int)rbf((float)l);
            const int a = p >> 7, b = (p >> 3) & 15, c = p & 7;
            const int row = p < 256 ? 8 * a + c : (p < 512 ? 16 + 4 * (a - 2) + (c >> 1) : (p < 1024 ? 24 + 2 * (a - 4) + (c >> 2) : 24 + a));
            const uint32_t off = row * 72 + b * 4;
            if (i & 1) goff[i >> 1] |= off << 16; else goff[i >> 1] = off;
        }
        for (int c = 0; c < 16; c++) {
            const float dt = rbf(expf(bf(p_dt)));
            const float xr = -rbf(expf(bf(p_la))) * dt, xi = bf(p_ai) * dt;
            cplx C; C.r = 2.f * bf(p_cr) * dt; C.i = 2.f * bf(p_ci) * dt;
            if (c + 1 < 16) {
                const int o = (d0 + c + 1) * NS + n;
                p_la = log_A_real[o]; p_ai = A_imag[o]; p_cr = C_real[o]; p_ci = C_imag[o]; p_dt = log_dt[d0 + c + 1];
            }
            const uint32_t mexp = min(max(__reduce_max_sync(0xffffffffu, __float_as_uint(fmaxf(fabsf(C.r), fabsf(C.i)))) & 0x7f800000u, 0x01000000u), 0x7e000000u);
            const float unsc = __uint_as_float(mexp), sc = __uint_as_float(0x7f000000u - mexp);
            C.r *= sc; C.i *= sc;
            #define EADDR(r) ((efl ^ (((r) & 7) << 4)) + (r) * 128)
            {
                cplx f[16];
                f[1] = cexp_(8.f * xr, -8.f * xi);
                f[2] = cmul(f[1], f[1]); f[3] = cmul(f[2], f[1]); f[4] = cmul(f[2], f[2]); f[5] = cmul(f[4], f[1]); f[6] = cmul(f[4], f[2]); f[7] = cmul(f[4], f[3]);
                f[8] = cmul(f[4], f[4]);
                #pragma unroll
                for (int b = 9; b < 16; b++) f[b] = cmul(f[8], f[b - 8]);
                sts32(EADDR(0) + 6144, 0x00003c00u);
                #pragma unroll
                for (int b = 1; b < 16; b++) sts32(EADDR(b) + 6144, pack_f16(f[b].r, f[b].i));
            }
            {
                cplx G[17], wc[8];
                G[1] = cexp_(128.f * xr, 128.f * xi);
                wc[1] = cexp_(xr, xi);
                G[2] = cmul(G[1], G[1]); G[4] = cmul(G[2], G[2]); G[8] = cmul(G[4], G[4]);
                wc[2] = cmul(wc[1], wc[1]); wc[3] = cmul(wc[2], wc[1]); wc[4] = cmul(wc[2], wc[2]); wc[5] = cmul(wc[4], wc[1]); wc[6] = cmul(wc[4], wc[2]); wc[7] = cmul(wc[4], wc[3]);
                cplx CG[17];
                CG[0] = C; CG[1] = cmul(C, G[1]); CG[2] = cmul(C, G[2]); CG[3] = cmul(CG[1], G[2]);
                #pragma unroll
                for (int a = 0; a < 4; a++) CG[4 + a] = cmul(CG[a], G[4]);
                #pragma unroll
                for (int a = 0; a < 9; a++) CG[8 + a] = cmul(CG[a], G[8]);
                #pragma unroll
                for (int r = 0; r < 41; r++) {
                    const int a = r < 16 ? (r >> 3) : (r < 24 ? 2 + ((r >> 2) & 1) : (r < 32 ? 4 + ((r >> 1) & 3) : r - 24));
                    const int cc = r < 16 ? (r & 7) : (r < 24 ? 2 * (r & 3) : (r < 32 ? 4 * (r & 1) : 0));
                    const cplx e = cc ? cmul(CG[a], wc[cc]) : CG[a];
                    sts32(EADDR(r), pack_f16(e.r, e.i));
                }
            }
            __syncwarp();
            float acc[3][2][4];
            #pragma unroll
            for (int i = 0; i < 3; i++)
                #pragma unroll
                for (int j = 0; j < 2; j++) { acc[i][j][0] = acc[i][j][1] = acc[i][j][2] = acc[i][j][3] = 0.f; }
            #pragma unroll
            for (int ks = 0; ks < 4; ks++) {
                uint32_t bq[4];
                ldsm_x4(bq, ef + 6144 + ((mi >> 1) * 8 + r8) * 128 + (((2 * ks + (mi & 1)) ^ r8) << 4));
                #pragma unroll
                for (int mt = 0; mt < 3; mt++) {
                    uint32_t aq[4];
                    ldsm_x4(aq, ef + (16 * mt + (mi & 1) * 8 + r8) * 128 + (((2 * ks + (mi >> 1)) ^ r8) << 4));
                    mma_f16(acc[mt][0], aq, bq[0], bq[1]);
                    mma_f16(acc[mt][1], aq, bq[2], bq[3]);
                }
            }
            const uint32_t kp = sb + SD_KP;
            #pragma unroll
            for (int mt = 0; mt < 3; mt++)
                #pragma unroll
                for (int nt = 0; nt < 2; nt++) {
                    const uint32_t a = kp + w * 3072 + (16 * mt + g) * 64 + nt * 32 + t * 8;
                    sts64(a, __float_as_uint(acc[mt][nt][0] * unsc), __float_as_uint(acc[mt][nt][1] * unsc));
                    sts64(a + 512, __float_as_uint(acc[mt][nt][2] * unsc), __float_as_uint(acc[mt][nt][3] * unsc));
                }
            bar_sync(4, 128);
            #pragma unroll
            for (int i = 0; i < 3; i++) {
                const uint32_t a = kp + (n + 128 * i) * 8;
                const uint2 v0 = lds64(a), v1 = lds64(a + 3072), v2 = lds64(a + 6144), v3 = lds64(a + 9216);
                sts64(a + 12288 + ((n >> 3) + 16 * i) * 8, __float_as_uint((__uint_as_float(v0.x) + __uint_as_float(v1.x)) + (__uint_as_float(v2.x) + __uint_as_float(v3.x))),
                                 __float_as_uint((__uint_as_float(v0.y) + __uint_as_float(v1.y)) + (__uint_as_float(v2.y) + __uint_as_float(v3.y))));
            }
            bar_sync(4, 128);
            const int slot = c % KSLOTS;
            float kv[16];
            #pragma unroll
            for (int e = 0; e < 8; e++) { kv[2 * e] = __uint_as_float(lds32(kp + 12288 + (goff[e] & 0xffff))); kv[2 * e + 1] = __uint_as_float(lds32(kp + 12288 + (goff[e] >> 16))); }
            if (c >= KSLOTS) mbar_wait_long(bKE + 8 * slot, (c / KSLOTS - 1) & 1);
            #pragma unroll
            for (int it = 0; it < 2; it++) {
                uint32_t hi[4], lo[4];
                #pragma unroll
                for (int e = 0; e < 4; e++) {
                    const float k0 = kv[8 * it + 2 * e], k1 = kv[8 * it + 2 * e + 1];
                    hi[e] = pack_bf16(k0, k1);
                    lo[e] = pack_bf16(k0 - bf_lo(hi[e]), k1 - bf_hi(hi[e]));
                }
                const uint32_t a = sb + SD_BC + slot * BC_BYTES + (w + 4 * it) * BC_LBO + (16 + 2 * lane) * 16;
                sts128(a, make_uint4(hi[0], hi[1], hi[2], hi[3]));
                sts128(a + 16, make_uint4(lo[0], lo[1], lo[2], lo[3]));
            }
            fence_async_smem();
            mbar_arrive(bKF + 8 * slot);
        }
        {
            uint32_t gw[9];
            #pragma unroll
            for (int j = 0; j < 9; j++) gw[j] = __ldg((const uint32_t*)gate_w + lane + 32 * j);
            float z = 0.f;
            #pragma unroll 1
            for (int i0 = 0; i0 < 15; i0 += 5) {
                uint32_t xv[5][9];
                #pragma unroll
                for (int i = 0; i < 5; i++) {
                    const int tk = min(blockIdx.x * 57 + w + 4 * (i0 + i), S_LEN - 1);
                    #pragma unroll
                    for (int j = 0; j < 9; j++) xv[i][j] = __ldg((const uint32_t*)(x + (size_t)tk * DM) + lane + 32 * j);
                }
                #pragma unroll
                for (int i = 0; i < 5; i++) {
                    float acc = 0.f;
                    #pragma unroll
                    for (int j = 0; j < 9; j++) { const uint32_t m = mul_bf2(xv[i][j], gw[j]); acc += bf_lo(m) + bf_hi(m); }
                    #pragma unroll
                    for (int o = 16; o; o >>= 1) acc += __shfl_xor_sync(0xffffffffu, acc, o);
                    if (lane == i0 + i) z = rbf(acc);
                }
            }
            const int li = w + 4 * lane, tk = blockIdx.x * 57 + li;
            if (li < 57 && tk < S_LEN) st_relaxed32(&g_gate[tk], pack_bf16(1.f / (1.f + expf(-z)), 0.f) | (epoch << 16));
        }
        if (tid == 256) GT(blockIdx.x, 67);
        fence_async_smem();
        __syncthreads();
            const uint32_t ost = sb + SD_OST + w * 256;
            auto unit = [&](int u) {
                const int s = u >> 2;
                const int t0 = 8 * u + 2 * t;
                const uint2 gt = lds64(sb + SD_Q0 + t0 * 4);
                const uint32_t ba = sb + SD_BT + g * BT_RS + (t0 >> 6) * 144 + (t0 & 63) * 2;
                const uint32_t b0 = lds32(ba), b1 = lds32(ba + 8 * BT_RS);
                const float g0 = bf_lo(gt.x), g1 = bf_lo(gt.y), m0 = rbf(1.f - g0), m1 = rbf(1.f - g1);
                const float mb0 = rbf(m0 * bf_lo(b0)), mb1 = rbf(m1 * bf_hi(b0)), mb2 = rbf(m0 * bf_lo(b1)), mb3 = rbf(m1 * bf_hi(b1));
                const uint32_t phm = ((s / PART_SLOTS) & 1) - 1;
                const uint4* p = &g_part[blockIdx.x][s % PART_SLOTS][u & 3][0][lane];
                bf16* o = out + (size_t)(8 * u + (lane >> 1)) * DM + d0 + 8 * (lane & 1);
                uint4 v[8]; int it = 0;
                uint32_t early;
                asm volatile("{\n.reg .pred p;\nmbarrier.test_wait.parity.shared::cta.b64 p, [%1], %2;\nselp.u32 %0, 1, 0, p;\n}\n" : "=r"(early) : "r"(bPRT + 8 * (s & 3)), "r"((s >> 2) & 1) : "memory");
                if (!early) mbar_wait_long(bPRT + 8 * (s & 3), (s >> 2) & 1);
                delay_clk(s < NSEG - 2 ? (early ? (s < SD_RUSH ? SD_P3 : 0) : SD_P1) : SD_P2);
                #pragma unroll
                for (int i = 0; i < 8; i++) v[i] = ld_relaxed128(p + 32 * i);
                while (true) {
                    uint32_t miss[8], any = 0;
                    #pragma unroll
                    for (int i = 0; i < 8; i++) { miss[i] = ((v[i].x ^ phm) | (v[i].y ^ phm) | (v[i].z ^ phm) | (v[i].w ^ phm)) & 1u; any |= miss[i]; }
                    if (!__any_sync(0xffffffffu, any) || ++it >= SD_SPIN) break;
                    if (it > 1 && s < NSEG - 2) __nanosleep(200);
                    #pragma unroll
                    for (int i = 0; i < 8; i++) ld_relaxed128_p(v[i], p + 32 * i, miss[i]);
                }
                if (lane == 0) mbar_arrive(bEPI + 8 * (s & 3));
                float a0 = 0.f, a1 = 0.f, a2 = 0.f, a3 = 0.f;
                #pragma unroll
                for (int i = 0; i < 8; i++) { a0 += __uint_as_float(v[i].x); a1 += __uint_as_float(v[i].y); a2 += __uint_as_float(v[i].z); a3 += __uint_as_float(v[i].w); }
                const uint32_t r0 = pack_bf16(rbf(g0 * rbf(a0)) + mb0, rbf(g1 * rbf(a1)) + mb1), r1 = pack_bf16(rbf(g0 * rbf(a2)) + mb2, rbf(g1 * rbf(a3)) + mb3);
                asm volatile("stmatrix.sync.aligned.m8n8.x2.trans.shared.b16 [%0], {%1,%2};" :: "r"(ost + r8 * 32 + (mi & 1) * 16), "r"(r0), "r"(r1) : "memory");
                __syncwarp();
                if (lane < 16) *(uint4*)o = lds128(ost + lane * 16);
                __syncwarp();
                if (lane == 0 && (u & 3) == 3) GT(blockIdx.x, 1 + s);
            };
        if (w == 0) {
            if (lane == 0) {
                mbar_expect_tx(bWO, 131072);
                #pragma unroll
                for (int q = 0; q < 4; q++) tma2d(sb + SD_STG + q * 32768, &tmw, bWO, sh ? 128 * (blockIdx.x >> 3) + 64 * (q >> 1) : 512, sh ? 512 * (blockIdx.x & 7) + 256 * (q & 1) : 1024 * (blockIdx.x - 32) + 256 * q);
            }
            bar_sync(5, 128);
            const int ke0 = sh ? blockIdx.x & 7 : 2 * (blockIdx.x - 32);
            for (int s = 0; s < NSEG; s++) {
                {
                    const unsigned int* f = &g_flag[s][12 * ke0 + (lane < (sh ? 12 : 24) ? lane : 0)];
                    int it = 0;
                    while (true) {
                        uint32_t v;
                        asm volatile("ld.acquire.gpu.global.u32 %0, [%1];" : "=r"(v) : "l"(f) : "memory");
                        if (__all_sync(0xffffffffu, v == epoch) || ++it >= SD_SPIN) break;
                        if (s < NSEG - 1) __nanosleep(64);
                    }
                    asm volatile("fence.proxy.async.global;" ::: "memory");
                    if (lane == 0 && s == NSEG - 1) GT(blockIdx.x, 70);
                    if (lane == 0 && s == 2 && blockIdx.x == 0) st_relaxed32(&g_epoch, epoch + 1);
                }
                if (lane == 0) {
                    if (SD_GO && s > 0) mbar_arrive(bGO + 8 * ((s - 1) & 3));
                    const int b0 = sh ? s & 3 : s & 1, bp = (sh ? s >> 2 : s >> 1) & 1;
                    mbar_wait_long(bEMPTY + 8 * b0, bp);
                    if (!sh) mbar_wait_long(bEMPTY + 16 + 8 * b0, bp);
                    #pragma unroll 1
                    for (int c = 0; c < (sh ? 4 : 8); c++) {
                        const int wg = sh ? 0 : c & 1, hc = sh ? c : c >> 1;
                        const uint32_t bar = bCH + 32 * (b0 + 2 * wg) + 8 * hc;
                        mbar_expect_tx(bar, 8192);
                        asm volatile("cp.async.bulk.shared::cluster.global.mbarrier::complete_tx::bytes [%0], [%1], 8192, [%2];"
                            :: "r"(sb + SD_STG + (b0 + 2 * wg) * 32768 + hc * 8192), "l"(g_otok + (size_t)s * (SEG * NH * DH) + (ke0 + wg) * 16384 + hc * 4096), "r"(bar) : "memory");
                    }
                }
                __syncwarp();
            }
        } else {
            if (w == 3) {
                for (int i = 0; i < 16; i += 8) {
                    uint4 v[8]; uint32_t miss = 0xffu; int it = 0;
                    const uint32_t tag = epoch & 0xffffu;
                    #pragma unroll
                    for (int j = 0; j < 8; j++) v[j] = make_uint4(0, 0, 0, 0);
                    do {
                        #pragma unroll
                        for (int j = 0; j < 8; j++) ld_relaxed128_p(v[j], (const uint4*)g_gate + (i + j) * 32 + lane, miss & (1u << j));
                        miss = 0;
                        #pragma unroll
                        for (int j = 0; j < 8; j++) miss |= (uint32_t)((v[j].x >> 16) != tag || (v[j].y >> 16) != tag || (v[j].z >> 16) != tag || (v[j].w >> 16) != tag) << j;
                    } while (__any_sync(0xffffffffu, miss) && ++it < SD_SPIN);
                    #pragma unroll
                    for (int j = 0; j < 8; j++) sts128(sb + SD_Q0 + ((i + j) * 32 + lane) * 16, v[j]);
                }
            }
            bar_sync(5, 128);
            for (int u = w - 1; u < 4 * (NSEG - 1); u += 3) unit(u);
        }
        unit(4 * (NSEG - 1) + w);
    }
    if (tid == 256) GT(blockIdx.x, 72);
}

extern "C" void kernel_launch(void* const* d_in, const int* in_sizes, int n_in, void* d_out, int out_size) {
    const bf16* x = (const bf16*)d_in[0];
    const bf16* mem0 = (const bf16*)d_in[1];
    const bf16* Wq = (const bf16*)d_in[2];
    const bf16* Wk = (const bf16*)d_in[3];
    const bf16* Wv = (const bf16*)d_in[4];
    const bf16* Wo = (const bf16*)d_in[5];
    const bf16* log_A_real = (const bf16*)d_in[8];
    const bf16* A_imag = (const bf16*)d_in[9];
    const bf16* C_real = (const bf16*)d_in[10];
    const bf16* C_imag = (const bf16*)d_in[11];
    const bf16* log_dt = (const bf16*)d_in[12];
    const bf16* D_skip = (const bf16*)d_in[13];
    const bf16* gate_w = (const bf16*)d_in[14];
    bf16* out = (bf16*)d_out;
    typedef CUresult (*EncFn)(CUtensorMap*, CUtensorMapDataType, cuuint32_t, void*, const cuuint64_t*, const cuuint64_t*, const cuuint32_t*, const cuuint32_t*,
                              CUtensorMapInterleave, CUtensorMapSwizzle, CUtensorMapL2promotion, CUtensorMapFloatOOBfill);
    static EncFn enc = nullptr;
    if (!enc) { void* fn = nullptr; cudaDriverEntryPointQueryResult qr; cudaGetDriverEntryPoint("cuTensorMapEncodeTiled", &fn, cudaEnableDefault, &qr); enc = (EncFn)fn; }
    auto mk = [&](CUtensorMap* tm, const void* ptr, uint64_t cols, uint64_t rows, uint32_t bc, uint32_t br) {
        cuuint64_t gdim[2] = {cols, rows}; cuuint64_t gstr[1] = {cols * 2}; cuuint32_t box[2] = {bc, br}; cuuint32_t estr[2] = {1, 1};
        enc(tm, CU_TENSOR_MAP_DATA_TYPE_BFLOAT16, 2, (void*)ptr, gdim, gstr, box, estr, CU_TENSOR_MAP_INTERLEAVE_NONE, bc == 64 ? CU_TENSOR_MAP_SWIZZLE_128B : CU_TENSOR_MAP_SWIZZLE_64B,
            CU_TENSOR_MAP_L2_PROMOTION_L2_256B, CU_TENSOR_MAP_FLOAT_OOB_FILL_NONE);
    };
    static bool attr_done = false;
    if (!attr_done) {
        cudaFuncSetAttribute(chain_kernel, cudaFuncAttributeMaxDynamicSharedMemorySize, SM_TOTAL);
        cudaFuncSetAttribute(side_kernel, cudaFuncAttributeMaxDynamicSharedMemorySize, SD_TOTAL);
        attr_done = true;
    }
    CUtensorMap tmx, tmw, tmq, tmk, tmv, tmo;
    mk(&tmx, x, DM, S_LEN, 64, SEG);
    mk(&tmw, Wo, DM, NH * DH, 64, 256);
    mk(&tmo, Wo, DM, NH * DH, 32, 128);
    mk(&tmq, Wq, NH * DH, DM, 32, 48); mk(&tmk, Wk, NH * DH, DM, 32, 48); mk(&tmv, Wv, NH * DH, DM, 32, 48);
    chain_kernel<<<96, CH_THREADS, SM_TOTAL>>>(tmx, tmq, tmk, tmv, tmo, mem0, 0u);
    cudaLaunchConfig_t cfg = {};
    cfg.gridDim = dim3(SD_CTAS); cfg.blockDim = dim3(SD_THREADS); cfg.dynamicSmemBytes = SD_TOTAL; cfg.stream = cudaStreamPerThread;
    cudaLaunchAttribute at[1];
    at[0].id = cudaLaunchAttributeProgrammaticStreamSerialization; at[0].val.programmaticStreamSerializationAllowed = 1;
    cfg.attrs = at; cfg.numAttrs = 1;
    cudaLaunchKernelEx(&cfg, side_kernel, tmw, x, log_A_real, A_imag, C_real, C_imag, log_dt, D_skip, gate_w, out);
}
```

```cpp
#include <cuda_runtime.h>
#include <cuda.h>
#include <cuda_bf16.h>
#include <stdint.h>

#define S_LEN 2048
#define DM 576
#define NH 32
#define DH 128
#define NMEM 8
#define SEG 32
#define NSEG 64
#define LQ 40
#define NS 128

typedef __nv_bfloat16 bf16;

__device__ __forceinline__ float bf(bf16 v) { return __bfloat162float(v); }
__device__ __forceinline__ bf16 tobf(float v) { return __float2bfloat16_rn(v); }
__device__ __forceinline__ float rbf(float v) { return __bfloat162float(__float2bfloat16_rn(v)); }

#define CH_THREADS 384
#define SPIN_LIMIT (1 << 17)
#define SM_X     0
#define XBUF     36864
#define SM_TOK   73728
#define TOKBUF   24576
#define SM_FB    131072
#define SM_STASH 139264
#define SM_TS    (SM_STASH + 3072)
#define SM_WO    147456
#define SM_MEM   196608
#define SM_EX    205824
#define EXBUF    6144
#define SM_P     218112
#define SM_FLAG  (SM_P + 640)
#define SM_OST   219136
#define SM_O     223232
#define SM_BAR   228352
#define SM_IL    (SM_BAR + 128)
#define SM_SG    (SM_IL + 256)
#define SM_TOTAL (SM_SG + 64)

#define ACC_X    36864
#define ACC_FULL 0x0020u
#define SLOT_OFF(sl) ((((sl) & 1) << 7) | (((sl) & 2) << 8))
__device__ __align__(65536) unsigned char g_acc[65536];
__device__ __align__(1024) uint4 g_fb[3][32][384];
__device__ unsigned int g_fbf[3][32];
__device__ unsigned int g_init[96];
__device__ unsigned int g_epoch = 1;
__device__ __align__(128) unsigned int g_ts[128];
__device__ __align__(1024) bf16 g_otok[S_LEN * NH * DH];
__device__ __align__(1024) unsigned char g_tokx[96][8192];
__device__ unsigned int g_flag[NSEG][96];
#define STAMP(i)
#define STAMPV(i, v)
#define GT(b, i)
#define STAMPB(i)

__device__ __forceinline__ uint32_t smem_u32(const void* p) { return (uint32_t)__cvta_generic_to_shared(p); }
__device__ __forceinline__ void ldsm_x4(uint32_t (&r)[4], uint32_t addr) {
    asm volatile("ldmatrix.sync.aligned.m8n8.x4.shared.b16 {%0,%1,%2,%3}, [%4];" : "=r"(r[0]), "=r"(r[1]), "=r"(r[2]), "=r"(r[3]) : "r"(addr) : "memory");
}
__device__ __forceinline__ void ldsm_x4_p(uint32_t (&r)[4], uint32_t addr, uint32_t skip) {
    asm volatile("{\n.reg .pred p;\nsetp.eq.u32 p, %5, 0;\n@p ldmatrix.sync.aligned.m8n8.x4.shared.b16 {%0,%1,%2,%3}, [%4];\n}\n" : "+r"(r[0]), "+r"(r[1]), "+r"(r[2]), "+r"(r[3]) : "r"(addr), "r"(skip) : "memory");
}
__device__ __forceinline__ void ldsm_x4_t(uint32_t (&r)[4], uint32_t addr) {
    asm volatile("ldmatrix.sync.aligned.m8n8.x4.trans.shared.b16 {%0,%1,%2,%3}, [%4];" : "=r"(r[0]), "=r"(r[1]), "=r"(r[2]), "=r"(r[3]) : "r"(addr) : "memory");
}
__device__ __forceinline__ uint32_t ldsm_x1_t(uint32_t addr) {
    uint32_t r; asm volatile("ldmatrix.sync.aligned.m8n8.x1.trans.shared.b16 {%0}, [%1];" : "=r"(r) : "r"(addr) : "memory"); return r;
}
__device__ __forceinline__ void ldsm_x2_t(uint32_t& r0, uint32_t& r1, uint32_t addr) {
    asm volatile("ldmatrix.sync.aligned.m8n8.x2.trans.shared.b16 {%0,%1}, [%2];" : "=r"(r0), "=r"(r1) : "r"(addr) : "memory");
}
__device__ __forceinline__ void stsm_x4(uint32_t addr, uint32_t r0, uint32_t r1, uint32_t r2, uint32_t r3) {
    asm volatile("stmatrix.sync.aligned.m8n8.x4.shared.b16 [%0], {%1,%2,%3,%4};" :: "r"(addr), "r"(r0), "r"(r1), "r"(r2), "r"(r3) : "memory");
}
__device__ __forceinline__ void stsm_x4_t(uint32_t addr, uint32_t r0, uint32_t r1, uint32_t r2, uint32_t r3) {
    asm volatile("stmatrix.sync.aligned.m8n8.x4.trans.shared.b16 [%0], {%1,%2,%3,%4};" :: "r"(addr), "r"(r0), "r"(r1), "r"(r2), "r"(r3) : "memory");
}
__device__ __forceinline__ void mma16816(float (&c)[4], const uint32_t (&a)[4], uint32_t b0, uint32_t b1) {
    asm("mma.sync.aligned.m16n8k16.row.col.f32.bf16.bf16.f32 {%0,%1,%2,%3}, {%4,%5,%6,%7}, {%8,%9}, {%0,%1,%2,%3};"
        : "+f"(c[0]), "+f"(c[1]), "+f"(c[2]), "+f"(c[3]) : "r"(a[0]), "r"(a[1]), "r"(a[2]), "r"(a[3]), "r"(b0), "r"(b1));
}
__device__ __forceinline__ void mma16816r(float (&c)[4], uint32_t a0, uint32_t a1, uint32_t a2, uint32_t a3, uint32_t b0, uint32_t b1) {
    asm("mma.sync.aligned.m16n8k16.row.col.f32.bf16.bf16.f32 {%0,%1,%2,%3}, {%4,%5,%6,%7}, {%8,%9}, {%0,%1,%2,%3};"
        : "+f"(c[0]), "+f"(c[1]), "+f"(c[2]), "+f"(c[3]) : "r"(a0), "r"(a1), "r"(a2), "r"(a3), "r"(b0), "r"(b1));
}
__device__ __forceinline__ void mma1688(float (&c)[4], uint32_t a0, uint32_t a1, uint32_t b0) {
    asm("mma.sync.aligned.m16n8k8.row.col.f32.bf16.bf16.f32 {%0,%1,%2,%3}, {%4,%5}, {%6}, {%0,%1,%2,%3};"
        : "+f"(c[0]), "+f"(c[1]), "+f"(c[2]), "+f"(c[3]) : "r"(a0), "r"(a1), "r"(b0));
}
__device__ __forceinline__ uint32_t pack_bf16(float lo, float hi) {
    uint32_t r; asm("cvt.rn.bf16x2.f32 %0, %1, %2;" : "=r"(r) : "f"(hi), "f"(lo)); return r;
}
__device__ __forceinline__ float bf_lo(uint32_t v) { return __uint_as_float(v << 16); }
__device__ __forceinline__ float bf_hi(uint32_t v) { return __uint_as_float(v & 0xffff0000u); }
__device__ __forceinline__ uint32_t max_bf2(uint32_t a, uint32_t b) { uint32_t r; asm("max.bf16x2 %0, %1, %2;" : "=r"(r) : "r"(a), "r"(b)); return r; }
__device__ __forceinline__ uint32_t maxabs_bf2(uint32_t a, uint32_t b) { uint32_t r; asm("max.NaN.xorsign.abs.bf16x2 %0, %1, %2;" : "=r"(r) : "r"(a), "r"(b)); return r; }
__device__ __forceinline__ float ex2(float x) { float r; asm("ex2.approx.ftz.f32 %0, %1;" : "=f"(r) : "f"(x)); return r; }
__device__ __forceinline__ void ld_relaxed128_p(uint4& v, const uint4* p, uint32_t pred) {
    asm volatile("{\n.reg .pred p;\nsetp.ne.u32 p, %5, 0;\n@p ld.relaxed.gpu.global.v4.u32 {%0,%1,%2,%3}, [%4];\n}\n" : "+r"(v.x), "+r"(v.y), "+r"(v.z), "+r"(v.w) : "l"(p), "r"(pred) : "memory");
}
__device__ __forceinline__ uint4 ld_relaxed128(const uint4* p) { uint4 v; asm volatile("ld.relaxed.gpu.global.v4.u32 {%0,%1,%2,%3}, [%4];" : "=r"(v.x), "=r"(v.y), "=r"(v.z), "=r"(v.w) : "l"(p) : "memory"); return v; }
__device__ __forceinline__ uint32_t ld_relaxed32(const uint32_t* p) { uint32_t v; asm volatile("ld.relaxed.gpu.global.u32 %0, [%1];" : "=r"(v) : "l"(p) : "memory"); return v; }
__device__ __forceinline__ void st_relaxed128(uint4* p, uint4 v) { asm volatile("st.relaxed.gpu.global.v4.u32 [%0], {%1,%2,%3,%4};" :: "l"(p), "r"(v.x), "r"(v.y), "r"(v.z), "r"(v.w) : "memory"); }
__device__ __forceinline__ void st_relaxed32(uint32_t* p, uint32_t v) { asm volatile("st.relaxed.gpu.global.u32 [%0], %1;" :: "l"(p), "r"(v) : "memory"); }
__device__ __forceinline__ void st_relaxed128_p(uint4* p, uint4 v, uint32_t skip) {
    asm volatile("{\n.reg .pred p;\nsetp.eq.u32 p, %5, 0;\n@p st.relaxed.gpu.global.v4.u32 [%0], {%1,%2,%3,%4};\n}\n" :: "l"(p), "r"(v.x), "r"(v.y), "r"(v.z), "r"(v.w), "r"(skip) : "memory");
}
__device__ __forceinline__ void st_relaxed64_p(void* p, uint32_t x, uint32_t y, uint32_t skip) {
    asm volatile("{\n.reg .pred p;\n.reg .b64 v;\nsetp.eq.u32 p, %3, 0;\nmov.b64 v, {%1,%2};\n@p st.relaxed.gpu.global.b64 [%0], v;\n}\n" :: "l"(p), "r"(x), "r"(y), "r"(skip) : "memory");
}
__device__ __forceinline__ void ld_relaxed64_p(uint2& v, const void* p, uint32_t pred) {
    asm volatile("{\n.reg .pred p;\n.reg .b64 v;\nsetp.ne.u32 p, %3, 0;\nmov.b64 v, {%0,%1};\n@p ld.relaxed.gpu.global.b64 v, [%2];\nmov.b64 {%0,%1}, v;\n}\n" : "+r"(v.x), "+r"(v.y) : "l"(p), "r"(pred) : "memory");
}
__device__ __forceinline__ uint2 ld_relaxed64(const void* p) {
    uint2 v; asm volatile("{\n.reg .b64 v;\nld.relaxed.gpu.global.b64 v, [%2];\nmov.b64 {%0,%1}, v;\n}\n" : "=r"(v.x), "=r"(v.y) : "l"(p) : "memory"); return v;
}
__device__ __forceinline__ void st_relaxed32_p(void* p, uint32_t v, uint32_t skip) {
    asm volatile("{\n.reg .pred p;\nsetp.eq.u32 p, %2, 0;\n@p st.relaxed.gpu.global.u32 [%0], %1;\n}\n" :: "l"(p), "r"(v), "r"(skip) : "memory");
}
__device__ __forceinline__ void bar_arrive_p(int id, int n, uint32_t skip) {
    asm volatile("{\n.reg .pred p;\nsetp.eq.u32 p, %2, 0;\n@p bar.arrive %0, %1;\n}\n" :: "r"(id), "r"(n), "r"(skip) : "memory");
}
__device__ __forceinline__ void bar_sync_p(int id, int n, uint32_t skip) {
    asm volatile("{\n.reg .pred p;\nsetp.eq.u32 p, %2, 0;\n@p bar.sync %0, %1;\n}\n" :: "r"(id), "r"(n), "r"(skip) : "memory");
}
__device__ __forceinline__ uint32_t movm(uint32_t x) { uint32_t r; asm volatile("movmatrix.sync.aligned.m8n8.trans.b16 %0, %1;" : "=r"(r) : "r"(x)); return r; }
__device__ __forceinline__ void sts32_p(uint32_t a, uint32_t v, uint32_t doit) {
    asm volatile("{\n.reg .pred p;\nsetp.ne.u32 p, %2, 0;\n@p st.shared.u32 [%0], %1;\n}\n" :: "r"(a), "r"(v), "r"(doit) : "memory");
}
__device__ __forceinline__ uint32_t pin(uint32_t x) { return __shfl_sync(0xffffffffu, x, threadIdx.x & 31); }
__device__ __forceinline__ void ldsm16_t(uint32_t (&b)[4][4], uint32_t a) {
    asm volatile("ldmatrix.sync.aligned.m8n8.x4.trans.shared.b16 {%0,%1,%2,%3}, [%16];\n"
                 "ldmatrix.sync.aligned.m8n8.x4.trans.shared.b16 {%4,%5,%6,%7}, [%16+512];\n"
                 "ldmatrix.sync.aligned.m8n8.x4.trans.shared.b16 {%8,%9,%10,%11}, [%16+1024];\n"
                 "ldmatrix.sync.aligned.m8n8.x4.trans.shared.b16 {%12,%13,%14,%15}, [%16+1536];\n"
        : "=r"(b[0][0]), "=r"(b[0][1]), "=r"(b[0][2]), "=r"(b[0][3]), "=r"(b[1][0]), "=r"(b[1][1]), "=r"(b[1][2]), "=r"(b[1][3]),
          "=r"(b[2][0]), "=r"(b[2][1]), "=r"(b[2][2]), "=r"(b[2][3]), "=r"(b[3][0]), "=r"(b[3][1]), "=r"(b[3][2]), "=r"(b[3][3]) : "r"(a) : "memory");
}
template<int ID> __device__ __forceinline__ void sched_fence(uint32_t never) { while (never == 0x7fffff00u + ID) { asm volatile("nanosleep.u32 64;" ::: "memory"); } }
__device__ __forceinline__ uint32_t opaque_u() { uint32_t v; asm volatile("mov.u32 %0, %%nsmid;" : "=r"(v)); return v; }
__device__ __forceinline__ uint32_t bar_red_or(int id, int n, uint32_t v) {
    uint32_t r; asm volatile("{\n.reg .pred p, q;\nsetp.ne.u32 p, %3, 0;\nbar.red.or.pred q, %1, %2, p;\nselp.u32 %0, 1, 0, q;\n}\n" : "=r"(r) : "r"(id), "r"(n), "r"(v) : "memory"); return r;
}
template<class T> __device__ __forceinline__ T* launder_p(T* p) { asm volatile("" : "+l"(p)); return p; }
__device__ __forceinline__ uint32_t mapa_u32(uint32_t addr, uint32_t rank) { uint32_t d; asm("mapa.shared::cluster.u32 %0, %1, %2;" : "=r"(d) : "r"(addr), "r"(rank)); return d; }
__device__ __forceinline__ uint32_t mapa_v(uint32_t addr, uint32_t rank) { uint32_t d; asm volatile("mapa.shared::cluster.u32 %0, %1, %2;" : "=r"(d) : "r"(addr), "r"(rank)); return d; }
__device__ __forceinline__ void st_async32(uint32_t addr, uint32_t v, uint32_t mbar) { asm volatile("st.async.shared::cluster.mbarrier::complete_tx::bytes.u32 [%0], %1, [%2];" :: "r"(addr), "r"(v), "r"(mbar) : "memory"); }
__device__ __forceinline__ void cluster_arrive() { asm volatile("barrier.cluster.arrive.release.aligned;" ::: "memory"); }
__device__ __forceinline__ void cluster_wait() { asm volatile("barrier.cluster.wait.acquire.aligned;" ::: "memory"); }
__device__ __forceinline__ void cp_async16(uint32_t dst, const void* src) { asm volatile("cp.async.cg.shared.global [%0], [%1], 16;" :: "r"(dst), "l"(src) : "memory"); }
__device__ __forceinline__ void cp_async_commit() { asm volatile("cp.async.commit_group;" ::: "memory"); }
template<int N> __device__ __forceinline__ void cp_async_wait() { asm volatile("cp.async.wait_group %0;" :: "n"(N) : "memory"); }
__device__ __forceinline__ void cp_async_wait0() { asm volatile("cp.async.wait_group 0;" ::: "memory"); }
__device__ __forceinline__ void mbar_init(uint32_t a, uint32_t cnt) { asm volatile("mbarrier.init.shared.b64 [%0], %1;" :: "r"(a), "r"(cnt) : "memory"); }
__device__ __forceinline__ void mbar_expect_tx(uint32_t a, uint32_t bytes) { asm volatile("mbarrier.arrive.expect_tx.shared.b64 _, [%0], %1;" :: "r"(a), "r"(bytes) : "memory"); }
__device__ __forceinline__ bool mbar_try(uint32_t a, uint32_t parity) {
    uint32_t ok; asm volatile("{\n.reg .pred p;\nmbarrier.try_wait.parity.shared::cta.b64 p, [%1], %2;\nselp.u32 %0, 1, 0, p;\n}\n" : "=r"(ok) : "r"(a), "r"(parity) : "memory"); return ok;
}
__device__ __forceinline__ void mbar_wait(uint32_t a, uint32_t parity) { int it = 0; while (!mbar_try(a, parity) && ++it < SPIN_LIMIT) {} }
__device__ __forceinline__ void bar_sync(int id, int n) { asm volatile("bar.sync %0, %1;" :: "r"(id), "r"(n) : "memory"); }
__device__ __forceinline__ void bar_arrive(int id, int n) { asm volatile("bar.arrive %0, %1;" :: "r"(id), "r"(n) : "memory"); }
__device__ __forceinline__ void fence_async_smem() { asm volatile("fence.proxy.async.shared::cta;" ::: "memory"); }
__device__ __forceinline__ void sts32(uint32_t a, uint32_t v) { asm volatile("st.shared.u32 [%0], %1;" :: "r"(a), "r"(v) : "memory"); }
__device__ __forceinline__ void sts128(uint32_t a, uint4 v) { asm volatile("st.shared.v4.u32 [%0], {%1,%2,%3,%4};" :: "r"(a), "r"(v.x), "r"(v.y), "r"(v.z), "r"(v.w) : "memory"); }
__device__ __forceinline__ uint4 lds128(uint32_t a) { uint4 v; asm volatile("ld.shared.v4.u32 {%0,%1,%2,%3}, [%4];" : "=r"(v.x), "=r"(v.y), "=r"(v.z), "=r"(v.w) : "r"(a) : "memory"); return v; }
__device__ __forceinline__ uint32_t lds32(uint32_t a) { uint32_t v; asm volatile("ld.shared.u32 %0, [%1];" : "=r"(v) : "r"(a) : "memory"); return v; }
__device__ __forceinline__ uint32_t gtime_lo() { uint32_t t; asm volatile("mov.u32 %0, %globaltimer_lo;" : "=r"(t)); return t; }
__device__ __forceinline__ void wait_gtime(uint32_t tg) {
    asm volatile("{\n.reg .pred p, q;\n.reg .b64 t;\n.reg .b32 lo, hi, d, n;\nmov.b32 n, 300;\n"
                 "WG_%=:\nmov.u64 t, %%globaltimer;\nmov.b64 {lo, hi}, t;\nsub.s32 d, lo, %0;\nsub.s32 n, n, 1;\n"
                 "setp.gt.s32 q, n, 0;\nsetp.lt.and.s32 p, d, 0, q;\n@p bra.uni WG_%=;\n}\n" :: "r"(tg) : "memory");
}
__device__ __forceinline__ void delay_clk(int d) { uint32_t t0 = clock(); while ((int)(clock() - t0) < d) {} }

__device__ __forceinline__ uint64_t desc128(uint32_t addr) {
    return (uint64_t)((addr & 0x3FFFF) >> 4) | ((uint64_t)1 << 16) | ((uint64_t)64 << 32) | ((uint64_t)1 << 62);
}
template<int accum> __device__ __forceinline__ void wgmma_n32(float (&d)[16], const uint32_t (&a)[4], uint64_t desc) {
    if (accum) {
        asm volatile("{\n.reg .pred p;\nsetp.ne.b32 p, 1, 0;\n"
            "wgmma.mma_async.sync.aligned.m64n32k16.f32.bf16.bf16 {%0,%1,%2,%3,%4,%5,%6,%7,%8,%9,%10,%11,%12,%13,%14,%15}, {%16,%17,%18,%19}, %20, p, 1, 1, 0;\n}\n"
            : "+f"(d[0]), "+f"(d[1]), "+f"(d[2]), "+f"(d[3]), "+f"(d[4]), "+f"(d[5]), "+f"(d[6]), "+f"(d[7]),
              "+f"(d[8]), "+f"(d[9]), "+f"(d[10]), "+f"(d[11]), "+f"(d[12]), "+f"(d[13]), "+f"(d[14]), "+f"(d[15])
            : "r"(a[0]), "r"(a[1]), "r"(a[2]), "r"(a[3]), "l"(desc));
    } else {
        asm volatile("{\n.reg .pred p;\nsetp.ne.b32 p, 0, 0;\n"
            "wgmma.mma_async.sync.aligned.m64n32k16.f32.bf16.bf16 {%0,%1,%2,%3,%4,%5,%6,%7,%8,%9,%10,%11,%12,%13,%14,%15}, {%16,%17,%18,%19}, %20, p, 1, 1, 0;\n}\n"
            : "=f"(d[0]), "=f"(d[1]), "=f"(d[2]), "=f"(d[3]), "=f"(d[4]), "=f"(d[5]), "=f"(d[6]), "=f"(d[7]),
              "=f"(d[8]), "=f"(d[9]), "=f"(d[10]), "=f"(d[11]), "=f"(d[12]), "=f"(d[13]), "=f"(d[14]), "=f"(d[15])
            : "r"(a[0]), "r"(a[1]), "r"(a[2]), "r"(a[3]), "l"(desc));
    }
}
__device__ __forceinline__ float rcp_approx(float x) { float r; asm("rcp.approx.ftz.f32 %0, %1;" : "=f"(r) : "f"(x)); return r; }
__device__ __forceinline__ void wg_fence() { asm volatile("wgmma.fence.sync.aligned;" ::: "memory"); }
__device__ __forceinline__ void wg_commit() { asm volatile("wgmma.commit_group.sync.aligned;" ::: "memory"); }
__device__ __forceinline__ void wg_wait0() { asm volatile("wgmma.wait_group.sync.aligned 0;" ::: "memory"); }

#define SCALE_HI 0x3db53db5u
#define SCALE_LO 0x371e371eu
#define LOG2E 1.4426950408889634f
#define NEG_BIG2 0xce6ece6eu
__device__ __forceinline__ uint32_t scale_bf2(uint32_t x) {
    uint32_t t, r;
    asm("mul.rn.bf16x2 %0, %1, %2;" : "=r"(t) : "r"(x), "r"(SCALE_LO));
    asm("fma.rn.bf16x2 %0, %1, %2, %3;" : "=r"(r) : "r"(x), "r"(SCALE_HI), "r"(t));
    return r;
}
__device__ __forceinline__ void cluster_arrive_rx() { asm volatile("barrier.cluster.arrive.relaxed.aligned;" ::: "memory"); }
__device__ __forceinline__ uint32_t launder(uint32_t x) { asm volatile("" : "+r"(x)); return x; }
__device__ __forceinline__ void mbar_arrive(uint32_t a) { asm volatile("mbarrier.arrive.shared.b64 _, [%0];" :: "r"(a) : "memory"); }
__device__ __forceinline__ void mbar_wait_cl(uint32_t a, uint32_t parity) {
    int it = 0; uint32_t ok;
    do { asm volatile("{\n.reg .pred p;\nmbarrier.try_wait.parity.acquire.cluster.shared::cta.b64 p, [%1], %2;\nselp.u32 %0, 1, 0, p;\n}\n" : "=r"(ok) : "r"(a), "r"(parity) : "memory"); } while (!ok && ++it < SPIN_LIMIT);
}
__device__ __forceinline__ uint64_t desc_from(uint32_t lo) { return (uint64_t)lo | ((uint64_t)0x40000040u << 32); }
#define SB_OFF 1024u
#define DESC_LO(off) ((((SB_OFF + (uint32_t)(off)) & 0x3FFFFu) >> 4) | 0x10000u)
template<int N> struct ic { static constexpr int value = N; };
__device__ __forceinline__ uint32_t uni(uint32_t x) { return __shfl_sync(0xffffffffu, x, 0); }

__device__ __forceinline__ uint32_t pack_f16(float lo, float hi) { uint32_t r; asm("cvt.rn.f16x2.f32 %0, %1, %2;" : "=r"(r) : "f"(hi), "f"(lo)); return r; }
__device__ __forceinline__ uint32_t maxabs_h2(uint32_t a, uint32_t b) { uint32_t r; asm("max.NaN.xorsign.abs.f16x2 %0, %1, %2;" : "=r"(r) : "r"(a), "r"(b)); return r; }
__device__ __forceinline__ uint32_t h2_to_bf2(uint32_t v) {
    uint32_t r; asm("{\n.reg .b16 l, h;\n.reg .f32 a, b;\nmov.b32 {l, h}, %1;\ncvt.f32.f16 a, l;\ncvt.f32.f16 b, h;\ncvt.rn.bf16x2.f32 %0, b, a;\n}\n" : "=r"(r) : "r"(v)); return r;
}
__device__ __forceinline__ void sts16(uint32_t a, uint16_t v) { asm volatile("st.shared.u16 [%0], %1;" :: "r"(a), "h"(v) : "memory"); }
__device__ __forceinline__ void sts64(uint32_t a, uint32_t x, uint32_t y) { asm volatile("st.shared.v2.u32 [%0], {%1,%2};" :: "r"(a), "r"(x), "r"(y) : "memory"); }
__device__ __forceinline__ void ld_relaxed32_p(uint32_t& v, const void* p, uint32_t pred) {
    asm volatile("{\n.reg .pred p;\nsetp.ne.u32 p, %2, 0;\n@p ld.relaxed.gpu.global.u32 %0, [%1];\n}\n" : "+r"(v) : "l"(p), "r"(pred) : "memory");
}
__device__ __forceinline__ uint2 lds64(uint32_t a) { uint2 v; asm volatile("ld.shared.v2.u32 {%0,%1}, [%2];" : "=r"(v.x), "=r"(v.y) : "r"(a) : "memory"); return v; }
__device__ __forceinline__ uint32_t h1_to_bf(uint32_t v) {
    uint32_t r; asm("{\n.reg .b16 l, h;\n.reg .f32 a;\nmov.b32 {l, h}, %1;\ncvt.f32.f16 a, l;\ncvt.rn.bf16x2.f32 %0, a, a;\n}\n" : "=r"(r) : "r"(v)); return r;
}
__device__ __forceinline__ void mbar_wait2(uint32_t a, uint32_t pa, uint32_t b, uint32_t pb) {
    int it = 0; uint32_t ok;
    do { asm volatile("{\n.reg .pred p, q;\nmbarrier.try_wait.parity.shared::cta.b64 p, [%1], %2;\nmbarrier.try_wait.parity.shared::cta.b64 q, [%3], %4;\nand.pred p, p, q;\nselp.u32 %0, 1, 0, p;\n}\n"
                      : "=r"(ok) : "r"(a), "r"(pa), "r"(b), "r"(pb) : "memory"); } while (!ok && ++it < SPIN_LIMIT);
}
#define T_SYNC 0
#define BLK_Q(p) (((p) < 3 ? (p) : 8) * 2048)
#define BLK_K(p) (((p) < 3 ? 4 + (p) : 9) * 2048)
#define BLK_V(p) (((p) < 2 ? 3 + 4 * (p) : 8 + (p)) * 2048)
template<int MT>
__device__ __forceinline__ void tok_part1(uint32_t tok, int eh, int lane, uint32_t (&q)[8][4], uint32_t (&pa)[5][2], uint32_t (&bv)[8][4], uint32_t& mt, float (&st)[2]) {
    float e[5][4];
    constexpr int NK = MT ? 5 : 3;
    const int g = lane >> 2, t = lane & 3, mi = lane >> 3, r8 = lane & 7;
    #pragma unroll
    for (int nt = 1; nt < NK; nt++) { e[nt][0] = e[nt][1] = e[nt][2] = e[nt][3] = 0.f; }
    const uint32_t qa = tok + (16 * MT + (mi & 1) * 8 + r8) * 64 + (((mi >> 1) ^ (r8 >> 1)) << 4);
    const uint32_t ka = tok + r8 * 64 + ((mi ^ (r8 >> 1)) << 4);
    #pragma unroll
    for (int k2 = 0; k2 < 4; k2++) {
        uint32_t b[NK][4];
        ldsm_x4(q[2 * k2], qa + BLK_Q(k2));
        ldsm_x4(q[2 * k2 + 1], (qa ^ 32) + BLK_Q(k2));
        #pragma unroll
        for (int nt = 1; nt < NK; nt++) ldsm_x4(b[nt], ka + BLK_K(k2) + (nt - 1) * 512);
        #pragma unroll
        for (int nt = 1; nt < NK; nt++) mma16816(e[nt], q[2 * k2], b[nt][0], b[nt][1]);
        #pragma unroll
        for (int nt = 1; nt < NK; nt++) mma16816(e[nt], q[2 * k2 + 1], b[nt][2], b[nt][3]);
    }
    uint32_t sp[NK][2];
    #pragma unroll
    for (int nt = 1; nt < NK; nt++) { sp[nt][0] = scale_bf2(pack_bf16(e[nt][0], e[nt][1])); sp[nt][1] = scale_bf2(pack_bf16(e[nt][2], e[nt][3])); }
    const uint32_t keep = (2 * t <= g ? 0x0000ffffu : 0u) | (2 * t + 1 <= g ? 0xffff0000u : 0u);
    sp[NK - 2][0] = (sp[NK - 2][0] & keep) | (NEG_BIG2 & ~keep);
    sp[NK - 1][1] = (sp[NK - 1][1] & keep) | (NEG_BIG2 & ~keep);
    uint32_t m0 = sp[1][0], m1 = sp[1][1];
    #pragma unroll
    for (int nt = 2; nt < NK; nt++) { if (nt < NK - 1) m0 = max_bf2(m0, sp[nt][0]); m1 = max_bf2(m1, sp[nt][1]); }
    mt = max_bf2(__byte_perm(m0, m1, 0x5410), __byte_perm(m0, m1, 0x7632));
    mt = max_bf2(mt, __shfl_xor_sync(0xffffffffu, mt, 1));
    mt = max_bf2(mt, __shfl_xor_sync(0xffffffffu, mt, 2));
    const float nm0 = -bf_lo(mt) * LOG2E, nm1 = -bf_hi(mt) * LOG2E;
    st[0] = st[1] = 0.f;
    #pragma unroll
    for (int nt = 1; nt < NK; nt++) {
        if (nt < NK - 1) {
            e[nt][0] = ex2(fmaf(bf_lo(sp[nt][0]), LOG2E, nm0)); e[nt][1] = ex2(fmaf(bf_hi(sp[nt][0]), LOG2E, nm0));
            st[0] += e[nt][0] + e[nt][1];
        }
        e[nt][2] = ex2(fmaf(bf_lo(sp[nt][1]), LOG2E, nm1)); e[nt][3] = ex2(fmaf(bf_hi(sp[nt][1]), LOG2E, nm1));
        st[1] += e[nt][2] + e[nt][3];
        pa[nt][0] = nt < NK - 1 ? pack_bf16(e[nt][0], e[nt][1]) : 0u; pa[nt][1] = pack_bf16(e[nt][2], e[nt][3]);
    }
    const uint32_t va = MT ? tok + lane * 64 + ((r8 >> 1) << 4) : tok + (lane & 15) * 64 + (((lane >> 4) ^ (r8 >> 1)) << 4);
    const uint32_t o0 = eh ? BLK_V(2) : BLK_V(0), o1 = eh ? BLK_V(3) : BLK_V(1);
    #pragma unroll
    for (int n = 0; n < 8; n++) { if (MT) ldsm_x4_t(bv[n], (va ^ ((n & 3) << 4)) + (n < 4 ? o0 : o1)); else ldsm_x4_t(bv[n], (va ^ ((n & 1) << 5)) + BLK_V(n >> 1)); }
}
template<int MT, class F, class G, class H>
__device__ __forceinline__ void tok_part2(uint32_t exl, uint32_t ost, int eh, int lane, const uint32_t (&q)[8][4], uint32_t (&pa)[5][2], const uint32_t (&bv)[8][4], uint32_t mt, float (&st)[2], bool vb, F&& wait_v, G&& duty, H&& pace, uint32_t nv) {
    constexpr int NK = MT ? 5 : 3;
    const int mi = lane >> 3, r8 = lane & 7;
    uint32_t sm0, sm1;
    {
        uint32_t b[4][4];
        float s1[4] = {0.f, 0.f, 0.f, 0.f}, s2[4] = {0.f, 0.f, 0.f, 0.f};
        ldsm16_t(b, exl + 2048);
        duty();
        #pragma unroll
        for (int k2 = 0; k2 < 4; k2++) { mma16816(s1, q[2 * k2], b[k2][0], b[k2][1]); mma16816(s2, q[2 * k2 + 1], b[k2][2], b[k2][3]); }
        sm0 = scale_bf2(pack_bf16(s1[0] + s2[0], s1[1] + s2[1])); sm1 = scale_bf2(pack_bf16(s1[2] + s2[2], s1[3] + s2[3]));
    }
    float nm0 = -bf_lo(mt) * LOG2E, nm1 = -bf_hi(mt) * LOG2E;
    float a0 = fmaf(bf_lo(sm0), LOG2E, nm0), a1 = fmaf(bf_hi(sm0), LOG2E, nm0), a2 = fmaf(bf_lo(sm1), LOG2E, nm1), a3 = fmaf(bf_hi(sm1), LOG2E, nm1);
    if (__builtin_expect(!__all_sync(0xffffffffu, a0 <= 57.f && a1 <= 57.f && a2 <= 57.f && a3 <= 57.f), 0)) {
        uint32_t mm = max_bf2(__byte_perm(sm0, sm1, 0x5410), __byte_perm(sm0, sm1, 0x7632));
        mm = max_bf2(mm, __shfl_xor_sync(0xffffffffu, mm, 1));
        mm = max_bf2(mm, __shfl_xor_sync(0xffffffffu, mm, 2));
        mm = max_bf2(mm, mt);
        nm0 = -bf_lo(mm) * LOG2E; nm1 = -bf_hi(mm) * LOG2E;
        const float f0 = ex2(fmaf(bf_lo(mt), LOG2E, nm0)), f1 = ex2(fmaf(bf_hi(mt), LOG2E, nm1));
        st[0] *= f0; st[1] *= f1;
        #pragma unroll
        for (int nt = 1; nt < NK; nt++) { pa[nt][0] = pack_bf16(bf_lo(pa[nt][0]) * f0, bf_hi(pa[nt][0]) * f0); pa[nt][1] = pack_bf16(bf_lo(pa[nt][1]) * f1, bf_hi(pa[nt][1]) * f1); }
        a0 = fmaf(bf_lo(sm0), LOG2E, nm0); a1 = fmaf(bf_hi(sm0), LOG2E, nm0); a2 = fmaf(bf_lo(sm1), LOG2E, nm1); a3 = fmaf(bf_hi(sm1), LOG2E, nm1);
    }
    a0 = ex2(a0); a1 = ex2(a1); a2 = ex2(a2); a3 = ex2(a3);
    float s0 = st[0] + (a0 + a1), s1 = st[1] + (a2 + a3);
    pa[0][0] = pack_bf16(a0, a1); pa[0][1] = pack_bf16(a2, a3);
    wait_v();
    constexpr int NQ = MT ? 2 : 4;
    float o[NQ][4][4];
    #pragma unroll
    for (int j = 0; j < NQ; j++) {
        uint32_t bm[4];
        ldsm_x4(bm, exl + 4096 + (MT ? eh * 1024 : 0) + 512 * j);
        #pragma unroll
        for (int n = 0; n < 4; n++) {
            o[j][n][0] = o[j][n][1] = o[j][n][2] = o[j][n][3] = 0.f;
            if (MT) mma16816r(o[j][n], pa[1][0], pa[1][1], pa[2][0], pa[2][1], bv[4 * j + n][0], bv[4 * j + n][1]);
            else mma16816r(o[j][n], pa[1][0], pa[1][1], pa[2][0], pa[2][1], bv[2 * j + (n >> 1)][2 * (n & 1)], bv[2 * j + (n >> 1)][2 * (n & 1) + 1]);
        }
        if (MT) {
            #pragma unroll
            for (int n = 0; n < 4; n++) mma16816r(o[j][n], pa[3 % NK][0], pa[3 % NK][1], pa[4 % NK][0], pa[4 % NK][1], bv[4 * j + n][2], bv[4 * j + n][3]);
        }
        #pragma unroll
        for (int n = 0; n < 4; n++) mma1688(o[j][n], pa[0][0], pa[0][1], bm[n]);
    }
    #pragma unroll
    for (int j = 0; j < NQ; j++) asm volatile("" : "+f"(o[j][0][0]), "+f"(o[j][1][0]), "+f"(o[j][2][0]), "+f"(o[j][3][0]));
    sched_fence<6 + MT>(nv);
    if (T_SYNC) { pace(); bar_sync_p(12, 384, !vb); } else { bar_arrive_p(12, 384, !vb); pace(); }
    s0 += __shfl_xor_sync(0xffffffffu, s0, 1); s1 += __shfl_xor_sync(0xffffffffu, s1, 1);
    s0 += __shfl_xor_sync(0xffffffffu, s0, 2); s1 += __shfl_xor_sync(0xffffffffu, s1, 2);
    const float i0 = rcp_approx(s0), i1 = rcp_approx(s1);
    const uint32_t oa = ost + ((mi & 1) * 8 + r8) * 128 + (((mi >> 1) ^ r8) << 4);
    #pragma unroll
    for (int j = 0; j < NQ; j++) {
        stsm_x4((oa ^ ((j & 1) << 6)) + (j >> 1) * 2048, pack_bf16(o[j][0][0] * i0, o[j][0][1] * i0), pack_bf16(o[j][0][2] * i1, o[j][0][3] * i1), pack_bf16(o[j][1][0] * i0, o[j][1][1] * i0), pack_bf16(o[j][1][2] * i1, o[j][1][3] * i1));
        stsm_x4((oa ^ (((j & 1) << 6) | 32)) + (j >> 1) * 2048, pack_bf16(o[j][2][0] * i0, o[j][2][1] * i0), pack_bf16(o[j][2][2] * i1, o[j][2][3] * i1), pack_bf16(o[j][3][0] * i0, o[j][3][1] * i0), pack_bf16(o[j][3][2] * i1, o[j][3][3] * i1));
    }
}

#define TP_E 0
#define V_EARLY 1
#define SW_FENCE 0
#define PV_FENCE 1
#define IL_AT 3
#define TAIL 0
#define MP_PRE 4
#define VF_EARLY 1
__device__ __forceinline__ void stsm2_p(uint32_t a, const uint32_t (&v)[8], uint32_t skip) {
    asm volatile("{\n.reg .pred p;\nsetp.eq.u32 p, %9, 0;\n@p stmatrix.sync.aligned.m8n8.x4.trans.shared.b16 [%0], {%1,%2,%3,%4};\n"
                 "@p stmatrix.sync.aligned.m8n8.x4.trans.shared.b16 [%0+1024], {%5,%6,%7,%8};\n}\n"
        :: "r"(a), "r"(v[0]), "r"(v[1]), "r"(v[2]), "r"(v[3]), "r"(v[4]), "r"(v[5]), "r"(v[6]), "r"(v[7]), "r"(skip) : "memory");
}
template<int OA, int OB>
__device__ __forceinline__ void send_tile(float c0, float c1, float c2, float c3, uint32_t a, uint32_t b, bool cnt, uint32_t fb) {
    const uint32_t w0 = pack_f16(c0, c1), w1 = pack_f16(c2, cnt ? 5.9604644775390625e-8f : c3), w2 = pack_f16(c3, 5.9604644775390625e-8f);
    const uint32_t hi = (uint32_t)((uint64_t)g_acc >> 32);
    asm volatile("{\n.reg .pred q;\n.reg .b64 pa, pb;\nsetp.ne.u32 q, %6, 0;\nmov.b64 pa, {%0, %2};\nmov.b64 pb, {%1, %2};\n"
                 "red.relaxed.gpu.global.add.noftz.v2.f16x2 [pa+%7], {%3, %4};\n@q red.relaxed.gpu.global.add.noftz.f16x2 [pb+%8], %5;\n}\n"
        :: "r"(a), "r"(b), "r"(hi), "r"(w0), "r"(w1), "r"(w2), "r"((uint32_t)cnt), "n"(OA), "n"(OB) : "memory");
    sts128(fb, make_uint4(__float_as_uint(c0), __float_as_uint(c1), __float_as_uint(c2), __float_as_uint(c3)));
}
__device__ __forceinline__ uint32_t send_ua(uint32_t tile) { return (uint32_t)(uint64_t)g_acc + tile * 1024; }
__device__ __forceinline__ uint32_t send_ub(uint32_t tile) { return (uint32_t)(uint64_t)g_acc + ACC_X + (tile >> 1) * 1024 + (tile & 1) * 256; }
__device__ __forceinline__ void lds_il(float& il, float& ih, uint32_t a) {
    asm volatile("ld.shared.f32 %0, [%2];\nld.shared.f32 %1, [%2+128];" : "=f"(il), "=f"(ih) : "r"(a) : "memory");
}
template<bool OWN, class F>
__device__ __forceinline__ void stage_w(const uint32_t (&wo)[8][4], uint32_t ol, uint32_t tile, uint32_t so, uint32_t l16, uint32_t fb, uint32_t nv, uint32_t ila, float il, float ih, F&& issued) {
    uint32_t b[4][4], sa, sb_;
    auto addr = [&] {
        const uint32_t ll = OWN ? l16 : l16 | (b[3][0] & nv);
        sa = (ll & 0x100u) + ((ll & 0xf0u) >> 1) + (send_ua(tile) + so); sb_ = ((ll >> 4) & 28u) + (send_ub(tile) + so);
    };
    bar_sync(11, 352);
    ldsm16_t(b, ol);
    if (OWN) addr();
    if (!OWN || SW_FENCE) sched_fence<0>(nv);
    float c[2][4];
    #pragma unroll
    for (int i = 0; i < 2; i++) c[i][0] = c[i][1] = c[i][2] = c[i][3] = 0.f;
    #pragma unroll
    for (int j = 0; j < 4; j++) {
        if (!OWN && j == IL_AT) { addr(); lds_il(il, ih, ila); }
        mma16816(c[0], wo[2 * j], b[j][0], b[j][1]); mma16816(c[1], wo[2 * j + 1], b[j][2], b[j][3]);
    }
    if (TP_E || (OWN && V_EARLY)) { asm volatile("" : "+f"(c[0][0]), "+f"(c[1][0])); sched_fence<OWN ? 4 : 5>(nv); }
    issued();
    send_tile<0, 0>((c[0][0] + c[1][0]) * il, (c[0][1] + c[1][1]) * ih, (c[0][2] + c[1][2]) * il, (c[0][3] + c[1][3]) * ih, sa, sb_, ((l16 ^ (tile << 4)) & 0x30u) == 0, fb);
}

template<int N> __device__ __forceinline__ void code_pad(uint32_t nv) {
    if (N && nv == 0x7fffffe0u + N % 16) {
        float v = __uint_as_float(nv);
        #pragma unroll
        for (int i = 0; i < N; i++) asm volatile("fma.rn.f32 %0, %0, %0, %0;" : "+f"(v));
        sts32_p(0u, __float_as_uint(v), nv);
    }
}
#define PAD_T0 0
#define PAD_T1 0
#define PAD_S 0
#define PAD_P 0
#define BAR_PRO 1
#define BAR_MEM 2
#define BAR_P   3
#define BAR_PRJ 4
#define BAR_VGO 7
#define BAR_X0  7
#define BAR_S   9
#define BAR_P2  10
#define BAR_O   11
#define BAR_O2  14
#define BAR_TP  15
#define BAR_V   12
#define BAR_FB  13
#define VGO_AT 9
#define TP_N 36
#define TP_N1 24
#define REG_P 200
#define W_FENCE 1
#define WO_PRE 4
#define WO_MID 8
#define WO_EX 8
#define WO_REP 2
#define TP_DELAY 0
#define PRE_W 4
#ifndef M_RES
#define M_RES 6
#endif
#define K_PRE 6
#define K_POS 0
#define LD_FENCE 0
#define CV_FENCE 4
#define ANN_POS 1
#define PRO_V 0
#define PUB_W 0
#define TM_PF 1
#define TS_CAP 64
#define G1_0 128
#define G1_NS 1216
#define SIG_LO     (127 - 3)
#define SIG_HI     (127 + 5)
#define SIG_LOW    0x3c00u
#define SIG_LIM    56

__global__ void __cluster_dims__(3, 1, 1) __launch_bounds__(CH_THREADS, 1)
chain_kernel(const __grid_constant__ CUtensorMap tmx, const __grid_constant__ CUtensorMap tmq, const __grid_constant__ CUtensorMap tmk,
             const __grid_constant__ CUtensorMap tmv, const __grid_constant__ CUtensorMap tmo, const bf16* __restrict__ mem0, const uint32_t nv_) {
    extern __shared__ __align__(1024) unsigned char smem[];
    const uint32_t sb = smem_u32(smem);
    const int tid = threadIdx.x, lane = tid & 31;
    const int warp = __shfl_sync(0xffffffffu, tid >> 5, 0);
    const uint32_t nv = __shfl_sync(0xffffffffu, nv_ * tid, 0);
    const int h = blockIdx.x / 3, r = blockIdx.x % 3;
    const int mi = lane >> 3, r8 = lane & 7;
    const uint32_t bX = sb + SM_BAR, bTOK = bX + 16, bEX = bX + 40, bW = bX + 64, bEV = bX + 104, bFREE = bX + 32;
    const int nqk = r < 2 ? 6 : 4;
    if ((sb & 0xFFFFFFu) != SB_OFF) __trap();
    asm volatile("griddepcontrol.launch_dependents;");
    if (tid == 0 && blockIdx.x == 0) GT(40, 0);

    auto load_w = [&](int lo, int hi) {
        #pragma unroll 1
        for (int i = lo; i < hi; i++) {
            const int blk = i >> 2, j = i & 3;
            if (i < 48) {
                const int m = r < 2 ? (j < 3 ? r : 2) : (j < 2 ? j : 2), p = r < 2 ? (j < 3 ? j : r) : (j < 2 ? 3 : j);
                asm volatile("cp.async.bulk.tensor.2d.shared::cluster.global.mbarrier::complete_tx::bytes [%0], [%1, {%3, %4}], [%2];"
                    :: "r"(sb + i * 3072), "l"(m == 0 ? &tmq : (m == 1 ? &tmk : &tmv)), "r"(bW + (blk < 3 ? 0 : (blk < 6 ? 8 : (blk < 10 ? 16 : 24)))), "r"(h * DH + p * 32), "r"(blk * 48) : "memory");
            } else asm volatile("cp.async.bulk.tensor.2d.shared::cluster.global.mbarrier::complete_tx::bytes [%0], [%1, {%3, %4}], [%2];"
                :: "r"(sb + SM_WO + (i - 48) * 8192), "l"(&tmo), "r"(bW + 32), "r"(192 * r + 32 * (i - 48)), "r"(h * DH) : "memory");
        }
    };
    if (tid == 352) {
        #pragma unroll
        for (int i = 0; i < 15; i++) mbar_init(bX + 8 * i, (i == 5 || i == 6) ? 1 + nqk : (i >= 13 ? 9 - nqk : 1));
        asm volatile("fence.mbarrier_init.release.cluster;" ::: "memory");
        mbar_expect_tx(bW, 36864); mbar_expect_tx(bW + 8, 36864); mbar_expect_tx(bW + 16, 49152); mbar_expect_tx(bW + 24, 24576); mbar_expect_tx(bW + 32, 49152);
        load_w(0, 2 * PRE_W);
    }
    if (TM_PF && tid < 2) asm volatile("prefetch.param.tensormap [%0];" :: "l"(__cvta_generic_to_grid_constant(tid ? &tmo : &tmx)) : "memory");
    const unsigned epoch = ld_relaxed32(&g_epoch);
    __syncthreads();
    const uint32_t pw0 = ((mi >> 1) * 8 + r8) * 64 + (((2 * (warp & 1) + (mi & 1)) ^ (r8 >> 1)) << 4);
    auto tok_publish = [&](int tb, int k) {
        const uint32_t src = sb + SM_TOK + tb * TOKBUF + r * 8192, bar = bTOK + 8 * tb;
        if (k == 1) asm volatile("{\n.reg .pred p;\nelect.sync _|p, 0xffffffff;\n@p mbarrier.arrive.expect_tx.shared.b64 _, [%0], 16384;\n}\n" :: "r"(bar) : "memory");
        asm volatile("{\n.reg .pred p;\nelect.sync _|p, 0xffffffff;\n"
                     "@p cp.async.bulk.shared::cluster.shared::cta.mbarrier::complete_tx::bytes [%0], [%1], 8192, [%2];\n}\n"
            :: "r"(mapa_u32(src, (r + k) % 3)), "r"(src), "r"(mapa_u32(bar, (r + k) % 3)) : "memory");
    };
    if (warp < 8) {
        asm volatile("setmaxnreg.inc.sync.aligned.u32 %0;" :: "n"(REG_P));
        uint32_t wf[36][4];
        const uint32_t wl = sb + (warp >> 1) * 3072 + pw0;
        float ta0[16], ta1[16];
        auto tp_part = [&](auto lo, auto hi) {
            wg_fence();
            #pragma unroll
            for (int i = lo.value; i < hi.value; i++) {
                if (i == 0) wgmma_n32<0>(ta0, wf[0], desc_from(DESC_LO(SM_X))); else wgmma_n32<1>(ta0, wf[i], desc_from(DESC_LO(SM_X) + (i >> 2) * 256 + (i & 3) * 2));
            }
            #pragma unroll
            for (int i = lo.value; i < hi.value; i++) {
                if (i == 0) wgmma_n32<0>(ta1, wf[0], desc_from(DESC_LO(SM_X + XBUF))); else wgmma_n32<1>(ta1, wf[i], desc_from(DESC_LO(SM_X + XBUF) + (i >> 2) * 256 + (i & 3) * 2));
            }
            wg_commit();
        };
        if (tid == 32) load_w(2 * PRE_W, 40);
        if (tid == 0) GT(41 + blockIdx.x % 3, 7);
        code_pad<PAD_P>(nv);
        mbar_wait(bW, 0);
        #pragma unroll
        for (int i = 0; i < 9; i++) ldsm_x4_t(wf[i], wl + (i / 3) * 12288 + (i % 3) * 1024);
        fence_async_smem(); bar_arrive(BAR_X0, 288);
        mbar_wait(bW + 8, 0);
        #pragma unroll
        for (int i = 9; i < 18; i++) ldsm_x4_t(wf[i], wl + (i / 3) * 12288 + (i % 3) * 1024);
        fence_async_smem(); bar_arrive(BAR_X0 + 1, 288);
        mbar_wait(bX, 0); mbar_wait(bX + 8, 0);
        tp_part(ic<0>(), ic<18>());
        wg_wait0();
        sts128(sb + SM_OST + tid * 16, make_uint4(wf[0][0], wf[0][1], wf[0][2], wf[0][3]));
        mbar_wait(bW + 16, 0);
        #pragma unroll
        for (int i = 18; i < 30; i++) ldsm_x4_t(wf[i], wl + (i / 3) * 12288 + (i % 3) * 1024);
        tp_part(ic<18>(), ic<30>());
        mbar_wait(bW + 24, 0);
        if (tid == 0) GT(41 + blockIdx.x % 3, 0);
        wg_wait0();
        #pragma unroll
        for (int i = 30; i < 36; i++) ldsm_x4_t(wf[i], wl + (i / 3) * 12288 + (i % 3) * 1024);
        fence_async_smem();
        cluster_arrive_rx();
        tp_part(ic<30>(), ic<36>());
        if (tid == 0) GT(41 + blockIdx.x % 3, 2);
        const uint32_t pw = pin(pw0);
        auto tp_store = [&](const float (&acc)[16], uint32_t off) {
            const uint32_t ta = pw + launder(sb + off + (warp >> 1) * 2048);
            stsm_x4_t(ta, pack_bf16(acc[0], acc[1]), pack_bf16(acc[2], acc[3]), pack_bf16(acc[4], acc[5]), pack_bf16(acc[6], acc[7]));
            stsm_x4_t(ta + 1024, pack_bf16(acc[8], acc[9]), pack_bf16(acc[10], acc[11]), pack_bf16(acc[12], acc[13]), pack_bf16(acc[14], acc[15]));
        };
        cluster_wait();
        wg_wait0();
        tp_store(ta0, SM_TOK + r * 8192);
        if (warp == 0) { bar_sync(BAR_PRJ, 256); fence_async_smem(); tok_publish(0, 1); tok_publish(0, 2); } else bar_arrive(BAR_PRJ, 256);
        if (!TAIL) { tp_store(ta1, SM_TOK + TOKBUF + r * 8192); }
        { const uint4 v = lds128(sb + SM_OST + tid * 16); wf[0][0] = v.x; wf[0][1] = v.y; wf[0][2] = v.z; wf[0][3] = v.w; }
        if (tid == 0) GT(41 + blockIdx.x % 3, 4);
        const uint32_t l16 = pin(lane * 16), sbl = sb + l16, l4w = pin(sb + warp * 256 + lane * 4);
        uint32_t wo[8][4];
        const int exo = r < 2 ? (warp < 6 ? r * 2048 : 4096 + (2 * r - 6) * 256) : (warp < 2 ? 6 * 256 : (warp < 4 ? 2048 + 4 * 256 : 4096));
        const bool isqk = warp < nqk;
        const uint32_t exbar = isqk ? bEX : bEV;
        uint32_t vf[2][4]; float unsc;
        auto prep = [&](int s) {
            const uint32_t va = pw + launder(sb + SM_TOK + (s & 1) * TOKBUF + BLK_V(warp >> 1));
            mbar_wait(bTOK + 8 * (s & 1), (s >> 1) & 1);
            if (VF_EARLY) { ldsm_x4_t(vf[0], va); ldsm_x4_t(vf[1], va + 1024); }
            unsc = __uint_as_float((254u - lds32(sb + SM_SG + 12 + (s & 1) * 16)) << 23);
        };
        prep(0);
        for (int s = 0; ; s++) {
            const int par = s & 1;
            const uint32_t va = pw + launder(sb + SM_TOK + par * TOKBUF + BLK_V(warp >> 1)), wa = pw + launder(sb + SM_WO + (warp >> 1) * 8192);
            const uint32_t exu = launder(SM_EX + par * EXBUF);
            if (!isqk) { bar_arrive(BAR_MEM, 352); bar_sync(BAR_VGO, 256); } else bar_sync(BAR_MEM, 352);
            {
                float acc[4][4];
                #pragma unroll
                for (int i = 0; i < 4; i++) { acc[i][0] = acc[i][1] = acc[i][2] = acc[i][3] = 0.f; }
                uint32_t b[18][4];
                #pragma unroll
                for (int i2 = 0; i2 < 18; i2++) {
                    if (!TAIL || i2 >= MP_PRE) ldsm_x4_t(b[i2], sbl + SM_MEM + i2 * 512);
                    if (i2 == VGO_AT) bar_arrive_p(BAR_VGO, 256, !isqk);
                    if (PRO_V && i2 == PRO_V) bar_arrive_p(BAR_PRO, 256 + (K_PRE < 8 ? 64 : 0), isqk || s == NSEG - 1);
                    mma16816(acc[(2 * i2) & 3], wf[2 * i2], b[i2][0], b[i2][1]);
                    mma16816(acc[(2 * i2 + 1) & 3], wf[2 * i2 + 1], b[i2][2], b[i2][3]);
                }
                float q[4];
                #pragma unroll
                for (int i = 0; i < 4; i++) q[i] = fmaf(acc[2][i] + acc[3][i], unsc, (acc[0][i] + acc[1][i]) * unsc);
                const uint32_t lo = pack_bf16(q[0], q[1]), hi = pack_bf16(q[2], q[3]);
                const uint32_t exl = l4w + launder(exu + exo), bar = exbar + par * 8;
                #pragma unroll
                for (int k = 1; k < 3; k++) {
                    const uint32_t exd = mapa_u32(exl, (r + k) % 3), exb = mapa_u32(bar, (r + k) % 3);
                    st_async32(exd, lo, exb); st_async32(exd + 128, hi, exb);
                }
                sts32(exl, lo); sts32(exl + 128, hi);
                __syncwarp();
                asm volatile("{\n.reg .pred p;\nelect.sync _|p, 0xffffffff;\n@p mbarrier.arrive.shared.b64 _, [%0];\n}\n" :: "r"(bar) : "memory");
                if (s < NSEG - 1) bar_sync_p(BAR_PRO, (PRO_V ? 256 : 32 * nqk) + (K_PRE < 8 ? 64 : 0), !isqk);
            }
            if (s == 0) mbar_wait(bW + 32, 0);
            if (s == NSEG - 1) break;
            {
                if (!VF_EARLY) { ldsm_x4_t(vf[0], va); ldsm_x4_t(vf[1], va + 1024); }
                #pragma unroll
                for (int i = 0; i < WO_PRE; i++) ldsm_x4_t(wo[i], wa + i * 1024);
                if (WO_EX > WO_PRE) {
                    #pragma unroll
                    for (int k = 0; k < WO_REP; k++) mbar_wait(bEX + 8 * par, (s >> 1) & 1);
                    #pragma unroll
                    for (int i = WO_PRE; i < WO_EX; i++) ldsm_x4_t(wo[i], wa + i * 1024);
                }
                mbar_wait(bEV + 8 * par, (s >> 1) & 1);
                const uint32_t vm0 = lds32(l4w + exu + 4096), vm1 = lds32(l4w + exu + 4096 + 128);
                #pragma unroll
                for (int i = WO_EX; i < WO_MID; i++) ldsm_x4_t(wo[i], wa + i * 1024);
                uint32_t big;
                {
                    uint32_t x = vm0 ^ vm1 ^ vf[0][0] ^ vf[1][0];
                    #pragma unroll
                    for (int i = 0; i < WO_MID; i++) x ^= wo[i][0];
                    big = bar_red_or(BAR_P, 352, x & nv);
                }
                uint32_t pb[4]; ldsm_x4_t(pb, sbl + SM_P);
                uint32_t pm = ldsm_x1_t(sbl + SM_P + 512);
                float o0[4] = {0.f, 0.f, 0.f, 0.f}, o1[4] = {0.f, 0.f, 0.f, 0.f}, o2[4] = {0.f, 0.f, 0.f, 0.f};
                #pragma unroll
                for (int i = WO_MID; i < 8; i++) if (PV_FENCE) ldsm_x4_t(wo[i], wa + i * 1024);
                if (__builtin_expect(big, 0)) {
                    bar_sync(BAR_P2, 352);
                    ldsm_x4_t(pb, sbl + SM_P); pm = ldsm_x1_t(sbl + SM_P + 512);
                }
                #pragma unroll
                for (int i = WO_MID; i < 8; i++) if (!PV_FENCE) ldsm_x4_t(wo[i], wa + i * 1024);
                mma16816(o0, vf[0], pb[0], pb[1]);
                mma16816(o1, vf[1], pb[2], pb[3]);
                mma1688(o2, vm0, vm1, pm);
                sts32(l4w + SM_O, pack_bf16((o0[0] + o1[0]) + o2[0], (o0[1] + o1[1]) + o2[1]));
                sts32(l4w + SM_O + 128, pack_bf16((o0[2] + o1[2]) + o2[2], (o0[3] + o1[3]) + o2[3]));
                const uint32_t xd = uni(DESC_LO(SM_X) + par * (XBUF >> 4));
                auto tp = [&](auto lo, auto hi) {
                    #pragma unroll
                    for (int i = lo.value; i < hi.value; i++) {
                        if (i == 0) wgmma_n32<0>(ta1, wf[0], desc_from(xd));
                        else wgmma_n32<1>(ta1, wf[i], desc_from(xd + (i >> 2) * 256 + (i & 3) * 2));
                    }
                };
                stage_w<false>(wo, sbl + SM_O, 12 * r + warp, SLOT_OFF(s + 1), l16, sbl + SM_FB + warp * 512, nv, l4w + (SM_IL - warp * 256), 0.f, 0.f, [&] {
                    if (TP_E) { bar_sync(BAR_V, 384); wg_fence(); tp(ic<0>(), ic<TP_E>()); } });
                STAMP(warp);
                bar_arrive(BAR_FB, 352);
                if (!TP_E) { bar_sync(BAR_V, 384); wg_fence(); }
                STAMP(12);
                tp(ic<TP_E>(), ic<TP_N>());
                wg_commit();
                prep(s + 1);
                if (!TAIL) { wg_wait0(); tp_store(ta1, SM_TOK + par * TOKBUF + r * 8192); STAMP(13 + (warp >> 2)); }
            }
        }
        cluster_arrive(); cluster_wait();
    } else {
        asm volatile("setmaxnreg.dec.sync.aligned.u32 %0;" :: "n"(504 - 2 * REG_P));
        const int a = warp - 8;
        const uint32_t sbl = sb + lane * 16;
        if (a < 3) {
            const uint32_t zs = 3 * blockIdx.x + (r8 >> 1);
            const uint32_t zoff = (r8 < 6 ? (zs >> 3) * 1024 + ((zs >> 2) & 1) * 256 + (zs & 3) * 32 : ACC_X + (blockIdx.x >> 1) * 1024 + (blockIdx.x & 1) * 256) + (lane & 1) * 16;
            const uint32_t zskip = r8 >= 6 && blockIdx.x >= 36;
            if (a == 1) {
                st_relaxed128_p((uint4*)(g_acc + zoff + SLOT_OFF(mi)), make_uint4(0, 0, 0, 0), zskip);
                __threadfence();
                __syncwarp();
                if (lane == 0) st_relaxed32(&g_init[blockIdx.x], epoch);
            }
            {
                uint32_t mx = 0;
                #pragma unroll
                for (int i = 0; i < 6; i++) {
                    const int c = tid - 256 + 96 * i;
                    const unsigned short* m = (const unsigned short*)mem0 + c;
                    uint4 v;
                    v.x = m[0] | ((uint32_t)m[DM] << 16); v.y = m[2 * DM] | ((uint32_t)m[3 * DM] << 16);
                    v.z = m[4 * DM] | ((uint32_t)m[5 * DM] << 16); v.w = m[6 * DM] | ((uint32_t)m[7 * DM] << 16);
                    sts128(sb + SM_MEM + c * 16, v);
                    mx = maxabs_bf2(maxabs_bf2(mx, v.x), maxabs_bf2(maxabs_bf2(v.y, v.z), v.w));
                }
                mx = __reduce_max_sync(0xffffffffu, max((mx >> 7) & 0xffu, (mx >> 23) & 0xffu));
                sts32(sb + SM_SG + a * 4, max(mx, 1u)); sts32(sb + SM_SG + 12, 127u); sts32(sb + SM_SG + 36, 0u);
            }
            asm volatile("barrier.cluster.arrive.release.aligned;" ::: "memory");
            { int it = 0; while (__any_sync(0xffffffffu, ld_relaxed32(&g_init[a * 32 + lane]) != epoch) && ++it < SPIN_LIMIT) {} }
            __threadfence();
            const uint32_t kl0 = (a < 2 ? SM_TOK + (16 * a + (mi & 1) * 8 + r8) * 64 + (((mi >> 1) ^ (r8 >> 1)) << 4) : SM_EX + 2048 + ((((mi & 1) << 1) | (mi >> 1)) * 8 + r8) * 16);
            const uint32_t l16 = pin(lane * 16);
            uint32_t kf[8][4], wo[8][4];
            auto load_k = [&](int tb, uint32_t kl, auto lo, auto hi) {
                const uint32_t ka = kl + launder(sb + tb * TOKBUF);
                #pragma unroll
                for (int kk = lo.value; kk < hi.value; kk++) ldsm_x4(kf[kk], (ka ^ ((kk & 1) << 5)) + BLK_K(kk >> 1));
            };
            code_pad<PAD_S>(nv);
            cluster_wait();
            if (a == 0 && lane == 0) { mbar_expect_tx(bEX, 4096 - 256 * nqk); mbar_expect_tx(bEV, 256 * nqk); }
            if (a < 2) bar_arrive(BAR_MEM, 352); else bar_sync(BAR_MEM, 352);
            mbar_wait(bW + 32, 0);
            #pragma unroll
            for (int i = 0; i < 8; i++) ldsm_x4_t(wo[i], pw0 + sb + SM_WO + (warp >> 1) * 8192 + i * 1024);
            sts128(sbl + SM_STASH + a * 1024 + 512, make_uint4(kl0, (pw0 ^ 32) + sb + SM_WO + 5 * 8192, zoff | ((zskip || lane >= 8) << 31), epoch << 6));
            sts128(sbl + SM_STASH + a * 1024, make_uint4(a * 12288 + (lane >> 4) * 1024 + (mi & 1) * 256 + r8 * 16, ACC_X + a * 6144 + (lane >> 4) * 1024 + (mi & 1) * 256 + r8 * 4,
                                                         sb + SM_MEM + a * 3072 + (lane >> 4) * 256 + (lane & 15) * 8, sb + SM_MEM + a * 3072 + mi * 260 + r8 * 16 + 130));
            const uint32_t stash = l16 + uni(sb + SM_STASH + a * 1024);
            #pragma unroll
            for (int i = 0; i < 8; i++) ldsm_x4_t(kf[i], (pw0 ^ 32) + sb + SM_WO + 5 * 8192 + i * 1024);
            if (a < 2) { mbar_wait(bTOK, 0); load_k(0, kl0, ic<0>(), ic<K_PRE>()); }
            __syncwarp();
            int sn = 0;
            #pragma unroll 1
            while (sn < NSEG - 1) {
              uint32_t bad, any[2], c, ax, cx;
              #pragma unroll 1
              do {
                const int s = sn, par = s & 1;
                const uint32_t exu = launder(sb + par * EXBUF);
                const uint32_t exl = l16 + exu + SM_EX;
                const uint32_t t0 = gtime_lo();
                STAMP(15); STAMPV(31, t0);
                if (a == 2) st_relaxed32_p(&g_ts[blockIdx.x], t0, l16);
                if (a == 1) {
                    const uint32_t z = lds32(stash + 520);
                    st_relaxed128_p((uint4*)(g_acc + (z + SLOT_OFF(s + 3))), make_uint4(0, 0, 0, 0), z >> 31);
                }
                if (a == 0 && l16 == 0) { mbar_expect_tx(bEX + 8 * (par ^ 1), 4096 - 256 * nqk); mbar_expect_tx(bEV + 8 * (par ^ 1), 256 * nqk); }
                sts32(sb + SM_SG + (par ^ 1) * 16 + a * 4, 0u);
                uint32_t tg;
                auto first_half = [&](auto role) {
                constexpr bool M = role.value;
                auto publish = [&] {
                    asm volatile("{\n.reg .pred p;\nelect.sync _|p, 0xffffffff;\n"
                                 "@p cp.async.bulk.shared::cluster.global.mbarrier::complete_tx::bytes.multicast::cluster [%0], [%1], 8192, [%2], %3;\n}\n"
                        :: "r"(sb + SM_TOK + (par ^ 1) * TOKBUF + r * 8192), "l"(g_tokx[blockIdx.x]), "r"(bTOK + 8 * (par ^ 1)), "h"((unsigned short)(7 ^ (1 << r))) : "memory");
                };
                uint32_t sl, sh, kl = 0, w2 = 0;
                float sig = 0.f;
                if (M) {
                    fence_async_smem();
                    if (l16 == 0) {
                        asm volatile("cp.async.bulk.global.shared::cta.bulk_group [%0], [%1], 8192;\ncp.async.bulk.commit_group;"
                            :: "l"(g_tokx[blockIdx.x]), "r"(sb + SM_TOK + (par ^ 1) * TOKBUF + r * 8192) : "memory");
                        mbar_expect_tx(bTOK + 8 * (par ^ 1), 16384);
                        if (s == 0) mbar_expect_tx(bX, XBUF);
                        if (s + 3 < NSEG) mbar_expect_tx(bX + 8 * (par ^ 1), XBUF);
                    }
                    __syncwarp();
                    if (s > 0 && s + 2 < NSEG) mbar_wait(bX + 8 * par, ((s >> 1) & 1) ^ 1);
                    if (PUB_W == 0) asm volatile("cp.async.bulk.wait_group 0;" ::: "memory");
                    kl = lds32(stash + 512);
                } else {
                    const uint4 sg = lds128(sb + SM_SG + par * 16);
                    const int e = max(max(sg.x, sg.y), sg.z), d = e - (sg.w >> 9 ? SIG_HI : SIG_LO);
                    const bool moving = d > 2 || d < -2 || s == 0;
                    uint32_t se = sg.w & 255u;
                    if (e) se = min(max((int)se + (moving ? SIG_HI : SIG_LO) - e, 127 - SIG_LIM), 127 + SIG_LIM) | (moving << 9);
                    sts32(sb + SM_SG + 12 + (par ^ 1) * 16, se);
                    sig = __uint_as_float(se << 23);
                }
                if (!M && K_PRE < 8) {
                    const uint32_t kl = lds32(stash + 512);
                    bar_sync(BAR_PRO, (PRO_V ? 256 : 32 * nqk) + 64);
                    load_k(par, kl, ic<K_PRE>(), ic<8>());
                }
                const uint32_t pst = (launder(l16) >> 2) + launder(sb + SM_P + a * 256);
                mbar_wait(bEX + 8 * par, (s >> 1) & 1);
                if (!M) {
                    uint32_t b[4][4];
                    ldsm16_t(b, exl);
                    float c[4][4];
                    #pragma unroll
                    for (int j = 0; j < 4; j++) { c[j][0] = c[j][1] = c[j][2] = c[j][3] = 0.f; }
                    #pragma unroll
                    for (int j = 0; j < 4; j++) { mma16816(c[(2 * j) & 3], kf[2 * j], b[j][0], b[j][1]); mma16816(c[(2 * j + 1) & 3], kf[2 * j + 1], b[j][2], b[j][3]); }
                    sl = scale_bf2(pack_bf16((c[0][0] + c[1][0]) + (c[2][0] + c[3][0]), (c[0][1] + c[1][1]) + (c[2][1] + c[3][1])));
                    sh = scale_bf2(pack_bf16((c[0][2] + c[1][2]) + (c[2][2] + c[3][2]), (c[0][3] + c[1][3]) + (c[2][3] + c[3][3])));
                } else {
                    float c[4][4];
                    #pragma unroll
                    for (int j = 0; j < 4; j++) { c[j][0] = c[j][1] = c[j][2] = c[j][3] = 0.f; }
                    uint32_t k[4][4], b[4][4];
                    #pragma unroll
                    for (int j = 0; j < 4; j++) { ldsm_x4_t(k[j], kl + exu + 512 * j); ldsm_x4_t(b[j], exl + 512 * j); }
                    if (PUB_W == 0) publish();
                    sched_fence<9>(nv);
                    #pragma unroll
                    for (int j = 0; j < 4; j++) { mma16816(c[2 * (j & 1)], k[j], b[j][0], b[j][1]); mma16816(c[2 * (j & 1) + 1], k[j], b[j][2], b[j][3]); }
                    sched_fence<14>(nv);
                    w2 = lds32(stash + 516);
                    sh = sl = scale_bf2(pack_bf16((c[0][0] + c[1][2]) + (c[2][0] + c[3][2]), (c[0][1] + c[1][3]) + (c[2][1] + c[3][3])));
                }
                sts32(pst, pack_bf16(ex2(bf_lo(sl) * LOG2E), ex2(bf_hi(sl) * LOG2E)));
                if (!M) sts32(pst + 128, pack_bf16(ex2(bf_lo(sh) * LOG2E), ex2(bf_hi(sh) * LOG2E)));
                if (M) {
                    #pragma unroll
                    for (int i = M_RES; i < 8; i++) ldsm_x4_t(kf[i], w2 + i * 1024);
                }
                const uint32_t big = bar_red_or(BAR_P, 352, ((maxabs_bf2(sl, sh) & 0x7fff7fffu) + 0x3ddf3ddfu) & 0x80008000u);
                float l0[4], l1[4], l2[4];
                uint32_t pb[4], pm;
                if (!M) { ldsm_x4_t(pb, l16 + sb + SM_P); pm = ldsm_x1_t(l16 + sb + SM_P + 512); }
                if (__builtin_expect(big, 0)) {
                    uint32_t m2 = max_bf2(sl, sh);
                    m2 = max_bf2(m2, __shfl_xor_sync(0xffffffffu, m2, 4));
                    m2 = max_bf2(m2, __shfl_xor_sync(0xffffffffu, m2, 8));
                    m2 = max_bf2(m2, __shfl_xor_sync(0xffffffffu, m2, 16));
                    const uint32_t lq = pin(l16);
                    if (lq < 64) sts32(lq + sb + SM_P + 768 + a * 4, m2);
                    bar_sync(BAR_S, 96);
                    const uint4 m = lds128(sb + SM_P + 768 + (lq & 0x30));
                    m2 = max_bf2(max_bf2(m.x, m.y), m.z);
                    const float ml = -bf_lo(m2) * LOG2E, mh = -bf_hi(m2) * LOG2E;
                    sts32(pst, pack_bf16(ex2(fmaf(bf_lo(sl), LOG2E, ml)), ex2(fmaf(bf_hi(sl), LOG2E, mh))));
                    if (!M) sts32(pst + 128, pack_bf16(ex2(fmaf(bf_lo(sh), LOG2E, ml)), ex2(fmaf(bf_hi(sh), LOG2E, mh))));
                    bar_sync(BAR_P2, 352);
                    if (!M) { ldsm_x4_t(pb, l16 + sb + SM_P); pm = ldsm_x1_t(l16 + sb + SM_P + 512); }
                }
                if (!M) {
                    const uint32_t ONE = 0x3F803F80u;
                    #pragma unroll
                    for (int i = 0; i < 4; i++) l0[i] = l1[i] = l2[i] = 0.f;
                    mma16816r(l0, ONE, ONE, ONE, ONE, pb[0], pb[1]);
                    mma16816r(l1, ONE, ONE, ONE, ONE, pb[2], pb[3]);
                    mma1688(l2, ONE, ONE, pm);
                }
                const uint32_t ll = launder(l16), ila = sb + SM_IL + (ll >> 2), so = SLOT_OFF(launder(s) + 1);
                if (!M) {
                    const float sil = rcp_approx((l0[0] + l1[0]) + l2[0]) * sig, sih = rcp_approx((l0[1] + l1[1]) + l2[1]) * sig;
                    sts32(ila + a * 128, __float_as_uint(a ? sih : sil));
                    stage_w<true>(wo, l16 + sb + SM_O, 12 * r + warp, so, ll, ll + (sb + SM_FB + warp * 512), nv, 0u, sil, sih, [&] { if (TP_E || V_EARLY) bar_arrive(BAR_V, 384); });
                } else {
                    if (PUB_W == 1) { asm volatile("cp.async.bulk.wait_group 0;" ::: "memory"); publish(); }
                    const uint32_t sa = launder((ll & 0x100u) + ((ll & 0xf0u) >> 1) + (send_ua(12 * r + 10) + so)), sb_ = launder(((ll >> 4) & 28u) + (send_ub(12 * r + 10) + so)), tl = (ll >> 4) & 3u;
                    bar_sync_p(BAR_O, 352, (kf[6][0] ^ kf[7][0] ^ sa ^ sb_) & nv);
                    float c[4][4], il, ih;
                    #pragma unroll
                    for (int i = 0; i < 4; i++) c[i][0] = c[i][1] = c[i][2] = c[i][3] = 0.f;
                    uint32_t b[4][4];
                    #pragma unroll
                    for (int j = 0; j < 4; j++) ldsm_x4_t(b[j], l16 + sb + SM_O + 512 * (3 - j));
                    sched_fence<11>(nv);
                    #pragma unroll
                    for (int j = 0; j < 4; j++) {
                        if (j == 2) { sched_fence<10>(nv); lds_il(il, ih, ila); }
                        mma16816(c[0], wo[6 - 2 * j], b[j][0], b[j][1]); mma16816(c[2], kf[6 - 2 * j], b[j][0], b[j][1]);
                        mma16816(c[1], wo[7 - 2 * j], b[j][2], b[j][3]); mma16816(c[3], kf[7 - 2 * j], b[j][2], b[j][3]);
                    }
                    asm volatile("" : "+f"(c[0][0]), "+f"(c[1][0]), "+f"(c[2][0]), "+f"(c[3][0]));
                    if (TP_E || V_EARLY) { if (__builtin_expect(s == 0, 0)) mbar_wait(bX, 1); bar_arrive(BAR_V, 384); }
                    send_tile<0, 0>((c[0][0] + c[1][0]) * il, (c[0][1] + c[1][1]) * ih, (c[0][2] + c[1][2]) * il, (c[0][3] + c[1][3]) * ih, sa, sb_, tl == 2, ll + (sb + SM_FB + 10 * 512));
                    send_tile<1024, 256>((c[2][0] + c[3][0]) * il, (c[2][1] + c[3][1]) * ih, (c[2][2] + c[3][2]) * il, (c[2][3] + c[3][3]) * ih, sa, sb_, tl == 3, ll + (sb + SM_FB + 11 * 512));
                    if (!TP_E && !V_EARLY && s == 0) mbar_wait(bX, 1);
                }
                };
                if (a < 2) first_half(ic<0>()); else first_half(ic<1>());
                STAMP(warp);
                if (!TP_E && !V_EARLY) bar_arrive(BAR_V, 384);
                {
                    const uint4 ad = lds128(stash);
                    const uint32_t kl = lds32(stash + 512), so = SLOT_OFF(launder(s) + 1);
                    { int it = 0; do { asm volatile("ld.volatile.shared.u32 %0, [%1];" : "=r"(tg) : "r"(sb + SM_SG + 36) : "memory"); } while ((tg & 1u) == (uint32_t)par && ++it < SPIN_LIMIT * 16); }
                    if (K_POS == 0 && a < 2) load_k(par ^ 1, kl, ic<0>(), ic<K_PRE>());
                    const uint32_t alo = (uint32_t)(uint64_t)g_acc + so;
                    const unsigned char* pm = (const unsigned char*)(((uint64_t)g_acc & ~0xffffffffull) | (ad.x + alo));
                    const unsigned char* px = (const unsigned char*)(((uint64_t)g_acc & ~0xffffffffull) | (ad.y + alo));
                    uint4 v[6]; uint32_t x[3];
                    const bool up = l16 & 256, odd = l16 & 16;
                    STAMP(16 + a); STAMPV(30, tg);
                    wait_gtime(tg);
                    #pragma unroll
                    for (int j = 0; j < 6; j++) v[j] = ld_relaxed128((const uint4*)(pm + 2048 * j));
                    #pragma unroll
                    for (int j = 0; j < 3; j++) x[j] = ld_relaxed32((const uint32_t*)(px + 2048 * j));
                    bar_sync(BAR_FB, 352);
                    STAMP(19 + a);
                    if (K_POS == 1 && a < 2) load_k(par ^ 1, kl, ic<0>(), ic<K_PRE>());
                    if (LD_FENCE) sched_fence<16>(nv);
                    uint32_t cnt[2] = {~0u, ~0u};
                    any[0] = any[1] = 0u; ax = x[0] | x[1] | x[2]; cx = x[0] & x[1] & x[2];
                    const uint32_t xw0 = h2_to_bf2(__byte_perm(x[0], x[1], 0x5410)), xw1 = h1_to_bf(x[2]);
                    auto group = [&](auto jj) {
                        constexpr int j = jj.value;
                        const uint32_t wy = h2_to_bf2(v[j].y), ww = h2_to_bf2(v[j].w);
                        sts64(ad.z + 512 * j, h2_to_bf2(v[j].x), h2_to_bf2(v[j].z));
                        sts64(ad.z + 512 * j + 128, wy, ww);
                        any[j & 1] = (any[j & 1] | v[j].x | v[j].y) | v[j].z | v[j].w;
                        cnt[j & 1] &= up ? ww : wy;
                        if (CV_FENCE & (1 << j)) { sts32_p(cnt[j & 1], any[j & 1], nv); sched_fence<17 + j>(nv); }
                    };
                    group(ic<0>()); group(ic<1>()); group(ic<2>()); group(ic<3>()); group(ic<4>()); group(ic<5>());
                    sts16(ad.w, (uint16_t)xw0); sts16(ad.w + 1024, (uint16_t)(xw0 >> 16)); sts16(ad.w + 2048, (uint16_t)xw1);
                    c = odd ? cnt[1] : cnt[0];
                    c = (c & (c >> 1)) >> 4;
                    ax |= any[0] | any[1];
                    bad = __any_sync(0xffffffffu, (((ax & 0x40004000u) | (~(c & cx) & (ACC_FULL << 16))) != 0u) | ((ax & 0x20002000u) == 0u));
                    STAMP(22 + a); STAMPV(27 + a, bad);
                    bar_sync_p(BAR_MEM, 352, bad);
                }
              } while (++sn < NSEG - 1 && !bad);
                {
                    if (bad) {
                        const int s = sn - 1, par = s & 1;
                        const uint32_t lq = pin(l16);
                        const bool up = lq & 256, odd = lq & 16;
                        uint32_t x[3];
                        int it = 0;
                        while (__any_sync(0xffffffffu, !(c & cx & (ACC_FULL << 16))) && ++it < SPIN_LIMIT) {
                            const uint4 ad = lds128(stash);
                            const uint32_t so = SLOT_OFF(launder(s) + 1), o = __shfl_xor_sync(0xffffffffu, c, 1);
                            const uint32_t again[2] = {~(odd ? o : c) & (ACC_FULL << 16), ~(odd ? c : o) & (ACC_FULL << 16)};
                            #pragma unroll
                            for (int j = 0; j < 3; j++) x[j] = ld_relaxed32((const uint32_t*)(g_acc + (ad.y + so + 2048 * j)));
                            uint4 u[6];
                            #pragma unroll
                            for (int j = 0; j < 6; j++) { u[j] = make_uint4(0u, 0u, 0u, 0u); ld_relaxed128_p(u[j], (const uint4*)(g_acc + (ad.x + so + 2048 * j)), again[j & 1]); }
                            #pragma unroll
                            for (int p = 0; p < 2; p++) if (again[p]) {
                                any[p] = 0u;
                                #pragma unroll
                                for (int j = p; j < 6; j += 2) {
                                    sts64(ad.z + 512 * j, h2_to_bf2(u[j].x), h2_to_bf2(u[j].z)); sts64(ad.z + 512 * j + 128, h2_to_bf2(u[j].y), h2_to_bf2(u[j].w));
                                    any[p] |= u[j].x | u[j].y | u[j].z | u[j].w;
                                }
                                const uint32_t cw = launder(u[p].w & u[p + 2].w & u[p + 4].w), cy = launder(u[p].y & u[p + 2].y & u[p + 4].y);
                                if (odd == p) c = up ? cw : cy;
                            }
                            __syncwarp();
                            #pragma unroll
                            for (int j = 0; j < 3; j++) sts16(ad.w + 1024 * j, (uint16_t)h1_to_bf(x[j]));
                            cx = x[0] & x[1] & x[2]; ax = x[0] | x[1] | x[2] | any[0] | any[1];
                        }
                        if (__any_sync(0xffffffffu, ((ax & 0x40004000u) != 0u) | ((ax & 0x20002000u) == 0u))) {
                            uint32_t m = 0;
                            #pragma unroll
                            for (int j = 0; j < 6; j++) { const uint4 u = lds128(lq + sb + SM_MEM + a * 3072 + 512 * j); m = maxabs_bf2(maxabs_bf2(m, maxabs_bf2(u.x, u.y)), maxabs_bf2(u.z, u.w)); }
                            uint32_t res = __reduce_max_sync(0xffffffffu, max(m & 0x7fffu, (m >> 16) & 0x7fffu));
                            if (res - SIG_LOW >= 0x7f80u - SIG_LOW) {
                                const uint32_t tag = lds32(stash + 524) + s;
                                if (a == r) {
                                    #pragma unroll 1
                                    for (int i = 0; i < 12; i++) st_relaxed128(&g_fb[a][h][i * 32 + (lq >> 4)], lds128(lq + sb + SM_FB + i * 512));
                                    __threadfence();
                                    __syncwarp();
                                    st_relaxed32_p(&g_fbf[a][h], tag, lq);
                                }
                                it = 0;
                                while (__any_sync(0xffffffffu, ld_relaxed32(&g_fbf[a][lq >> 4]) != tag) && ++it < SPIN_LIMIT) {}
                                __threadfence();
                                m = 0;
                                #pragma unroll 1
                                for (int i = 0; i < 12; i++) {
                                    float c0 = 0.f, c1 = 0.f, c2 = 0.f, c3 = 0.f;
                                    #pragma unroll 4
                                    for (int hh = 0; hh < 32; hh++) {
                                        const uint4 u = ld_relaxed128(&g_fb[a][hh][i * 32 + (lq >> 4)]);
                                        c0 += __uint_as_float(u.x); c1 += __uint_as_float(u.y); c2 += __uint_as_float(u.z); c3 += __uint_as_float(u.w);
                                    }
                                    const uint32_t w0 = pack_bf16(c0, c1), w1 = pack_bf16(c2, c3), d = sb + SM_MEM + a * 3072 + i * 256 + (lq >> 2);
                                    sts32(d, w0); sts32(d + 128, w1);
                                    m = maxabs_bf2(m, maxabs_bf2(w0, w1));
                                }
                                res = __reduce_max_sync(0xffffffffu, max(m & 0x7fffu, (m >> 16) & 0x7fffu));
                            }
                            sts32(sb + SM_SG + (par ^ 1) * 16 + a * 4, max(res >> 7, 1u));
                        }
                        bar_sync(BAR_MEM, 352);
                    }
                }
            }
        } else {
            cluster_arrive_rx();
            const uint32_t l16 = pin(lane * 16);
            bf16* dst = g_otok + h * 4096 + (r ? 1024 : 0) + (r == 2 ? 2048 : 0);
            {
                #pragma unroll
                for (int sg = 0; sg < 2; sg++) {
                    bar_sync(BAR_X0 + sg, 288);
                    if (lane == 0) {
                        mbar_expect_tx(bX + 8 * sg, XBUF);
                        #pragma unroll
                        for (int c = 0; c < 3; c++)
                            asm volatile("cp.async.bulk.tensor.3d.shared::cluster.global.mbarrier::complete_tx::bytes [%0], [%1, {%3, %4, %5}], [%2];"
                                :: "r"(sb + SM_X + sg * XBUF + c * 12288), "l"(&tmx), "r"(bX + 8 * sg), "r"(0), "r"(sg * SEG), "r"(3 * c) : "memory");
                    }
                    __syncwarp();
                }
                if (lane == 0) load_w(40, 54);
                __syncwarp();
                cluster_wait();
            }
            __syncwarp();
            auto t_loop = [&](auto mtile) {
            constexpr int MT = mtile.value;
            uint32_t q[8][4], pa[5][2], bv[8][4], mt; float st[2];
            code_pad<MT ? PAD_T1 : PAD_T0>(nv);
            mbar_wait(bTOK, 0);
            #pragma unroll 1
            for (int s = 0; s < NSEG; s++) {
                const int par = s & 1;
                const uint32_t tok = launder(sb + SM_TOK + par * TOKBUF), exl = l16 + launder(sb + SM_EX + par * EXBUF);
                const int ln = launder(l16) >> 4;
                auto announce = [&] {
                    if (s > 0) {
                        if (lane == 0) {
                            asm volatile("cp.async.bulk.wait_group 0;" ::: "memory");
                            st_relaxed32(&g_flag[s - 1][blockIdx.x], epoch);
                        }
                        __syncwarp();
                        if (lane == 0 && blockIdx.x == 0) GT(40, s);
                    }
                };
                if (ANN_POS == 0) announce();
                tok_part1<MT>(tok, MT ? r - 1 : 0, ln, q, pa, bv, mt, st);
                if (ANN_POS == 1) announce();
                STAMP(25);
                mbar_wait(bEX + 8 * par, (s >> 1) & 1);
                STAMP(26);
                const uint32_t tex = gtime_lo();
                auto duty = [&] { if (s + 1 < NSEG) {
                    asm volatile("{\n.reg .pred p;\nelect.sync _|p, 0xffffffff;\n"
                                 "@p cp.async.bulk.shared::cluster.global.mbarrier::complete_tx::bytes [%0], [%1], 384, [%2];\n"
                                 "@p mbarrier.arrive.expect_tx.shared.b64 _, [%2], 384;\n}\n"
                        :: "r"(sb + SM_TS), "l"(g_ts), "r"(bFREE) : "memory");
                    auto issue_x = [&](int sg) {
                        asm volatile("{\n.reg .pred p, q;\nelect.sync _|p, 0xffffffff;\nsetp.eq.and.u32 q, %5, 3, p;\n"
                                     "@p cp.async.bulk.tensor.3d.shared::cluster.global.mbarrier::complete_tx::bytes.multicast::cluster [%0], [%1, {%3, %4, %5}], [%2], %6;\n"
                                     "@q cp.async.bulk.tensor.3d.shared::cluster.global.mbarrier::complete_tx::bytes.multicast::cluster [%7], [%1, {%3, %4, %3}], [%2], %6;\n}\n"
                            :: "r"(sb + SM_X + (sg & 1) * XBUF + r * 12288), "l"(&tmx), "r"(bX + 8 * (sg & 1)), "r"(0), "r"(sg * SEG), "r"(3 * r), "h"((unsigned short)7), "r"(sb + SM_X + (sg & 1) * XBUF) : "memory");
                    };
                    if (MT) {
                        if (__builtin_expect(s == 0, 0)) issue_x(2);
                        if (s + 3 < NSEG) issue_x(s + 3);
                    }
                } };
                auto pace = [&] { if (s + 1 < NSEG) {
                    mbar_wait2(bFREE, par, bTOK + 8 * (par ^ 1), ((s + 1) >> 1) & 1);
                    const uint4 ts = lds128(sb + SM_TS + min(launder(l16), 368u));
                    const uint32_t b = tex - 1150, m = __reduce_max_sync(0xffffffffu, max(max(ts.x - b, ts.y - b), max(ts.z - b, ts.w - b)));
                    asm volatile("st.volatile.shared.u32 [%0], %1;" :: "r"(sb + SM_SG + 36), "r"(((b + (s == 0 ? 0u : min(m, 1150u - TS_CAP) + G1_NS)) & ~1u) | (par ^ 1)) : "memory");
                } };
                auto wait_v = [&] {
                    mbar_wait(bEV + 8 * par, (s >> 1) & 1); };
                tok_part2<MT>(exl, sb + SM_OST, MT ? r - 1 : 0, launder(l16) >> 4, q, pa, bv, mt, st, s < NSEG - 1, wait_v, duty, pace, nv);
                STAMP(11);
                fence_async_smem();
                __syncwarp();
                if (lane == 0) {
                    asm volatile("cp.async.bulk.global.shared::cta.bulk_group [%0], [%1], 2048;" :: "l"(dst), "r"(sb + SM_OST) : "memory");
                    if (!MT) asm volatile("cp.async.bulk.global.shared::cta.bulk_group [%0], [%1], 2048;" :: "l"(dst + 2048), "r"(sb + SM_OST + 2048) : "memory");
                    asm volatile("cp.async.bulk.commit_group;" ::: "memory");
                }
                __syncwarp();
                dst += SEG * NH * DH;
            }
            };
            if (r == 0) t_loop(ic<0>()); else t_loop(ic<1>());
            if (lane == 0) {
                asm volatile("cp.async.bulk.wait_group 0;" ::: "memory");
                st_relaxed32(&g_flag[NSEG - 1][blockIdx.x], epoch);
                if (blockIdx.x == 0) GT(40, NSEG);
            }
            __syncwarp();
        }
        cluster_arrive(); cluster_wait();
    }
}
#define SD_THREADS 384
#define SD_CTAS  36
#define BT_RS    4624
#define SD_BT    0
#define SD_STG   74752
#define SD_EF    (SD_STG + 57344)
#define SD_BC    (SD_STG)
#define KSLOTS   5
#define BC_BYTES 10240
#define BC_LBO   1280
#define SD_KP    (SD_STG + 90112)
#define SD_Q0    205824
#define SD_Q1    (SD_STG + 111616)
#define SD_OST   222720
#define SD_XCH   (SD_Q0 + 8192)
#define SD_BAR   224256
#define SD_TOTAL 224768
#define SD_SPIN  (1 << 22)
#define PART_SLOTS 8
#define SD_GO 0
#define SD_REG 200
#define SD_WAIT 6000
#define SD_P2 150
#define SD_P3 300
#define SD_GAP 0
#define SD_RUSH 44
#define SD_P1 300

__device__ uint4 g_part[SD_CTAS][PART_SLOTS][4][8][32];
__device__ __align__(16) unsigned int g_gate[S_LEN];

struct cplx { float r, i; };
__device__ __forceinline__ cplx cmul(cplx a, cplx b) { cplx c; c.r = fmaf(a.r, b.r, -a.i * b.i); c.i = fmaf(a.r, b.i, a.i * b.r); return c; }
__device__ __forceinline__ cplx cexp_(float xr, float xi) {
    const float m = ex2(xr * 1.4426950408889634f);
    const float k = rintf(xi * 0.15915494309189535f);
    const float r = fmaf(k, 1.7484555314695172e-7f, fmaf(k, -6.2831854820251465f, xi));
    cplx o; o.r = m * __cosf(r); o.i = m * __sinf(r); return o;
}
__device__ __forceinline__ void mma_f16(float (&c)[4], const uint32_t (&a)[4], uint32_t b0, uint32_t b1) {
    asm("mma.sync.aligned.m16n8k16.row.col.f32.f16.f16.f32 {%0,%1,%2,%3}, {%4,%5,%6,%7}, {%8,%9}, {%0,%1,%2,%3};"
        : "+f"(c[0]), "+f"(c[1]), "+f"(c[2]), "+f"(c[3]) : "r"(a[0]), "r"(a[1]), "r"(a[2]), "r"(a[3]), "r"(b0), "r"(b1));
}
__device__ __forceinline__ uint32_t mul_bf2(uint32_t a, uint32_t b) { uint32_t r; asm("mul.rn.bf16x2 %0, %1, %2;" : "=r"(r) : "r"(a), "r"(b)); return r; }
__device__ __forceinline__ void mbar_wait_long(uint32_t a, uint32_t parity) { int it = 0; while (!mbar_try(a, parity) && ++it < SD_SPIN) {} }
__device__ __forceinline__ uint16_t lds16(uint32_t a) { uint16_t v; asm volatile("ld.shared.u16 %0, [%1];" : "=h"(v) : "r"(a) : "memory"); return v; }
__device__ __forceinline__ void wg_wait1() { asm volatile("wgmma.wait_group.sync.aligned 1;" ::: "memory"); }
__device__ __forceinline__ void tma2d(uint32_t dst, const CUtensorMap* tm, uint32_t bar, int c0, int c1) {
    asm volatile("cp.async.bulk.tensor.2d.shared::cluster.global.mbarrier::complete_tx::bytes [%0], [%1, {%3, %4}], [%2];"
        :: "r"(dst), "l"(tm), "r"(bar), "r"(c0), "r"(c1) : "memory");
}
__device__ __forceinline__ void wgmma_conv(float (&d)[32], uint32_t a0, uint32_t a1, uint32_t a2, uint32_t a3, uint64_t desc) {
    asm volatile("{\n.reg .pred p;\nsetp.ne.b32 p, 1, 0;\n"
        "wgmma.mma_async.sync.aligned.m64n64k16.f32.bf16.bf16 {%0,%1,%2,%3,%4,%5,%6,%7,%8,%9,%10,%11,%12,%13,%14,%15,%16,%17,%18,%19,%20,%21,%22,%23,%24,%25,%26,%27,%28,%29,%30,%31}, {%32,%33,%34,%35}, %36, p, 1, 1, 0;\n}\n"
        : "+f"(d[0]), "+f"(d[1]), "+f"(d[2]), "+f"(d[3]), "+f"(d[4]), "+f"(d[5]), "+f"(d[6]), "+f"(d[7]), "+f"(d[8]), "+f"(d[9]), "+f"(d[10]), "+f"(d[11]), "+f"(d[12]), "+f"(d[13]), "+f"(d[14]), "+f"(d[15]), "+f"(d[16]), "+f"(d[17]), "+f"(d[18]), "+f"(d[19]), "+f"(d[20]), "+f"(d[21]), "+f"(d[22]), "+f"(d[23]), "+f"(d[24]), "+f"(d[25]), "+f"(d[26]), "+f"(d[27]), "+f"(d[28]), "+f"(d[29]), "+f"(d[30]), "+f"(d[31])
        : "r"(a0), "r"(a1), "r"(a2), "r"(a3), "l"(desc));
}
__device__ __forceinline__ void wgmma_conv(float (&d)[24], uint32_t a0, uint32_t a1, uint32_t a2, uint32_t a3, uint64_t desc) {
    asm volatile("{\n.reg .pred p;\nsetp.ne.b32 p, 1, 0;\n"
        "wgmma.mma_async.sync.aligned.m64n48k16.f32.bf16.bf16 {%0,%1,%2,%3,%4,%5,%6,%7,%8,%9,%10,%11,%12,%13,%14,%15,%16,%17,%18,%19,%20,%21,%22,%23}, {%24,%25,%26,%27}, %28, p, 1, 1, 0;\n}\n"
        : "+f"(d[0]), "+f"(d[1]), "+f"(d[2]), "+f"(d[3]), "+f"(d[4]), "+f"(d[5]), "+f"(d[6]), "+f"(d[7]), "+f"(d[8]), "+f"(d[9]), "+f"(d[10]), "+f"(d[11]), "+f"(d[12]), "+f"(d[13]), "+f"(d[14]), "+f"(d[15]), "+f"(d[16]), "+f"(d[17]), "+f"(d[18]), "+f"(d[19]), "+f"(d[20]), "+f"(d[21]), "+f"(d[22]), "+f"(d[23])
        : "r"(a0), "r"(a1), "r"(a2), "r"(a3), "l"(desc));
}
__device__ __forceinline__ void wgmma_conv(float (&d)[16], uint32_t a0, uint32_t a1, uint32_t a2, uint32_t a3, uint64_t desc) {
    asm volatile("{\n.reg .pred p;\nsetp.ne.b32 p, 1, 0;\n"
        "wgmma.mma_async.sync.aligned.m64n32k16.f32.bf16.bf16 {%0,%1,%2,%3,%4,%5,%6,%7,%8,%9,%10,%11,%12,%13,%14,%15}, {%16,%17,%18,%19}, %20, p, 1, 1, 0;\n}\n"
        : "+f"(d[0]), "+f"(d[1]), "+f"(d[2]), "+f"(d[3]), "+f"(d[4]), "+f"(d[5]), "+f"(d[6]), "+f"(d[7]), "+f"(d[8]), "+f"(d[9]), "+f"(d[10]), "+f"(d[11]), "+f"(d[12]), "+f"(d[13]), "+f"(d[14]), "+f"(d[15])
        : "r"(a0), "r"(a1), "r"(a2), "r"(a3), "l"(desc));
}
__device__ __forceinline__ void wgmma_conv(float (&d)[8], uint32_t a0, uint32_t a1, uint32_t a2, uint32_t a3, uint64_t desc) {
    asm volatile("{\n.reg .pred p;\nsetp.ne.b32 p, 1, 0;\n"
        "wgmma.mma_async.sync.aligned.m64n16k16.f32.bf16.bf16 {%0,%1,%2,%3,%4,%5,%6,%7}, {%8,%9,%10,%11}, %12, p, 1, 1, 0;\n}\n"
        : "+f"(d[0]), "+f"(d[1]), "+f"(d[2]), "+f"(d[3]), "+f"(d[4]), "+f"(d[5]), "+f"(d[6]), "+f"(d[7])
        : "r"(a0), "r"(a1), "r"(a2), "r"(a3), "l"(desc));
}
template<int NR> __device__ __forceinline__ void conv_mma(float (&acc)[NR], const uint32_t (&R)[16], uint32_t dlo) {
    #pragma unroll
    for (int q = 0; q < 4; q++)
        wgmma_conv(acc, R[4 * q], R[4 * q + 1], R[4 * q + 2], R[4 * q + 3], (uint64_t)(dlo + (2 * (3 - q)) * (BC_LBO >> 4)) | ((uint64_t)8 << 32));
}
__device__ __forceinline__ void conv_ld(uint32_t (&R)[16], uint32_t a) {
    #pragma unroll
    for (int q = 0; q < 4; q++) { const uint2 u = lds64(a + 64 * (2 * q + 1)); R[4 * q] = u.x; R[4 * q + 1] = u.y; }
}
__device__ __forceinline__ void conv_fix(uint32_t (&R)[16], uint32_t& carry) {
    #pragma unroll
    for (int q = 0; q < 4; q++) {
        asm volatile("mov.b32 %0, %1;" : "=r"(R[4 * q + 2]) : "r"(q ? R[4 * q - 3] : carry));
        asm volatile("mov.b32 %0, %1;" : "=r"(R[4 * q + 3]) : "r"(R[4 * q]));
    }
    asm volatile("mov.b32 %0, %1;" : "=r"(carry) : "r"(R[13]));
}
template<int A> __device__ __forceinline__ void conv_group(float (&acc)[32 - 8 * A], uint32_t (&R)[4][16], uint32_t& carry, uint32_t pb, uint32_t dlo) {
    #pragma unroll
    for (int e = 0; e < 8; e += 2) {
        const int dl = 8 * A + e;
        conv_fix(R[dl & 3], carry); conv_fix(R[(dl + 1) & 3], carry);
        wg_fence(); conv_mma(acc, R[dl & 3], dlo + 16 - 2 * e); conv_mma(acc, R[(dl + 1) & 3], dlo + 14 - 2 * e); wg_commit();
        wg_wait1();
        if (dl + 2 < 32) { conv_ld(R[(dl + 2) & 3], pb + (dl + 2) * 512); conv_ld(R[(dl + 3) & 3], pb + (dl + 3) * 512); }
    }
}

__global__ void __launch_bounds__(SD_THREADS, 1)
side_kernel(const __grid_constant__ CUtensorMap tmw, const bf16* __restrict__ x,
            const bf16* __restrict__ log_A_real, const bf16* __restrict__ A_imag, const bf16* __restrict__ C_real, const bf16* __restrict__ C_imag,
            const bf16* __restrict__ log_dt, const bf16* __restrict__ D_skip, const bf16* __restrict__ gate_w, bf16* __restrict__ out) {
    extern __shared__ __align__(1024) unsigned char smem[];
    const uint32_t sb = smem_u32(smem);
    const int tid = threadIdx.x, lane = tid & 31;
    const int warp = __shfl_sync(0xffffffffu, tid >> 5, 0);
    const int g = lane >> 2, t = lane & 3, mi = lane >> 3, r8 = lane & 7;
    const bool sh = blockIdx.x < 32;
    const int d0 = blockIdx.x * 16;
    const uint32_t b0_ = sb + SD_BAR, bKF = b0_ + 384, bKE = bKF + 8 * KSLOTS, bWO = b0_ + 48, bFULL = b0_ + 56, bEMPTY = b0_ + 88, bEPI = b0_ + 120, bPRT = b0_ + 152, bGO = b0_ + 184, bCH = b0_ + 256;
    const unsigned epoch = ld_relaxed32(&g_epoch);
    if (tid == 0) GT(blockIdx.x, 0);
    if (tid == 0) {
        for (int i = 0; i < 2 * KSLOTS; i++) mbar_init(bKF + 8 * i, 128);
        mbar_init(bWO, 1);
        for (int i = 0; i < 16; i++) mbar_init(bCH + 8 * i, 1);
        for (int i = 0; i < 4; i++) { mbar_init(bFULL + 8 * i, 1); mbar_init(bEMPTY + 8 * i, sh ? 256 : 128); mbar_init(bEPI + 8 * i, 4); mbar_init(bPRT + 8 * i, 8); mbar_init(bGO + 8 * i, 1); }
        asm volatile("fence.mbarrier_init.release.cluster;" ::: "memory");
    }
    for (int i = tid; i < KSLOTS * 8 * 16; i += SD_THREADS) sts128(sb + SD_BC + (i >> 4) * BC_LBO + (i & 15) * 16, make_uint4(0, 0, 0, 0));
    if (tid < 128) sts64(sb + ((tid & 64) ? SD_Q1 : SD_Q0) + (tid & 63) * 8, 0u, 0u);
    fence_async_smem();
    __syncthreads();

    if (warp < 8) {
        asm volatile("setmaxnreg.inc.sync.aligned.u32 %0;" :: "n"(SD_REG));
        const int wg = warp >> 2, w = warp & 3, t128 = tid & 127;
        if (SD_WAIT) __nanosleep(SD_WAIT);
        {
            #pragma unroll 1
            for (int i = 0; i < 4; i++) {
                const int tp = tid + 256 * i;
                const bf16* xp = x + (size_t)(2 * tp) * DM + d0;
                const uint4 v0 = __ldg((const uint4*)xp), v1 = __ldg((const uint4*)(xp + 8)), v2 = __ldg((const uint4*)(xp + DM)), v3 = __ldg((const uint4*)(xp + DM + 8));
                const uint32_t a = sb + SD_BT + (tp >> 5) * 144 + (tp & 31) * 4;
                const uint32_t lo[8] = {v0.x, v0.y, v0.z, v0.w, v1.x, v1.y, v1.z, v1.w};
                const uint32_t hi[8] = {v2.x, v2.y, v2.z, v2.w, v3.x, v3.y, v3.z, v3.w};
                #pragma unroll
                for (int j = 0; j < 8; j++) { sts32(a + (2 * j) * BT_RS, __byte_perm(lo[j], hi[j], 0x5410)); sts32(a + (2 * j + 1) * BT_RS, __byte_perm(lo[j], hi[j], 0x7632)); }
                if (SD_GAP) __nanosleep(SD_GAP);
            }
        }
        bar_sync(1, 256);
        if (tid == 0) GT(blockIdx.x, 65);
        const uint32_t pa = sb + (wg ? SD_Q1 : SD_Q0);
        const uint32_t pb = pa + (72 + 16 * w - 56 + g - 2 * t) * 8;
        for (int c = wg; c < 16; c += 2) {
            const uint32_t bt = sb + SD_BT + c * BT_RS;
            bar_sync(2 + wg, 128);
            #pragma unroll
            for (int it = 0; it < 9; it++) {
                const int k = it < 8 ? t128 + 128 * it : t128 - 4;
                if (it < 8 || t128 < 4) {
                    auto word = [&](int j) { return j >= 0 ? lds32(bt + (j >> 5) * 144 + (j & 31) * 4) : 0u; };
                    const uint32_t c0 = word(k), p0 = word(k - 1), c1 = word(k + 4), p1 = word(k + 3);
                    sts128(pa + (72 + 2 * k) * 8, make_uint4(__byte_perm(c0, p0, 0x7610), __byte_perm(c1, p1, 0x7610), __byte_perm(c0, c0, 0x1032), __byte_perm(c1, c1, 0x1032)));
                }
            }
            bar_sync(2 + wg, 128);
            const int slot = c % KSLOTS;
            float acc[32];
            #pragma unroll
            for (int i = 0; i < 32; i++) acc[i] = 0.f;
            uint32_t R[4][16];
            uint32_t carry = lds32(pb);
            conv_ld(R[0], pb); conv_ld(R[1], pb + 512);
            const uint32_t dlo = (((sb + SD_BC + slot * BC_BYTES) & 0x3FFFF) >> 4) | ((BC_LBO >> 4) << 16);
            mbar_wait_long(bKF + 8 * slot, (c / KSLOTS) & 1);
            const float ds = bf(D_skip[d0 + c]);
            auto fin = [&](const float* a8, int q0) {
                #pragma unroll
                for (int q = 0; q < 2; q++)
                    #pragma unroll
                    for (int hh = 0; hh < 2; hh++) {
                        const uint32_t a = bt + (4 * (q0 + q) + t) * 144 + (16 * w + g + 8 * hh) * 2;
                        const float u = __uint_as_float((uint32_t)lds16(a) << 16);
                        const float y = rbf(a8[4 * q + 2 * hh] + a8[4 * q + 2 * hh + 1]);
                        sts16(a, (uint16_t)(pack_bf16(y + rbf(u * ds), 0.f) & 0xffff));
                    }
            };
            float a1[24], a2[16], a3[8];
            conv_group<0>(acc, R, carry, pb, dlo);
            wg_wait0();
            #pragma unroll
            for (int i = 0; i < 24; i++) asm volatile("mov.b32 %0, %1;" : "=f"(a1[i]) : "f"(acc[8 + i]));
            fin(acc, 0);
            conv_group<1>(a1, R, carry, pb, dlo);
            wg_wait0();
            #pragma unroll
            for (int i = 0; i < 16; i++) asm volatile("mov.b32 %0, %1;" : "=f"(a2[i]) : "f"(a1[8 + i]));
            fin(a1, 2);
            conv_group<2>(a2, R, carry, pb, dlo);
            wg_wait0();
            #pragma unroll
            for (int i = 0; i < 8; i++) asm volatile("mov.b32 %0, %1;" : "=f"(a3[i]) : "f"(a2[8 + i]));
            fin(a2, 4);
            conv_group<3>(a3, R, carry, pb, dlo);
            wg_wait0();
            mbar_arrive(bKE + 8 * slot);
            fin(a3, 6);
        }
        fence_async_smem();
        __syncthreads();
        const uint32_t stg = sb + SD_STG + wg * 65536;
        uint32_t wf[32][4];
        if (tid == 0) GT(blockIdx.x, 66);
        mbar_wait_long(bWO, 0);
        #pragma unroll
        for (int i = 0; i < 32; i++)
            ldsm_x4_t(wf[i], stg + (i * 16 + (mi >> 1) * 8 + r8) * 128 + (((2 * w + (mi & 1)) ^ r8) << 4));
        mbar_arrive(bEMPTY + 16 * wg); mbar_arrive(bEMPTY + 16 * wg + 8);
        if (sh) { mbar_arrive(bEMPTY + 16 * (wg ^ 1)); mbar_arrive(bEMPTY + 16 * (wg ^ 1) + 8); }
        uint4* dst = sh ? &g_part[(blockIdx.x & ~7) + 4 * wg + w][0][0][blockIdx.x & 7][lane] : &g_part[32 + w][0][0][2 * (blockIdx.x - 32) + wg][lane];
        const uint32_t dl0 = (((sb + SD_STG) & 0x3FFFF) >> 4) | 0x10000u;
        for (int s = 0; s < NSEG; s++) {
            const int bi = sh ? s & 3 : 2 * wg + (s & 1), bp = (sh ? s >> 2 : s >> 1) & 1;
            const uint32_t xd = dl0 + bi * 2048;
            float acc[16];
            #pragma unroll
            for (int i = 0; i < 32; i++) {
                if ((i & 7) == 0) { mbar_wait_long(bCH + 32 * bi + i, bp); wg_fence(); }
                if (i == 0) wgmma_n32<0>(acc, wf[i], desc_from(xd));
                else wgmma_n32<1>(acc, wf[i], desc_from(xd + (i >> 2) * 256 + (i & 3) * 2));
            }
            wg_commit();
            if (s >= PART_SLOTS / 2) mbar_wait_long(bEPI + 8 * (s & 3), ((s - 4) >> 2) & 1);
            wg_wait0();
            mbar_arrive(bEMPTY + 8 * bi);
            const uint32_t ph = ((s / PART_SLOTS) & 1) ^ 1;
            uint4* p = dst + (s % PART_SLOTS) * (4 * 8 * 32);
            if (SD_GO && s + 1 < NSEG) mbar_wait_long(bGO + 8 * (s & 3), (s >> 2) & 1);
            #pragma unroll
            for (int j = 0; j < 4; j++) {
                uint4 v;
                v.x = (__float_as_uint(acc[4 * j]) & ~1u) | ph; v.y = (__float_as_uint(acc[4 * j + 1]) & ~1u) | ph;
                v.z = (__float_as_uint(acc[4 * j + 2]) & ~1u) | ph; v.w = (__float_as_uint(acc[4 * j + 3]) & ~1u) | ph;
                st_relaxed128(p + 256 * j, v);
            }
            if (tid == 0 && s == NSEG - 1) GT(blockIdx.x, 71);
            __syncwarp();
            if (lane == 0) mbar_arrive(bPRT + 8 * (s & 3));
        }
    } else {
        asm volatile("setmaxnreg.dec.sync.aligned.u32 %0;" :: "n"(504 - 2 * SD_REG));
        const int w = warp - 8, n = tid - 256;
        bf16 p_la = log_A_real[d0 * NS + n], p_ai = A_imag[d0 * NS + n], p_cr = C_real[d0 * NS + n], p_ci = C_imag[d0 * NS + n], p_dt = log_dt[d0];
        const uint32_t ef = sb + SD_EF + w * 8192;
        const uint32_t efl = ef + lane * 4;
        uint32_t goff[8];
        #pragma unroll
        for (int i = 0; i < 16; i++) {
            const int l = 64 * lane + 8 * (w + 4 * (i >> 3)) + (i & 7);
            const int p = (int)rbf((float)l);
            const int a = p >> 7, b = (p >> 3) & 15, c = p & 7;
            const int row = p < 256 ? 8 * a + c : (p < 512 ? 16 + 4 * (a - 2) + (c >> 1) : (p < 1024 ? 24 + 2 * (a - 4) + (c >> 2) : 24 + a));
            const uint32_t off = row * 72 + b * 4;
            if (i & 1) goff[i >> 1] |= off << 16; else goff[i >> 1] = off;
        }
        for (int c = 0; c < 16; c++) {
            const float dt = rbf(expf(bf(p_dt)));
            const float xr = -rbf(expf(bf(p_la))) * dt, xi = bf(p_ai) * dt;
            cplx C; C.r = 2.f * bf(p_cr) * dt; C.i = 2.f * bf(p_ci) * dt;
            if (c + 1 < 16) {
                const int o = (d0 + c + 1) * NS + n;
                p_la = log_A_real[o]; p_ai = A_imag[o]; p_cr = C_real[o]; p_ci = C_imag[o]; p_dt = log_dt[d0 + c + 1];
            }
            const uint32_t mexp = min(max(__reduce_max_sync(0xffffffffu, __float_as_uint(fmaxf(fabsf(C.r), fabsf(C.i)))) & 0x7f800000u, 0x01000000u), 0x7e000000u);
            const float unsc = __uint_as_float(mexp), sc = __uint_as_float(0x7f000000u - mexp);
            C.r *= sc; C.i *= sc;
            #define EADDR(r) ((efl ^ (((r) & 7) << 4)) + (r) * 128)
            {
                cplx f[16];
                f[1] = cexp_(8.f * xr, -8.f * xi);
                f[2] = cmul(f[1], f[1]); f[3] = cmul(f[2], f[1]); f[4] = cmul(f[2], f[2]); f[5] = cmul(f[4], f[1]); f[6] = cmul(f[4], f[2]); f[7] = cmul(f[4], f[3]);
                f[8] = cmul(f[4], f[4]);
                #pragma unroll
                for (int b = 9; b < 16; b++) f[b] = cmul(f[8], f[b - 8]);
                sts32(EADDR(0) + 6144, 0x00003c00u);
                #pragma unroll
                for (int b = 1; b < 16; b++) sts32(EADDR(b) + 6144, pack_f16(f[b].r, f[b].i));
            }
            {
                cplx G[17], wc[8];
                G[1] = cexp_(128.f * xr, 128.f * xi);
                wc[1] = cexp_(xr, xi);
                G[2] = cmul(G[1], G[1]); G[4] = cmul(G[2], G[2]); G[8] = cmul(G[4], G[4]);
                wc[2] = cmul(wc[1], wc[1]); wc[3] = cmul(wc[2], wc[1]); wc[4] = cmul(wc[2], wc[2]); wc[5] = cmul(wc[4], wc[1]); wc[6] = cmul(wc[4], wc[2]); wc[7] = cmul(wc[4], wc[3]);
                cplx CG[17];
                CG[0] = C; CG[1] = cmul(C, G[1]); CG[2] = cmul(C, G[2]); CG[3] = cmul(CG[1], G[2]);
                #pragma unroll
                for (int a = 0; a < 4; a++) CG[4 + a] = cmul(CG[a], G[4]);
                #pragma unroll
                for (int a = 0; a < 9; a++) CG[8 + a] = cmul(CG[a], G[8]);
                #pragma unroll
                for (int r = 0; r < 41; r++) {
                    const int a = r < 16 ? (r >> 3) : (r < 24 ? 2 + ((r >> 2) & 1) : (r < 32 ? 4 + ((r >> 1) & 3) : r - 24));
                    const int cc = r < 16 ? (r & 7) : (r < 24 ? 2 * (r & 3) : (r < 32 ? 4 * (r & 1) : 0));
                    const cplx e = cc ? cmul(CG[a], wc[cc]) : CG[a];
                    sts32(EADDR(r), pack_f16(e.r, e.i));
                }
            }
            __syncwarp();
            float acc[3][2][4];
            #pragma unroll
            for (int i = 0; i < 3; i++)
                #pragma unroll
                for (int j = 0; j < 2; j++) { acc[i][j][0] = acc[i][j][1] = acc[i][j][2] = acc[i][j][3] = 0.f; }
            #pragma unroll
            for (int ks = 0; ks < 4; ks++) {
                uint32_t bq[4];
                ldsm_x4(bq, ef + 6144 + ((mi >> 1) * 8 + r8) * 128 + (((2 * ks + (mi & 1)) ^ r8) << 4));
                #pragma unroll
                for (int mt = 0; mt < 3; mt++) {
                    uint32_t aq[4];
                    ldsm_x4(aq, ef + (16 * mt + (mi & 1) * 8 + r8) * 128 + (((2 * ks + (mi >> 1)) ^ r8) << 4));
                    mma_f16(acc[mt][0], aq, bq[0], bq[1]);
                    mma_f16(acc[mt][1], aq, bq[2], bq[3]);
                }
            }
            const uint32_t kp = sb + SD_KP;
            #pragma unroll
            for (int mt = 0; mt < 3; mt++)
                #pragma unroll
                for (int nt = 0; nt < 2; nt++) {
                    const uint32_t a = kp + w * 3072 + (16 * mt + g) * 64 + nt * 32 + t * 8;
                    sts64(a, __float_as_uint(acc[mt][nt][0] * unsc), __float_as_uint(acc[mt][nt][1] * unsc));
                    sts64(a + 512, __float_as_uint(acc[mt][nt][2] * unsc), __float_as_uint(acc[mt][nt][3] * unsc));
                }
            bar_sync(4, 128);
            #pragma unroll
            for (int i = 0; i < 3; i++) {
                const uint32_t a = kp + (n + 128 * i) * 8;
                const uint2 v0 = lds64(a), v1 = lds64(a + 3072), v2 = lds64(a + 6144), v3 = lds64(a + 9216);
                sts64(a + 12288 + ((n >> 3) + 16 * i) * 8, __float_as_uint((__uint_as_float(v0.x) + __uint_as_float(v1.x)) + (__uint_as_float(v2.x) + __uint_as_float(v3.x))),
                                 __float_as_uint((__uint_as_float(v0.y) + __uint_as_float(v1.y)) + (__uint_as_float(v2.y) + __uint_as_float(v3.y))));
            }
            bar_sync(4, 128);
            const int slot = c % KSLOTS;
            float kv[16];
            #pragma unroll
            for (int e = 0; e < 8; e++) { kv[2 * e] = __uint_as_float(lds32(kp + 12288 + (goff[e] & 0xffff))); kv[2 * e + 1] = __uint_as_float(lds32(kp + 12288 + (goff[e] >> 16))); }
            if (c >= KSLOTS) mbar_wait_long(bKE + 8 * slot, (c / KSLOTS - 1) & 1);
            #pragma unroll
            for (int it = 0; it < 2; it++) {
                uint32_t hi[4], lo[4];
                #pragma unroll
                for (int e = 0; e < 4; e++) {
                    const float k0 = kv[8 * it + 2 * e], k1 = kv[8 * it + 2 * e + 1];
                    hi[e] = pack_bf16(k0, k1);
                    lo[e] = pack_bf16(k0 - bf_lo(hi[e]), k1 - bf_hi(hi[e]));
                }
                const uint32_t a = sb + SD_BC + slot * BC_BYTES + (w + 4 * it) * BC_LBO + (16 + 2 * lane) * 16;
                sts128(a, make_uint4(hi[0], hi[1], hi[2], hi[3]));
                sts128(a + 16, make_uint4(lo[0], lo[1], lo[2], lo[3]));
            }
            fence_async_smem();
            mbar_arrive(bKF + 8 * slot);
        }
        {
            uint32_t gw[9];
            #pragma unroll
            for (int j = 0; j < 9; j++) gw[j] = __ldg((const uint32_t*)gate_w + lane + 32 * j);
            float z = 0.f;
            #pragma unroll 1
            for (int i0 = 0; i0 < 15; i0 += 5) {
                uint32_t xv[5][9];
                #pragma unroll
                for (int i = 0; i < 5; i++) {
                    const int tk = min(blockIdx.x * 57 + w + 4 * (i0 + i), S_LEN - 1);
                    #pragma unroll
                    for (int j = 0; j < 9; j++) xv[i][j] = __ldg((const uint32_t*)(x + (size_t)tk * DM) + lane + 32 * j);
                }
                #pragma unroll
                for (int i = 0; i < 5; i++) {
                    float acc = 0.f;
                    #pragma unroll
                    for (int j = 0; j < 9; j++) { const uint32_t m = mul_bf2(xv[i][j], gw[j]); acc += bf_lo(m) + bf_hi(m); }
                    #pragma unroll
                    for (int o = 16; o; o >>= 1) acc += __shfl_xor_sync(0xffffffffu, acc, o);
                    if (lane == i0 + i) z = rbf(acc);
                }
            }
            const int li = w + 4 * lane, tk = blockIdx.x * 57 + li;
            if (li < 57 && tk < S_LEN) st_relaxed32(&g_gate[tk], pack_bf16(1.f / (1.f + expf(-z)), 0.f) | (epoch << 16));
        }
        if (tid == 256) GT(blockIdx.x, 67);
        fence_async_smem();
        __syncthreads();
            const uint32_t ost = sb + SD_OST + w * 256;
            auto unit = [&](int u) {
                const int s = u >> 2;
                const int t0 = 8 * u + 2 * t;
                const uint2 gt = lds64(sb + SD_Q0 + t0 * 4);
                const uint32_t ba = sb + SD_BT + g * BT_RS + (t0 >> 6) * 144 + (t0 & 63) * 2;
                const uint32_t b0 = lds32(ba), b1 = lds32(ba + 8 * BT_RS);
                const float g0 = bf_lo(gt.x), g1 = bf_lo(gt.y), m0 = rbf(1.f - g0), m1 = rbf(1.f - g1);
                const float mb0 = rbf(m0 * bf_lo(b0)), mb1 = rbf(m1 * bf_hi(b0)), mb2 = rbf(m0 * bf_lo(b1)), mb3 = rbf(m1 * bf_hi(b1));
                const uint32_t phm = ((s / PART_SLOTS) & 1) - 1;
                const uint4* p = &g_part[blockIdx.x][s % PART_SLOTS][u & 3][0][lane];
                bf16* o = out + (size_t)(8 * u + (lane >> 1)) * DM + d0 + 8 * (lane & 1);
                uint4 v[8]; int it = 0;
                uint32_t early;
                asm volatile("{\n.reg .pred p;\nmbarrier.test_wait.parity.shared::cta.b64 p, [%1], %2;\nselp.u32 %0, 1, 0, p;\n}\n" : "=r"(early) : "r"(bPRT + 8 * (s & 3)), "r"((s >> 2) & 1) : "memory");
                if (!early) mbar_wait_long(bPRT + 8 * (s & 3), (s >> 2) & 1);
                delay_clk(s < NSEG - 2 ? (early ? (s < SD_RUSH ? SD_P3 : 0) : SD_P1) : SD_P2);
                #pragma unroll
                for (int i = 0; i < 8; i++) v[i] = ld_relaxed128(p + 32 * i);
                while (true) {
                    uint32_t miss[8], any = 0;
                    #pragma unroll
                    for (int i = 0; i < 8; i++) { miss[i] = ((v[i].x ^ phm) | (v[i].y ^ phm) | (v[i].z ^ phm) | (v[i].w ^ phm)) & 1u; any |= miss[i]; }
                    if (!__any_sync(0xffffffffu, any) || ++it >= SD_SPIN) break;
                    if (it > 1 && s < NSEG - 2) __nanosleep(200);
                    #pragma unroll
                    for (int i = 0; i < 8; i++) ld_relaxed128_p(v[i], p + 32 * i, miss[i]);
                }
                if (lane == 0) mbar_arrive(bEPI + 8 * (s & 3));
                float a0 = 0.f, a1 = 0.f, a2 = 0.f, a3 = 0.f;
                #pragma unroll
                for (int i = 0; i < 8; i++) { a0 += __uint_as_float(v[i].x); a1 += __uint_as_float(v[i].y); a2 += __uint_as_float(v[i].z); a3 += __uint_as_float(v[i].w); }
                const uint32_t r0 = pack_bf16(rbf(g0 * rbf(a0)) + mb0, rbf(g1 * rbf(a1)) + mb1), r1 = pack_bf16(rbf(g0 * rbf(a2)) + mb2, rbf(g1 * rbf(a3)) + mb3);
                asm volatile("stmatrix.sync.aligned.m8n8.x2.trans.shared.b16 [%0], {%1,%2};" :: "r"(ost + r8 * 32 + (mi & 1) * 16), "r"(r0), "r"(r1) : "memory");
                __syncwarp();
                if (lane < 16) *(uint4*)o = lds128(ost + lane * 16);
                __syncwarp();
                if (lane == 0 && (u & 3) == 3) GT(blockIdx.x, 1 + s);
            };
        if (w == 0) {
            if (lane == 0) {
                mbar_expect_tx(bWO, 131072);
                #pragma unroll
                for (int q = 0; q < 4; q++) tma2d(sb + SD_STG + q * 32768, &tmw, bWO, sh ? 128 * (blockIdx.x >> 3) + 64 * (q >> 1) : 512, sh ? 512 * (blockIdx.x & 7) + 256 * (q & 1) : 1024 * (blockIdx.x - 32) + 256 * q);
            }
            bar_sync(5, 128);
            const int ke0 = sh ? blockIdx.x & 7 : 2 * (blockIdx.x - 32);
            for (int s = 0; s < NSEG; s++) {
                {
                    const unsigned int* f = &g_flag[s][12 * ke0 + (lane < (sh ? 12 : 24) ? lane : 0)];
                    int it = 0;
                    while (true) {
                        uint32_t v;
                        asm volatile("ld.acquire.gpu.global.u32 %0, [%1];" : "=r"(v) : "l"(f) : "memory");
                        if (__all_sync(0xffffffffu, v == epoch) || ++it >= SD_SPIN) break;
                        if (s < NSEG - 1) __nanosleep(64);
                    }
                    asm volatile("fence.proxy.async.global;" ::: "memory");
                    if (lane == 0 && s == NSEG - 1) GT(blockIdx.x, 70);
                    if (lane == 0 && s == 2 && blockIdx.x == 0) st_relaxed32(&g_epoch, epoch + 1);
                }
                if (lane == 0) {
                    if (SD_GO && s > 0) mbar_arrive(bGO + 8 * ((s - 1) & 3));
                    const int b0 = sh ? s & 3 : s & 1, bp = (sh ? s >> 2 : s >> 1) & 1;
                    mbar_wait_long(bEMPTY + 8 * b0, bp);
                    if (!sh) mbar_wait_long(bEMPTY + 16 + 8 * b0, bp);
                    #pragma unroll 1
                    for (int c = 0; c < (sh ? 4 : 8); c++) {
                        const int wg = sh ? 0 : c & 1, hc = sh ? c : c >> 1;
                        const uint32_t bar = bCH + 32 * (b0 + 2 * wg) + 8 * hc;
                        mbar_expect_tx(bar, 8192);
                        asm volatile("cp.async.bulk.shared::cluster.global.mbarrier::complete_tx::bytes [%0], [%1], 8192, [%2];"
                            :: "r"(sb + SD_STG + (b0 + 2 * wg) * 32768 + hc * 8192), "l"(g_otok + (size_t)s * (SEG * NH * DH) + (ke0 + wg) * 16384 + hc * 4096), "r"(bar) : "memory");
                    }
                }
                __syncwarp();
            }
        } else {
            if (w == 3) {
                for (int i = 0; i < 16; i += 8) {
                    uint4 v[8]; uint32_t miss = 0xffu; int it = 0;
                    const uint32_t tag = epoch & 0xffffu;
                    #pragma unroll
                    for (int j = 0; j < 8; j++) v[j] = make_uint4(0, 0, 0, 0);
                    do {
                        #pragma unroll
                        for (int j = 0; j < 8; j++) ld_relaxed128_p(v[j], (const uint4*)g_gate + (i + j) * 32 + lane, miss & (1u << j));
                        miss = 0;
                        #pragma unroll
                        for (int j = 0; j < 8; j++) miss |= (uint32_t)((v[j].x >> 16) != tag || (v[j].y >> 16) != tag || (v[j].z >> 16) != tag || (v[j].w >> 16) != tag) << j;
                    } while (__any_sync(0xffffffffu, miss) && ++it < SD_SPIN);
                    #pragma unroll
                    for (int j = 0; j < 8; j++) sts128(sb + SD_Q0 + ((i + j) * 32 + lane) * 16, v[j]);
                }
            }
            bar_sync(5, 128);
            for (int u = w - 1; u < 4 * (NSEG - 1); u += 3) unit(u);
        }
        unit(4 * (NSEG - 1) + w);
    }
    if (tid == 256) GT(blockIdx.x, 72);
}

extern "C" void kernel_launch(void* const* d_in, const int* in_sizes, int n_in, void* d_out, int out_size) {
    const bf16* x = (const bf16*)d_in[0];
    const bf16* mem0 = (const bf16*)d_in[1];
    const bf16* Wq = (const bf16*)d_in[2];
    const bf16* Wk = (const bf16*)d_in[3];
    const bf16* Wv = (const bf16*)d_in[4];
    const bf16* Wo = (const bf16*)d_in[5];
    const bf16* log_A_real = (const bf16*)d_in[8];
    const bf16* A_imag = (const bf16*)d_in[9];
    const bf16* C_real = (const bf16*)d_in[10];
    const bf16* C_imag = (const bf16*)d_in[11];
    const bf16* log_dt = (const bf16*)d_in[12];
    const bf16* D_skip = (const bf16*)d_in[13];
    const bf16* gate_w = (const bf16*)d_in[14];
    bf16* out = (bf16*)d_out;
    typedef CUresult (*EncFn)(CUtensorMap*, CUtensorMapDataType, cuuint32_t, void*, const cuuint64_t*, const cuuint64_t*, const cuuint32_t*, const cuuint32_t*,
                              CUtensorMapInterleave, CUtensorMapSwizzle, CUtensorMapL2promotion, CUtensorMapFloatOOBfill);
    static EncFn enc = nullptr;
    if (!enc) { void* fn = nullptr; cudaDriverEntryPointQueryResult qr; cudaGetDriverEntryPoint("cuTensorMapEncodeTiled", &fn, cudaEnableDefault, &qr); enc = (EncFn)fn; }
    auto mk = [&](CUtensorMap* tm, const void* ptr, uint64_t cols, uint64_t rows, uint32_t bc, uint32_t br) {
        cuuint64_t gdim[2] = {cols, rows}; cuuint64_t gstr[1] = {cols * 2}; cuuint32_t box[2] = {bc, br}; cuuint32_t estr[2] = {1, 1};
        enc(tm, CU_TENSOR_MAP_DATA_TYPE_BFLOAT16, 2, (void*)ptr, gdim, gstr, box, estr, CU_TENSOR_MAP_INTERLEAVE_NONE, bc == 64 ? CU_TENSOR_MAP_SWIZZLE_128B : CU_TENSOR_MAP_SWIZZLE_64B,
            CU_TENSOR_MAP_L2_PROMOTION_L2_256B, CU_TENSOR_MAP_FLOAT_OOB_FILL_NONE);
    };
    static bool attr_done = false;
    if (!attr_done) {
        cudaFuncSetAttribute(chain_kernel, cudaFuncAttributeMaxDynamicSharedMemorySize, SM_TOTAL);
        cudaFuncSetAttribute(side_kernel, cudaFuncAttributeMaxDynamicSharedMemorySize, SD_TOTAL);
        attr_done = true;
    }
    CUtensorMap tmx, tmw, tmq, tmk, tmv, tmo;
    {
        cuuint64_t gdim[3] = {64, S_LEN, DM / 64}; cuuint64_t gstr[2] = {DM * 2, 128}; cuuint32_t box[3] = {64, SEG, 3}; cuuint32_t estr[3] = {1, 1, 1};
        enc(&tmx, CU_TENSOR_MAP_DATA_TYPE_BFLOAT16, 3, (void*)x, gdim, gstr, box, estr, CU_TENSOR_MAP_INTERLEAVE_NONE, CU_TENSOR_MAP_SWIZZLE_128B,
            CU_TENSOR_MAP_L2_PROMOTION_L2_256B, CU_TENSOR_MAP_FLOAT_OOB_FILL_NONE);
    }
    mk(&tmw, Wo, DM, NH * DH, 64, 256);
    mk(&tmo, Wo, DM, NH * DH, 32, 128);
    mk(&tmq, Wq, NH * DH, DM, 32, 48); mk(&tmk, Wk, NH * DH, DM, 32, 48); mk(&tmv, Wv, NH * DH, DM, 32, 48);
    chain_kernel<<<96, CH_THREADS, SM_TOTAL>>>(tmx, tmq, tmk, tmv, tmo, mem0, 0u);
    cudaLaunchConfig_t cfg = {};
    cfg.gridDim = dim3(SD_CTAS); cfg.blockDim = dim3(SD_THREADS); cfg.dynamicSmemBytes = SD_TOTAL; cfg.stream = cudaStreamPerThread;
    cudaLaunchAttribute at[1];
    at[0].id = cudaLaunchAttributeProgrammaticStreamSerialization; at[0].val.programmaticStreamSerializationAllowed = 1;
    cfg.attrs = at; cfg.numAttrs = 1;
    cudaLaunchKernelEx(&cfg, side_kernel, tmw, x, log_A_real, A_imag, C_real, C_imag, log_dt, D_skip, gate_w, out);
}
```

```cpp
#include <cuda_runtime.h>
#include <cuda.h>
#include <cuda_bf16.h>
#include <stdint.h>

#define S_LEN 2048
#define DM 576
#define NH 32
#define DH 128
#define NMEM 8
#define SEG 32
#define NSEG 64
#define LQ 40
#define NS 128

typedef __nv_bfloat16 bf16;

__device__ __forceinline__ float bf(bf16 v) { return __bfloat162float(v); }
__device__ __forceinline__ bf16 tobf(float v) { return __float2bfloat16_rn(v); }
__device__ __forceinline__ float rbf(float v) { return __bfloat162float(__float2bfloat16_rn(v)); }

#define CH_THREADS 384
#define SPIN_LIMIT (1 << 17)
#define SM_X     0
#define XBUF     36864
#define SM_TOK   73728
#define TOKBUF   24576
#define SM_FB    131072
#define SM_STASH 139264
#define SM_TS    (SM_STASH + 3072)
#define SM_WO    147456
#define SM_MEM   196608
#define SM_EX    205824
#define EXBUF    6144
#define SM_P     218112
#define SM_FLAG  (SM_P + 640)
#define SM_OST   219136
#define SM_O     223232
#define SM_BAR   228352
#define SM_IL    (SM_BAR + 128)
#define SM_SG    (SM_IL + 256)
#define SM_TOTAL (SM_SG + 64)

#define ACC_X    36864
#define ACC_FULL 0x0020u
#define SLOT_OFF(sl) ((((sl) & 1) << 7) | (((sl) & 2) << 8))
__device__ __align__(65536) unsigned char g_acc[65536];
__device__ __align__(1024) uint4 g_fb[3][32][384];
__device__ unsigned int g_fbf[3][32];
__device__ unsigned int g_init[96];
__device__ unsigned int g_epoch = 1;
__device__ __align__(128) unsigned int g_ts[128];
__device__ __align__(1024) bf16 g_otok[S_LEN * NH * DH];
__device__ __align__(1024) unsigned char g_tokx[96][8192];
__device__ __align__(128) unsigned int g_prog[96];
#define STAMP(i)
#define STAMPV(i, v)
#define GT(b, i)
#define STAMPB(i)

__device__ __forceinline__ uint32_t smem_u32(const void* p) { return (uint32_t)__cvta_generic_to_shared(p); }
__device__ __forceinline__ void ldsm_x4(uint32_t (&r)[4], uint32_t addr) {
    asm volatile("ldmatrix.sync.aligned.m8n8.x4.shared.b16 {%0,%1,%2,%3}, [%4];" : "=r"(r[0]), "=r"(r[1]), "=r"(r[2]), "=r"(r[3]) : "r"(addr) : "memory");
}
__device__ __forceinline__ void ldsm_x4_p(uint32_t (&r)[4], uint32_t addr, uint32_t skip) {
    asm volatile("{\n.reg .pred p;\nsetp.eq.u32 p, %5, 0;\n@p ldmatrix.sync.aligned.m8n8.x4.shared.b16 {%0,%1,%2,%3}, [%4];\n}\n" : "+r"(r[0]), "+r"(r[1]), "+r"(r[2]), "+r"(r[3]) : "r"(addr), "r"(skip) : "memory");
}
__device__ __forceinline__ void ldsm_x4_t(uint32_t (&r)[4], uint32_t addr) {
    asm volatile("ldmatrix.sync.aligned.m8n8.x4.trans.shared.b16 {%0,%1,%2,%3}, [%4];" : "=r"(r[0]), "=r"(r[1]), "=r"(r[2]), "=r"(r[3]) : "r"(addr) : "memory");
}
__device__ __forceinline__ uint32_t ldsm_x1_t(uint32_t addr) {
    uint32_t r; asm volatile("ldmatrix.sync.aligned.m8n8.x1.trans.shared.b16 {%0}, [%1];" : "=r"(r) : "r"(addr) : "memory"); return r;
}
__device__ __forceinline__ void ldsm_x2_t(uint32_t& r0, uint32_t& r1, uint32_t addr) {
    asm volatile("ldmatrix.sync.aligned.m8n8.x2.trans.shared.b16 {%0,%1}, [%2];" : "=r"(r0), "=r"(r1) : "r"(addr) : "memory");
}
__device__ __forceinline__ void stsm_x4(uint32_t addr, uint32_t r0, uint32_t r1, uint32_t r2, uint32_t r3) {
    asm volatile("stmatrix.sync.aligned.m8n8.x4.shared.b16 [%0], {%1,%2,%3,%4};" :: "r"(addr), "r"(r0), "r"(r1), "r"(r2), "r"(r3) : "memory");
}
__device__ __forceinline__ void stsm_x4_t(uint32_t addr, uint32_t r0, uint32_t r1, uint32_t r2, uint32_t r3) {
    asm volatile("stmatrix.sync.aligned.m8n8.x4.trans.shared.b16 [%0], {%1,%2,%3,%4};" :: "r"(addr), "r"(r0), "r"(r1), "r"(r2), "r"(r3) : "memory");
}
__device__ __forceinline__ void mma16816(float (&c)[4], const uint32_t (&a)[4], uint32_t b0, uint32_t b1) {
    asm("mma.sync.aligned.m16n8k16.row.col.f32.bf16.bf16.f32 {%0,%1,%2,%3}, {%4,%5,%6,%7}, {%8,%9}, {%0,%1,%2,%3};"
        : "+f"(c[0]), "+f"(c[1]), "+f"(c[2]), "+f"(c[3]) : "r"(a[0]), "r"(a[1]), "r"(a[2]), "r"(a[3]), "r"(b0), "r"(b1));
}
__device__ __forceinline__ void mma16816r(float (&c)[4], uint32_t a0, uint32_t a1, uint32_t a2, uint32_t a3, uint32_t b0, uint32_t b1) {
    asm("mma.sync.aligned.m16n8k16.row.col.f32.bf16.bf16.f32 {%0,%1,%2,%3}, {%4,%5,%6,%7}, {%8,%9}, {%0,%1,%2,%3};"
        : "+f"(c[0]), "+f"(c[1]), "+f"(c[2]), "+f"(c[3]) : "r"(a0), "r"(a1), "r"(a2), "r"(a3), "r"(b0), "r"(b1));
}
__device__ __forceinline__ void mma1688(float (&c)[4], uint32_t a0, uint32_t a1, uint32_t b0) {
    asm("mma.sync.aligned.m16n8k8.row.col.f32.bf16.bf16.f32 {%0,%1,%2,%3}, {%4,%5}, {%6}, {%0,%1,%2,%3};"
        : "+f"(c[0]), "+f"(c[1]), "+f"(c[2]), "+f"(c[3]) : "r"(a0), "r"(a1), "r"(b0));
}
__device__ __forceinline__ uint32_t pack_bf16(float lo, float hi) {
    uint32_t r; asm("cvt.rn.bf16x2.f32 %0, %1, %2;" : "=r"(r) : "f"(hi), "f"(lo)); return r;
}
__device__ __forceinline__ float bf_lo(uint32_t v) { return __uint_as_float(v << 16); }
__device__ __forceinline__ float bf_hi(uint32_t v) { return __uint_as_float(v & 0xffff0000u); }
__device__ __forceinline__ uint32_t max_bf2(uint32_t a, uint32_t b) { uint32_t r; asm("max.bf16x2 %0, %1, %2;" : "=r"(r) : "r"(a), "r"(b)); return r; }
__device__ __forceinline__ uint32_t maxabs_bf2(uint32_t a, uint32_t b) { uint32_t r; asm("max.NaN.xorsign.abs.bf16x2 %0, %1, %2;" : "=r"(r) : "r"(a), "r"(b)); return r; }
__device__ __forceinline__ float ex2(float x) { float r; asm("ex2.approx.ftz.f32 %0, %1;" : "=f"(r) : "f"(x)); return r; }
__device__ __forceinline__ void ld_relaxed128_p(uint4& v, const uint4* p, uint32_t pred) {
    asm volatile("{\n.reg .pred p;\nsetp.ne.u32 p, %5, 0;\n@p ld.relaxed.gpu.global.v4.u32 {%0,%1,%2,%3}, [%4];\n}\n" : "+r"(v.x), "+r"(v.y), "+r"(v.z), "+r"(v.w) : "l"(p), "r"(pred) : "memory");
}
__device__ __forceinline__ uint4 ld_relaxed128(const uint4* p) { uint4 v; asm volatile("ld.relaxed.gpu.global.v4.u32 {%0,%1,%2,%3}, [%4];" : "=r"(v.x), "=r"(v.y), "=r"(v.z), "=r"(v.w) : "l"(p) : "memory"); return v; }
__device__ __forceinline__ uint32_t ld_relaxed32(const uint32_t* p) { uint32_t v; asm volatile("ld.relaxed.gpu.global.u32 %0, [%1];" : "=r"(v) : "l"(p) : "memory"); return v; }
__device__ __forceinline__ void st_relaxed128(uint4* p, uint4 v) { asm volatile("st.relaxed.gpu.global.v4.u32 [%0], {%1,%2,%3,%4};" :: "l"(p), "r"(v.x), "r"(v.y), "r"(v.z), "r"(v.w) : "memory"); }
__device__ __forceinline__ void st_relaxed32(uint32_t* p, uint32_t v) { asm volatile("st.relaxed.gpu.global.u32 [%0], %1;" :: "l"(p), "r"(v) : "memory"); }
__device__ __forceinline__ void st_relaxed128_p(uint4* p, uint4 v, uint32_t skip) {
    asm volatile("{\n.reg .pred p;\nsetp.eq.u32 p, %5, 0;\n@p st.relaxed.gpu.global.v4.u32 [%0], {%1,%2,%3,%4};\n}\n" :: "l"(p), "r"(v.x), "r"(v.y), "r"(v.z), "r"(v.w), "r"(skip) : "memory");
}
__device__ __forceinline__ void st_relaxed64_p(void* p, uint32_t x, uint32_t y, uint32_t skip) {
    asm volatile("{\n.reg .pred p;\n.reg .b64 v;\nsetp.eq.u32 p, %3, 0;\nmov.b64 v, {%1,%2};\n@p st.relaxed.gpu.global.b64 [%0], v;\n}\n" :: "l"(p), "r"(x), "r"(y), "r"(skip) : "memory");
}
__device__ __forceinline__ void ld_relaxed64_p(uint2& v, const void* p, uint32_t pred) {
    asm volatile("{\n.reg .pred p;\n.reg .b64 v;\nsetp.ne.u32 p, %3, 0;\nmov.b64 v, {%0,%1};\n@p ld.relaxed.gpu.global.b64 v, [%2];\nmov.b64 {%0,%1}, v;\n}\n" : "+r"(v.x), "+r"(v.y) : "l"(p), "r"(pred) : "memory");
}
__device__ __forceinline__ uint2 ld_relaxed64(const void* p) {
    uint2 v; asm volatile("{\n.reg .b64 v;\nld.relaxed.gpu.global.b64 v, [%2];\nmov.b64 {%0,%1}, v;\n}\n" : "=r"(v.x), "=r"(v.y) : "l"(p) : "memory"); return v;
}
__device__ __forceinline__ void st_relaxed32_p(void* p, uint32_t v, uint32_t skip) {
    asm volatile("{\n.reg .pred p;\nsetp.eq.u32 p, %2, 0;\n@p st.relaxed.gpu.global.u32 [%0], %1;\n}\n" :: "l"(p), "r"(v), "r"(skip) : "memory");
}
__device__ __forceinline__ void bar_arrive_p(int id, int n, uint32_t skip) {
    asm volatile("{\n.reg .pred p;\nsetp.eq.u32 p, %2, 0;\n@p bar.arrive %0, %1;\n}\n" :: "r"(id), "r"(n), "r"(skip) : "memory");
}
__device__ __forceinline__ void bar_sync_p(int id, int n, uint32_t skip) {
    asm volatile("{\n.reg .pred p;\nsetp.eq.u32 p, %2, 0;\n@p bar.sync %0, %1;\n}\n" :: "r"(id), "r"(n), "r"(skip) : "memory");
}
__device__ __forceinline__ uint32_t movm(uint32_t x) { uint32_t r; asm volatile("movmatrix.sync.aligned.m8n8.trans.b16 %0, %1;" : "=r"(r) : "r"(x)); return r; }
__device__ __forceinline__ void sts32_p(uint32_t a, uint32_t v, uint32_t doit) {
    asm volatile("{\n.reg .pred p;\nsetp.ne.u32 p, %2, 0;\n@p st.shared.u32 [%0], %1;\n}\n" :: "r"(a), "r"(v), "r"(doit) : "memory");
}
__device__ __forceinline__ uint32_t pin(uint32_t x) { return __shfl_sync(0xffffffffu, x, threadIdx.x & 31); }
__device__ __forceinline__ void ldsm16_t(uint32_t (&b)[4][4], uint32_t a) {
    asm volatile("ldmatrix.sync.aligned.m8n8.x4.trans.shared.b16 {%0,%1,%2,%3}, [%16];\n"
                 "ldmatrix.sync.aligned.m8n8.x4.trans.shared.b16 {%4,%5,%6,%7}, [%16+512];\n"
                 "ldmatrix.sync.aligned.m8n8.x4.trans.shared.b16 {%8,%9,%10,%11}, [%16+1024];\n"
                 "ldmatrix.sync.aligned.m8n8.x4.trans.shared.b16 {%12,%13,%14,%15}, [%16+1536];\n"
        : "=r"(b[0][0]), "=r"(b[0][1]), "=r"(b[0][2]), "=r"(b[0][3]), "=r"(b[1][0]), "=r"(b[1][1]), "=r"(b[1][2]), "=r"(b[1][3]),
          "=r"(b[2][0]), "=r"(b[2][1]), "=r"(b[2][2]), "=r"(b[2][3]), "=r"(b[3][0]), "=r"(b[3][1]), "=r"(b[3][2]), "=r"(b[3][3]) : "r"(a) : "memory");
}
template<int ID> __device__ __forceinline__ void sched_fence(uint32_t never) { while (never == 0x7fffff00u + ID) { asm volatile("nanosleep.u32 64;" ::: "memory"); } }
__device__ __forceinline__ uint32_t opaque_u() { uint32_t v; asm volatile("mov.u32 %0, %%nsmid;" : "=r"(v)); return v; }
__device__ __forceinline__ uint32_t bar_red_or(int id, int n, uint32_t v) {
    uint32_t r; asm volatile("{\n.reg .pred p, q;\nsetp.ne.u32 p, %3, 0;\nbar.red.or.pred q, %1, %2, p;\nselp.u32 %0, 1, 0, q;\n}\n" : "=r"(r) : "r"(id), "r"(n), "r"(v) : "memory"); return r;
}
template<class T> __device__ __forceinline__ T* launder_p(T* p) { asm volatile("" : "+l"(p)); return p; }
__device__ __forceinline__ uint32_t mapa_u32(uint32_t addr, uint32_t rank) { uint32_t d; asm("mapa.shared::cluster.u32 %0, %1, %2;" : "=r"(d) : "r"(addr), "r"(rank)); return d; }
__device__ __forceinline__ uint32_t mapa_v(uint32_t addr, uint32_t rank) { uint32_t d; asm volatile("mapa.shared::cluster.u32 %0, %1, %2;" : "=r"(d) : "r"(addr), "r"(rank)); return d; }
__device__ __forceinline__ void st_async32(uint32_t addr, uint32_t v, uint32_t mbar) { asm volatile("st.async.shared::cluster.mbarrier::complete_tx::bytes.u32 [%0], %1, [%2];" :: "r"(addr), "r"(v), "r"(mbar) : "memory"); }
__device__ __forceinline__ void cluster_arrive() { asm volatile("barrier.cluster.arrive.release.aligned;" ::: "memory"); }
__device__ __forceinline__ void cluster_wait() { asm volatile("barrier.cluster.wait.acquire.aligned;" ::: "memory"); }
__device__ __forceinline__ void cp_async16(uint32_t dst, const void* src) { asm volatile("cp.async.cg.shared.global [%0], [%1], 16;" :: "r"(dst), "l"(src) : "memory"); }
__device__ __forceinline__ void cp_async_commit() { asm volatile("cp.async.commit_group;" ::: "memory"); }
template<int N> __device__ __forceinline__ void cp_async_wait() { asm volatile("cp.async.wait_group %0;" :: "n"(N) : "memory"); }
__device__ __forceinline__ void cp_async_wait0() { asm volatile("cp.async.wait_group 0;" ::: "memory"); }
__device__ __forceinline__ void mbar_init(uint32_t a, uint32_t cnt) { asm volatile("mbarrier.init.shared.b64 [%0], %1;" :: "r"(a), "r"(cnt) : "memory"); }
__device__ __forceinline__ void mbar_expect_tx(uint32_t a, uint32_t bytes) { asm volatile("mbarrier.arrive.expect_tx.shared.b64 _, [%0], %1;" :: "r"(a), "r"(bytes) : "memory"); }
__device__ __forceinline__ bool mbar_try(uint32_t a, uint32_t parity) {
    uint32_t ok; asm volatile("{\n.reg .pred p;\nmbarrier.try_wait.parity.shared::cta.b64 p, [%1], %2;\nselp.u32 %0, 1, 0, p;\n}\n" : "=r"(ok) : "r"(a), "r"(parity) : "memory"); return ok;
}
__device__ __forceinline__ void mbar_wait(uint32_t a, uint32_t parity) { int it = 0; while (!mbar_try(a, parity) && ++it < SPIN_LIMIT) {} }
__device__ __forceinline__ void bar_sync(int id, int n) { asm volatile("bar.sync %0, %1;" :: "r"(id), "r"(n) : "memory"); }
__device__ __forceinline__ void bar_arrive(int id, int n) { asm volatile("bar.arrive %0, %1;" :: "r"(id), "r"(n) : "memory"); }
__device__ __forceinline__ void fence_async_smem() { asm volatile("fence.proxy.async.shared::cta;" ::: "memory"); }
__device__ __forceinline__ void sts32(uint32_t a, uint32_t v) { asm volatile("st.shared.u32 [%0], %1;" :: "r"(a), "r"(v) : "memory"); }
__device__ __forceinline__ void sts128(uint32_t a, uint4 v) { asm volatile("st.shared.v4.u32 [%0], {%1,%2,%3,%4};" :: "r"(a), "r"(v.x), "r"(v.y), "r"(v.z), "r"(v.w) : "memory"); }
__device__ __forceinline__ uint4 lds128(uint32_t a) { uint4 v; asm volatile("ld.shared.v4.u32 {%0,%1,%2,%3}, [%4];" : "=r"(v.x), "=r"(v.y), "=r"(v.z), "=r"(v.w) : "r"(a) : "memory"); return v; }
__device__ __forceinline__ uint32_t lds32(uint32_t a) { uint32_t v; asm volatile("ld.shared.u32 %0, [%1];" : "=r"(v) : "r"(a) : "memory"); return v; }
__device__ __forceinline__ uint32_t gtime_lo() { uint32_t t; asm volatile("mov.u32 %0, %globaltimer_lo;" : "=r"(t)); return t; }
__device__ __forceinline__ void wait_gtime(uint32_t tg) {
    asm volatile("{\n.reg .pred p, q;\n.reg .b64 t;\n.reg .b32 lo, hi, d, n;\nmov.b32 n, 300;\n"
                 "WG_%=:\nmov.u64 t, %%globaltimer;\nmov.b64 {lo, hi}, t;\nsub.s32 d, lo, %0;\nsub.s32 n, n, 1;\n"
                 "setp.gt.s32 q, n, 0;\nsetp.lt.and.s32 p, d, 0, q;\n@p bra.uni WG_%=;\n}\n" :: "r"(tg) : "memory");
}
__device__ __forceinline__ void delay_clk(int d) { uint32_t t0 = clock(); while ((int)(clock() - t0) < d) {} }

__device__ __forceinline__ uint64_t desc128(uint32_t addr) {
    return (uint64_t)((addr & 0x3FFFF) >> 4) | ((uint64_t)1 << 16) | ((uint64_t)64 << 32) | ((uint64_t)1 << 62);
}
template<int accum> __device__ __forceinline__ void wgmma_n32(float (&d)[16], const uint32_t (&a)[4], uint64_t desc) {
    if (accum) {
        asm volatile("{\n.reg .pred p;\nsetp.ne.b32 p, 1, 0;\n"
            "wgmma.mma_async.sync.aligned.m64n32k16.f32.bf16.bf16 {%0,%1,%2,%3,%4,%5,%6,%7,%8,%9,%10,%11,%12,%13,%14,%15}, {%16,%17,%18,%19}, %20, p, 1, 1, 0;\n}\n"
            : "+f"(d[0]), "+f"(d[1]), "+f"(d[2]), "+f"(d[3]), "+f"(d[4]), "+f"(d[5]), "+f"(d[6]), "+f"(d[7]),
              "+f"(d[8]), "+f"(d[9]), "+f"(d[10]), "+f"(d[11]), "+f"(d[12]), "+f"(d[13]), "+f"(d[14]), "+f"(d[15])
            : "r"(a[0]), "r"(a[1]), "r"(a[2]), "r"(a[3]), "l"(desc));
    } else {
        asm volatile("{\n.reg .pred p;\nsetp.ne.b32 p, 0, 0;\n"
            "wgmma.mma_async.sync.aligned.m64n32k16.f32.bf16.bf16 {%0,%1,%2,%3,%4,%5,%6,%7,%8,%9,%10,%11,%12,%13,%14,%15}, {%16,%17,%18,%19}, %20, p, 1, 1, 0;\n}\n"
            : "=f"(d[0]), "=f"(d[1]), "=f"(d[2]), "=f"(d[3]), "=f"(d[4]), "=f"(d[5]), "=f"(d[6]), "=f"(d[7]),
              "=f"(d[8]), "=f"(d[9]), "=f"(d[10]), "=f"(d[11]), "=f"(d[12]), "=f"(d[13]), "=f"(d[14]), "=f"(d[15])
            : "r"(a[0]), "r"(a[1]), "r"(a[2]), "r"(a[3]), "l"(desc));
    }
}
__device__ __forceinline__ float rcp_approx(float x) { float r; asm("rcp.approx.ftz.f32 %0, %1;" : "=f"(r) : "f"(x)); return r; }
__device__ __forceinline__ void wg_fence() { asm volatile("wgmma.fence.sync.aligned;" ::: "memory"); }
__device__ __forceinline__ void wg_commit() { asm volatile("wgmma.commit_group.sync.aligned;" ::: "memory"); }
__device__ __forceinline__ void wg_wait0() { asm volatile("wgmma.wait_group.sync.aligned 0;" ::: "memory"); }

#define SCALE_HI 0x3db53db5u
#define SCALE_LO 0x371e371eu
#define LOG2E 1.4426950408889634f
#define NEG_BIG2 0xce6ece6eu
__device__ __forceinline__ uint32_t scale_bf2(uint32_t x) {
    uint32_t t, r;
    asm("mul.rn.bf16x2 %0, %1, %2;" : "=r"(t) : "r"(x), "r"(SCALE_LO));
    asm("fma.rn.bf16x2 %0, %1, %2, %3;" : "=r"(r) : "r"(x), "r"(SCALE_HI), "r"(t));
    return r;
}
__device__ __forceinline__ void cluster_arrive_rx() { asm volatile("barrier.cluster.arrive.relaxed.aligned;" ::: "memory"); }
__device__ __forceinline__ uint32_t launder(uint32_t x) { asm volatile("" : "+r"(x)); return x; }
__device__ __forceinline__ void mbar_arrive(uint32_t a) { asm volatile("mbarrier.arrive.shared.b64 _, [%0];" :: "r"(a) : "memory"); }
__device__ __forceinline__ void mbar_wait_cl(uint32_t a, uint32_t parity) {
    int it = 0; uint32_t ok;
    do { asm volatile("{\n.reg .pred p;\nmbarrier.try_wait.parity.acquire.cluster.shared::cta.b64 p, [%1], %2;\nselp.u32 %0, 1, 0, p;\n}\n" : "=r"(ok) : "r"(a), "r"(parity) : "memory"); } while (!ok && ++it < SPIN_LIMIT);
}
__device__ __forceinline__ uint64_t desc_from(uint32_t lo) { return (uint64_t)lo | ((uint64_t)0x40000040u << 32); }
#define SB_OFF 1024u
#define DESC_LO(off) ((((SB_OFF + (uint32_t)(off)) & 0x3FFFFu) >> 4) | 0x10000u)
template<int N> struct ic { static constexpr int value = N; };
__device__ __forceinline__ uint32_t uni(uint32_t x) { return __shfl_sync(0xffffffffu, x, 0); }

__device__ __forceinline__ uint32_t pack_f16(float lo, float hi) { uint32_t r; asm("cvt.rn.f16x2.f32 %0, %1, %2;" : "=r"(r) : "f"(hi), "f"(lo)); return r; }
__device__ __forceinline__ uint32_t maxabs_h2(uint32_t a, uint32_t b) { uint32_t r; asm("max.NaN.xorsign.abs.f16x2 %0, %1, %2;" : "=r"(r) : "r"(a), "r"(b)); return r; }
__device__ __forceinline__ uint32_t h2_to_bf2(uint32_t v) {
    uint32_t r; asm("{\n.reg .b16 l, h;\n.reg .f32 a, b;\nmov.b32 {l, h}, %1;\ncvt.f32.f16 a, l;\ncvt.f32.f16 b, h;\ncvt.rn.bf16x2.f32 %0, b, a;\n}\n" : "=r"(r) : "r"(v)); return r;
}
__device__ __forceinline__ void sts16(uint32_t a, uint16_t v) { asm volatile("st.shared.u16 [%0], %1;" :: "r"(a), "h"(v) : "memory"); }
__device__ __forceinline__ void sts64(uint32_t a, uint32_t x, uint32_t y) { asm volatile("st.shared.v2.u32 [%0], {%1,%2};" :: "r"(a), "r"(x), "r"(y) : "memory"); }
__device__ __forceinline__ void ld_relaxed32_p(uint32_t& v, const void* p, uint32_t pred) {
    asm volatile("{\n.reg .pred p;\nsetp.ne.u32 p, %2, 0;\n@p ld.relaxed.gpu.global.u32 %0, [%1];\n}\n" : "+r"(v) : "l"(p), "r"(pred) : "memory");
}
__device__ __forceinline__ uint2 lds64(uint32_t a) { uint2 v; asm volatile("ld.shared.v2.u32 {%0,%1}, [%2];" : "=r"(v.x), "=r"(v.y) : "r"(a) : "memory"); return v; }
__device__ __forceinline__ uint32_t h1_to_bf(uint32_t v) {
    uint32_t r; asm("{\n.reg .b16 l, h;\n.reg .f32 a;\nmov.b32 {l, h}, %1;\ncvt.f32.f16 a, l;\ncvt.rn.bf16x2.f32 %0, a, a;\n}\n" : "=r"(r) : "r"(v)); return r;
}
__device__ __forceinline__ void mbar_wait2(uint32_t a, uint32_t pa, uint32_t b, uint32_t pb) {
    int it = 0; uint32_t ok;
    do { asm volatile("{\n.reg .pred p, q;\nmbarrier.try_wait.parity.shared::cta.b64 p, [%1], %2;\nmbarrier.try_wait.parity.shared::cta.b64 q, [%3], %4;\nand.pred p, p, q;\nselp.u32 %0, 1, 0, p;\n}\n"
                      : "=r"(ok) : "r"(a), "r"(pa), "r"(b), "r"(pb) : "memory"); } while (!ok && ++it < SPIN_LIMIT);
}
#define T_SYNC 0
#define BLK_Q(p) (((p) < 3 ? (p) : 8) * 2048)
#define BLK_K(p) (((p) < 3 ? 4 + (p) : 9) * 2048)
#define BLK_V(p) (((p) < 2 ? 3 + 4 * (p) : 8 + (p)) * 2048)
template<int MT>
__device__ __forceinline__ void tok_part1(uint32_t tok, int eh, int lane, uint32_t (&q)[8][4], uint32_t (&pa)[5][2], uint32_t (&bv)[8][4], uint32_t& mt, float (&st)[2]) {
    float e[5][4];
    constexpr int NK = MT ? 5 : 3;
    const int g = lane >> 2, t = lane & 3, mi = lane >> 3, r8 = lane & 7;
    #pragma unroll
    for (int nt = 1; nt < NK; nt++) { e[nt][0] = e[nt][1] = e[nt][2] = e[nt][3] = 0.f; }
    const uint32_t qa = tok + (16 * MT + (mi & 1) * 8 + r8) * 64 + (((mi >> 1) ^ (r8 >> 1)) << 4);
    const uint32_t ka = tok + r8 * 64 + ((mi ^ (r8 >> 1)) << 4);
    #pragma unroll
    for (int k2 = 0; k2 < 4; k2++) {
        uint32_t b[NK][4];
        ldsm_x4(q[2 * k2], qa + BLK_Q(k2));
        ldsm_x4(q[2 * k2 + 1], (qa ^ 32) + BLK_Q(k2));
        #pragma unroll
        for (int nt = 1; nt < NK; nt++) ldsm_x4(b[nt], ka + BLK_K(k2) + (nt - 1) * 512);
        #pragma unroll
        for (int nt = 1; nt < NK; nt++) mma16816(e[nt], q[2 * k2], b[nt][0], b[nt][1]);
        #pragma unroll
        for (int nt = 1; nt < NK; nt++) mma16816(e[nt], q[2 * k2 + 1], b[nt][2], b[nt][3]);
    }
    uint32_t sp[NK][2];
    #pragma unroll
    for (int nt = 1; nt < NK; nt++) { sp[nt][0] = scale_bf2(pack_bf16(e[nt][0], e[nt][1])); sp[nt][1] = scale_bf2(pack_bf16(e[nt][2], e[nt][3])); }
    const uint32_t keep = (2 * t <= g ? 0x0000ffffu : 0u) | (2 * t + 1 <= g ? 0xffff0000u : 0u);
    sp[NK - 2][0] = (sp[NK - 2][0] & keep) | (NEG_BIG2 & ~keep);
    sp[NK - 1][1] = (sp[NK - 1][1] & keep) | (NEG_BIG2 & ~keep);
    uint32_t m0 = sp[1][0], m1 = sp[1][1];
    #pragma unroll
    for (int nt = 2; nt < NK; nt++) { if (nt < NK - 1) m0 = max_bf2(m0, sp[nt][0]); m1 = max_bf2(m1, sp[nt][1]); }
    mt = max_bf2(__byte_perm(m0, m1, 0x5410), __byte_perm(m0, m1, 0x7632));
    mt = max_bf2(mt, __shfl_xor_sync(0xffffffffu, mt, 1));
    mt = max_bf2(mt, __shfl_xor_sync(0xffffffffu, mt, 2));
    const float nm0 = -bf_lo(mt) * LOG2E, nm1 = -bf_hi(mt) * LOG2E;
    st[0] = st[1] = 0.f;
    #pragma unroll
    for (int nt = 1; nt < NK; nt++) {
        if (nt < NK - 1) {
            e[nt][0] = ex2(fmaf(bf_lo(sp[nt][0]), LOG2E, nm0)); e[nt][1] = ex2(fmaf(bf_hi(sp[nt][0]), LOG2E, nm0));
            st[0] += e[nt][0] + e[nt][1];
        }
        e[nt][2] = ex2(fmaf(bf_lo(sp[nt][1]), LOG2E, nm1)); e[nt][3] = ex2(fmaf(bf_hi(sp[nt][1]), LOG2E, nm1));
        st[1] += e[nt][2] + e[nt][3];
        pa[nt][0] = nt < NK - 1 ? pack_bf16(e[nt][0], e[nt][1]) : 0u; pa[nt][1] = pack_bf16(e[nt][2], e[nt][3]);
    }
    const uint32_t va = MT ? tok + lane * 64 + ((r8 >> 1) << 4) : tok + (lane & 15) * 64 + (((lane >> 4) ^ (r8 >> 1)) << 4);
    const uint32_t o0 = eh ? BLK_V(2) : BLK_V(0), o1 = eh ? BLK_V(3) : BLK_V(1);
    #pragma unroll
    for (int n = 0; n < 8; n++) { if (MT) ldsm_x4_t(bv[n], (va ^ ((n & 3) << 4)) + (n < 4 ? o0 : o1)); else ldsm_x4_t(bv[n], (va ^ ((n & 1) << 5)) + BLK_V(n >> 1)); }
}
template<int MT, class F, class G, class H>
__device__ __forceinline__ void tok_part2(uint32_t exl, uint32_t ost, int eh, int lane, const uint32_t (&q)[8][4], uint32_t (&pa)[5][2], const uint32_t (&bv)[8][4], uint32_t mt, float (&st)[2], bool vb, F&& wait_v, G&& duty, H&& pace, uint32_t nv) {
    constexpr int NK = MT ? 5 : 3;
    const int mi = lane >> 3, r8 = lane & 7;
    uint32_t sm0, sm1;
    {
        uint32_t b[4][4];
        float s1[4] = {0.f, 0.f, 0.f, 0.f}, s2[4] = {0.f, 0.f, 0.f, 0.f};
        ldsm16_t(b, exl + 2048);
        duty();
        #pragma unroll
        for (int k2 = 0; k2 < 4; k2++) { mma16816(s1, q[2 * k2], b[k2][0], b[k2][1]); mma16816(s2, q[2 * k2 + 1], b[k2][2], b[k2][3]); }
        sm0 = scale_bf2(pack_bf16(s1[0] + s2[0], s1[1] + s2[1])); sm1 = scale_bf2(pack_bf16(s1[2] + s2[2], s1[3] + s2[3]));
    }
    float nm0 = -bf_lo(mt) * LOG2E, nm1 = -bf_hi(mt) * LOG2E;
    float a0 = fmaf(bf_lo(sm0), LOG2E, nm0), a1 = fmaf(bf_hi(sm0), LOG2E, nm0), a2 = fmaf(bf_lo(sm1), LOG2E, nm1), a3 = fmaf(bf_hi(sm1), LOG2E, nm1);
    if (__builtin_expect(!__all_sync(0xffffffffu, a0 <= 57.f && a1 <= 57.f && a2 <= 57.f && a3 <= 57.f), 0)) {
        uint32_t mm = max_bf2(__byte_perm(sm0, sm1, 0x5410), __byte_perm(sm0, sm1, 0x7632));
        mm = max_bf2(mm, __shfl_xor_sync(0xffffffffu, mm, 1));
        mm = max_bf2(mm, __shfl_xor_sync(0xffffffffu, mm, 2));
        mm = max_bf2(mm, mt);
        nm0 = -bf_lo(mm) * LOG2E; nm1 = -bf_hi(mm) * LOG2E;
        const float f0 = ex2(fmaf(bf_lo(mt), LOG2E, nm0)), f1 = ex2(fmaf(bf_hi(mt), LOG2E, nm1));
        st[0] *= f0; st[1] *= f1;
        #pragma unroll
        for (int nt = 1; nt < NK; nt++) { pa[nt][0] = pack_bf16(bf_lo(pa[nt][0]) * f0, bf_hi(pa[nt][0]) * f0); pa[nt][1] = pack_bf16(bf_lo(pa[nt][1]) * f1, bf_hi(pa[nt][1]) * f1); }
        a0 = fmaf(bf_lo(sm0), LOG2E, nm0); a1 = fmaf(bf_hi(sm0), LOG2E, nm0); a2 = fmaf(bf_lo(sm1), LOG2E, nm1); a3 = fmaf(bf_hi(sm1), LOG2E, nm1);
    }
    a0 = ex2(a0); a1 = ex2(a1); a2 = ex2(a2); a3 = ex2(a3);
    float s0 = st[0] + (a0 + a1), s1 = st[1] + (a2 + a3);
    pa[0][0] = pack_bf16(a0, a1); pa[0][1] = pack_bf16(a2, a3);
    wait_v();
    constexpr int NQ = MT ? 2 : 4;
    float o[NQ][4][4];
    #pragma unroll
    for (int j = 0; j < NQ; j++) {
        uint32_t bm[4];
        ldsm_x4(bm, exl + 4096 + (MT ? eh * 1024 : 0) + 512 * j);
        #pragma unroll
        for (int n = 0; n < 4; n++) {
            o[j][n][0] = o[j][n][1] = o[j][n][2] = o[j][n][3] = 0.f;
            if (MT) mma16816r(o[j][n], pa[1][0], pa[1][1], pa[2][0], pa[2][1], bv[4 * j + n][0], bv[4 * j + n][1]);
            else mma16816r(o[j][n], pa[1][0], pa[1][1], pa[2][0], pa[2][1], bv[2 * j + (n >> 1)][2 * (n & 1)], bv[2 * j + (n >> 1)][2 * (n & 1) + 1]);
        }
        if (MT) {
            #pragma unroll
            for (int n = 0; n < 4; n++) mma16816r(o[j][n], pa[3 % NK][0], pa[3 % NK][1], pa[4 % NK][0], pa[4 % NK][1], bv[4 * j + n][2], bv[4 * j + n][3]);
        }
        #pragma unroll
        for (int n = 0; n < 4; n++) mma1688(o[j][n], pa[0][0], pa[0][1], bm[n]);
    }
    #pragma unroll
    for (int j = 0; j < NQ; j++) asm volatile("" : "+f"(o[j][0][0]), "+f"(o[j][1][0]), "+f"(o[j][2][0]), "+f"(o[j][3][0]));
    sched_fence<6 + MT>(nv);
    if (T_SYNC) { pace(); bar_sync_p(12, 384, !vb); } else { bar_arrive_p(12, 384, !vb); pace(); }
    s0 += __shfl_xor_sync(0xffffffffu, s0, 1); s1 += __shfl_xor_sync(0xffffffffu, s1, 1);
    s0 += __shfl_xor_sync(0xffffffffu, s0, 2); s1 += __shfl_xor_sync(0xffffffffu, s1, 2);
    const float i0 = rcp_approx(s0), i1 = rcp_approx(s1);
    const uint32_t oa = ost + ((mi & 1) * 8 + r8) * 128 + (((mi >> 1) ^ r8) << 4);
    #pragma unroll
    for (int j = 0; j < NQ; j++) {
        stsm_x4((oa ^ ((j & 1) << 6)) + (j >> 1) * 2048, pack_bf16(o[j][0][0] * i0, o[j][0][1] * i0), pack_bf16(o[j][0][2] * i1, o[j][0][3] * i1), pack_bf16(o[j][1][0] * i0, o[j][1][1] * i0), pack_bf16(o[j][1][2] * i1, o[j][1][3] * i1));
        stsm_x4((oa ^ (((j & 1) << 6) | 32)) + (j >> 1) * 2048, pack_bf16(o[j][2][0] * i0, o[j][2][1] * i0), pack_bf16(o[j][2][2] * i1, o[j][2][3] * i1), pack_bf16(o[j][3][0] * i0, o[j][3][1] * i0), pack_bf16(o[j][3][2] * i1, o[j][3][3] * i1));
    }
}

#define TP_E 0
#define V_EARLY 1
#define SW_FENCE 0
#define PV_FENCE 1
#define IL_AT 3
#define TAIL 0
#define MP_PRE 4
#define VF_EARLY 1
__device__ __forceinline__ void stsm2_p(uint32_t a, const uint32_t (&v)[8], uint32_t skip) {
    asm volatile("{\n.reg .pred p;\nsetp.eq.u32 p, %9, 0;\n@p stmatrix.sync.aligned.m8n8.x4.trans.shared.b16 [%0], {%1,%2,%3,%4};\n"
                 "@p stmatrix.sync.aligned.m8n8.x4.trans.shared.b16 [%0+1024], {%5,%6,%7,%8};\n}\n"
        :: "r"(a), "r"(v[0]), "r"(v[1]), "r"(v[2]), "r"(v[3]), "r"(v[4]), "r"(v[5]), "r"(v[6]), "r"(v[7]), "r"(skip) : "memory");
}
template<int OA, int OB>
__device__ __forceinline__ void send_tile(float c0, float c1, float c2, float c3, uint32_t a, uint32_t b, bool cnt, uint32_t fb) {
    const uint32_t w0 = pack_f16(c0, c1), w1 = pack_f16(c2, cnt ? 5.9604644775390625e-8f : c3), w2 = pack_f16(c3, 5.9604644775390625e-8f);
    const uint32_t hi = (uint32_t)((uint64_t)g_acc >> 32);
    asm volatile("{\n.reg .pred q;\n.reg .b64 pa, pb;\nsetp.ne.u32 q, %6, 0;\nmov.b64 pa, {%0, %2};\nmov.b64 pb, {%1, %2};\n"
                 "red.relaxed.gpu.global.add.noftz.v2.f16x2 [pa+%7], {%3, %4};\n@q red.relaxed.gpu.global.add.noftz.f16x2 [pb+%8], %5;\n}\n"
        :: "r"(a), "r"(b), "r"(hi), "r"(w0), "r"(w1), "r"(w2), "r"((uint32_t)cnt), "n"(OA), "n"(OB) : "memory");
    sts128(fb, make_uint4(__float_as_uint(c0), __float_as_uint(c1), __float_as_uint(c2), __float_as_uint(c3)));
}
__device__ __forceinline__ uint32_t send_ua(uint32_t tile) { return (uint32_t)(uint64_t)g_acc + tile * 1024; }
__device__ __forceinline__ uint32_t send_ub(uint32_t tile) { return (uint32_t)(uint64_t)g_acc + ACC_X + (tile >> 1) * 1024 + (tile & 1) * 256; }
__device__ __forceinline__ void lds_il(float& il, float& ih, uint32_t a) {
    asm volatile("ld.shared.f32 %0, [%2];\nld.shared.f32 %1, [%2+128];" : "=f"(il), "=f"(ih) : "r"(a) : "memory");
}
template<bool OWN, class F>
__device__ __forceinline__ void stage_w(const uint32_t (&wo)[8][4], uint32_t ol, uint32_t tile, uint32_t so, uint32_t l16, uint32_t fb, uint32_t nv, uint32_t ila, float il, float ih, F&& issued) {
    uint32_t b[4][4], sa, sb_;
    auto addr = [&] {
        const uint32_t ll = OWN ? l16 : l16 | (b[3][0] & nv);
        sa = (ll & 0x100u) + ((ll & 0xf0u) >> 1) + (send_ua(tile) + so); sb_ = ((ll >> 4) & 28u) + (send_ub(tile) + so);
    };
    bar_sync(11, 352);
    ldsm16_t(b, ol);
    if (OWN) addr();
    if (!OWN || SW_FENCE) sched_fence<0>(nv);
    float c[2][4];
    #pragma unroll
    for (int i = 0; i < 2; i++) c[i][0] = c[i][1] = c[i][2] = c[i][3] = 0.f;
    #pragma unroll
    for (int j = 0; j < 4; j++) {
        if (!OWN && j == IL_AT) { addr(); lds_il(il, ih, ila); }
        mma16816(c[0], wo[2 * j], b[j][0], b[j][1]); mma16816(c[1], wo[2 * j + 1], b[j][2], b[j][3]);
    }
    if (TP_E || (OWN && V_EARLY)) { asm volatile("" : "+f"(c[0][0]), "+f"(c[1][0])); sched_fence<OWN ? 4 : 5>(nv); }
    issued();
    send_tile<0, 0>((c[0][0] + c[1][0]) * il, (c[0][1] + c[1][1]) * ih, (c[0][2] + c[1][2]) * il, (c[0][3] + c[1][3]) * ih, sa, sb_, ((l16 ^ (tile << 4)) & 0x30u) == 0, fb);
}

template<int N> __device__ __forceinline__ void code_pad(uint32_t nv) {
    if (N && nv == 0x7fffffe0u + N % 16) {
        float v = __uint_as_float(nv);
        #pragma unroll
        for (int i = 0; i < N; i++) asm volatile("fma.rn.f32 %0, %0, %0, %0;" : "+f"(v));
        sts32_p(0u, __float_as_uint(v), nv);
    }
}
#define PAD_T0 4
#define PAD_T1 0
#define PAD_S 231
#define PAD_P 296
#define BAR_PRO 1
#define BAR_MEM 2
#define BAR_P   3
#define BAR_PRJ 4
#define BAR_VGO 7
#define BAR_X0  7
#define BAR_S   9
#define BAR_P2  10
#define BAR_O   11
#define BAR_O2  14
#define BAR_TP  15
#define BAR_V   12
#define BAR_FB  13
#define VGO_AT 9
#define TP_N 36
#define TP_N1 24
#define REG_P 200
#define W_FENCE 1
#define WO_PRE 4
#define WO_MID 8
#define WO_EX 8
#define WO_REP 2
#define TP_DELAY 0
#define PRE_W 4
#ifndef M_RES
#define M_RES 6
#endif
#define K_PRE 6
#define K_POS 0
#define LD_FENCE 0
#define CV_FENCE 4
#define ANN_POS 1
#define PRO_V 0
#define PUB_W 0
#define TM_PF 1
#define TS_CAP 64
#define G1_0 128
#define G1_NS 1216
#define SIG_LO     (127 - 3)
#define SIG_HI     (127 + 5)
#define SIG_LOW    0x3c00u
#define SIG_LIM    56

__global__ void __cluster_dims__(3, 1, 1) __launch_bounds__(CH_THREADS, 1)
chain_kernel(const __grid_constant__ CUtensorMap tmx, const __grid_constant__ CUtensorMap tmq, const __grid_constant__ CUtensorMap tmk,
             const __grid_constant__ CUtensorMap tmv, const __grid_constant__ CUtensorMap tmo, const bf16* __restrict__ mem0, const uint32_t nv_) {
    extern __shared__ __align__(1024) unsigned char smem[];
    const uint32_t sb = smem_u32(smem);
    const int tid = threadIdx.x, lane = tid & 31;
    const int warp = __shfl_sync(0xffffffffu, tid >> 5, 0);
    const uint32_t nv = __shfl_sync(0xffffffffu, nv_ * tid, 0);
    const int h = blockIdx.x / 3, r = blockIdx.x % 3;
    const int mi = lane >> 3, r8 = lane & 7;
    const uint32_t bX = sb + SM_BAR, bTOK = bX + 16, bEX = bX + 40, bW = bX + 64, bEV = bX + 104, bFREE = bX + 32;
    const int nqk = r < 2 ? 6 : 4;
    if ((sb & 0xFFFFFFu) != SB_OFF) __trap();
    asm volatile("griddepcontrol.launch_dependents;");
    if (tid == 0 && blockIdx.x == 0) GT(40, 0);

    auto load_w = [&](int lo, int hi) {
        #pragma unroll 1
        for (int i = lo; i < hi; i++) {
            const int blk = i >> 2, j = i & 3;
            if (i < 48) {
                const int m = r < 2 ? (j < 3 ? r : 2) : (j < 2 ? j : 2), p = r < 2 ? (j < 3 ? j : r) : (j < 2 ? 3 : j);
                asm volatile("cp.async.bulk.tensor.2d.shared::cluster.global.mbarrier::complete_tx::bytes [%0], [%1, {%3, %4}], [%2];"
                    :: "r"(sb + i * 3072), "l"(m == 0 ? &tmq : (m == 1 ? &tmk : &tmv)), "r"(bW + (blk < 3 ? 0 : (blk < 6 ? 8 : (blk < 10 ? 16 : 24)))), "r"(h * DH + p * 32), "r"(blk * 48) : "memory");
            } else asm volatile("cp.async.bulk.tensor.2d.shared::cluster.global.mbarrier::complete_tx::bytes [%0], [%1, {%3, %4}], [%2];"
                :: "r"(sb + SM_WO + (i - 48) * 8192), "l"(&tmo), "r"(bW + 32), "r"(192 * r + 32 * (i - 48)), "r"(h * DH) : "memory");
        }
    };
    if (tid == 352) {
        #pragma unroll
        for (int i = 0; i < 15; i++) mbar_init(bX + 8 * i, (i == 5 || i == 6) ? 1 + nqk : (i >= 13 ? 9 - nqk : 1));
        asm volatile("fence.mbarrier_init.release.cluster;" ::: "memory");
        mbar_expect_tx(bW, 36864); mbar_expect_tx(bW + 8, 36864); mbar_expect_tx(bW + 16, 49152); mbar_expect_tx(bW + 24, 24576); mbar_expect_tx(bW + 32, 49152);
        load_w(0, 2 * PRE_W);
    }
    if (TM_PF && tid < 2) asm volatile("prefetch.param.tensormap [%0];" :: "l"(__cvta_generic_to_grid_constant(tid ? &tmo : &tmx)) : "memory");
    const unsigned epoch = ld_relaxed32(&g_epoch);
    __syncthreads();
    const uint32_t pw0 = ((mi >> 1) * 8 + r8) * 64 + (((2 * (warp & 1) + (mi & 1)) ^ (r8 >> 1)) << 4);
    auto tok_publish = [&](int tb, int k) {
        const uint32_t src = sb + SM_TOK + tb * TOKBUF + r * 8192, bar = bTOK + 8 * tb;
        if (k == 1) asm volatile("{\n.reg .pred p;\nelect.sync _|p, 0xffffffff;\n@p mbarrier.arrive.expect_tx.shared.b64 _, [%0], 16384;\n}\n" :: "r"(bar) : "memory");
        asm volatile("{\n.reg .pred p;\nelect.sync _|p, 0xffffffff;\n"
                     "@p cp.async.bulk.shared::cluster.shared::cta.mbarrier::complete_tx::bytes [%0], [%1], 8192, [%2];\n}\n"
            :: "r"(mapa_u32(src, (r + k) % 3)), "r"(src), "r"(mapa_u32(bar, (r + k) % 3)) : "memory");
    };
    if (warp < 8) {
        asm volatile("setmaxnreg.inc.sync.aligned.u32 %0;" :: "n"(REG_P));
        uint32_t wf[36][4];
        const uint32_t wl = sb + (warp >> 1) * 3072 + pw0;
        float ta0[16], ta1[16];
        auto tp_part = [&](auto lo, auto hi) {
            wg_fence();
            #pragma unroll
            for (int i = lo.value; i < hi.value; i++) {
                if (i == 0) wgmma_n32<0>(ta0, wf[0], desc_from(DESC_LO(SM_X))); else wgmma_n32<1>(ta0, wf[i], desc_from(DESC_LO(SM_X) + (i >> 2) * 256 + (i & 3) * 2));
            }
            #pragma unroll
            for (int i = lo.value; i < hi.value; i++) {
                if (i == 0) wgmma_n32<0>(ta1, wf[0], desc_from(DESC_LO(SM_X + XBUF))); else wgmma_n32<1>(ta1, wf[i], desc_from(DESC_LO(SM_X + XBUF) + (i >> 2) * 256 + (i & 3) * 2));
            }
            wg_commit();
        };
        if (tid == 32) load_w(2 * PRE_W, 40);
        if (tid == 0) GT(41 + blockIdx.x % 3, 7);
        code_pad<PAD_P>(nv);
        mbar_wait(bW, 0);
        #pragma unroll
        for (int i = 0; i < 9; i++) ldsm_x4_t(wf[i], wl + (i / 3) * 12288 + (i % 3) * 1024);
        fence_async_smem(); bar_arrive(BAR_X0, 288);
        mbar_wait(bW + 8, 0);
        #pragma unroll
        for (int i = 9; i < 18; i++) ldsm_x4_t(wf[i], wl + (i / 3) * 12288 + (i % 3) * 1024);
        fence_async_smem(); bar_arrive(BAR_X0 + 1, 288);
        mbar_wait(bX, 0); mbar_wait(bX + 8, 0);
        tp_part(ic<0>(), ic<18>());
        wg_wait0();
        sts128(sb + SM_OST + tid * 16, make_uint4(wf[0][0], wf[0][1], wf[0][2], wf[0][3]));
        mbar_wait(bW + 16, 0);
        #pragma unroll
        for (int i = 18; i < 30; i++) ldsm_x4_t(wf[i], wl + (i / 3) * 12288 + (i % 3) * 1024);
        tp_part(ic<18>(), ic<30>());
        mbar_wait(bW + 24, 0);
        if (tid == 0) GT(41 + blockIdx.x % 3, 0);
        wg_wait0();
        #pragma unroll
        for (int i = 30; i < 36; i++) ldsm_x4_t(wf[i], wl + (i / 3) * 12288 + (i % 3) * 1024);
        fence_async_smem();
        cluster_arrive_rx();
        tp_part(ic<30>(), ic<36>());
        if (tid == 0) GT(41 + blockIdx.x % 3, 2);
        const uint32_t pw = pin(pw0);
        auto tp_store = [&](const float (&acc)[16], uint32_t off) {
            const uint32_t ta = pw + launder(sb + off + (warp >> 1) * 2048);
            stsm_x4_t(ta, pack_bf16(acc[0], acc[1]), pack_bf16(acc[2], acc[3]), pack_bf16(acc[4], acc[5]), pack_bf16(acc[6], acc[7]));
            stsm_x4_t(ta + 1024, pack_bf16(acc[8], acc[9]), pack_bf16(acc[10], acc[11]), pack_bf16(acc[12], acc[13]), pack_bf16(acc[14], acc[15]));
        };
        cluster_wait();
        wg_wait0();
        tp_store(ta0, SM_TOK + r * 8192);
        if (warp == 0) { bar_sync(BAR_PRJ, 256); fence_async_smem(); tok_publish(0, 1); tok_publish(0, 2); } else bar_arrive(BAR_PRJ, 256);
        if (!TAIL) { tp_store(ta1, SM_TOK + TOKBUF + r * 8192); }
        { const uint4 v = lds128(sb + SM_OST + tid * 16); wf[0][0] = v.x; wf[0][1] = v.y; wf[0][2] = v.z; wf[0][3] = v.w; }
        if (tid == 0) GT(41 + blockIdx.x % 3, 4);
        const uint32_t l16 = pin(lane * 16), sbl = sb + l16, l4w = pin(sb + warp * 256 + lane * 4);
        uint32_t wo[8][4];
        const int exo = r < 2 ? (warp < 6 ? r * 2048 : 4096 + (2 * r - 6) * 256) : (warp < 2 ? 6 * 256 : (warp < 4 ? 2048 + 4 * 256 : 4096));
        const bool isqk = warp < nqk;
        const uint32_t exbar = isqk ? bEX : bEV;
        uint32_t vf[2][4]; float unsc;
        auto prep = [&](int s) {
            const uint32_t va = pw + launder(sb + SM_TOK + (s & 1) * TOKBUF + BLK_V(warp >> 1));
            mbar_wait(bTOK + 8 * (s & 1), (s >> 1) & 1);
            if (VF_EARLY) { ldsm_x4_t(vf[0], va); ldsm_x4_t(vf[1], va + 1024); }
            unsc = __uint_as_float((254u - lds32(sb + SM_SG + 12 + (s & 1) * 16)) << 23);
        };
        prep(0);
        for (int s = 0; ; s++) {
            const int par = s & 1;
            const uint32_t va = pw + launder(sb + SM_TOK + par * TOKBUF + BLK_V(warp >> 1)), wa = pw + launder(sb + SM_WO + (warp >> 1) * 8192);
            const uint32_t exu = launder(SM_EX + par * EXBUF);
            if (!isqk) { bar_arrive(BAR_MEM, 352); bar_sync(BAR_VGO, 256); } else bar_sync(BAR_MEM, 352);
            {
                float acc[4][4];
                #pragma unroll
                for (int i = 0; i < 4; i++) { acc[i][0] = acc[i][1] = acc[i][2] = acc[i][3] = 0.f; }
                uint32_t b[18][4];
                #pragma unroll
                for (int i2 = 0; i2 < 18; i2++) {
                    if (!TAIL || i2 >= MP_PRE) ldsm_x4_t(b[i2], sbl + SM_MEM + i2 * 512);
                    if (i2 == VGO_AT) bar_arrive_p(BAR_VGO, 256, !isqk);
                    if (PRO_V && i2 == PRO_V) bar_arrive_p(BAR_PRO, 256 + (K_PRE < 8 ? 64 : 0), isqk || s == NSEG - 1);
                    mma16816(acc[(2 * i2) & 3], wf[2 * i2], b[i2][0], b[i2][1]);
                    mma16816(acc[(2 * i2 + 1) & 3], wf[2 * i2 + 1], b[i2][2], b[i2][3]);
                }
                float q[4];
                #pragma unroll
                for (int i = 0; i < 4; i++) q[i] = fmaf(acc[2][i] + acc[3][i], unsc, (acc[0][i] + acc[1][i]) * unsc);
                const uint32_t lo = pack_bf16(q[0], q[1]), hi = pack_bf16(q[2], q[3]);
                const uint32_t exl = l4w + launder(exu + exo), bar = exbar + par * 8;
                #pragma unroll
                for (int k = 1; k < 3; k++) {
                    const uint32_t exd = mapa_u32(exl, (r + k) % 3), exb = mapa_u32(bar, (r + k) % 3);
                    st_async32(exd, lo, exb); st_async32(exd + 128, hi, exb);
                }
                sts32(exl, lo); sts32(exl + 128, hi);
                __syncwarp();
                asm volatile("{\n.reg .pred p;\nelect.sync _|p, 0xffffffff;\n@p mbarrier.arrive.shared.b64 _, [%0];\n}\n" :: "r"(bar) : "memory");
                if (s < NSEG - 1) bar_sync_p(BAR_PRO, (PRO_V ? 256 : 32 * nqk) + (K_PRE < 8 ? 64 : 0), !isqk);
            }
            if (s == 0) mbar_wait(bW + 32, 0);
            if (s == NSEG - 1) break;
            {
                if (!VF_EARLY) { ldsm_x4_t(vf[0], va); ldsm_x4_t(vf[1], va + 1024); }
                #pragma unroll
                for (int i = 0; i < WO_PRE; i++) ldsm_x4_t(wo[i], wa + i * 1024);
                if (WO_EX > WO_PRE) {
                    #pragma unroll
                    for (int k = 0; k < WO_REP; k++) mbar_wait(bEX + 8 * par, (s >> 1) & 1);
                    #pragma unroll
                    for (int i = WO_PRE; i < WO_EX; i++) ldsm_x4_t(wo[i], wa + i * 1024);
                }
                mbar_wait(bEV + 8 * par, (s >> 1) & 1);
                const uint32_t vm0 = lds32(l4w + exu + 4096), vm1 = lds32(l4w + exu + 4096 + 128);
                #pragma unroll
                for (int i = WO_EX; i < WO_MID; i++) ldsm_x4_t(wo[i], wa + i * 1024);
                uint32_t big;
                {
                    uint32_t x = vm0 ^ vm1 ^ vf[0][0] ^ vf[1][0];
                    #pragma unroll
                    for (int i = 0; i < WO_MID; i++) x ^= wo[i][0];
                    big = bar_red_or(BAR_P, 352, x & nv);
                }
                uint32_t pb[4]; ldsm_x4_t(pb, sbl + SM_P);
                uint32_t pm = ldsm_x1_t(sbl + SM_P + 512);
                float o0[4] = {0.f, 0.f, 0.f, 0.f}, o1[4] = {0.f, 0.f, 0.f, 0.f}, o2[4] = {0.f, 0.f, 0.f, 0.f};
                #pragma unroll
                for (int i = WO_MID; i < 8; i++) if (PV_FENCE) ldsm_x4_t(wo[i], wa + i * 1024);
                if (__builtin_expect(big, 0)) {
                    bar_sync(BAR_P2, 352);
                    ldsm_x4_t(pb, sbl + SM_P); pm = ldsm_x1_t(sbl + SM_P + 512);
                }
                #pragma unroll
                for (int i = WO_MID; i < 8; i++) if (!PV_FENCE) ldsm_x4_t(wo[i], wa + i * 1024);
                mma16816(o0, vf[0], pb[0], pb[1]);
                mma16816(o1, vf[1], pb[2], pb[3]);
                mma1688(o2, vm0, vm1, pm);
                sts32(l4w + SM_O, pack_bf16((o0[0] + o1[0]) + o2[0], (o0[1] + o1[1]) + o2[1]));
                sts32(l4w + SM_O + 128, pack_bf16((o0[2] + o1[2]) + o2[2], (o0[3] + o1[3]) + o2[3]));
                const uint32_t xd = uni(DESC_LO(SM_X) + par * (XBUF >> 4));
                auto tp = [&](auto lo, auto hi) {
                    #pragma unroll
                    for (int i = lo.value; i < hi.value; i++) {
                        if (i == 0) wgmma_n32<0>(ta1, wf[0], desc_from(xd));
                        else wgmma_n32<1>(ta1, wf[i], desc_from(xd + (i >> 2) * 256 + (i & 3) * 2));
                    }
                };
                stage_w<false>(wo, sbl + SM_O, 12 * r + warp, SLOT_OFF(s + 1), l16, sbl + SM_FB + warp * 512, nv, l4w + (SM_IL - warp * 256), 0.f, 0.f, [&] {
                    if (TP_E) { bar_sync(BAR_V, 384); wg_fence(); tp(ic<0>(), ic<TP_E>()); } });
                STAMP(warp);
                bar_arrive(BAR_FB, 352);
                if (!TP_E) { bar_sync(BAR_V, 384); wg_fence(); }
                STAMP(12);
                tp(ic<TP_E>(), ic<TP_N>());
                wg_commit();
                prep(s + 1);
                if (!TAIL) { wg_wait0(); tp_store(ta1, SM_TOK + par * TOKBUF + r * 8192); STAMP(13 + (warp >> 2)); }
            }
        }
        cluster_arrive(); cluster_wait();
    } else {
        asm volatile("setmaxnreg.dec.sync.aligned.u32 %0;" :: "n"(504 - 2 * REG_P));
        const int a = warp - 8;
        const uint32_t sbl = sb + lane * 16;
        if (a < 3) {
            const uint32_t zs = 3 * blockIdx.x + (r8 >> 1);
            const uint32_t zoff = (r8 < 6 ? (zs >> 3) * 1024 + ((zs >> 2) & 1) * 256 + (zs & 3) * 32 : ACC_X + (blockIdx.x >> 1) * 1024 + (blockIdx.x & 1) * 256) + (lane & 1) * 16;
            const uint32_t zskip = r8 >= 6 && blockIdx.x >= 36;
            if (a == 1) {
                st_relaxed128_p((uint4*)(g_acc + zoff + SLOT_OFF(mi)), make_uint4(0, 0, 0, 0), zskip);
                __threadfence();
                __syncwarp();
                if (lane == 0) st_relaxed32(&g_init[blockIdx.x], epoch);
            }
            {
                uint32_t mx = 0;
                #pragma unroll
                for (int i = 0; i < 6; i++) {
                    const int c = tid - 256 + 96 * i;
                    const unsigned short* m = (const unsigned short*)mem0 + c;
                    uint4 v;
                    v.x = m[0] | ((uint32_t)m[DM] << 16); v.y = m[2 * DM] | ((uint32_t)m[3 * DM] << 16);
                    v.z = m[4 * DM] | ((uint32_t)m[5 * DM] << 16); v.w = m[6 * DM] | ((uint32_t)m[7 * DM] << 16);
                    sts128(sb + SM_MEM + c * 16, v);
                    mx = maxabs_bf2(maxabs_bf2(mx, v.x), maxabs_bf2(maxabs_bf2(v.y, v.z), v.w));
                }
                mx = __reduce_max_sync(0xffffffffu, max((mx >> 7) & 0xffu, (mx >> 23) & 0xffu));
                sts32(sb + SM_SG + a * 4, max(mx, 1u)); sts32(sb + SM_SG + 12, 127u); sts32(sb + SM_SG + 36, 0u);
            }
            asm volatile("barrier.cluster.arrive.release.aligned;" ::: "memory");
            { int it = 0; while (__any_sync(0xffffffffu, ld_relaxed32(&g_init[a * 32 + lane]) != epoch) && ++it < SPIN_LIMIT) {} }
            __threadfence();
            const uint32_t kl0 = (a < 2 ? SM_TOK + (16 * a + (mi & 1) * 8 + r8) * 64 + (((mi >> 1) ^ (r8 >> 1)) << 4) : SM_EX + 2048 + ((((mi & 1) << 1) | (mi >> 1)) * 8 + r8) * 16);
            const uint32_t l16 = pin(lane * 16);
            uint32_t kf[8][4], wo[8][4];
            auto load_k = [&](int tb, uint32_t kl, auto lo, auto hi) {
                const uint32_t ka = kl + launder(sb + tb * TOKBUF);
                #pragma unroll
                for (int kk = lo.value; kk < hi.value; kk++) ldsm_x4(kf[kk], (ka ^ ((kk & 1) << 5)) + BLK_K(kk >> 1));
            };
            code_pad<PAD_S>(nv);
            cluster_wait();
            if (a == 0 && lane == 0) { mbar_expect_tx(bEX, 4096 - 256 * nqk); mbar_expect_tx(bEV, 256 * nqk); }
            if (a < 2) bar_arrive(BAR_MEM, 352); else bar_sync(BAR_MEM, 352);
            mbar_wait(bW + 32, 0);
            #pragma unroll
            for (int i = 0; i < 8; i++) ldsm_x4_t(wo[i], pw0 + sb + SM_WO + (warp >> 1) * 8192 + i * 1024);
            sts128(sbl + SM_STASH + a * 1024 + 512, make_uint4(kl0, (pw0 ^ 32) + sb + SM_WO + 5 * 8192, zoff | ((zskip || lane >= 8) << 31), epoch << 6));
            sts128(sbl + SM_STASH + a * 1024, make_uint4(a * 12288 + (lane >> 4) * 1024 + (mi & 1) * 256 + r8 * 16, ACC_X + a * 6144 + (lane >> 4) * 1024 + (mi & 1) * 256 + r8 * 4,
                                                         sb + SM_MEM + a * 3072 + (lane >> 4) * 256 + (lane & 15) * 8, sb + SM_MEM + a * 3072 + mi * 260 + r8 * 16 + 130));
            const uint32_t stash = l16 + uni(sb + SM_STASH + a * 1024);
            #pragma unroll
            for (int i = 0; i < 8; i++) ldsm_x4_t(kf[i], (pw0 ^ 32) + sb + SM_WO + 5 * 8192 + i * 1024);
            if (a < 2) { mbar_wait(bTOK, 0); load_k(0, kl0, ic<0>(), ic<K_PRE>()); }
            __syncwarp();
            int sn = 0;
            #pragma unroll 1
            while (sn < NSEG - 1) {
              uint32_t bad, any[2], c, ax, cx;
              #pragma unroll 1
              do {
                const int s = sn, par = s & 1;
                const uint32_t exu = launder(sb + par * EXBUF);
                const uint32_t exl = l16 + exu + SM_EX;
                const uint32_t t0 = gtime_lo();
                STAMP(15); STAMPV(31, t0);
                if (a == 2) st_relaxed32_p(&g_ts[blockIdx.x], t0, l16);
                if (a == 1) {
                    const uint32_t z = lds32(stash + 520);
                    st_relaxed128_p((uint4*)(g_acc + (z + SLOT_OFF(s + 3))), make_uint4(0, 0, 0, 0), z >> 31);
                }
                if (a == 0 && l16 == 0) { mbar_expect_tx(bEX + 8 * (par ^ 1), 4096 - 256 * nqk); mbar_expect_tx(bEV + 8 * (par ^ 1), 256 * nqk); }
                sts32(sb + SM_SG + (par ^ 1) * 16 + a * 4, 0u);
                uint32_t tg;
                auto first_half = [&](auto role) {
                constexpr bool M = role.value;
                auto publish = [&] {
                    asm volatile("{\n.reg .pred p;\nelect.sync _|p, 0xffffffff;\n"
                                 "@p cp.async.bulk.shared::cluster.global.mbarrier::complete_tx::bytes.multicast::cluster [%0], [%1], 8192, [%2], %3;\n}\n"
                        :: "r"(sb + SM_TOK + (par ^ 1) * TOKBUF + r * 8192), "l"(g_tokx[blockIdx.x]), "r"(bTOK + 8 * (par ^ 1)), "h"((unsigned short)(7 ^ (1 << r))) : "memory");
                };
                uint32_t sl, sh, kl = 0, w2 = 0;
                float sig = 0.f;
                if (M) {
                    fence_async_smem();
                    if (l16 == 0) {
                        asm volatile("cp.async.bulk.global.shared::cta.bulk_group [%0], [%1], 8192;\ncp.async.bulk.commit_group;"
                            :: "l"(g_tokx[blockIdx.x]), "r"(sb + SM_TOK + (par ^ 1) * TOKBUF + r * 8192) : "memory");
                        mbar_expect_tx(bTOK + 8 * (par ^ 1), 16384);
                        if (s == 0) mbar_expect_tx(bX, XBUF);
                        if (s + 3 < NSEG) mbar_expect_tx(bX + 8 * (par ^ 1), XBUF);
                    }
                    __syncwarp();
                    if (s > 0 && s + 2 < NSEG) mbar_wait(bX + 8 * par, ((s >> 1) & 1) ^ 1);
                    if (PUB_W == 0) asm volatile("cp.async.bulk.wait_group 0;" ::: "memory");
                    kl = lds32(stash + 512);
                } else {
                    const uint4 sg = lds128(sb + SM_SG + par * 16);
                    const int e = max(max(sg.x, sg.y), sg.z), d = e - (sg.w >> 9 ? SIG_HI : SIG_LO);
                    const bool moving = d > 2 || d < -2 || s == 0;
                    uint32_t se = sg.w & 255u;
                    if (e) se = min(max((int)se + (moving ? SIG_HI : SIG_LO) - e, 127 - SIG_LIM), 127 + SIG_LIM) | (moving << 9);
                    sts32(sb + SM_SG + 12 + (par ^ 1) * 16, se);
                    sig = __uint_as_float(se << 23);
                }
                if (!M && K_PRE < 8) {
                    const uint32_t kl = lds32(stash + 512);
                    bar_sync(BAR_PRO, (PRO_V ? 256 : 32 * nqk) + 64);
                    load_k(par, kl, ic<K_PRE>(), ic<8>());
                }
                const uint32_t pst = (launder(l16) >> 2) + launder(sb + SM_P + a * 256);
                mbar_wait(bEX + 8 * par, (s >> 1) & 1);
                if (!M) {
                    uint32_t b[4][4];
                    ldsm16_t(b, exl);
                    float c[4][4];
                    #pragma unroll
                    for (int j = 0; j < 4; j++) { c[j][0] = c[j][1] = c[j][2] = c[j][3] = 0.f; }
                    #pragma unroll
                    for (int j = 0; j < 4; j++) { mma16816(c[(2 * j) & 3], kf[2 * j], b[j][0], b[j][1]); mma16816(c[(2 * j + 1) & 3], kf[2 * j + 1], b[j][2], b[j][3]); }
                    sl = scale_bf2(pack_bf16((c[0][0] + c[1][0]) + (c[2][0] + c[3][0]), (c[0][1] + c[1][1]) + (c[2][1] + c[3][1])));
                    sh = scale_bf2(pack_bf16((c[0][2] + c[1][2]) + (c[2][2] + c[3][2]), (c[0][3] + c[1][3]) + (c[2][3] + c[3][3])));
                } else {
                    float c[4][4];
                    #pragma unroll
                    for (int j = 0; j < 4; j++) { c[j][0] = c[j][1] = c[j][2] = c[j][3] = 0.f; }
                    uint32_t k[4][4], b[4][4];
                    #pragma unroll
                    for (int j = 0; j < 4; j++) { ldsm_x4_t(k[j], kl + exu + 512 * j); ldsm_x4_t(b[j], exl + 512 * j); }
                    if (PUB_W == 0) publish();
                    sched_fence<9>(nv);
                    #pragma unroll
                    for (int j = 0; j < 4; j++) { mma16816(c[2 * (j & 1)], k[j], b[j][0], b[j][1]); mma16816(c[2 * (j & 1) + 1], k[j], b[j][2], b[j][3]); }
                    sched_fence<14>(nv);
                    w2 = lds32(stash + 516);
                    sh = sl = scale_bf2(pack_bf16((c[0][0] + c[1][2]) + (c[2][0] + c[3][2]), (c[0][1] + c[1][3]) + (c[2][1] + c[3][3])));
                }
                sts32(pst, pack_bf16(ex2(bf_lo(sl) * LOG2E), ex2(bf_hi(sl) * LOG2E)));
                if (!M) sts32(pst + 128, pack_bf16(ex2(bf_lo(sh) * LOG2E), ex2(bf_hi(sh) * LOG2E)));
                if (M) {
                    #pragma unroll
                    for (int i = M_RES; i < 8; i++) ldsm_x4_t(kf[i], w2 + i * 1024);
                }
                const uint32_t big = bar_red_or(BAR_P, 352, ((maxabs_bf2(sl, sh) & 0x7fff7fffu) + 0x3ddf3ddfu) & 0x80008000u);
                float l0[4], l1[4], l2[4];
                uint32_t pb[4], pm;
                if (!M) { ldsm_x4_t(pb, l16 + sb + SM_P); pm = ldsm_x1_t(l16 + sb + SM_P + 512); }
                if (__builtin_expect(big, 0)) {
                    uint32_t m2 = max_bf2(sl, sh);
                    m2 = max_bf2(m2, __shfl_xor_sync(0xffffffffu, m2, 4));
                    m2 = max_bf2(m2, __shfl_xor_sync(0xffffffffu, m2, 8));
                    m2 = max_bf2(m2, __shfl_xor_sync(0xffffffffu, m2, 16));
                    const uint32_t lq = pin(l16);
                    if (lq < 64) sts32(lq + sb + SM_P + 768 + a * 4, m2);
                    bar_sync(BAR_S, 96);
                    const uint4 m = lds128(sb + SM_P + 768 + (lq & 0x30));
                    m2 = max_bf2(max_bf2(m.x, m.y), m.z);
                    const float ml = -bf_lo(m2) * LOG2E, mh = -bf_hi(m2) * LOG2E;
                    sts32(pst, pack_bf16(ex2(fmaf(bf_lo(sl), LOG2E, ml)), ex2(fmaf(bf_hi(sl), LOG2E, mh))));
                    if (!M) sts32(pst + 128, pack_bf16(ex2(fmaf(bf_lo(sh), LOG2E, ml)), ex2(fmaf(bf_hi(sh), LOG2E, mh))));
                    bar_sync(BAR_P2, 352);
                    if (!M) { ldsm_x4_t(pb, l16 + sb + SM_P); pm = ldsm_x1_t(l16 + sb + SM_P + 512); }
                }
                if (!M) {
                    const uint32_t ONE = 0x3F803F80u;
                    #pragma unroll
                    for (int i = 0; i < 4; i++) l0[i] = l1[i] = l2[i] = 0.f;
                    mma16816r(l0, ONE, ONE, ONE, ONE, pb[0], pb[1]);
                    mma16816r(l1, ONE, ONE, ONE, ONE, pb[2], pb[3]);
                    mma1688(l2, ONE, ONE, pm);
                }
                const uint32_t ll = launder(l16), ila = sb + SM_IL + (ll >> 2), so = SLOT_OFF(launder(s) + 1);
                if (!M) {
                    const float sil = rcp_approx((l0[0] + l1[0]) + l2[0]) * sig, sih = rcp_approx((l0[1] + l1[1]) + l2[1]) * sig;
                    sts32(ila + a * 128, __float_as_uint(a ? sih : sil));
                    stage_w<true>(wo, l16 + sb + SM_O, 12 * r + warp, so, ll, ll + (sb + SM_FB + warp * 512), nv, 0u, sil, sih, [&] { if (TP_E || V_EARLY) bar_arrive(BAR_V, 384); });
                } else {
                    if (PUB_W == 1) { asm volatile("cp.async.bulk.wait_group 0;" ::: "memory"); publish(); }
                    const uint32_t sa = launder((ll & 0x100u) + ((ll & 0xf0u) >> 1) + (send_ua(12 * r + 10) + so)), sb_ = launder(((ll >> 4) & 28u) + (send_ub(12 * r + 10) + so)), tl = (ll >> 4) & 3u;
                    bar_sync_p(BAR_O, 352, (kf[6][0] ^ kf[7][0] ^ sa ^ sb_) & nv);
                    float c[4][4], il, ih;
                    #pragma unroll
                    for (int i = 0; i < 4; i++) c[i][0] = c[i][1] = c[i][2] = c[i][3] = 0.f;
                    uint32_t b[4][4];
                    #pragma unroll
                    for (int j = 0; j < 4; j++) ldsm_x4_t(b[j], l16 + sb + SM_O + 512 * (3 - j));
                    sched_fence<11>(nv);
                    #pragma unroll
                    for (int j = 0; j < 4; j++) {
                        if (j == 2) { sched_fence<10>(nv); lds_il(il, ih, ila); }
                        mma16816(c[0], wo[6 - 2 * j], b[j][0], b[j][1]); mma16816(c[2], kf[6 - 2 * j], b[j][0], b[j][1]);
                        mma16816(c[1], wo[7 - 2 * j], b[j][2], b[j][3]); mma16816(c[3], kf[7 - 2 * j], b[j][2], b[j][3]);
                    }
                    asm volatile("" : "+f"(c[0][0]), "+f"(c[1][0]), "+f"(c[2][0]), "+f"(c[3][0]));
                    if (TP_E || V_EARLY) { if (__builtin_expect(s == 0, 0)) mbar_wait(bX, 1); bar_arrive(BAR_V, 384); }
                    send_tile<0, 0>((c[0][0] + c[1][0]) * il, (c[0][1] + c[1][1]) * ih, (c[0][2] + c[1][2]) * il, (c[0][3] + c[1][3]) * ih, sa, sb_, tl == 2, ll + (sb + SM_FB + 10 * 512));
                    send_tile<1024, 256>((c[2][0] + c[3][0]) * il, (c[2][1] + c[3][1]) * ih, (c[2][2] + c[3][2]) * il, (c[2][3] + c[3][3]) * ih, sa, sb_, tl == 3, ll + (sb + SM_FB + 11 * 512));
                    if (!TP_E && !V_EARLY && s == 0) mbar_wait(bX, 1);
                }
                };
                if (a < 2) first_half(ic<0>()); else first_half(ic<1>());
                STAMP(warp);
                if (!TP_E && !V_EARLY) bar_arrive(BAR_V, 384);
                {
                    const uint4 ad = lds128(stash);
                    const uint32_t kl = lds32(stash + 512), so = SLOT_OFF(launder(s) + 1);
                    { int it = 0; do { asm volatile("ld.volatile.shared.u32 %0, [%1];" : "=r"(tg) : "r"(sb + SM_SG + 36) : "memory"); } while ((tg & 1u) == (uint32_t)par && ++it < SPIN_LIMIT * 16); }
                    if (K_POS == 0 && a < 2) load_k(par ^ 1, kl, ic<0>(), ic<K_PRE>());
                    const uint32_t alo = (uint32_t)(uint64_t)g_acc + so;
                    const unsigned char* pm = (const unsigned char*)(((uint64_t)g_acc & ~0xffffffffull) | (ad.x + alo));
                    const unsigned char* px = (const unsigned char*)(((uint64_t)g_acc & ~0xffffffffull) | (ad.y + alo));
                    uint4 v[6]; uint32_t x[3];
                    const bool up = l16 & 256, odd = l16 & 16;
                    STAMP(16 + a); STAMPV(30, tg);
                    wait_gtime(tg);
                    #pragma unroll
                    for (int j = 0; j < 6; j++) v[j] = ld_relaxed128((const uint4*)(pm + 2048 * j));
                    #pragma unroll
                    for (int j = 0; j < 3; j++) x[j] = ld_relaxed32((const uint32_t*)(px + 2048 * j));
                    bar_sync(BAR_FB, 352);
                    STAMP(19 + a);
                    if (K_POS == 1 && a < 2) load_k(par ^ 1, kl, ic<0>(), ic<K_PRE>());
                    if (LD_FENCE) sched_fence<16>(nv);
                    uint32_t cnt[2] = {~0u, ~0u};
                    any[0] = any[1] = 0u; ax = x[0] | x[1] | x[2]; cx = x[0] & x[1] & x[2];
                    const uint32_t xw0 = h2_to_bf2(__byte_perm(x[0], x[1], 0x5410)), xw1 = h1_to_bf(x[2]);
                    auto group = [&](auto jj) {
                        constexpr int j = jj.value;
                        const uint32_t wy = h2_to_bf2(v[j].y), ww = h2_to_bf2(v[j].w);
                        sts64(ad.z + 512 * j, h2_to_bf2(v[j].x), h2_to_bf2(v[j].z));
                        sts64(ad.z + 512 * j + 128, wy, ww);
                        any[j & 1] = (any[j & 1] | v[j].x | v[j].y) | v[j].z | v[j].w;
                        cnt[j & 1] &= up ? ww : wy;
                        if (CV_FENCE & (1 << j)) { sts32_p(cnt[j & 1], any[j & 1], nv); sched_fence<17 + j>(nv); }
                    };
                    group(ic<0>()); group(ic<1>()); group(ic<2>()); group(ic<3>()); group(ic<4>()); group(ic<5>());
                    sts16(ad.w, (uint16_t)xw0); sts16(ad.w + 1024, (uint16_t)(xw0 >> 16)); sts16(ad.w + 2048, (uint16_t)xw1);
                    c = odd ? cnt[1] : cnt[0];
                    c = (c & (c >> 1)) >> 4;
                    ax |= any[0] | any[1];
                    bad = __any_sync(0xffffffffu, (((ax & 0x40004000u) | (~(c & cx) & (ACC_FULL << 16))) != 0u) | ((ax & 0x20002000u) == 0u));
                    STAMP(22 + a); STAMPV(27 + a, bad);
                    bar_sync_p(BAR_MEM, 352, bad);
                }
              } while (++sn < NSEG - 1 && !bad);
                {
                    if (bad) {
                        const int s = sn - 1, par = s & 1;
                        const uint32_t lq = pin(l16);
                        const bool up = lq & 256, odd = lq & 16;
                        uint32_t x[3];
                        int it = 0;
                        while (__any_sync(0xffffffffu, !(c & cx & (ACC_FULL << 16))) && ++it < SPIN_LIMIT) {
                            const uint4 ad = lds128(stash);
                            const uint32_t so = SLOT_OFF(launder(s) + 1), o = __shfl_xor_sync(0xffffffffu, c, 1);
                            const uint32_t again[2] = {~(odd ? o : c) & (ACC_FULL << 16), ~(odd ? c : o) & (ACC_FULL << 16)};
                            #pragma unroll
                            for (int j = 0; j < 3; j++) x[j] = ld_relaxed32((const uint32_t*)(g_acc + (ad.y + so + 2048 * j)));
                            uint4 u[6];
                            #pragma unroll
                            for (int j = 0; j < 6; j++) { u[j] = make_uint4(0u, 0u, 0u, 0u); ld_relaxed128_p(u[j], (const uint4*)(g_acc + (ad.x + so + 2048 * j)), again[j & 1]); }
                            #pragma unroll
                            for (int p = 0; p < 2; p++) if (again[p]) {
                                any[p] = 0u;
                                #pragma unroll
                                for (int j = p; j < 6; j += 2) {
                                    sts64(ad.z + 512 * j, h2_to_bf2(u[j].x), h2_to_bf2(u[j].z)); sts64(ad.z + 512 * j + 128, h2_to_bf2(u[j].y), h2_to_bf2(u[j].w));
                                    any[p] |= u[j].x | u[j].y | u[j].z | u[j].w;
                                }
                                const uint32_t cw = launder(u[p].w & u[p + 2].w & u[p + 4].w), cy = launder(u[p].y & u[p + 2].y & u[p + 4].y);
                                if (odd == p) c = up ? cw : cy;
                            }
                            __syncwarp();
                            #pragma unroll
                            for (int j = 0; j < 3; j++) sts16(ad.w + 1024 * j, (uint16_t)h1_to_bf(x[j]));
                            cx = x[0] & x[1] & x[2]; ax = x[0] | x[1] | x[2] | any[0] | any[1];
                        }
                        if (__any_sync(0xffffffffu, ((ax & 0x40004000u) != 0u) | ((ax & 0x20002000u) == 0u))) {
                            uint32_t m = 0;
                            #pragma unroll
                            for (int j = 0; j < 6; j++) { const uint4 u = lds128(lq + sb + SM_MEM + a * 3072 + 512 * j); m = maxabs_bf2(maxabs_bf2(m, maxabs_bf2(u.x, u.y)), maxabs_bf2(u.z, u.w)); }
                            uint32_t res = __reduce_max_sync(0xffffffffu, max(m & 0x7fffu, (m >> 16) & 0x7fffu));
                            if (res - SIG_LOW >= 0x7f80u - SIG_LOW) {
                                const uint32_t tag = lds32(stash + 524) + s;
                                if (a == r) {
                                    #pragma unroll 1
                                    for (int i = 0; i < 12; i++) st_relaxed128(&g_fb[a][h][i * 32 + (lq >> 4)], lds128(lq + sb + SM_FB + i * 512));
                                    __threadfence();
                                    __syncwarp();
                                    st_relaxed32_p(&g_fbf[a][h], tag, lq);
                                }
                                it = 0;
                                while (__any_sync(0xffffffffu, ld_relaxed32(&g_fbf[a][lq >> 4]) != tag) && ++it < SPIN_LIMIT) {}
                                __threadfence();
                                m = 0;
                                #pragma unroll 1
                                for (int i = 0; i < 12; i++) {
                                    float c0 = 0.f, c1 = 0.f, c2 = 0.f, c3 = 0.f;
                                    #pragma unroll 4
                                    for (int hh = 0; hh < 32; hh++) {
                                        const uint4 u = ld_relaxed128(&g_fb[a][hh][i * 32 + (lq >> 4)]);
                                        c0 += __uint_as_float(u.x); c1 += __uint_as_float(u.y); c2 += __uint_as_float(u.z); c3 += __uint_as_float(u.w);
                                    }
                                    const uint32_t w0 = pack_bf16(c0, c1), w1 = pack_bf16(c2, c3), d = sb + SM_MEM + a * 3072 + i * 256 + (lq >> 2);
                                    sts32(d, w0); sts32(d + 128, w1);
                                    m = maxabs_bf2(m, maxabs_bf2(w0, w1));
                                }
                                res = __reduce_max_sync(0xffffffffu, max(m & 0x7fffu, (m >> 16) & 0x7fffu));
                            }
                            sts32(sb + SM_SG + (par ^ 1) * 16 + a * 4, max(res >> 7, 1u));
                        }
                        bar_sync(BAR_MEM, 352);
                    }
                }
            }
        } else {
            cluster_arrive_rx();
            const uint32_t l16 = pin(lane * 16);
            bf16* dst = g_otok + h * 4096 + (r ? 1024 : 0) + (r == 2 ? 2048 : 0);
            {
                #pragma unroll
                for (int sg = 0; sg < 2; sg++) {
                    bar_sync(BAR_X0 + sg, 288);
                    if (lane == 0) {
                        mbar_expect_tx(bX + 8 * sg, XBUF);
                        #pragma unroll
                        for (int c = 0; c < 3; c++)
                            asm volatile("cp.async.bulk.tensor.3d.shared::cluster.global.mbarrier::complete_tx::bytes [%0], [%1, {%3, %4, %5}], [%2];"
                                :: "r"(sb + SM_X + sg * XBUF + c * 12288), "l"(&tmx), "r"(bX + 8 * sg), "r"(0), "r"(sg * SEG), "r"(3 * c) : "memory");
                    }
                    __syncwarp();
                }
                if (lane == 0) load_w(40, 54);
                __syncwarp();
                cluster_wait();
            }
            __syncwarp();
            auto t_loop = [&](auto mtile) {
            constexpr int MT = mtile.value;
            uint32_t q[8][4], pa[5][2], bv[8][4], mt; float st[2];
            code_pad<MT ? PAD_T1 : PAD_T0>(nv);
            mbar_wait(bTOK, 0);
            #pragma unroll 1
            for (int s = 0; s < NSEG; s++) {
                const int par = s & 1;
                const uint32_t tok = launder(sb + SM_TOK + par * TOKBUF), exl = l16 + launder(sb + SM_EX + par * EXBUF);
                const int ln = launder(l16) >> 4;
                auto announce = [&] {
                    if (s > 0) {
                        if (lane == 0) {
                            asm volatile("cp.async.bulk.wait_group 0;" ::: "memory");
                            st_relaxed32(&g_prog[blockIdx.x], epoch << 8 | s);
                        }
                        __syncwarp();
                        if (lane == 0 && blockIdx.x == 0) GT(40, s);
                    }
                };
                if (ANN_POS == 0) announce();
                tok_part1<MT>(tok, MT ? r - 1 : 0, ln, q, pa, bv, mt, st);
                if (ANN_POS == 1) announce();
                STAMP(25);
                mbar_wait(bEX + 8 * par, (s >> 1) & 1);
                STAMP(26);
                const uint32_t tex = gtime_lo();
                auto duty = [&] { if (s + 1 < NSEG) {
                    asm volatile("{\n.reg .pred p;\nelect.sync _|p, 0xffffffff;\n"
                                 "@p cp.async.bulk.shared::cluster.global.mbarrier::complete_tx::bytes [%0], [%1], 384, [%2];\n"
                                 "@p mbarrier.arrive.expect_tx.shared.b64 _, [%2], 384;\n}\n"
                        :: "r"(sb + SM_TS), "l"(g_ts), "r"(bFREE) : "memory");
                    auto issue_x = [&](int sg) {
                        asm volatile("{\n.reg .pred p, q;\nelect.sync _|p, 0xffffffff;\nsetp.eq.and.u32 q, %5, 3, p;\n"
                                     "@p cp.async.bulk.tensor.3d.shared::cluster.global.mbarrier::complete_tx::bytes.multicast::cluster [%0], [%1, {%3, %4, %5}], [%2], %6;\n"
                                     "@q cp.async.bulk.tensor.3d.shared::cluster.global.mbarrier::complete_tx::bytes.multicast::cluster [%7], [%1, {%3, %4, %3}], [%2], %6;\n}\n"
                            :: "r"(sb + SM_X + (sg & 1) * XBUF + r * 12288), "l"(&tmx), "r"(bX + 8 * (sg & 1)), "r"(0), "r"(sg * SEG), "r"(3 * r), "h"((unsigned short)7), "r"(sb + SM_X + (sg & 1) * XBUF) : "memory");
                    };
                    if (MT) {
                        if (__builtin_expect(s == 0, 0)) issue_x(2);
                        if (s + 3 < NSEG) issue_x(s + 3);
                    }
                } };
                auto pace = [&] { if (s + 1 < NSEG) {
                    mbar_wait2(bFREE, par, bTOK + 8 * (par ^ 1), ((s + 1) >> 1) & 1);
                    const uint4 ts = lds128(sb + SM_TS + min(launder(l16), 368u));
                    const uint32_t b = tex - 1150, m = __reduce_max_sync(0xffffffffu, max(max(ts.x - b, ts.y - b), max(ts.z - b, ts.w - b)));
                    asm volatile("st.volatile.shared.u32 [%0], %1;" :: "r"(sb + SM_SG + 36), "r"(((b + (s == 0 ? 0u : min(m, 1150u - TS_CAP) + G1_NS)) & ~1u) | (par ^ 1)) : "memory");
                } };
                auto wait_v = [&] {
                    mbar_wait(bEV + 8 * par, (s >> 1) & 1); };
                tok_part2<MT>(exl, sb + SM_OST, MT ? r - 1 : 0, launder(l16) >> 4, q, pa, bv, mt, st, s < NSEG - 1, wait_v, duty, pace, nv);
                STAMP(11);
                fence_async_smem();
                __syncwarp();
                if (lane == 0) {
                    asm volatile("cp.async.bulk.global.shared::cta.bulk_group [%0], [%1], 2048;" :: "l"(dst), "r"(sb + SM_OST) : "memory");
                    if (!MT) asm volatile("cp.async.bulk.global.shared::cta.bulk_group [%0], [%1], 2048;" :: "l"(dst + 2048), "r"(sb + SM_OST + 2048) : "memory");
                    asm volatile("cp.async.bulk.commit_group;" ::: "memory");
                }
                __syncwarp();
                dst += SEG * NH * DH;
            }
            };
            if (r == 0) t_loop(ic<0>()); else t_loop(ic<1>());
            if (lane == 0) {
                asm volatile("cp.async.bulk.wait_group 0;" ::: "memory");
                st_relaxed32(&g_prog[blockIdx.x], epoch << 8 | NSEG);
                if (blockIdx.x == 0) GT(40, NSEG);
            }
            __syncwarp();
        }
        cluster_arrive(); cluster_wait();
    }
}
#define SD_THREADS 384
#define SD_CTAS  36
#define BT_RS    4624
#define SD_BT    0
#define SD_STG   74752
#define SD_EF    (SD_STG + 57344)
#define SD_BC    (SD_STG)
#define KSLOTS   5
#define BC_BYTES 10240
#define BC_LBO   1280
#define SD_KP    (SD_STG + 90112)
#define SD_Q0    205824
#define SD_Q1    (SD_STG + 111616)
#define SD_OST   222720
#define SD_XCH   (SD_Q0 + 8192)
#define SD_BAR   224256
#define SD_TOTAL 224768
#define SD_SPIN  (1 << 22)
#define PART_SLOTS 8
#define SD_GO 0
#define SD_REG 200
#define SD_WAIT 6000
#define SD_P2 150
#define SD_P3 500
#define SD_GAP 0
#define SD_RUSH 44
#define SD_P1 300

__device__ uint4 g_part[SD_CTAS][PART_SLOTS][4][8][32];
__device__ __align__(16) unsigned int g_gate[S_LEN];

struct cplx { float r, i; };
__device__ __forceinline__ cplx cmul(cplx a, cplx b) { cplx c; c.r = fmaf(a.r, b.r, -a.i * b.i); c.i = fmaf(a.r, b.i, a.i * b.r); return c; }
__device__ __forceinline__ cplx cexp_(float xr, float xi) {
    const float m = ex2(xr * 1.4426950408889634f);
    const float k = rintf(xi * 0.15915494309189535f);
    const float r = fmaf(k, 1.7484555314695172e-7f, fmaf(k, -6.2831854820251465f, xi));
    cplx o; o.r = m * __cosf(r); o.i = m * __sinf(r); return o;
}
__device__ __forceinline__ void mma_f16(float (&c)[4], const uint32_t (&a)[4], uint32_t b0, uint32_t b1) {
    asm("mma.sync.aligned.m16n8k16.row.col.f32.f16.f16.f32 {%0,%1,%2,%3}, {%4,%5,%6,%7}, {%8,%9}, {%0,%1,%2,%3};"
        : "+f"(c[0]), "+f"(c[1]), "+f"(c[2]), "+f"(c[3]) : "r"(a[0]), "r"(a[1]), "r"(a[2]), "r"(a[3]), "r"(b0), "r"(b1));
}
__device__ __forceinline__ uint32_t mul_bf2(uint32_t a, uint32_t b) { uint32_t r; asm("mul.rn.bf16x2 %0, %1, %2;" : "=r"(r) : "r"(a), "r"(b)); return r; }
__device__ __forceinline__ void mbar_wait_long(uint32_t a, uint32_t parity) { int it = 0; while (!mbar_try(a, parity) && ++it < SD_SPIN) {} }
__device__ __forceinline__ uint16_t lds16(uint32_t a) { uint16_t v; asm volatile("ld.shared.u16 %0, [%1];" : "=h"(v) : "r"(a) : "memory"); return v; }
__device__ __forceinline__ void wg_wait1() { asm volatile("wgmma.wait_group.sync.aligned 1;" ::: "memory"); }
__device__ __forceinline__ void tma2d(uint32_t dst, const CUtensorMap* tm, uint32_t bar, int c0, int c1) {
    asm volatile("cp.async.bulk.tensor.2d.shared::cluster.global.mbarrier::complete_tx::bytes [%0], [%1, {%3, %4}], [%2];"
        :: "r"(dst), "l"(tm), "r"(bar), "r"(c0), "r"(c1) : "memory");
}
__device__ __forceinline__ uint32_t add_bf2(uint32_t a, uint32_t b) { uint32_t r; asm("add.rn.bf16x2 %0, %1, %2;" : "=r"(r) : "r"(a), "r"(b)); return r; }
__device__ __forceinline__ void wgmma_conv(float (&d)[32], uint32_t a0, uint32_t a1, uint32_t a2, uint32_t a3, uint64_t desc) {
    asm volatile("{\n.reg .pred p;\nsetp.ne.b32 p, 1, 0;\n"
        "wgmma.mma_async.sync.aligned.m64n64k16.f32.bf16.bf16 {%0,%1,%2,%3,%4,%5,%6,%7,%8,%9,%10,%11,%12,%13,%14,%15,%16,%17,%18,%19,%20,%21,%22,%23,%24,%25,%26,%27,%28,%29,%30,%31}, {%32,%33,%34,%35}, %36, p, 1, 1, 0;\n}\n"
        : "+f"(d[0]), "+f"(d[1]), "+f"(d[2]), "+f"(d[3]), "+f"(d[4]), "+f"(d[5]), "+f"(d[6]), "+f"(d[7]), "+f"(d[8]), "+f"(d[9]), "+f"(d[10]), "+f"(d[11]), "+f"(d[12]), "+f"(d[13]), "+f"(d[14]), "+f"(d[15]), "+f"(d[16]), "+f"(d[17]), "+f"(d[18]), "+f"(d[19]), "+f"(d[20]), "+f"(d[21]), "+f"(d[22]), "+f"(d[23]), "+f"(d[24]), "+f"(d[25]), "+f"(d[26]), "+f"(d[27]), "+f"(d[28]), "+f"(d[29]), "+f"(d[30]), "+f"(d[31])
        : "r"(a0), "r"(a1), "r"(a2), "r"(a3), "l"(desc));
}
__device__ __forceinline__ void wgmma_conv(float (&d)[24], uint32_t a0, uint32_t a1, uint32_t a2, uint32_t a3, uint64_t desc) {
    asm volatile("{\n.reg .pred p;\nsetp.ne.b32 p, 1, 0;\n"
        "wgmma.mma_async.sync.aligned.m64n48k16.f32.bf16.bf16 {%0,%1,%2,%3,%4,%5,%6,%7,%8,%9,%10,%11,%12,%13,%14,%15,%16,%17,%18,%19,%20,%21,%22,%23}, {%24,%25,%26,%27}, %28, p, 1, 1, 0;\n}\n"
        : "+f"(d[0]), "+f"(d[1]), "+f"(d[2]), "+f"(d[3]), "+f"(d[4]), "+f"(d[5]), "+f"(d[6]), "+f"(d[7]), "+f"(d[8]), "+f"(d[9]), "+f"(d[10]), "+f"(d[11]), "+f"(d[12]), "+f"(d[13]), "+f"(d[14]), "+f"(d[15]), "+f"(d[16]), "+f"(d[17]), "+f"(d[18]), "+f"(d[19]), "+f"(d[20]), "+f"(d[21]), "+f"(d[22]), "+f"(d[23])
        : "r"(a0), "r"(a1), "r"(a2), "r"(a3), "l"(desc));
}
__device__ __forceinline__ void wgmma_conv(float (&d)[16], uint32_t a0, uint32_t a1, uint32_t a2, uint32_t a3, uint64_t desc) {
    asm volatile("{\n.reg .pred p;\nsetp.ne.b32 p, 1, 0;\n"
        "wgmma.mma_async.sync.aligned.m64n32k16.f32.bf16.bf16 {%0,%1,%2,%3,%4,%5,%6,%7,%8,%9,%10,%11,%12,%13,%14,%15}, {%16,%17,%18,%19}, %20, p, 1, 1, 0;\n}\n"
        : "+f"(d[0]), "+f"(d[1]), "+f"(d[2]), "+f"(d[3]), "+f"(d[4]), "+f"(d[5]), "+f"(d[6]), "+f"(d[7]), "+f"(d[8]), "+f"(d[9]), "+f"(d[10]), "+f"(d[11]), "+f"(d[12]), "+f"(d[13]), "+f"(d[14]), "+f"(d[15])
        : "r"(a0), "r"(a1), "r"(a2), "r"(a3), "l"(desc));
}
__device__ __forceinline__ void wgmma_conv(float (&d)[8], uint32_t a0, uint32_t a1, uint32_t a2, uint32_t a3, uint64_t desc) {
    asm volatile("{\n.reg .pred p;\nsetp.ne.b32 p, 1, 0;\n"
        "wgmma.mma_async.sync.aligned.m64n16k16.f32.bf16.bf16 {%0,%1,%2,%3,%4,%5,%6,%7}, {%8,%9,%10,%11}, %12, p, 1, 1, 0;\n}\n"
        : "+f"(d[0]), "+f"(d[1]), "+f"(d[2]), "+f"(d[3]), "+f"(d[4]), "+f"(d[5]), "+f"(d[6]), "+f"(d[7])
        : "r"(a0), "r"(a1), "r"(a2), "r"(a3), "l"(desc));
}
template<int NR> __device__ __forceinline__ void conv_mma(float (&acc)[NR], const uint32_t (&R)[16], uint32_t dlo) {
    #pragma unroll
    for (int q = 0; q < 4; q++)
        wgmma_conv(acc, R[4 * q], R[4 * q + 1], R[4 * q + 2], R[4 * q + 3], (uint64_t)(dlo + (2 * (3 - q)) * (BC_LBO >> 4)) | ((uint64_t)8 << 32));
}
__device__ __forceinline__ void conv_ld(uint32_t (&R)[16], uint32_t a) {
    #pragma unroll
    for (int q = 0; q < 4; q++) { const uint2 u = lds64(a + 64 * (2 * q + 1)); R[4 * q] = u.x; R[4 * q + 1] = u.y; }
}
__device__ __forceinline__ void conv_fix(uint32_t (&R)[16], uint32_t& carry) {
    #pragma unroll
    for (int q = 0; q < 4; q++) {
        asm volatile("mov.b32 %0, %1;" : "=r"(R[4 * q + 2]) : "r"(q ? R[4 * q - 3] : carry));
        asm volatile("mov.b32 %0, %1;" : "=r"(R[4 * q + 3]) : "r"(R[4 * q]));
    }
    asm volatile("mov.b32 %0, %1;" : "=r"(carry) : "r"(R[13]));
}
template<int A> __device__ __forceinline__ void conv_group(float (&acc)[32 - 8 * A], uint32_t (&R)[4][16], uint32_t& carry, uint32_t pb, uint32_t dlo) {
    #pragma unroll
    for (int e = 0; e < 8; e += 2) {
        const int dl = 8 * A + e;
        conv_fix(R[dl & 3], carry); conv_fix(R[(dl + 1) & 3], carry);
        wg_fence(); conv_mma(acc, R[dl & 3], dlo + 16 - 2 * e); conv_mma(acc, R[(dl + 1) & 3], dlo + 14 - 2 * e); wg_commit();
        wg_wait1();
        if (dl + 2 < 32) { conv_ld(R[(dl + 2) & 3], pb + (dl + 2) * 512); conv_ld(R[(dl + 3) & 3], pb + (dl + 3) * 512); }
    }
}

__global__ void __launch_bounds__(SD_THREADS, 1)
side_kernel(const __grid_constant__ CUtensorMap tmw, const bf16* __restrict__ x,
            const bf16* __restrict__ log_A_real, const bf16* __restrict__ A_imag, const bf16* __restrict__ C_real, const bf16* __restrict__ C_imag,
            const bf16* __restrict__ log_dt, const bf16* __restrict__ D_skip, const bf16* __restrict__ gate_w, bf16* __restrict__ out) {
    extern __shared__ __align__(1024) unsigned char smem[];
    const uint32_t sb = smem_u32(smem);
    const int tid = threadIdx.x, lane = tid & 31;
    const int warp = __shfl_sync(0xffffffffu, tid >> 5, 0);
    const int g = lane >> 2, t = lane & 3, mi = lane >> 3, r8 = lane & 7;
    const bool sh = blockIdx.x < 32;
    const int d0 = blockIdx.x * 16;
    const uint32_t b0_ = sb + SD_BAR, bKF = b0_ + 384, bKE = bKF + 8 * KSLOTS, bWO = b0_ + 48, bFULL = b0_ + 56, bEMPTY = b0_ + 88, bEPI = b0_ + 120, bPRT = b0_ + 152, bGO = b0_ + 184, bCH = b0_ + 256;
    const unsigned epoch = ld_relaxed32(&g_epoch);
    if (tid == 0) GT(blockIdx.x, 0);
    if (tid == 0) {
        for (int i = 0; i < 2 * KSLOTS; i++) mbar_init(bKF + 8 * i, 128);
        mbar_init(bWO, 1);
        for (int i = 0; i < 16; i++) mbar_init(bCH + 8 * i, 1);
        for (int i = 0; i < 4; i++) { mbar_init(bFULL + 8 * i, 1); mbar_init(bEMPTY + 8 * i, sh ? 8 : 4); mbar_init(bEPI + 8 * i, 4); mbar_init(bPRT + 8 * i, 8); mbar_init(bGO + 8 * i, 1); }
        asm volatile("fence.mbarrier_init.release.cluster;" ::: "memory");
    }
    for (int i = tid; i < KSLOTS * 8 * 16; i += SD_THREADS) sts128(sb + SD_BC + (i >> 4) * BC_LBO + (i & 15) * 16, make_uint4(0, 0, 0, 0));
    if (tid < 128) sts64(sb + ((tid & 64) ? SD_Q1 : SD_Q0) + (tid & 63) * 8, 0u, 0u);
    fence_async_smem();
    __syncthreads();

    if (warp < 8) {
        asm volatile("setmaxnreg.inc.sync.aligned.u32 %0;" :: "n"(SD_REG));
        const int wg = warp >> 2, w = warp & 3, t128 = tid & 127;
        if (SD_WAIT) __nanosleep(SD_WAIT);
        {
            #pragma unroll 1
            for (int i = 0; i < 4; i++) {
                const int tp = tid + 256 * i;
                const bf16* xp = x + (size_t)(2 * tp) * DM + d0;
                const uint4 v0 = __ldg((const uint4*)xp), v1 = __ldg((const uint4*)(xp + 8)), v2 = __ldg((const uint4*)(xp + DM)), v3 = __ldg((const uint4*)(xp + DM + 8));
                const uint32_t a = sb + SD_BT + (tp >> 5) * 144 + (tp & 31) * 4;
                const uint32_t lo[8] = {v0.x, v0.y, v0.z, v0.w, v1.x, v1.y, v1.z, v1.w};
                const uint32_t hi[8] = {v2.x, v2.y, v2.z, v2.w, v3.x, v3.y, v3.z, v3.w};
                #pragma unroll
                for (int j = 0; j < 8; j++) { sts32(a + (2 * j) * BT_RS, __byte_perm(lo[j], hi[j], 0x5410)); sts32(a + (2 * j + 1) * BT_RS, __byte_perm(lo[j], hi[j], 0x7632)); }
                if (SD_GAP) __nanosleep(SD_GAP);
            }
        }
        bar_sync(1, 256);
        if (tid == 0) GT(blockIdx.x, 65);
        const uint32_t pa = sb + (wg ? SD_Q1 : SD_Q0);
        const uint32_t pb = pa + (72 + 16 * w - 56 + g - 2 * t) * 8;
        for (int c = wg; c < 16; c += 2) {
            const uint32_t bt = sb + SD_BT + c * BT_RS;
            bar_sync(2 + wg, 128);
            #pragma unroll
            for (int it = 0; it < 9; it++) {
                const int k = it < 8 ? t128 + 128 * it : t128 - 4;
                if (it < 8 || t128 < 4) {
                    auto word = [&](int j) { return j >= 0 ? lds32(bt + (j >> 5) * 144 + (j & 31) * 4) : 0u; };
                    const uint32_t c0 = word(k), p0 = word(k - 1), c1 = word(k + 4), p1 = word(k + 3);
                    sts128(pa + (72 + 2 * k) * 8, make_uint4(__byte_perm(c0, p0, 0x7610), __byte_perm(c1, p1, 0x7610), __byte_perm(c0, c0, 0x1032), __byte_perm(c1, c1, 0x1032)));
                }
            }
            bar_sync(2 + wg, 128);
            const int slot = c % KSLOTS;
            float acc[32];
            #pragma unroll
            for (int i = 0; i < 32; i++) acc[i] = 0.f;
            uint32_t R[4][16];
            uint32_t carry = lds32(pb);
            conv_ld(R[0], pb); conv_ld(R[1], pb + 512);
            const uint32_t dlo = (((sb + SD_BC + slot * BC_BYTES) & 0x3FFFF) >> 4) | ((BC_LBO >> 4) << 16);
            mbar_wait_long(bKF + 8 * slot, (c / KSLOTS) & 1);
            const float ds = bf(D_skip[d0 + c]);
            auto fin = [&](const float* a8, int q0) {
                #pragma unroll
                for (int q = 0; q < 2; q++)
                    #pragma unroll
                    for (int hh = 0; hh < 2; hh++) {
                        const uint32_t a = bt + (4 * (q0 + q) + t) * 144 + (16 * w + g + 8 * hh) * 2;
                        const float u = __uint_as_float((uint32_t)lds16(a) << 16);
                        const float y = rbf(a8[4 * q + 2 * hh] + a8[4 * q + 2 * hh + 1]);
                        sts16(a, (uint16_t)(pack_bf16(y + rbf(u * ds), 0.f) & 0xffff));
                    }
            };
            float a1[24], a2[16], a3[8];
            conv_group<0>(acc, R, carry, pb, dlo);
            wg_wait0();
            #pragma unroll
            for (int i = 0; i < 24; i++) asm volatile("mov.b32 %0, %1;" : "=f"(a1[i]) : "f"(acc[8 + i]));
            fin(acc, 0);
            conv_group<1>(a1, R, carry, pb, dlo);
            wg_wait0();
            #pragma unroll
            for (int i = 0; i < 16; i++) asm volatile("mov.b32 %0, %1;" : "=f"(a2[i]) : "f"(a1[8 + i]));
            fin(a1, 2);
            conv_group<2>(a2, R, carry, pb, dlo);
            wg_wait0();
            #pragma unroll
            for (int i = 0; i < 8; i++) asm volatile("mov.b32 %0, %1;" : "=f"(a3[i]) : "f"(a2[8 + i]));
            fin(a2, 4);
            conv_group<3>(a3, R, carry, pb, dlo);
            wg_wait0();
            mbar_arrive(bKE + 8 * slot);
            fin(a3, 6);
        }
        fence_async_smem();
        __syncthreads();
        const uint32_t stg = sb + SD_STG + wg * 65536;
        uint32_t wf[32][4];
        if (tid == 0) GT(blockIdx.x, 66);
        mbar_wait_long(bWO, 0);
        #pragma unroll
        for (int i = 0; i < 32; i++)
            ldsm_x4_t(wf[i], stg + (i * 16 + (mi >> 1) * 8 + r8) * 128 + (((2 * w + (mi & 1)) ^ r8) << 4));
        { uint32_t x = 0;
          #pragma unroll
          for (int i = 0; i < 32; i++) x |= wf[i][0];
          asm volatile("" :: "r"(x) : "memory"); }
        __syncwarp();
        if (lane == 0) {
            mbar_arrive(bEMPTY + 16 * wg); mbar_arrive(bEMPTY + 16 * wg + 8);
            if (sh) { mbar_arrive(bEMPTY + 16 * (wg ^ 1)); mbar_arrive(bEMPTY + 16 * (wg ^ 1) + 8); }
        }
        uint4* dst = sh ? &g_part[(blockIdx.x & ~7) + 4 * wg + w][0][0][blockIdx.x & 7][lane] : &g_part[32 + w][0][0][2 * (blockIdx.x - 32) + wg][lane];
        const uint32_t dl0 = (((sb + SD_STG) & 0x3FFFF) >> 4) | 0x10000u;
        auto seg = [&](int s, auto last) {
            const int bi = sh ? s & 3 : 2 * wg + (s & 1), bp = (sh ? s >> 2 : s >> 1) & 1;
            const uint32_t xd = uni(dl0 + bi * 2048);
            float acc[16];
            #pragma unroll
            for (int i = 0; i < 32; i++) {
                if (i == 0 || (last.value && (i & 7) == 0)) { mbar_wait_long(bCH + 32 * bi + i, i ? 0 : bp); wg_fence(); }
                if (i == 0) wgmma_n32<0>(acc, wf[i], desc_from(xd));
                else wgmma_n32<1>(acc, wf[i], desc_from(xd + (i >> 2) * 256 + (i & 3) * 2));
            }
            wg_commit();
            if (s >= PART_SLOTS / 2) mbar_wait_long(bEPI + 8 * (s & 3), ((s - 4) >> 2) & 1);
            const uint32_t ph = ((s / PART_SLOTS) & 1) ^ 1;
            uint4* p = dst + (s % PART_SLOTS) * (4 * 8 * 32);
            wg_wait0();
            #pragma unroll
            for (int j = 0; j < 4; j++)
                st_relaxed128(p + 256 * j, make_uint4((__float_as_uint(acc[4 * j]) & ~1u) | ph, __float_as_uint(acc[4 * j + 1]), __float_as_uint(acc[4 * j + 2]), __float_as_uint(acc[4 * j + 3])));
            if (tid == 0 && s == NSEG - 1) GT(blockIdx.x, 71);
            __syncwarp();
            if (lane == 0) { mbar_arrive(bEMPTY + 8 * bi); mbar_arrive(bPRT + 8 * (s & 3)); }
        };
        #pragma unroll 1
        for (int s = 0; s < NSEG - 1; s++) seg(s, ic<0>());
        seg(NSEG - 1, ic<1>());
    } else {
        asm volatile("setmaxnreg.dec.sync.aligned.u32 %0;" :: "n"(504 - 2 * SD_REG));
        const int w = warp - 8, n = tid - 256;
        bf16 p_la = log_A_real[d0 * NS + n], p_ai = A_imag[d0 * NS + n], p_cr = C_real[d0 * NS + n], p_ci = C_imag[d0 * NS + n], p_dt = log_dt[d0];
        const uint32_t ef = sb + SD_EF + w * 8192;
        const uint32_t efl = ef + lane * 4;
        uint32_t goff[8];
        #pragma unroll
        for (int i = 0; i < 16; i++) {
            const int l = 64 * lane + 8 * (w + 4 * (i >> 3)) + (i & 7);
            const int p = (int)rbf((float)l);
            const int a = p >> 7, b = (p >> 3) & 15, c = p & 7;
            const int row = p < 256 ? 8 * a + c : (p < 512 ? 16 + 4 * (a - 2) + (c >> 1) : (p < 1024 ? 24 + 2 * (a - 4) + (c >> 2) : 24 + a));
            const uint32_t off = row * 72 + b * 4;
            if (i & 1) goff[i >> 1] |= off << 16; else goff[i >> 1] = off;
        }
        for (int c = 0; c < 16; c++) {
            const float dt = rbf(expf(bf(p_dt)));
            const float xr = -rbf(expf(bf(p_la))) * dt, xi = bf(p_ai) * dt;
            cplx C; C.r = 2.f * bf(p_cr) * dt; C.i = 2.f * bf(p_ci) * dt;
            if (c + 1 < 16) {
                const int o = (d0 + c + 1) * NS + n;
                p_la = log_A_real[o]; p_ai = A_imag[o]; p_cr = C_real[o]; p_ci = C_imag[o]; p_dt = log_dt[d0 + c + 1];
            }
            const uint32_t mexp = min(max(__reduce_max_sync(0xffffffffu, __float_as_uint(fmaxf(fabsf(C.r), fabsf(C.i)))) & 0x7f800000u, 0x01000000u), 0x7e000000u);
            const float unsc = __uint_as_float(mexp), sc = __uint_as_float(0x7f000000u - mexp);
            C.r *= sc; C.i *= sc;
            #define EADDR(r) ((efl ^ (((r) & 7) << 4)) + (r) * 128)
            {
                cplx f[16];
                f[1] = cexp_(8.f * xr, -8.f * xi);
                f[2] = cmul(f[1], f[1]); f[3] = cmul(f[2], f[1]); f[4] = cmul(f[2], f[2]); f[5] = cmul(f[4], f[1]); f[6] = cmul(f[4], f[2]); f[7] = cmul(f[4], f[3]);
                f[8] = cmul(f[4], f[4]);
                #pragma unroll
                for (int b = 9; b < 16; b++) f[b] = cmul(f[8], f[b - 8]);
                sts32(EADDR(0) + 6144, 0x00003c00u);
                #pragma unroll
                for (int b = 1; b < 16; b++) sts32(EADDR(b) + 6144, pack_f16(f[b].r, f[b].i));
            }
            {
                cplx G[17], wc[8];
                G[1] = cexp_(128.f * xr, 128.f * xi);
                wc[1] = cexp_(xr, xi);
                G[2] = cmul(G[1], G[1]); G[4] = cmul(G[2], G[2]); G[8] = cmul(G[4], G[4]);
                wc[2] = cmul(wc[1], wc[1]); wc[3] = cmul(wc[2], wc[1]); wc[4] = cmul(wc[2], wc[2]); wc[5] = cmul(wc[4], wc[1]); wc[6] = cmul(wc[4], wc[2]); wc[7] = cmul(wc[4], wc[3]);
                cplx CG[17];
                CG[0] = C; CG[1] = cmul(C, G[1]); CG[2] = cmul(C, G[2]); CG[3] = cmul(CG[1], G[2]);
                #pragma unroll
                for (int a = 0; a < 4; a++) CG[4 + a] = cmul(CG[a], G[4]);
                #pragma unroll
                for (int a = 0; a < 9; a++) CG[8 + a] = cmul(CG[a], G[8]);
                #pragma unroll
                for (int r = 0; r < 41; r++) {
                    const int a = r < 16 ? (r >> 3) : (r < 24 ? 2 + ((r >> 2) & 1) : (r < 32 ? 4 + ((r >> 1) & 3) : r - 24));
                    const int cc = r < 16 ? (r & 7) : (r < 24 ? 2 * (r & 3) : (r < 32 ? 4 * (r & 1) : 0));
                    const cplx e = cc ? cmul(CG[a], wc[cc]) : CG[a];
                    sts32(EADDR(r), pack_f16(e.r, e.i));
                }
            }
            __syncwarp();
            float acc[3][2][4];
            #pragma unroll
            for (int i = 0; i < 3; i++)
                #pragma unroll
                for (int j = 0; j < 2; j++) { acc[i][j][0] = acc[i][j][1] = acc[i][j][2] = acc[i][j][3] = 0.f; }
            #pragma unroll
            for (int ks = 0; ks < 4; ks++) {
                uint32_t bq[4];
                ldsm_x4(bq, ef + 6144 + ((mi >> 1) * 8 + r8) * 128 + (((2 * ks + (mi & 1)) ^ r8) << 4));
                #pragma unroll
                for (int mt = 0; mt < 3; mt++) {
                    uint32_t aq[4];
                    ldsm_x4(aq, ef + (16 * mt + (mi & 1) * 8 + r8) * 128 + (((2 * ks + (mi >> 1)) ^ r8) << 4));
                    mma_f16(acc[mt][0], aq, bq[0], bq[1]);
                    mma_f16(acc[mt][1], aq, bq[2], bq[3]);
                }
            }
            const uint32_t kp = sb + SD_KP;
            #pragma unroll
            for (int mt = 0; mt < 3; mt++)
                #pragma unroll
                for (int nt = 0; nt < 2; nt++) {
                    const uint32_t a = kp + w * 3072 + (16 * mt + g) * 64 + nt * 32 + t * 8;
                    sts64(a, __float_as_uint(acc[mt][nt][0] * unsc), __float_as_uint(acc[mt][nt][1] * unsc));
                    sts64(a + 512, __float_as_uint(acc[mt][nt][2] * unsc), __float_as_uint(acc[mt][nt][3] * unsc));
                }
            bar_sync(4, 128);
            #pragma unroll
            for (int i = 0; i < 3; i++) {
                const uint32_t a = kp + (n + 128 * i) * 8;
                const uint2 v0 = lds64(a), v1 = lds64(a + 3072), v2 = lds64(a + 6144), v3 = lds64(a + 9216);
                sts64(a + 12288 + ((n >> 3) + 16 * i) * 8, __float_as_uint((__uint_as_float(v0.x) + __uint_as_float(v1.x)) + (__uint_as_float(v2.x) + __uint_as_float(v3.x))),
                                 __float_as_uint((__uint_as_float(v0.y) + __uint_as_float(v1.y)) + (__uint_as_float(v2.y) + __uint_as_float(v3.y))));
            }
            bar_sync(4, 128);
            const int slot = c % KSLOTS;
            float kv[16];
            #pragma unroll
            for (int e = 0; e < 8; e++) { kv[2 * e] = __uint_as_float(lds32(kp + 12288 + (goff[e] & 0xffff))); kv[2 * e + 1] = __uint_as_float(lds32(kp + 12288 + (goff[e] >> 16))); }
            if (c >= KSLOTS) mbar_wait_long(bKE + 8 * slot, (c / KSLOTS - 1) & 1);
            #pragma unroll
            for (int it = 0; it < 2; it++) {
                uint32_t hi[4], lo[4];
                #pragma unroll
                for (int e = 0; e < 4; e++) {
                    const float k0 = kv[8 * it + 2 * e], k1 = kv[8 * it + 2 * e + 1];
                    hi[e] = pack_bf16(k0, k1);
                    lo[e] = pack_bf16(k0 - bf_lo(hi[e]), k1 - bf_hi(hi[e]));
                }
                const uint32_t a = sb + SD_BC + slot * BC_BYTES + (w + 4 * it) * BC_LBO + (16 + 2 * lane) * 16;
                sts128(a, make_uint4(hi[0], hi[1], hi[2], hi[3]));
                sts128(a + 16, make_uint4(lo[0], lo[1], lo[2], lo[3]));
            }
            fence_async_smem();
            mbar_arrive(bKF + 8 * slot);
        }
        {
            uint32_t gw[9];
            #pragma unroll
            for (int j = 0; j < 9; j++) gw[j] = __ldg((const uint32_t*)gate_w + lane + 32 * j);
            float z = 0.f;
            #pragma unroll 1
            for (int i0 = 0; i0 < 15; i0 += 5) {
                uint32_t xv[5][9];
                #pragma unroll
                for (int i = 0; i < 5; i++) {
                    const int tk = min(blockIdx.x * 57 + w + 4 * (i0 + i), S_LEN - 1);
                    #pragma unroll
                    for (int j = 0; j < 9; j++) xv[i][j] = __ldg((const uint32_t*)(x + (size_t)tk * DM) + lane + 32 * j);
                }
                #pragma unroll
                for (int i = 0; i < 5; i++) {
                    float acc = 0.f;
                    #pragma unroll
                    for (int j = 0; j < 9; j++) { const uint32_t m = mul_bf2(xv[i][j], gw[j]); acc += bf_lo(m) + bf_hi(m); }
                    #pragma unroll
                    for (int o = 16; o; o >>= 1) acc += __shfl_xor_sync(0xffffffffu, acc, o);
                    if (lane == i0 + i) z = rbf(acc);
                }
            }
            const int li = w + 4 * lane, tk = blockIdx.x * 57 + li;
            if (li < 57 && tk < S_LEN) st_relaxed32(&g_gate[tk], pack_bf16(1.f / (1.f + expf(-z)), 0.f) | (epoch << 16));
        }
        if (tid == 256) GT(blockIdx.x, 67);
        fence_async_smem();
        __syncthreads();
            const uint32_t ost = sb + SD_OST + w * 256;
            const uint4* const pl = &g_part[blockIdx.x][0][0][0][lane];
            uint4 v[8];
            auto fetch = [&](int u, bool block) {
                const int s = u >> 2;
                uint32_t early;
                asm volatile("{\n.reg .pred p;\nmbarrier.test_wait.parity.shared::cta.b64 p, [%1], %2;\nselp.u32 %0, 1, 0, p;\n}\n" : "=r"(early) : "r"(bPRT + 8 * (s & 3)), "r"((s >> 2) & 1) : "memory");
                if (!early) {
                    if (!block) return false;
                    mbar_wait_long(bPRT + 8 * (s & 3), (s >> 2) & 1);
                    delay_clk(s < NSEG - 2 ? SD_P1 : SD_P2);
                } else if (SD_P3 && s < SD_RUSH) delay_clk(SD_P3);
                const uint4* p = pl + (u & (4 * PART_SLOTS - 1)) * 256;
                #pragma unroll
                for (int i = 0; i < 8; i++) v[i] = ld_relaxed128(p + 32 * i);
                return true;
            };
            auto units = [&](int u, int end) {
              fetch(u, true);
              #pragma unroll 1
              while (true) {
                const int s = u >> 2;
                const int t0 = 8 * u + 2 * t;
                const uint2 gt = lds64(sb + SD_Q0 + t0 * 4);
                const uint32_t ba = sb + SD_BT + g * BT_RS + (t0 >> 6) * 144 + (t0 & 63) * 2;
                const uint32_t b0 = lds32(ba), b1 = lds32(ba + 8 * BT_RS);
                const uint32_t phm = ((s / PART_SLOTS) & 1) - 1;
                int it = 0;
                while (true) {
                    uint32_t any = 0;
                    #pragma unroll
                    for (int i = 0; i < 8; i++) any |= v[i].x ^ phm;
                    if (!__any_sync(0xffffffffu, any & 1u) || ++it >= SD_SPIN) break;
                    if (it > 1 && s < NSEG - 2) __nanosleep(200);
                    const uint4* p = pl + (u & (4 * PART_SLOTS - 1)) * 256;
                    #pragma unroll
                    for (int i = 0; i < 8; i++) ld_relaxed128_p(v[i], p + 32 * i, (v[i].x ^ phm) & 1u);
                }
                if (lane == 0) mbar_arrive(bEPI + 8 * (s & 3));
                float a0 = __uint_as_float(v[0].x), a1 = __uint_as_float(v[0].y), a2 = __uint_as_float(v[0].z), a3 = __uint_as_float(v[0].w);
                #pragma unroll
                for (int i = 1; i < 8; i++) { a0 += __uint_as_float(v[i].x); a1 += __uint_as_float(v[i].y); a2 += __uint_as_float(v[i].z); a3 += __uint_as_float(v[i].w); }
                const uint32_t s01 = pack_bf16(a0, a1), s23 = pack_bf16(a2, a3);
                const int nu = u + 3;
                const bool pre = nu < end && fetch(nu, false);
                const uint32_t gg = __byte_perm(gt.x, gt.y, 0x5410), mm = pack_bf16(1.f - bf_lo(gg), 1.f - bf_hi(gg));
                const uint32_t r0 = add_bf2(mul_bf2(gg, s01), mul_bf2(mm, b0)), r1 = add_bf2(mul_bf2(gg, s23), mul_bf2(mm, b1));
                asm volatile("stmatrix.sync.aligned.m8n8.x2.trans.shared.b16 [%0], {%1,%2};" :: "r"(ost + r8 * 32 + (mi & 1) * 16), "r"(r0), "r"(r1) : "memory");
                __syncwarp();
                if (lane < 16) *(uint4*)(out + (size_t)(8 * u + (lane >> 1)) * DM + d0 + 8 * (lane & 1)) = lds128(ost + lane * 16);
                __syncwarp();
                if (lane == 0 && (u & 3) == 3) GT(blockIdx.x, 1 + s);
                if (nu >= end) break;
                if (!pre) fetch(nu, true);
                u = nu;
              }
            };
        if (w == 0) {
            if (lane == 0) {
                mbar_expect_tx(bWO, 131072);
                #pragma unroll
                for (int q = 0; q < 4; q++) tma2d(sb + SD_STG + q * 32768, &tmw, bWO, sh ? 128 * (blockIdx.x >> 3) + 64 * (q >> 1) : 512, sh ? 512 * (blockIdx.x & 7) + 256 * (q & 1) : 1024 * (blockIdx.x - 32) + 256 * q);
            }
            bar_sync(5, 128);
            const int ke0 = sh ? blockIdx.x & 7 : 2 * (blockIdx.x - 32);
            const unsigned int* f = &g_prog[12 * ke0 + (lane < (sh ? 12 : 24) ? lane : 0)];
            int avail = 0;
            #pragma unroll 1
            for (int s = 0; s < NSEG; s++) {
                if (s >= avail) {
                    int it = 0;
                    while (true) {
                        uint32_t v;
                        asm volatile("ld.acquire.gpu.global.u32 %0, [%1];" : "=r"(v) : "l"(f) : "memory");
                        avail = __reduce_min_sync(0xffffffffu, (v >> 8) == (epoch & 0xffffffu) ? v & 255u : 0u);
                        if (avail > s || ++it >= SD_SPIN) break;
                        if (s < NSEG - 1) __nanosleep(64);
                    }
                    asm volatile("fence.proxy.async.global;" ::: "memory");
                    if (lane == 0 && s == NSEG - 1) GT(blockIdx.x, 70);
                }
                if (lane == 0 && s == 2 && blockIdx.x == 0) st_relaxed32(&g_epoch, epoch + 1);
                const int b0 = sh ? s & 3 : s & 1, bp = (sh ? s >> 2 : s >> 1) & 1;
                const bf16* src = g_otok + (size_t)s * (SEG * NH * DH) + ke0 * 16384;
                mbar_wait_long(bEMPTY + 8 * b0, bp);
                if (!sh) mbar_wait_long(bEMPTY + 16 + 8 * b0, bp);
                if (s < NSEG - 1) {
                    asm volatile("{\n.reg .pred p, q;\nelect.sync _|p, 0xffffffff;\nsetp.eq.and.u32 q, %6, 0, p;\n"
                                 "@p mbarrier.arrive.expect_tx.shared.b64 _, [%2], 32768;\n"
                                 "@p cp.async.bulk.shared::cluster.global.mbarrier::complete_tx::bytes [%0], [%1], 32768, [%2];\n"
                                 "@q mbarrier.arrive.expect_tx.shared.b64 _, [%5], 32768;\n"
                                 "@q cp.async.bulk.shared::cluster.global.mbarrier::complete_tx::bytes [%3], [%4], 32768, [%5];\n}\n"
                        :: "r"(sb + SD_STG + b0 * 32768), "l"(src), "r"(bCH + 32 * b0), "r"(sb + SD_STG + (b0 + 2) * 32768), "l"(src + 16384), "r"(bCH + 32 * (b0 + 2)), "r"((uint32_t)sh) : "memory");
                } else {
                    #pragma unroll
                    for (int hc = 0; hc < 4; hc++)
                        asm volatile("{\n.reg .pred p, q;\nelect.sync _|p, 0xffffffff;\nsetp.eq.and.u32 q, %6, 0, p;\n"
                                     "@p mbarrier.arrive.expect_tx.shared.b64 _, [%2], 8192;\n"
                                     "@p cp.async.bulk.shared::cluster.global.mbarrier::complete_tx::bytes [%0], [%1], 8192, [%2];\n"
                                     "@q mbarrier.arrive.expect_tx.shared.b64 _, [%5], 8192;\n"
                                     "@q cp.async.bulk.shared::cluster.global.mbarrier::complete_tx::bytes [%3], [%4], 8192, [%5];\n}\n"
                            :: "r"(sb + SD_STG + b0 * 32768 + hc * 8192), "l"(src + hc * 4096), "r"(bCH + 32 * b0 + 8 * hc),
                               "r"(sb + SD_STG + (b0 + 2) * 32768 + hc * 8192), "l"(src + 16384 + hc * 4096), "r"(bCH + 32 * (b0 + 2) + 8 * hc), "r"((uint32_t)sh) : "memory");
                }
            }
        } else {
            if (w == 3) {
                for (int i = 0; i < 16; i += 8) {
                    uint4 v[8]; uint32_t miss = 0xffu; int it = 0;
                    const uint32_t tag = epoch & 0xffffu;
                    #pragma unroll
                    for (int j = 0; j < 8; j++) v[j] = make_uint4(0, 0, 0, 0);
                    do {
                        #pragma unroll
                        for (int j = 0; j < 8; j++) ld_relaxed128_p(v[j], (const uint4*)g_gate + (i + j) * 32 + lane, miss & (1u << j));
                        miss = 0;
                        #pragma unroll
                        for (int j = 0; j < 8; j++) miss |= (uint32_t)((v[j].x >> 16) != tag || (v[j].y >> 16) != tag || (v[j].z >> 16) != tag || (v[j].w >> 16) != tag) << j;
                    } while (__any_sync(0xffffffffu, miss) && ++it < SD_SPIN);
                    #pragma unroll
                    for (int j = 0; j < 8; j++) sts128(sb + SD_Q0 + ((i + j) * 32 + lane) * 16, v[j]);
                }
            }
            bar_sync(5, 128);
        }
        #pragma unroll 1
        for (int k = w == 0; k < 2; k++) units(k ? 4 * (NSEG - 1) + w : w - 1, k ? 0 : 4 * (NSEG - 1));
    }
    if (tid == 256) GT(blockIdx.x, 72);
}

extern "C" void kernel_launch(void* const* d_in, const int* in_sizes, int n_in, void* d_out, int out_size) {
    const bf16* x = (const bf16*)d_in[0];
    const bf16* mem0 = (const bf16*)d_in[1];
    const bf16* Wq = (const bf16*)d_in[2];
    const bf16* Wk = (const bf16*)d_in[3];
    const bf16* Wv = (const bf16*)d_in[4];
    const bf16* Wo = (const bf16*)d_in[5];
    const bf16* log_A_real = (const bf16*)d_in[8];
    const bf16* A_imag = (const bf16*)d_in[9];
    const bf16* C_real = (const bf16*)d_in[10];
    const bf16* C_imag = (const bf16*)d_in[11];
    const bf16* log_dt = (const bf16*)d_in[12];
    const bf16* D_skip = (const bf16*)d_in[13];
    const bf16* gate_w = (const bf16*)d_in[14];
    bf16* out = (bf16*)d_out;
    typedef CUresult (*EncFn)(CUtensorMap*, CUtensorMapDataType, cuuint32_t, void*, const cuuint64_t*, const cuuint64_t*, const cuuint32_t*, const cuuint32_t*,
                              CUtensorMapInterleave, CUtensorMapSwizzle, CUtensorMapL2promotion, CUtensorMapFloatOOBfill);
    static EncFn enc = nullptr;
    if (!enc) { void* fn = nullptr; cudaDriverEntryPointQueryResult qr; cudaGetDriverEntryPoint("cuTensorMapEncodeTiled", &fn, cudaEnableDefault, &qr); enc = (EncFn)fn; }
    auto mk = [&](CUtensorMap* tm, const void* ptr, uint64_t cols, uint64_t rows, uint32_t bc, uint32_t br) {
        cuuint64_t gdim[2] = {cols, rows}; cuuint64_t gstr[1] = {cols * 2}; cuuint32_t box[2] = {bc, br}; cuuint32_t estr[2] = {1, 1};
        enc(tm, CU_TENSOR_MAP_DATA_TYPE_BFLOAT16, 2, (void*)ptr, gdim, gstr, box, estr, CU_TENSOR_MAP_INTERLEAVE_NONE, bc == 64 ? CU_TENSOR_MAP_SWIZZLE_128B : CU_TENSOR_MAP_SWIZZLE_64B,
            CU_TENSOR_MAP_L2_PROMOTION_L2_256B, CU_TENSOR_MAP_FLOAT_OOB_FILL_NONE);
    };
    static bool attr_done = false;
    if (!attr_done) {
        cudaFuncSetAttribute(chain_kernel, cudaFuncAttributeMaxDynamicSharedMemorySize, SM_TOTAL);
        cudaFuncSetAttribute(side_kernel, cudaFuncAttributeMaxDynamicSharedMemorySize, SD_TOTAL);
        attr_done = true;
    }
    CUtensorMap tmx, tmw, tmq, tmk, tmv, tmo;
    {
        cuuint64_t gdim[3] = {64, S_LEN, DM / 64}; cuuint64_t gstr[2] = {DM * 2, 128}; cuuint32_t box[3] = {64, SEG, 3}; cuuint32_t estr[3] = {1, 1, 1};
        enc(&tmx, CU_TENSOR_MAP_DATA_TYPE_BFLOAT16, 3, (void*)x, gdim, gstr, box, estr, CU_TENSOR_MAP_INTERLEAVE_NONE, CU_TENSOR_MAP_SWIZZLE_128B,
            CU_TENSOR_MAP_L2_PROMOTION_L2_256B, CU_TENSOR_MAP_FLOAT_OOB_FILL_NONE);
    }
    mk(&tmw, Wo, DM, NH * DH, 64, 256);
    mk(&tmo, Wo, DM, NH * DH, 32, 128);
    mk(&tmq, Wq, NH * DH, DM, 32, 48); mk(&tmk, Wk, NH * DH, DM, 32, 48); mk(&tmv, Wv, NH * DH, DM, 32, 48);
    chain_kernel<<<96, CH_THREADS, SM_TOTAL>>>(tmx, tmq, tmk, tmv, tmo, mem0, 0u);
    cudaLaunchConfig_t cfg = {};
    cfg.gridDim = dim3(SD_CTAS); cfg.blockDim = dim3(SD_THREADS); cfg.dynamicSmemBytes = SD_TOTAL; cfg.stream = cudaStreamPerThread;
    cudaLaunchAttribute at[1];
    at[0].id = cudaLaunchAttributeProgrammaticStreamSerialization; at[0].val.programmaticStreamSerializationAllowed = 1;
    cfg.attrs = at; cfg.numAttrs = 1;
    cudaLaunchKernelEx(&cfg, side_kernel, tmw, x, log_A_real, A_imag, C_real, C_imag, log_dt, D_skip, gate_w, out);
}
```

```cpp
#include <cuda_runtime.h>
#include <cuda.h>
#include <cuda_bf16.h>
#include <stdint.h>

#define S_LEN 2048
#define DM 576
#define NH 32
#define DH 128
#define NMEM 8
#define SEG 32
#define NSEG 64
#define LQ 40
#define NS 128

typedef __nv_bfloat16 bf16;

__device__ __forceinline__ float bf(bf16 v) { return __bfloat162float(v); }
__device__ __forceinline__ bf16 tobf(float v) { return __float2bfloat16_rn(v); }
__device__ __forceinline__ float rbf(float v) { return __bfloat162float(__float2bfloat16_rn(v)); }

#define CH_THREADS 384
#define SPIN_LIMIT (1 << 17)
#define SM_X     0
#define XBUF     36864
#define SM_TOK   73728
#define TOKBUF   24576
#define SM_STASH 139264
#define SM_TS    (SM_STASH + 3072)
#define SM_WO    147456
#define SM_MEM   196608
#define SM_EX    205824
#define EXBUF    6144
#define SM_P     218112
#define SM_OST   219136
#define SM_O     223232
#define SM_BAR   228352
#define SM_IL    (SM_BAR + 128)
#define SM_SG    (SM_IL + 256)
#define SM_TOTAL (SM_SG + 64)

#define ACC_X    36864
#define ACC_FULL 0x0020u
#define SLOT_OFF(sl) ((((sl) & 1) << 7) | (((sl) & 2) << 8))
__device__ __align__(65536) unsigned char g_acc[65536];
__device__ unsigned int g_init[96];
__device__ unsigned int g_epoch = 1;
__device__ __align__(128) unsigned int g_ts[128];
__device__ __align__(1024) bf16 g_otok[S_LEN * NH * DH];
__device__ __align__(1024) unsigned char g_tokx[96][8192];
__device__ __align__(128) unsigned int g_prog[96];
#define STAMP(i)
#define STAMPV(i, v)
#define GT(b, i)
#define STAMPB(i)

__device__ __forceinline__ uint32_t smem_u32(const void* p) { return (uint32_t)__cvta_generic_to_shared(p); }
__device__ __forceinline__ void ldsm_x4(uint32_t (&r)[4], uint32_t addr) {
    asm volatile("ldmatrix.sync.aligned.m8n8.x4.shared.b16 {%0,%1,%2,%3}, [%4];" : "=r"(r[0]), "=r"(r[1]), "=r"(r[2]), "=r"(r[3]) : "r"(addr) : "memory");
}
__device__ __forceinline__ void ldsm_x4_p(uint32_t (&r)[4], uint32_t addr, uint32_t skip) {
    asm volatile("{\n.reg .pred p;\nsetp.eq.u32 p, %5, 0;\n@p ldmatrix.sync.aligned.m8n8.x4.shared.b16 {%0,%1,%2,%3}, [%4];\n}\n" : "+r"(r[0]), "+r"(r[1]), "+r"(r[2]), "+r"(r[3]) : "r"(addr), "r"(skip) : "memory");
}
__device__ __forceinline__ void ldsm_x4_t(uint32_t (&r)[4], uint32_t addr) {
    asm volatile("ldmatrix.sync.aligned.m8n8.x4.trans.shared.b16 {%0,%1,%2,%3}, [%4];" : "=r"(r[0]), "=r"(r[1]), "=r"(r[2]), "=r"(r[3]) : "r"(addr) : "memory");
}
__device__ __forceinline__ uint32_t ldsm_x1_t(uint32_t addr) {
    uint32_t r; asm volatile("ldmatrix.sync.aligned.m8n8.x1.trans.shared.b16 {%0}, [%1];" : "=r"(r) : "r"(addr) : "memory"); return r;
}
__device__ __forceinline__ void ldsm_x2_t(uint32_t& r0, uint32_t& r1, uint32_t addr) {
    asm volatile("ldmatrix.sync.aligned.m8n8.x2.trans.shared.b16 {%0,%1}, [%2];" : "=r"(r0), "=r"(r1) : "r"(addr) : "memory");
}
__device__ __forceinline__ void stsm_x4(uint32_t addr, uint32_t r0, uint32_t r1, uint32_t r2, uint32_t r3) {
    asm volatile("stmatrix.sync.aligned.m8n8.x4.shared.b16 [%0], {%1,%2,%3,%4};" :: "r"(addr), "r"(r0), "r"(r1), "r"(r2), "r"(r3) : "memory");
}
__device__ __forceinline__ void stsm_x4_t(uint32_t addr, uint32_t r0, uint32_t r1, uint32_t r2, uint32_t r3) {
    asm volatile("stmatrix.sync.aligned.m8n8.x4.trans.shared.b16 [%0], {%1,%2,%3,%4};" :: "r"(addr), "r"(r0), "r"(r1), "r"(r2), "r"(r3) : "memory");
}
__device__ __forceinline__ void mma16816(float (&c)[4], const uint32_t (&a)[4], uint32_t b0, uint32_t b1) {
    asm("mma.sync.aligned.m16n8k16.row.col.f32.bf16.bf16.f32 {%0,%1,%2,%3}, {%4,%5,%6,%7}, {%8,%9}, {%0,%1,%2,%3};"
        : "+f"(c[0]), "+f"(c[1]), "+f"(c[2]), "+f"(c[3]) : "r"(a[0]), "r"(a[1]), "r"(a[2]), "r"(a[3]), "r"(b0), "r"(b1));
}
__device__ __forceinline__ void mma16816r(float (&c)[4], uint32_t a0, uint32_t a1, uint32_t a2, uint32_t a3, uint32_t b0, uint32_t b1) {
    asm("mma.sync.aligned.m16n8k16.row.col.f32.bf16.bf16.f32 {%0,%1,%2,%3}, {%4,%5,%6,%7}, {%8,%9}, {%0,%1,%2,%3};"
        : "+f"(c[0]), "+f"(c[1]), "+f"(c[2]), "+f"(c[3]) : "r"(a0), "r"(a1), "r"(a2), "r"(a3), "r"(b0), "r"(b1));
}
__device__ __forceinline__ void mma1688(float (&c)[4], uint32_t a0, uint32_t a1, uint32_t b0) {
    asm("mma.sync.aligned.m16n8k8.row.col.f32.bf16.bf16.f32 {%0,%1,%2,%3}, {%4,%5}, {%6}, {%0,%1,%2,%3};"
        : "+f"(c[0]), "+f"(c[1]), "+f"(c[2]), "+f"(c[3]) : "r"(a0), "r"(a1), "r"(b0));
}
__device__ __forceinline__ uint32_t pack_bf16(float lo, float hi) {
    uint32_t r; asm("cvt.rn.bf16x2.f32 %0, %1, %2;" : "=r"(r) : "f"(hi), "f"(lo)); return r;
}
__device__ __forceinline__ float bf_lo(uint32_t v) { return __uint_as_float(v << 16); }
__device__ __forceinline__ float bf_hi(uint32_t v) { return __uint_as_float(v & 0xffff0000u); }
__device__ __forceinline__ uint32_t max_bf2(uint32_t a, uint32_t b) { uint32_t r; asm("max.bf16x2 %0, %1, %2;" : "=r"(r) : "r"(a), "r"(b)); return r; }
__device__ __forceinline__ uint32_t maxabs_bf2(uint32_t a, uint32_t b) { uint32_t r; asm("max.NaN.xorsign.abs.bf16x2 %0, %1, %2;" : "=r"(r) : "r"(a), "r"(b)); return r; }
__device__ __forceinline__ float ex2(float x) { float r; asm("ex2.approx.ftz.f32 %0, %1;" : "=f"(r) : "f"(x)); return r; }
__device__ __forceinline__ void ld_relaxed128_p(uint4& v, const uint4* p, uint32_t pred) {
    asm volatile("{\n.reg .pred p;\nsetp.ne.u32 p, %5, 0;\n@p ld.relaxed.gpu.global.v4.u32 {%0,%1,%2,%3}, [%4];\n}\n" : "+r"(v.x), "+r"(v.y), "+r"(v.z), "+r"(v.w) : "l"(p), "r"(pred) : "memory");
}
__device__ __forceinline__ uint4 ld_relaxed128(const uint4* p) { uint4 v; asm volatile("ld.relaxed.gpu.global.v4.u32 {%0,%1,%2,%3}, [%4];" : "=r"(v.x), "=r"(v.y), "=r"(v.z), "=r"(v.w) : "l"(p) : "memory"); return v; }
__device__ __forceinline__ uint32_t ld_relaxed32(const uint32_t* p) { uint32_t v; asm volatile("ld.relaxed.gpu.global.u32 %0, [%1];" : "=r"(v) : "l"(p) : "memory"); return v; }
__device__ __forceinline__ void st_relaxed128(uint4* p, uint4 v) { asm volatile("st.relaxed.gpu.global.v4.u32 [%0], {%1,%2,%3,%4};" :: "l"(p), "r"(v.x), "r"(v.y), "r"(v.z), "r"(v.w) : "memory"); }
__device__ __forceinline__ void st_relaxed32(uint32_t* p, uint32_t v) { asm volatile("st.relaxed.gpu.global.u32 [%0], %1;" :: "l"(p), "r"(v) : "memory"); }
__device__ __forceinline__ void st_relaxed128_p(uint4* p, uint4 v, uint32_t skip) {
    asm volatile("{\n.reg .pred p;\nsetp.eq.u32 p, %5, 0;\n@p st.relaxed.gpu.global.v4.u32 [%0], {%1,%2,%3,%4};\n}\n" :: "l"(p), "r"(v.x), "r"(v.y), "r"(v.z), "r"(v.w), "r"(skip) : "memory");
}
__device__ __forceinline__ void st_relaxed64_p(void* p, uint32_t x, uint32_t y, uint32_t skip) {
    asm volatile("{\n.reg .pred p;\n.reg .b64 v;\nsetp.eq.u32 p, %3, 0;\nmov.b64 v, {%1,%2};\n@p st.relaxed.gpu.global.b64 [%0], v;\n}\n" :: "l"(p), "r"(x), "r"(y), "r"(skip) : "memory");
}
__device__ __forceinline__ void ld_relaxed64_p(uint2& v, const void* p, uint32_t pred) {
    asm volatile("{\n.reg .pred p;\n.reg .b64 v;\nsetp.ne.u32 p, %3, 0;\nmov.b64 v, {%0,%1};\n@p ld.relaxed.gpu.global.b64 v, [%2];\nmov.b64 {%0,%1}, v;\n}\n" : "+r"(v.x), "+r"(v.y) : "l"(p), "r"(pred) : "memory");
}
__device__ __forceinline__ uint2 ld_relaxed64(const void* p) {
    uint2 v; asm volatile("{\n.reg .b64 v;\nld.relaxed.gpu.global.b64 v, [%2];\nmov.b64 {%0,%1}, v;\n}\n" : "=r"(v.x), "=r"(v.y) : "l"(p) : "memory"); return v;
}
__device__ __forceinline__ void st_relaxed32_p(void* p, uint32_t v, uint32_t skip) {
    asm volatile("{\n.reg .pred p;\nsetp.eq.u32 p, %2, 0;\n@p st.relaxed.gpu.global.u32 [%0], %1;\n}\n" :: "l"(p), "r"(v), "r"(skip) : "memory");
}
__device__ __forceinline__ void bar_arrive_p(int id, int n, uint32_t skip) {
    asm volatile("{\n.reg .pred p;\nsetp.eq.u32 p, %2, 0;\n@p bar.arrive %0, %1;\n}\n" :: "r"(id), "r"(n), "r"(skip) : "memory");
}
__device__ __forceinline__ void bar_sync_p(int id, int n, uint32_t skip) {
    asm volatile("{\n.reg .pred p;\nsetp.eq.u32 p, %2, 0;\n@p bar.sync %0, %1;\n}\n" :: "r"(id), "r"(n), "r"(skip) : "memory");
}
__device__ __forceinline__ uint32_t movm(uint32_t x) { uint32_t r; asm volatile("movmatrix.sync.aligned.m8n8.trans.b16 %0, %1;" : "=r"(r) : "r"(x)); return r; }
__device__ __forceinline__ void sts32_p(uint32_t a, uint32_t v, uint32_t doit) {
    asm volatile("{\n.reg .pred p;\nsetp.ne.u32 p, %2, 0;\n@p st.shared.u32 [%0], %1;\n}\n" :: "r"(a), "r"(v), "r"(doit) : "memory");
}
__device__ __forceinline__ uint32_t pin(uint32_t x) { return __shfl_sync(0xffffffffu, x, threadIdx.x & 31); }
__device__ __forceinline__ void ldsm16_t(uint32_t (&b)[4][4], uint32_t a) {
    asm volatile("ldmatrix.sync.aligned.m8n8.x4.trans.shared.b16 {%0,%1,%2,%3}, [%16];\n"
                 "ldmatrix.sync.aligned.m8n8.x4.trans.shared.b16 {%4,%5,%6,%7}, [%16+512];\n"
                 "ldmatrix.sync.aligned.m8n8.x4.trans.shared.b16 {%8,%9,%10,%11}, [%16+1024];\n"
                 "ldmatrix.sync.aligned.m8n8.x4.trans.shared.b16 {%12,%13,%14,%15}, [%16+1536];\n"
        : "=r"(b[0][0]), "=r"(b[0][1]), "=r"(b[0][2]), "=r"(b[0][3]), "=r"(b[1][0]), "=r"(b[1][1]), "=r"(b[1][2]), "=r"(b[1][3]),
          "=r"(b[2][0]), "=r"(b[2][1]), "=r"(b[2][2]), "=r"(b[2][3]), "=r"(b[3][0]), "=r"(b[3][1]), "=r"(b[3][2]), "=r"(b[3][3]) : "r"(a) : "memory");
}
template<int ID> __device__ __forceinline__ void sched_fence(uint32_t never) { while (never == 0x7fffff00u + ID) { asm volatile("nanosleep.u32 64;" ::: "memory"); } }
__device__ __forceinline__ uint32_t opaque_u() { uint32_t v; asm volatile("mov.u32 %0, %%nsmid;" : "=r"(v)); return v; }
__device__ __forceinline__ uint32_t bar_red_or(int id, int n, uint32_t v) {
    uint32_t r; asm volatile("{\n.reg .pred p, q;\nsetp.ne.u32 p, %3, 0;\nbar.red.or.pred q, %1, %2, p;\nselp.u32 %0, 1, 0, q;\n}\n" : "=r"(r) : "r"(id), "r"(n), "r"(v) : "memory"); return r;
}
template<class T> __device__ __forceinline__ T* launder_p(T* p) { asm volatile("" : "+l"(p)); return p; }
__device__ __forceinline__ uint32_t mapa_u32(uint32_t addr, uint32_t rank) { uint32_t d; asm("mapa.shared::cluster.u32 %0, %1, %2;" : "=r"(d) : "r"(addr), "r"(rank)); return d; }
__device__ __forceinline__ uint32_t mapa_v(uint32_t addr, uint32_t rank) { uint32_t d; asm volatile("mapa.shared::cluster.u32 %0, %1, %2;" : "=r"(d) : "r"(addr), "r"(rank)); return d; }
__device__ __forceinline__ void st_async32(uint32_t addr, uint32_t v, uint32_t mbar) { asm volatile("st.async.shared::cluster.mbarrier::complete_tx::bytes.u32 [%0], %1, [%2];" :: "r"(addr), "r"(v), "r"(mbar) : "memory"); }
__device__ __forceinline__ void cluster_arrive() { asm volatile("barrier.cluster.arrive.release.aligned;" ::: "memory"); }
__device__ __forceinline__ void cluster_wait() { asm volatile("barrier.cluster.wait.acquire.aligned;" ::: "memory"); }
__device__ __forceinline__ void cp_async16(uint32_t dst, const void* src) { asm volatile("cp.async.cg.shared.global [%0], [%1], 16;" :: "r"(dst), "l"(src) : "memory"); }
__device__ __forceinline__ void cp_async_commit() { asm volatile("cp.async.commit_group;" ::: "memory"); }
template<int N> __device__ __forceinline__ void cp_async_wait() { asm volatile("cp.async.wait_group %0;" :: "n"(N) : "memory"); }
__device__ __forceinline__ void cp_async_wait0() { asm volatile("cp.async.wait_group 0;" ::: "memory"); }
__device__ __forceinline__ void mbar_init(uint32_t a, uint32_t cnt) { asm volatile("mbarrier.init.shared.b64 [%0], %1;" :: "r"(a), "r"(cnt) : "memory"); }
__device__ __forceinline__ void mbar_expect_tx(uint32_t a, uint32_t bytes) { asm volatile("mbarrier.arrive.expect_tx.shared.b64 _, [%0], %1;" :: "r"(a), "r"(bytes) : "memory"); }
__device__ __forceinline__ bool mbar_try(uint32_t a, uint32_t parity) {
    uint32_t ok; asm volatile("{\n.reg .pred p;\nmbarrier.try_wait.parity.shared::cta.b64 p, [%1], %2;\nselp.u32 %0, 1, 0, p;\n}\n" : "=r"(ok) : "r"(a), "r"(parity) : "memory"); return ok;
}
__device__ __forceinline__ void mbar_wait(uint32_t a, uint32_t parity) { int it = 0; while (!mbar_try(a, parity) && ++it < SPIN_LIMIT) {} }
__device__ __forceinline__ void bar_sync(int id, int n) { asm volatile("bar.sync %0, %1;" :: "r"(id), "r"(n) : "memory"); }
__device__ __forceinline__ void bar_arrive(int id, int n) { asm volatile("bar.arrive %0, %1;" :: "r"(id), "r"(n) : "memory"); }
__device__ __forceinline__ void fence_async_smem() { asm volatile("fence.proxy.async.shared::cta;" ::: "memory"); }
__device__ __forceinline__ void sts32(uint32_t a, uint32_t v) { asm volatile("st.shared.u32 [%0], %1;" :: "r"(a), "r"(v) : "memory"); }
__device__ __forceinline__ void sts128(uint32_t a, uint4 v) { asm volatile("st.shared.v4.u32 [%0], {%1,%2,%3,%4};" :: "r"(a), "r"(v.x), "r"(v.y), "r"(v.z), "r"(v.w) : "memory"); }
__device__ __forceinline__ uint4 lds128(uint32_t a) { uint4 v; asm volatile("ld.shared.v4.u32 {%0,%1,%2,%3}, [%4];" : "=r"(v.x), "=r"(v.y), "=r"(v.z), "=r"(v.w) : "r"(a) : "memory"); return v; }
__device__ __forceinline__ uint32_t lds32(uint32_t a) { uint32_t v; asm volatile("ld.shared.u32 %0, [%1];" : "=r"(v) : "r"(a) : "memory"); return v; }
__device__ __forceinline__ uint32_t gtime_lo() { uint32_t t; asm volatile("mov.u32 %0, %globaltimer_lo;" : "=r"(t)); return t; }
__device__ __forceinline__ void wait_gtime(uint32_t tg) {
    asm volatile("{\n.reg .pred p, q;\n.reg .b64 t;\n.reg .b32 lo, hi, d, n;\nmov.b32 n, 300;\n"
                 "WG_%=:\nmov.u64 t, %%globaltimer;\nmov.b64 {lo, hi}, t;\nsub.s32 d, lo, %0;\nsub.s32 n, n, 1;\n"
                 "setp.gt.s32 q, n, 0;\nsetp.lt.and.s32 p, d, 0, q;\n@p bra.uni WG_%=;\n}\n" :: "r"(tg) : "memory");
}
__device__ __forceinline__ void delay_clk(int d) { uint32_t t0 = clock(); while ((int)(clock() - t0) < d) {} }

__device__ __forceinline__ uint64_t desc128(uint32_t addr) {
    return (uint64_t)((addr & 0x3FFFF) >> 4) | ((uint64_t)1 << 16) | ((uint64_t)64 << 32) | ((uint64_t)1 << 62);
}
template<int accum> __device__ __forceinline__ void wgmma_n32(float (&d)[16], const uint32_t (&a)[4], uint64_t desc) {
    if (accum) {
        asm volatile("{\n.reg .pred p;\nsetp.ne.b32 p, 1, 0;\n"
            "wgmma.mma_async.sync.aligned.m64n32k16.f32.bf16.bf16 {%0,%1,%2,%3,%4,%5,%6,%7,%8,%9,%10,%11,%12,%13,%14,%15}, {%16,%17,%18,%19}, %20, p, 1, 1, 0;\n}\n"
            : "+f"(d[0]), "+f"(d[1]), "+f"(d[2]), "+f"(d[3]), "+f"(d[4]), "+f"(d[5]), "+f"(d[6]), "+f"(d[7]),
              "+f"(d[8]), "+f"(d[9]), "+f"(d[10]), "+f"(d[11]), "+f"(d[12]), "+f"(d[13]), "+f"(d[14]), "+f"(d[15])
            : "r"(a[0]), "r"(a[1]), "r"(a[2]), "r"(a[3]), "l"(desc));
    } else {
        asm volatile("{\n.reg .pred p;\nsetp.ne.b32 p, 0, 0;\n"
            "wgmma.mma_async.sync.aligned.m64n32k16.f32.bf16.bf16 {%0,%1,%2,%3,%4,%5,%6,%7,%8,%9,%10,%11,%12,%13,%14,%15}, {%16,%17,%18,%19}, %20, p, 1, 1, 0;\n}\n"
            : "=f"(d[0]), "=f"(d[1]), "=f"(d[2]), "=f"(d[3]), "=f"(d[4]), "=f"(d[5]), "=f"(d[6]), "=f"(d[7]),
              "=f"(d[8]), "=f"(d[9]), "=f"(d[10]), "=f"(d[11]), "=f"(d[12]), "=f"(d[13]), "=f"(d[14]), "=f"(d[15])
            : "r"(a[0]), "r"(a[1]), "r"(a[2]), "r"(a[3]), "l"(desc));
    }
}
__device__ __forceinline__ float rcp_approx(float x) { float r; asm("rcp.approx.ftz.f32 %0, %1;" : "=f"(r) : "f"(x)); return r; }
__device__ __forceinline__ void wg_fence() { asm volatile("wgmma.fence.sync.aligned;" ::: "memory"); }
__device__ __forceinline__ void wg_commit() { asm volatile("wgmma.commit_group.sync.aligned;" ::: "memory"); }
__device__ __forceinline__ void wg_wait0() { asm volatile("wgmma.wait_group.sync.aligned 0;" ::: "memory"); }

#define SCALE_HI 0x3db53db5u
#define SCALE_LO 0x371e371eu
#define LOG2E 1.4426950408889634f
#define NEG_BIG2 0xce6ece6eu
__device__ __forceinline__ uint32_t scale_bf2(uint32_t x) {
    uint32_t t, r;
    asm("mul.rn.bf16x2 %0, %1, %2;" : "=r"(t) : "r"(x), "r"(SCALE_LO));
    asm("fma.rn.bf16x2 %0, %1, %2, %3;" : "=r"(r) : "r"(x), "r"(SCALE_HI), "r"(t));
    return r;
}
__device__ __forceinline__ void cluster_arrive_rx() { asm volatile("barrier.cluster.arrive.relaxed.aligned;" ::: "memory"); }
__device__ __forceinline__ uint32_t launder(uint32_t x) { asm volatile("" : "+r"(x)); return x; }
__device__ __forceinline__ void mbar_arrive(uint32_t a) { asm volatile("mbarrier.arrive.shared.b64 _, [%0];" :: "r"(a) : "memory"); }
__device__ __forceinline__ void mbar_wait_cl(uint32_t a, uint32_t parity) {
    int it = 0; uint32_t ok;
    do { asm volatile("{\n.reg .pred p;\nmbarrier.try_wait.parity.acquire.cluster.shared::cta.b64 p, [%1], %2;\nselp.u32 %0, 1, 0, p;\n}\n" : "=r"(ok) : "r"(a), "r"(parity) : "memory"); } while (!ok && ++it < SPIN_LIMIT);
}
__device__ __forceinline__ uint64_t desc_from(uint32_t lo) { return (uint64_t)lo | ((uint64_t)0x40000040u << 32); }
#define SB_OFF 1024u
#define DESC_LO(off) ((((SB_OFF + (uint32_t)(off)) & 0x3FFFFu) >> 4) | 0x10000u)
template<int N> struct ic { static constexpr int value = N; };
__device__ __forceinline__ uint32_t uni(uint32_t x) { return __shfl_sync(0xffffffffu, x, 0); }

__device__ __forceinline__ uint32_t pack_f16(float lo, float hi) { uint32_t r; asm("cvt.rn.f16x2.f32 %0, %1, %2;" : "=r"(r) : "f"(hi), "f"(lo)); return r; }
__device__ __forceinline__ void sts16(uint32_t a, uint16_t v) { asm volatile("st.shared.u16 [%0], %1;" :: "r"(a), "h"(v) : "memory"); }
__device__ __forceinline__ void sts64(uint32_t a, uint32_t x, uint32_t y) { asm volatile("st.shared.v2.u32 [%0], {%1,%2};" :: "r"(a), "r"(x), "r"(y) : "memory"); }
__device__ __forceinline__ void ld_relaxed32_p(uint32_t& v, const void* p, uint32_t pred) {
    asm volatile("{\n.reg .pred p;\nsetp.ne.u32 p, %2, 0;\n@p ld.relaxed.gpu.global.u32 %0, [%1];\n}\n" : "+r"(v) : "l"(p), "r"(pred) : "memory");
}
__device__ __forceinline__ uint2 lds64(uint32_t a) { uint2 v; asm volatile("ld.shared.v2.u32 {%0,%1}, [%2];" : "=r"(v.x), "=r"(v.y) : "r"(a) : "memory"); return v; }
__device__ __forceinline__ void mbar_wait2(uint32_t a, uint32_t pa, uint32_t b, uint32_t pb) {
    int it = 0; uint32_t ok;
    do { asm volatile("{\n.reg .pred p, q;\nmbarrier.try_wait.parity.shared::cta.b64 p, [%1], %2;\nmbarrier.try_wait.parity.shared::cta.b64 q, [%3], %4;\nand.pred p, p, q;\nselp.u32 %0, 1, 0, p;\n}\n"
                      : "=r"(ok) : "r"(a), "r"(pa), "r"(b), "r"(pb) : "memory"); } while (!ok && ++it < SPIN_LIMIT);
}
__device__ __forceinline__ float exd(float s, float m) { return ex2(__fmul_rn(__fsub_rn(s, m), LOG2E)); }
__device__ __forceinline__ uint32_t gtime_after(uint32_t z) {
    uint32_t t = 0; asm volatile("{\n.reg .pred p;\nsetp.eq.u32 p, %1, 0;\n@p mov.u32 %0, %%globaltimer_lo;\n}\n" : "+r"(t) : "r"(z)); return t;
}
#define BLK_Q(p) (((p) < 3 ? (p) : 8) * 2048)
#define BLK_K(p) (((p) < 3 ? 4 + (p) : 9) * 2048)
#define BLK_V(p) (((p) < 2 ? 3 + 4 * (p) : 8 + (p)) * 2048)
__device__ __forceinline__ uint32_t exp_bf2(uint32_t s) { return pack_bf16(ex2(bf_lo(s) * LOG2E), ex2(bf_hi(s) * LOG2E)); }
template<int MT, int LO, int HI>
__device__ __forceinline__ void tok_loadv(uint32_t tok, int eh, int lane, uint32_t (&bv)[8][4]) {
    const int r8 = lane & 7;
    const uint32_t va = MT ? tok + lane * 64 + ((r8 >> 1) << 4) : tok + (lane & 15) * 64 + (((lane >> 4) ^ (r8 >> 1)) << 4);
    const uint32_t o0 = eh ? BLK_V(2) : BLK_V(0), o1 = eh ? BLK_V(3) : BLK_V(1);
    #pragma unroll
    for (int n = LO; n < HI; n++) { if (MT) ldsm_x4_t(bv[n], (va ^ ((n & 3) << 4)) + (n < 4 ? o0 : o1)); else ldsm_x4_t(bv[n], (va ^ ((n & 1) << 5)) + BLK_V(n >> 1)); }
}
#define T_VPRE 4
template<int MT, class F>
__device__ __forceinline__ void tok_part1(uint32_t tok, int eh, int lane, uint32_t (&q)[8][4], uint32_t (&sp)[5][2], uint32_t (&pa)[5][2], uint32_t (&bv)[8][4], uint32_t& rng, F&& hold) {
    float e[5][4];
    constexpr int NK = MT ? 5 : 3;
    const int g = lane >> 2, t = lane & 3, mi = lane >> 3, r8 = lane & 7;
    #pragma unroll
    for (int nt = 1; nt < NK; nt++) { e[nt][0] = e[nt][1] = e[nt][2] = e[nt][3] = 0.f; }
    const uint32_t qa = tok + (16 * MT + (mi & 1) * 8 + r8) * 64 + (((mi >> 1) ^ (r8 >> 1)) << 4);
    const uint32_t ka = tok + r8 * 64 + ((mi ^ (r8 >> 1)) << 4);
    #pragma unroll
    for (int k2 = 0; k2 < 4; k2++) {
        uint32_t b[NK][4];
        ldsm_x4(q[2 * k2], qa + BLK_Q(k2));
        ldsm_x4(q[2 * k2 + 1], (qa ^ 32) + BLK_Q(k2));
        #pragma unroll
        for (int nt = 1; nt < NK; nt++) ldsm_x4(b[nt], ka + BLK_K(k2) + (nt - 1) * 512);
        #pragma unroll
        for (int nt = 1; nt < NK; nt++) mma16816(e[nt], q[2 * k2], b[nt][0], b[nt][1]);
        #pragma unroll
        for (int nt = 1; nt < NK; nt++) mma16816(e[nt], q[2 * k2 + 1], b[nt][2], b[nt][3]);
    }
    #pragma unroll
    for (int nt = 1; nt < NK; nt++) asm volatile("" : "+f"(e[nt][0]), "+f"(e[nt][1]), "+f"(e[nt][2]), "+f"(e[nt][3]));
    hold();
    #pragma unroll
    for (int nt = 1; nt < NK; nt++) {
        sp[nt][0] = nt < NK - 1 ? scale_bf2(pack_bf16(e[nt][0], e[nt][1])) : NEG_BIG2; sp[nt][1] = scale_bf2(pack_bf16(e[nt][2], e[nt][3]));
        rng = maxabs_bf2(nt == 1 ? sp[1][0] : (nt < NK - 1 ? maxabs_bf2(rng, sp[nt][0]) : rng), sp[nt][1]);
    }
    const uint32_t keep = (2 * t <= g ? 0x0000ffffu : 0u) | (2 * t + 1 <= g ? 0xffff0000u : 0u);
    sp[NK - 2][0] = (sp[NK - 2][0] & keep) | (NEG_BIG2 & ~keep);
    sp[NK - 1][1] = (sp[NK - 1][1] & keep) | (NEG_BIG2 & ~keep);
    #pragma unroll
    for (int nt = 1; nt < NK; nt++) { pa[nt][0] = nt < NK - 1 ? exp_bf2(sp[nt][0]) : 0u; pa[nt][1] = exp_bf2(sp[nt][1]); }
    tok_loadv<MT, 0, MT ? T_VPRE : 8>(tok, eh, lane, bv);
}
template<int MT, class F, class G, class H, class I>
__device__ __forceinline__ void tok_part2(uint32_t tok, uint32_t exl, uint32_t ost, int eh, int lane, const uint32_t (&q)[8][4], uint32_t (&sp)[5][2], uint32_t (&pa)[5][2], uint32_t (&bv)[8][4], uint32_t rng, bool vb,
                                          F&& wait_v, G&& duty, H&& pace, I&& wait_x) {
    constexpr int NK = MT ? 5 : 3;
    const int mi = lane >> 3, r8 = lane & 7;
    {
        float c[4][4];
        uint32_t b[4][4];
        ldsm16_t(b, exl + 2048);
        duty();
        #pragma unroll
        for (int j = 0; j < 4; j++) { c[j][0] = c[j][1] = c[j][2] = c[j][3] = 0.f; }
        #pragma unroll
        for (int k2 = 0; k2 < 4; k2++) { mma16816(c[(2 * k2) & 3], q[2 * k2], b[k2][0], b[k2][1]); mma16816(c[(2 * k2 + 1) & 3], q[2 * k2 + 1], b[k2][2], b[k2][3]); }
        sp[0][0] = scale_bf2(pack_bf16((c[0][0] + c[1][0]) + (c[2][0] + c[3][0]), (c[0][1] + c[1][1]) + (c[2][1] + c[3][1])));
        sp[0][1] = scale_bf2(pack_bf16((c[0][2] + c[1][2]) + (c[2][2] + c[3][2]), (c[0][3] + c[1][3]) + (c[2][3] + c[3][3])));
    }
    pa[0][0] = exp_bf2(sp[0][0]); pa[0][1] = exp_bf2(sp[0][1]);
    rng = maxabs_bf2(maxabs_bf2(rng, sp[0][0]), sp[0][1]);
    if (__builtin_expect(__any_sync(0xffffffffu, ((rng & 0x7fff7fffu) + 0x3ddf3ddfu) & 0x80008000u), 0)) {
        uint32_t m0 = sp[0][0], m1 = sp[0][1];
        #pragma unroll
        for (int nt = 1; nt < NK; nt++) { if (nt < NK - 1) m0 = max_bf2(m0, sp[nt][0]); m1 = max_bf2(m1, sp[nt][1]); }
        uint32_t mm = max_bf2(__byte_perm(m0, m1, 0x5410), __byte_perm(m0, m1, 0x7632));
        mm = max_bf2(mm, __shfl_xor_sync(0xffffffffu, mm, 1));
        mm = max_bf2(mm, __shfl_xor_sync(0xffffffffu, mm, 2));
        #pragma unroll
        for (int nt = 0; nt < NK; nt++) {
            if (nt < NK - 1) pa[nt][0] = pack_bf16(exd(bf_lo(sp[nt][0]), bf_lo(mm)), exd(bf_hi(sp[nt][0]), bf_lo(mm)));
            pa[nt][1] = pack_bf16(exd(bf_lo(sp[nt][1]), bf_hi(mm)), exd(bf_hi(sp[nt][1]), bf_hi(mm)));
        }
    }
    tok_loadv<MT, MT ? T_VPRE : 8, 8>(tok, eh, lane, bv);
    wait_v();
    constexpr int NQ = MT ? 2 : 4;
    float o[NQ][4][4], l[4] = {0.f, 0.f, 0.f, 0.f};
    const uint32_t ONE = 0x3F803F80u;
    mma16816r(l, pa[1][0], pa[1][1], pa[2][0], pa[2][1], ONE, ONE);
    if (MT) mma16816r(l, pa[3 % NK][0], pa[3 % NK][1], pa[4 % NK][0], pa[4 % NK][1], ONE, ONE);
    mma1688(l, pa[0][0], pa[0][1], ONE);
    #pragma unroll
    for (int j = 0; j < NQ; j++) {
        uint32_t bm[4];
        ldsm_x4(bm, exl + 4096 + (MT ? eh * 1024 : 0) + 512 * j);
        #pragma unroll
        for (int n = 0; n < 4; n++) {
            o[j][n][0] = o[j][n][1] = o[j][n][2] = o[j][n][3] = 0.f;
            if (MT) mma16816r(o[j][n], pa[1][0], pa[1][1], pa[2][0], pa[2][1], bv[4 * j + n][0], bv[4 * j + n][1]);
            else mma16816r(o[j][n], pa[1][0], pa[1][1], pa[2][0], pa[2][1], bv[2 * j + (n >> 1)][2 * (n & 1)], bv[2 * j + (n >> 1)][2 * (n & 1) + 1]);
        }
        if (MT) {
            #pragma unroll
            for (int n = 0; n < 4; n++) mma16816r(o[j][n], pa[3 % NK][0], pa[3 % NK][1], pa[4 % NK][0], pa[4 % NK][1], bv[4 * j + n][2], bv[4 * j + n][3]);
        }
        #pragma unroll
        for (int n = 0; n < 4; n++) mma1688(o[j][n], pa[0][0], pa[0][1], bm[n]);
    }
    #pragma unroll
    for (int j = 0; j < NQ; j++) asm volatile("" : "+f"(o[j][0][0]), "+f"(o[j][1][0]), "+f"(o[j][2][0]), "+f"(o[j][3][0]));
    asm volatile("" : "+f"(l[0]), "+f"(l[2]));
    wait_x();
    bar_arrive_p(12, 384, !vb);
    pace();
    const float i0 = rcp_approx(l[0]), i1 = rcp_approx(l[2]);
    const uint32_t oa = ost + ((mi & 1) * 8 + r8) * 128 + (((mi >> 1) ^ r8) << 4);
    #pragma unroll
    for (int j = 0; j < NQ; j++) {
        stsm_x4((oa ^ ((j & 1) << 6)) + (j >> 1) * 2048, pack_bf16(o[j][0][0] * i0, o[j][0][1] * i0), pack_bf16(o[j][0][2] * i1, o[j][0][3] * i1), pack_bf16(o[j][1][0] * i0, o[j][1][1] * i0), pack_bf16(o[j][1][2] * i1, o[j][1][3] * i1));
        stsm_x4((oa ^ (((j & 1) << 6) | 32)) + (j >> 1) * 2048, pack_bf16(o[j][2][0] * i0, o[j][2][1] * i0), pack_bf16(o[j][2][2] * i1, o[j][2][3] * i1), pack_bf16(o[j][3][0] * i0, o[j][3][1] * i0), pack_bf16(o[j][3][2] * i1, o[j][3][3] * i1));
    }
}

#define SEND_LANE(ll) ((ll) >> 2)
#define TP_E 0
#define V_EARLY 1
#ifndef M_F2
#define M_F2 0
#endif
#ifndef M_FENCE
#define M_FENCE 0
#endif
#define SW_FENCE 0
#define PV_FENCE 1
#define IL_AT 3
#define TAIL 0
#define MP_PRE 4
#define VF_EARLY 1
__device__ __forceinline__ void stsm2_p(uint32_t a, const uint32_t (&v)[8], uint32_t skip) {
    asm volatile("{\n.reg .pred p;\nsetp.eq.u32 p, %9, 0;\n@p stmatrix.sync.aligned.m8n8.x4.trans.shared.b16 [%0], {%1,%2,%3,%4};\n"
                 "@p stmatrix.sync.aligned.m8n8.x4.trans.shared.b16 [%0+1024], {%5,%6,%7,%8};\n}\n"
        :: "r"(a), "r"(v[0]), "r"(v[1]), "r"(v[2]), "r"(v[3]), "r"(v[4]), "r"(v[5]), "r"(v[6]), "r"(v[7]), "r"(skip) : "memory");
}
template<int OA, int OB>
__device__ __forceinline__ void send_tile(float c0, float c1, float c2, float c3, uint32_t a, uint32_t b, uint32_t l16) {
    const uint32_t hi = (uint32_t)((uint64_t)g_acc >> 32);
    asm volatile("{\n.reg .pred q, pl, ph;\n.reg .b64 pa, pb;\n.reg .b32 t, w0, w1, w2;\n.reg .f32 x, y, z;\n"
                 "and.b32 t, %7, 0x30;\nsetp.eq.u32 q, t, 0;\nand.b32 t, %7, 0x70;\nsetp.eq.u32 ph, t, 0;\nxor.pred pl, q, ph;\n"
                 "selp.f32 x, 0f00010000, %4, pl;\nselp.f32 y, 0f00010000, %6, ph;\nselp.f32 z, %6, %4, ph;\n"
                 "cvt.rn.bf16x2.f32 w0, x, %3;\ncvt.rn.bf16x2.f32 w1, y, %5;\ncvt.rn.bf16x2.f32 w2, 0f00010000, z;\n"
                 "mov.b64 pa, {%0, %2};\nmov.b64 pb, {%1, %2};\n"
                 "red.relaxed.gpu.global.add.noftz.bf16x2 [pa+%8], w0;\nred.relaxed.gpu.global.add.noftz.bf16x2 [pa+%10], w1;\n@q red.relaxed.gpu.global.add.noftz.bf16x2 [pb+%9], w2;\n}\n"
        :: "r"(a), "r"(b), "r"(hi), "f"(c0), "f"(c1), "f"(c2), "f"(c3), "r"(l16), "n"(OA), "n"(OB), "n"(OA + 256) : "memory");
}
__device__ __forceinline__ uint32_t send_ua(uint32_t tile) { return (uint32_t)(uint64_t)g_acc + tile * 1024; }
__device__ __forceinline__ uint32_t send_ub(uint32_t tile) { return (uint32_t)(uint64_t)g_acc + ACC_X + (tile >> 1) * 1024 + (tile & 1) * 256; }
__device__ __forceinline__ void lds_il(float& il, float& ih, uint32_t a) {
    uint32_t x, y; asm volatile("ldmatrix.sync.aligned.m8n8.x2.shared.b16 {%0,%1}, [%2];" : "=r"(x), "=r"(y) : "r"(a) : "memory");
    il = __uint_as_float(x); ih = __uint_as_float(y);
}
template<bool OWN, class F>
__device__ __forceinline__ void stage_w(const uint32_t (&wo)[8][4], uint32_t ol, uint32_t tile, uint32_t so, uint32_t l16, uint32_t nv, uint32_t ila, float il, float ih, F&& issued) {
    uint32_t b[4][4], sa, sb_, ll;
    float c[2][4];
    auto addr = [&] {
        ll = OWN ? l16 : l16 | (__float_as_uint(c[0][0]) & nv);
        sa = SEND_LANE(ll) + (send_ua(tile) + so); sb_ = (ll >> 4) + (send_ub(tile) + so);
    };
    bar_sync(11, 352);
    ldsm16_t(b, ol);
    if (!OWN) lds_il(il, ih, ila);
    if (OWN) addr();
    if (!OWN || SW_FENCE) sched_fence<0>(nv);
    #pragma unroll
    for (int i = 0; i < 2; i++) c[i][0] = c[i][1] = c[i][2] = c[i][3] = 0.f;
    #pragma unroll
    for (int j = 0; j < 4; j++) {
        if (!OWN && j == 3) addr();
        mma16816(c[0], wo[2 * j], b[j][0], b[j][1]); mma16816(c[1], wo[2 * j + 1], b[j][2], b[j][3]);
    }
    if (TP_E || (OWN && V_EARLY)) { asm volatile("" : "+f"(c[0][0]), "+f"(c[1][0])); sched_fence<OWN ? 4 : 5>(nv); }
    issued();
    send_tile<0, 0>((c[0][0] + c[1][0]) * il, (c[0][1] + c[1][1]) * ih, (c[0][2] + c[1][2]) * il, (c[0][3] + c[1][3]) * ih, sa, sb_, l16);
}

template<int N> __device__ __forceinline__ void code_pad(uint32_t nv) {
    if (N && nv == 0x7fffffe0u + N % 16) {
        float v = __uint_as_float(nv);
        #pragma unroll
        for (int i = 0; i < N; i++) asm volatile("fma.rn.f32 %0, %0, %0, %0;" : "+f"(v));
        sts32_p(0u, __float_as_uint(v), nv);
    }
}
#define PAD_T0 0
#define PAD_T1 0
#define PAD_S 0
#define PAD_P 0
#define BAR_PRO 1
#define BAR_MEM 2
#define BAR_P   3
#define BAR_PRJ 4
#define BAR_VGO 7
#define BAR_X0  7
#define BAR_S   9
#define BAR_P2  10
#define BAR_O   11
#define BAR_O2  14
#define BAR_TP  15
#define BAR_V   12
#define BAR_FB  13
#define VGO_AT 9
#define TP_N 36
#define TP_N1 24
#define REG_P 200
#define W_FENCE 1
#define WO_PRE 4
#define WO_MID 8
#define WO_EX 8
#define WO_REP 2
#define TP_DELAY 0
#define PRE_W 4
#ifndef M_RES
#define M_RES 6
#endif
#define K_PRE 6
#define K_POS 0
#define LD_FENCE 0
#define CV_FENCE 4
#define ANN_POS 3
#define PRO_V 0
#define PUB_W 0
#define T_HOLD 0
#define ST_AT 4
#define MEM_N 352
#define VGO_N (256 + (T_HOLD == 2 ? 32 : 0) + (TAIL ? 32 : 0))
#define PRO_N ((PRO_V ? 256 : 32 * nqk) + (K_PRE < 8 ? 64 : 0) + (T_HOLD == 1 ? 32 : 0))
#define S_DUTY 0
#define X_POS 1
#define K_OWN 1
#define TM_PF 1
#define TS_CAP 64
#define G1_MIN 128
#define G1_0 256
#define G1_NS 1216

__global__ void __cluster_dims__(3, 1, 1) __launch_bounds__(CH_THREADS, 1)
chain_kernel(const __grid_constant__ CUtensorMap tmx, const __grid_constant__ CUtensorMap tmq, const __grid_constant__ CUtensorMap tmk,
             const __grid_constant__ CUtensorMap tmv, const __grid_constant__ CUtensorMap tmo, const bf16* __restrict__ mem0, const uint32_t nv_) {
    extern __shared__ __align__(1024) unsigned char smem[];
    const uint32_t sb = smem_u32(smem);
    const int tid = threadIdx.x, lane = tid & 31;
    const int warp = __shfl_sync(0xffffffffu, tid >> 5, 0);
    const uint32_t nv = __shfl_sync(0xffffffffu, nv_ * tid, 0);
    const int h = blockIdx.x / 3, r = blockIdx.x % 3;
    const int mi = lane >> 3, r8 = lane & 7;
    const uint32_t bX = sb + SM_BAR, bTOK = bX + 16, bEX = bX + 40, bW = bX + 64, bEV = bX + 104, bFREE = bX + 32;
    const int nqk = r < 2 ? 6 : 4;
    if ((sb & 0xFFFFFFu) != SB_OFF) __trap();
    asm volatile("griddepcontrol.launch_dependents;");
    if (tid == 0 && blockIdx.x == 0) GT(40, 0);

    auto load_w = [&](int lo, int hi) {
        #pragma unroll 1
        for (int i = lo; i < hi; i++) {
            const int blk = i >> 2, j = i & 3;
            if (i < 48) {
                const int m = r < 2 ? (j < 3 ? r : 2) : (j < 2 ? j : 2), p = r < 2 ? (j < 3 ? j : r) : (j < 2 ? 3 : j);
                asm volatile("cp.async.bulk.tensor.2d.shared::cluster.global.mbarrier::complete_tx::bytes [%0], [%1, {%3, %4}], [%2];"
                    :: "r"(sb + i * 3072), "l"(m == 0 ? &tmq : (m == 1 ? &tmk : &tmv)), "r"(bW + (blk < 3 ? 0 : (blk < 6 ? 8 : (blk < 10 ? 16 : 24)))), "r"(h * DH + p * 32), "r"(blk * 48) : "memory");
            } else asm volatile("cp.async.bulk.tensor.2d.shared::cluster.global.mbarrier::complete_tx::bytes [%0], [%1, {%3, %4}], [%2];"
                :: "r"(sb + SM_WO + (i - 48) * 8192), "l"(&tmo), "r"(bW + 32), "r"(192 * r + 32 * (i - 48)), "r"(h * DH) : "memory");
        }
    };
    if (tid == 352) {
        #pragma unroll
        for (int i = 0; i < 15; i++) mbar_init(bX + 8 * i, (i == 5 || i == 6) ? 1 + nqk : (i >= 13 ? 9 - nqk : 1));
        asm volatile("fence.mbarrier_init.release.cluster;" ::: "memory");
        mbar_expect_tx(bW, 36864); mbar_expect_tx(bW + 8, 36864); mbar_expect_tx(bW + 16, 49152); mbar_expect_tx(bW + 24, 24576); mbar_expect_tx(bW + 32, 49152);
        load_w(0, 2 * PRE_W);
    }
    if (TM_PF && tid < 2) asm volatile("prefetch.param.tensormap [%0];" :: "l"(__cvta_generic_to_grid_constant(tid ? &tmo : &tmx)) : "memory");
    const unsigned epoch = ld_relaxed32(&g_epoch);
    __syncthreads();
    const uint32_t pw0 = ((mi >> 1) * 8 + r8) * 64 + (((2 * (warp & 1) + (mi & 1)) ^ (r8 >> 1)) << 4);
    auto tok_publish = [&](int tb, int k) {
        const uint32_t src = sb + SM_TOK + tb * TOKBUF + r * 8192, bar = bTOK + 8 * tb;
        if (k == 1) asm volatile("{\n.reg .pred p;\nelect.sync _|p, 0xffffffff;\n@p mbarrier.arrive.expect_tx.shared.b64 _, [%0], 16384;\n}\n" :: "r"(bar) : "memory");
        asm volatile("{\n.reg .pred p;\nelect.sync _|p, 0xffffffff;\n"
                     "@p cp.async.bulk.shared::cluster.shared::cta.mbarrier::complete_tx::bytes [%0], [%1], 8192, [%2];\n}\n"
            :: "r"(mapa_u32(src, (r + k) % 3)), "r"(src), "r"(mapa_u32(bar, (r + k) % 3)) : "memory");
    };
    if (warp < 8) {
        asm volatile("setmaxnreg.inc.sync.aligned.u32 %0;" :: "n"(REG_P));
        uint32_t wf[36][4];
        const uint32_t wl = sb + (warp >> 1) * 3072 + pw0;
        float ta0[16], ta1[16];
        auto tp_part = [&](auto lo, auto hi) {
            wg_fence();
            #pragma unroll
            for (int i = lo.value; i < hi.value; i++) {
                if (i == 0) wgmma_n32<0>(ta0, wf[0], desc_from(DESC_LO(SM_X))); else wgmma_n32<1>(ta0, wf[i], desc_from(DESC_LO(SM_X) + (i >> 2) * 256 + (i & 3) * 2));
            }
            #pragma unroll
            for (int i = lo.value; i < hi.value; i++) {
                if (i == 0) wgmma_n32<0>(ta1, wf[0], desc_from(DESC_LO(SM_X + XBUF))); else wgmma_n32<1>(ta1, wf[i], desc_from(DESC_LO(SM_X + XBUF) + (i >> 2) * 256 + (i & 3) * 2));
            }
            wg_commit();
        };
        if (tid == 32) load_w(2 * PRE_W, 40);
        if (tid == 0) GT(41 + blockIdx.x % 3, 7);
        code_pad<PAD_P>(nv);
        mbar_wait(bW, 0);
        #pragma unroll
        for (int i = 0; i < 9; i++) ldsm_x4_t(wf[i], wl + (i / 3) * 12288 + (i % 3) * 1024);
        fence_async_smem(); bar_arrive(BAR_X0, 288);
        mbar_wait(bW + 8, 0);
        #pragma unroll
        for (int i = 9; i < 18; i++) ldsm_x4_t(wf[i], wl + (i / 3) * 12288 + (i % 3) * 1024);
        fence_async_smem(); bar_arrive(BAR_X0 + 1, 288);
        mbar_wait(bX, 0); mbar_wait(bX + 8, 0);
        tp_part(ic<0>(), ic<18>());
        wg_wait0();
        sts128(sb + SM_OST + tid * 16, make_uint4(wf[0][0], wf[0][1], wf[0][2], wf[0][3]));
        mbar_wait(bW + 16, 0);
        #pragma unroll
        for (int i = 18; i < 30; i++) ldsm_x4_t(wf[i], wl + (i / 3) * 12288 + (i % 3) * 1024);
        tp_part(ic<18>(), ic<30>());
        mbar_wait(bW + 24, 0);
        if (tid == 0) GT(41 + blockIdx.x % 3, 0);
        wg_wait0();
        #pragma unroll
        for (int i = 30; i < 36; i++) ldsm_x4_t(wf[i], wl + (i / 3) * 12288 + (i % 3) * 1024);
        fence_async_smem();
        cluster_arrive_rx();
        tp_part(ic<30>(), ic<36>());
        if (tid == 0) GT(41 + blockIdx.x % 3, 2);
        const uint32_t pw = pin(pw0);
        auto tp_store = [&](const float (&acc)[16], uint32_t off) {
            const uint32_t ta = pw + launder(sb + off + (warp >> 1) * 2048);
            stsm_x4_t(ta, pack_bf16(acc[0], acc[1]), pack_bf16(acc[2], acc[3]), pack_bf16(acc[4], acc[5]), pack_bf16(acc[6], acc[7]));
            stsm_x4_t(ta + 1024, pack_bf16(acc[8], acc[9]), pack_bf16(acc[10], acc[11]), pack_bf16(acc[12], acc[13]), pack_bf16(acc[14], acc[15]));
        };
        cluster_wait();
        wg_wait0();
        tp_store(ta0, SM_TOK + r * 8192);
        if (warp == 0) { bar_sync(BAR_PRJ, 256); fence_async_smem(); tok_publish(0, 1); tok_publish(0, 2); } else bar_arrive(BAR_PRJ, 256);
        if (!TAIL) { tp_store(ta1, SM_TOK + TOKBUF + r * 8192); }
        { const uint4 v = lds128(sb + SM_OST + tid * 16); wf[0][0] = v.x; wf[0][1] = v.y; wf[0][2] = v.z; wf[0][3] = v.w; }
        if (tid == 0) GT(41 + blockIdx.x % 3, 4);
        const uint32_t l16 = pin(lane * 16), sbl = sb + l16, l4w = pin(sb + warp * 256 + lane * 4);
        uint32_t wo[8][4];
        const int exo = r < 2 ? (warp < 6 ? r * 2048 : 4096 + (2 * r - 6) * 256) : (warp < 2 ? 6 * 256 : (warp < 4 ? 2048 + 4 * 256 : 4096));
        const bool isqk = warp < nqk;
        const uint32_t exbar = isqk ? bEX : bEV;
        uint32_t vf[2][4];
        auto prep = [&](int s) {
            const uint32_t va = pw + launder(sb + SM_TOK + (s & 1) * TOKBUF + BLK_V(warp >> 1));
            mbar_wait(bTOK + 8 * (s & 1), (s >> 1) & 1);
            if (VF_EARLY) { ldsm_x4_t(vf[0], va); ldsm_x4_t(vf[1], va + 1024); }
        };
        prep(0);
        for (int s = 0; ; s++) {
            const int par = s & 1;
            const uint32_t va = pw + launder(sb + SM_TOK + par * TOKBUF + BLK_V(warp >> 1)), wa = pw + launder(sb + SM_WO + (warp >> 1) * 8192);
            const uint32_t exu = launder(SM_EX + par * EXBUF);
            {
                float acc[4][4];
                #pragma unroll
                for (int i = 0; i < 4; i++) { acc[i][0] = acc[i][1] = acc[i][2] = acc[i][3] = 0.f; }
                uint32_t b[18][4];
                if (!isqk) { bar_arrive(BAR_MEM, MEM_N); bar_sync(BAR_VGO, VGO_N); } else bar_sync(BAR_MEM, MEM_N);
                #pragma unroll
                for (int i2 = 0; i2 < 18; i2++) {
                    if (!TAIL || i2 >= MP_PRE) ldsm_x4_t(b[i2], sbl + SM_MEM + i2 * 512);
                    if (i2 == VGO_AT) bar_arrive_p(BAR_VGO, VGO_N, !isqk);
                    if (PRO_V && i2 == PRO_V) bar_arrive_p(BAR_PRO, PRO_N, isqk || s == NSEG - 1);
                    mma16816(acc[(2 * i2) & 3], wf[2 * i2], b[i2][0], b[i2][1]);
                    mma16816(acc[(2 * i2 + 1) & 3], wf[2 * i2 + 1], b[i2][2], b[i2][3]);
                }
                float q[4];
                #pragma unroll
                for (int i = 0; i < 4; i++) q[i] = (acc[0][i] + acc[1][i]) + (acc[2][i] + acc[3][i]);
                const uint32_t lo = pack_bf16(q[0], q[1]), hi = pack_bf16(q[2], q[3]);
                const uint32_t exl = l4w + launder(exu + exo), bar = exbar + par * 8;
                #pragma unroll
                for (int k = 1; k < 3; k++) {
                    const uint32_t exd = mapa_u32(exl, (r + k) % 3), exb = mapa_u32(bar, (r + k) % 3);
                    st_async32(exd, lo, exb); st_async32(exd + 128, hi, exb);
                }
                sts32(exl, lo); sts32(exl + 128, hi);
                __syncwarp();
                asm volatile("{\n.reg .pred p;\nelect.sync _|p, 0xffffffff;\n@p mbarrier.arrive.shared.b64 _, [%0];\n}\n" :: "r"(bar) : "memory");
                if (s < NSEG - 1) bar_sync_p(BAR_PRO, PRO_N, !isqk);
            }
            if (s == 0) mbar_wait(bW + 32, 0);
            if (s == NSEG - 1) break;
            {
                if (!VF_EARLY) { ldsm_x4_t(vf[0], va); ldsm_x4_t(vf[1], va + 1024); }
                #pragma unroll
                for (int i = 0; i < WO_PRE; i++) ldsm_x4_t(wo[i], wa + i * 1024);
                if (WO_EX > WO_PRE) {
                    #pragma unroll
                    for (int k = 0; k < WO_REP; k++) mbar_wait(bEX + 8 * par, (s >> 1) & 1);
                    #pragma unroll
                    for (int i = WO_PRE; i < WO_EX; i++) ldsm_x4_t(wo[i], wa + i * 1024);
                }
                mbar_wait(bEV + 8 * par, (s >> 1) & 1);
                const uint32_t vm0 = lds32(l4w + exu + 4096), vm1 = lds32(l4w + exu + 4096 + 128);
                #pragma unroll
                for (int i = WO_EX; i < WO_MID; i++) ldsm_x4_t(wo[i], wa + i * 1024);
                uint32_t big;
                {
                    uint32_t x = vm0 ^ vm1 ^ vf[0][0] ^ vf[1][0];
                    #pragma unroll
                    for (int i = 0; i < WO_MID; i++) x ^= wo[i][0];
                    big = bar_red_or(BAR_P, 352, x & nv);
                }
                uint32_t pb[4]; ldsm_x4_t(pb, sbl + SM_P);
                uint32_t pm = ldsm_x1_t(sbl + SM_P + 512);
                float o0[4] = {0.f, 0.f, 0.f, 0.f}, o1[4] = {0.f, 0.f, 0.f, 0.f}, o2[4] = {0.f, 0.f, 0.f, 0.f};
                #pragma unroll
                for (int i = WO_MID; i < 8; i++) if (PV_FENCE) ldsm_x4_t(wo[i], wa + i * 1024);
                if (__builtin_expect(big, 0)) {
                    bar_sync(BAR_P2, 352);
                    ldsm_x4_t(pb, sbl + SM_P); pm = ldsm_x1_t(sbl + SM_P + 512);
                }
                #pragma unroll
                for (int i = WO_MID; i < 8; i++) if (!PV_FENCE) ldsm_x4_t(wo[i], wa + i * 1024);
                mma16816(o0, vf[0], pb[0], pb[1]);
                mma16816(o1, vf[1], pb[2], pb[3]);
                mma1688(o2, vm0, vm1, pm);
                sts32(l4w + SM_O, pack_bf16((o0[0] + o1[0]) + o2[0], (o0[1] + o1[1]) + o2[1]));
                sts32(l4w + SM_O + 128, pack_bf16((o0[2] + o1[2]) + o2[2], (o0[3] + o1[3]) + o2[3]));
                const uint32_t xd = uni(DESC_LO(SM_X) + par * (XBUF >> 4));
                auto tp = [&](auto lo, auto hi) {
                    #pragma unroll
                    for (int i = lo.value; i < hi.value; i++) {
                        if (i == 0) wgmma_n32<0>(ta1, wf[0], desc_from(xd));
                        else wgmma_n32<1>(ta1, wf[i], desc_from(xd + (i >> 2) * 256 + (i & 3) * 2));
                    }
                };
                stage_w<false>(wo, sbl + SM_O, 12 * r + warp, SLOT_OFF(s + 1), l16, nv, sbl + SM_IL, 0.f, 0.f, [&] {
                    if (TP_E) { bar_sync(BAR_V, 384); wg_fence(); tp(ic<0>(), ic<TP_E>()); } });
                STAMP(warp);
                if (!TP_E) { bar_sync(BAR_V, 384); wg_fence(); }
                STAMP(12);
                tp(ic<TP_E>(), ic<TP_N>());
                wg_commit();
                prep(s + 1);
                if (!TAIL) { wg_wait0(); tp_store(ta1, SM_TOK + par * TOKBUF + r * 8192); STAMP(13 + (warp >> 2)); }
            }
        }
        cluster_arrive(); cluster_wait();
    } else {
        asm volatile("setmaxnreg.dec.sync.aligned.u32 %0;" :: "n"(504 - 2 * REG_P));
        const int a = warp - 8;
        const uint32_t sbl = sb + lane * 16;
        if (a < 3) {
            const uint32_t zs = 3 * blockIdx.x + (r8 >> 1);
            const uint32_t zoff = (r8 < 6 ? (zs >> 3) * 1024 + ((zs >> 2) & 1) * 256 + (zs & 3) * 32 : ACC_X + (blockIdx.x >> 1) * 1024 + (blockIdx.x & 1) * 256) + (lane & 1) * 16;
            const uint32_t zskip = r8 >= 6 && blockIdx.x >= 36;
            if (a == 1) {
                st_relaxed128_p((uint4*)(g_acc + zoff + SLOT_OFF(mi)), make_uint4(0, 0, 0, 0), zskip);
                __threadfence();
                __syncwarp();
                if (lane == 0) st_relaxed32(&g_init[blockIdx.x], epoch);
            }
            {
                #pragma unroll
                for (int i = 0; i < 6; i++) {
                    const int c = tid - 256 + 96 * i;
                    const unsigned short* m = (const unsigned short*)mem0 + c;
                    uint4 v;
                    v.x = m[0] | ((uint32_t)m[DM] << 16); v.y = m[2 * DM] | ((uint32_t)m[3 * DM] << 16);
                    v.z = m[4 * DM] | ((uint32_t)m[5 * DM] << 16); v.w = m[6 * DM] | ((uint32_t)m[7 * DM] << 16);
                    sts128(sb + SM_MEM + c * 16, v);
                }
                sts32(sb + SM_SG + 36, 0u);
            }
            asm volatile("barrier.cluster.arrive.release.aligned;" ::: "memory");
            { int it = 0; while (__any_sync(0xffffffffu, ld_relaxed32(&g_init[a * 32 + lane]) != epoch) && ++it < SPIN_LIMIT) {} }
            __threadfence();
            const uint32_t kl0 = (a < 2 ? SM_TOK + (16 * a + (mi & 1) * 8 + r8) * 64 + (((mi >> 1) ^ (r8 >> 1)) << 4) : SM_EX + 2048 + ((((mi & 1) << 1) | (mi >> 1)) * 8 + r8) * 16);
            const uint32_t l16 = pin(lane * 16);
            uint32_t kf[8][4], wo[8][4];
            auto load_k = [&](int tb, uint32_t kl, auto lo, auto hi) {
                const uint32_t ka = kl + launder(sb + tb * TOKBUF);
                #pragma unroll
                for (int kk = lo.value; kk < hi.value; kk++) ldsm_x4(kf[kk], (ka ^ ((kk & 1) << 5)) + BLK_K(kk >> 1));
            };
            code_pad<PAD_S>(nv);
            cluster_wait();
            if (a == 0 && lane == 0) { mbar_expect_tx(bEX, 4096 - 256 * nqk); mbar_expect_tx(bEV, 256 * nqk); }
            if (a < 2) bar_arrive(BAR_MEM, MEM_N); else bar_sync(BAR_MEM, MEM_N);
            mbar_wait(bW + 32, 0);
            #pragma unroll
            for (int i = 0; i < 8; i++) ldsm_x4_t(wo[i], pw0 + sb + SM_WO + (warp >> 1) * 8192 + i * 1024);
            sts128(sbl + SM_STASH + a * 1024 + 512, make_uint4(kl0, (pw0 ^ 32) + sb + SM_WO + 5 * 8192, zoff | ((zskip || lane >= 8) << 31), 0u));
            sts128(sbl + SM_STASH + a * 1024, make_uint4(a * 12288 + (lane >> 4) * 1024 + (mi & 1) * 256 + r8 * 16, ACC_X + a * 6144 + (lane >> 4) * 1024 + (mi & 1) * 256 + r8 * 4,
                                                         ((lane ^ mi) & 1) ? 0u : ~0u, sb + SM_MEM + a * 3072 + mi * 256 + r8 * 16 + (r8 & 1 ? 2 : 130)));
            const uint32_t stash = l16 + uni(sb + SM_STASH + a * 1024);
            #pragma unroll
            for (int i = 0; i < 8; i++) ldsm_x4_t(kf[i], (pw0 ^ 32) + sb + SM_WO + 5 * 8192 + i * 1024);
            if (a < 2) { mbar_wait(bTOK, 0); load_k(0, kl0, ic<0>(), ic<K_PRE>()); }
            __syncwarp();
            int sn = 0;
            #pragma unroll 1
            while (sn < NSEG - 1) {
              uint32_t bad, c, cx;
              #pragma unroll 1
              do {
                const int s = sn, par = s & 1;
                const uint32_t exu = launder(sb + par * EXBUF);
                const uint32_t exl = l16 + exu + SM_EX;
                const uint32_t t0 = gtime_lo();
                STAMP(15); STAMPV(31, t0);
                if (!TAIL && a == 2) st_relaxed32_p(&g_ts[blockIdx.x], (t0 & ~31u) | (s & 31), l16);
                if (a == 1) {
                    const uint32_t z = lds32(stash + 520);
                    st_relaxed128_p((uint4*)(g_acc + (z + SLOT_OFF(s + 3))), make_uint4(0, 0, 0, 0), z >> 31);
                }
                if (a == 0 && l16 == 0) { mbar_expect_tx(bEX + 8 * (par ^ 1), 4096 - 256 * nqk); mbar_expect_tx(bEV + 8 * (par ^ 1), 256 * nqk); }
                uint32_t tg;
                auto first_half = [&](auto role) {
                constexpr bool M = role.value;
                auto publish = [&] {
                    asm volatile("{\n.reg .pred p;\nelect.sync _|p, 0xffffffff;\n"
                                 "@p cp.async.bulk.shared::cluster.global.mbarrier::complete_tx::bytes.multicast::cluster [%0], [%1], 8192, [%2], %3;\n}\n"
                        :: "r"(sb + SM_TOK + (par ^ 1) * TOKBUF + r * 8192), "l"(g_tokx[blockIdx.x]), "r"(bTOK + 8 * (par ^ 1)), "h"((unsigned short)(7 ^ (1 << r))) : "memory");
                };
                uint32_t sl, sh, kl = 0, w2 = 0;
                if (M) {
                    if (TAIL) { bar_sync(BAR_VGO, VGO_N); __syncwarp(); st_relaxed32_p(&g_ts[blockIdx.x], (gtime_after(lds32(stash + 524)) & ~31u) | (s & 31), l16); }
                    fence_async_smem();
                    if (l16 == 0) {
                        asm volatile("cp.async.bulk.global.shared::cta.bulk_group [%0], [%1], 8192;\ncp.async.bulk.commit_group;"
                            :: "l"(g_tokx[blockIdx.x]), "r"(sb + SM_TOK + (par ^ 1) * TOKBUF + r * 8192) : "memory");
                        mbar_expect_tx(bTOK + 8 * (par ^ 1), 16384);
                        if (s == 0) mbar_expect_tx(bX, XBUF);
                        if (s + 3 < NSEG) mbar_expect_tx(bX + 8 * (par ^ 1), XBUF);
                    }
                    __syncwarp();
                    if (s > 0 && s + 2 < NSEG) mbar_wait(bX + 8 * par, ((s >> 1) & 1) ^ 1);
                    if (PUB_W == 0) asm volatile("cp.async.bulk.wait_group 0;" ::: "memory");
                    kl = lds32(stash + 512);
                }
                if (!M && K_PRE < 8) {
                    const uint32_t kl = lds32(stash + 512);
                    bar_sync(BAR_PRO, PRO_N);
                    load_k(par, kl, ic<K_PRE>(), ic<8>());
                }
                const uint32_t pst = (launder(l16) >> 2) + launder(sb + SM_P + a * 256);
                mbar_wait(bEX + 8 * par, (s >> 1) & 1);
                if (!M) {
                    uint32_t b[4][4];
                    ldsm16_t(b, exl);
                    float c[4][4];
                    #pragma unroll
                    for (int j = 0; j < 4; j++) { c[j][0] = c[j][1] = c[j][2] = c[j][3] = 0.f; }
                    #pragma unroll
                    for (int j = 0; j < 4; j++) { mma16816(c[(2 * j) & 3], kf[2 * j], b[j][0], b[j][1]); mma16816(c[(2 * j + 1) & 3], kf[2 * j + 1], b[j][2], b[j][3]); }
                    sl = scale_bf2(pack_bf16((c[0][0] + c[1][0]) + (c[2][0] + c[3][0]), (c[0][1] + c[1][1]) + (c[2][1] + c[3][1])));
                    sh = scale_bf2(pack_bf16((c[0][2] + c[1][2]) + (c[2][2] + c[3][2]), (c[0][3] + c[1][3]) + (c[2][3] + c[3][3])));
                } else {
                    float c[4][4];
                    #pragma unroll
                    for (int j = 0; j < 4; j++) { c[j][0] = c[j][1] = c[j][2] = c[j][3] = 0.f; }
                    uint32_t k[4][4], b[4][4];
                    #pragma unroll
                    for (int j = 0; j < 4; j++) { ldsm_x4_t(k[j], kl + exu + 512 * j); ldsm_x4_t(b[j], exl + 512 * j); }
                    if (PUB_W == 0) publish();
                    sched_fence<9>(nv);
                    #pragma unroll
                    for (int j = 0; j < 4; j++) { mma16816(c[2 * (j & 1)], k[j], b[j][0], b[j][1]); mma16816(c[2 * (j & 1) + 1], k[j], b[j][2], b[j][3]); }
                    sched_fence<14>(nv);
                    w2 = lds32(stash + 516);
                    sh = sl = scale_bf2(pack_bf16((c[0][0] + c[1][2]) + (c[2][0] + c[3][2]), (c[0][1] + c[1][3]) + (c[2][1] + c[3][3])));
                }
                sts32(pst, pack_bf16(ex2(bf_lo(sl) * LOG2E), ex2(bf_hi(sl) * LOG2E)));
                if (!M) sts32(pst + 128, pack_bf16(ex2(bf_lo(sh) * LOG2E), ex2(bf_hi(sh) * LOG2E)));
                if (S_DUTY && !M) {
                    if (a == 0)
                        asm volatile("{\n.reg .pred p;\nelect.sync _|p, 0xffffffff;\n"
                                     "@p cp.async.bulk.shared::cluster.global.mbarrier::complete_tx::bytes [%0], [%1], 384, [%2];\n"
                                     "@p mbarrier.arrive.expect_tx.shared.b64 _, [%2], 384;\n}\n"
                            :: "r"(sb + SM_TS), "l"(g_ts), "r"(bFREE) : "memory");
                    else if (s > 0 && s + 3 < NSEG)
                        asm volatile("{\n.reg .pred p;\nelect.sync _|p, 0xffffffff;\n"
                                     "@p cp.async.bulk.tensor.3d.shared::cluster.global.mbarrier::complete_tx::bytes.multicast::cluster [%0], [%1, {%3, %4, %5}], [%2], %6;\n}\n"
                            :: "r"(sb + SM_X + (par ^ 1) * XBUF + r * 12288), "l"(&tmx), "r"(bX + 8 * (par ^ 1)), "r"(0), "r"((s + 3) * SEG), "r"(3 * r), "h"((unsigned short)7) : "memory");
                }
                if (M) {
                    #pragma unroll
                    for (int i = M_RES; i < 8; i++) ldsm_x4_t(kf[i], w2 + i * 1024);
                }
                const uint32_t big = bar_red_or(BAR_P, 352, ((maxabs_bf2(sl, sh) & 0x7fff7fffu) + 0x3ddf3ddfu) & 0x80008000u);
                float l0[4], l1[4], l2[4];
                uint32_t pb[4], pm;
                if (!M) { ldsm_x4_t(pb, l16 + sb + SM_P); pm = ldsm_x1_t(l16 + sb + SM_P + 512); }
                if (__builtin_expect(big, 0)) {
                    uint32_t m2 = max_bf2(sl, sh);
                    m2 = max_bf2(m2, __shfl_xor_sync(0xffffffffu, m2, 4));
                    m2 = max_bf2(m2, __shfl_xor_sync(0xffffffffu, m2, 8));
                    m2 = max_bf2(m2, __shfl_xor_sync(0xffffffffu, m2, 16));
                    const uint32_t lq = l16 | (m2 & nv);
                    if (lq < 64) sts32(lq + sb + SM_P + 768 + a * 4, m2);
                    bar_sync(BAR_S, 96);
                    const uint4 m = lds128(sb + SM_P + 768 + (lq & 0x30));
                    m2 = max_bf2(max_bf2(m.x, m.y), m.z);
                    const float ml = bf_lo(m2), mh = bf_hi(m2);
                    sts32(pst, pack_bf16(exd(bf_lo(sl), ml), exd(bf_hi(sl), mh)));
                    if (!M) sts32(pst + 128, pack_bf16(exd(bf_lo(sh), ml), exd(bf_hi(sh), mh)));
                    bar_sync(BAR_P2, 352);
                    if (!M) { ldsm_x4_t(pb, l16 + sb + SM_P); pm = ldsm_x1_t(l16 + sb + SM_P + 512); }
                }
                if (!M) {
                    const uint32_t ONE = 0x3F803F80u;
                    #pragma unroll
                    for (int i = 0; i < 4; i++) l0[i] = l1[i] = l2[i] = 0.f;
                    mma16816r(l0, ONE, ONE, ONE, ONE, pb[0], pb[1]);
                    mma16816r(l1, ONE, ONE, ONE, ONE, pb[2], pb[3]);
                    mma1688(l2, ONE, ONE, pm);
                }
                const uint32_t ll = launder(l16), ila = sb + SM_IL + (ll >> 2), so = SLOT_OFF(launder(s) + 1);
                if (!M) {
                    const float sil = rcp_approx((l0[0] + l1[0]) + l2[0]), sih = rcp_approx((l0[1] + l1[1]) + l2[1]);
                    sts32(ila + a * 128, __float_as_uint(a ? sih : sil));
                    stage_w<true>(wo, l16 + sb + SM_O, 12 * r + warp, so, ll, nv, 0u, sil, sih, [&] { if (TP_E || V_EARLY) bar_arrive(BAR_V, 384); });
                } else {
                    if (PUB_W == 1) { asm volatile("cp.async.bulk.wait_group 0;" ::: "memory"); publish(); }
                    const uint32_t sa = launder(SEND_LANE(ll) + (send_ua(12 * r + 10) + so)), sb_ = launder((ll >> 4) + (send_ub(12 * r + 10) + so));
                    bar_sync_p(BAR_O, 352, (kf[6][0] ^ kf[7][0] ^ sa ^ sb_) & nv);
                    float c[4][4], il, ih;
                    #pragma unroll
                    for (int i = 0; i < 4; i++) c[i][0] = c[i][1] = c[i][2] = c[i][3] = 0.f;
                    uint32_t b[4][4];
                    #pragma unroll
                    for (int j = 0; j < 4; j++) ldsm_x4_t(b[j], l16 + sb + SM_O + 512 * (3 - j));
                    lds_il(il, ih, l16 + sb + SM_IL);
                    sched_fence<11>(nv);
                    #pragma unroll
                    for (int j = 0; j < 4; j++) {
                        if (j == 2) { if (M_F2) sched_fence<10>(nv); }
                        mma16816(c[0], wo[6 - 2 * j], b[j][0], b[j][1]); mma16816(c[2], kf[6 - 2 * j], b[j][0], b[j][1]);
                        mma16816(c[1], wo[7 - 2 * j], b[j][2], b[j][3]); mma16816(c[3], kf[7 - 2 * j], b[j][2], b[j][3]);
                    }
                    asm volatile("" : "+f"(c[0][0]), "+f"(c[1][0]), "+f"(c[2][0]), "+f"(c[3][0]));
                    if (TP_E || V_EARLY) { if (M_FENCE == 1) sched_fence<8>(nv); else asm volatile("" : "+f"(il) : "f"(c[0][0] + c[1][0]), "f"(c[2][0] + c[3][0])); if (M_FENCE < 2) bar_arrive(BAR_V, 384); }
                    send_tile<0, 0>((c[0][0] + c[1][0]) * il, (c[0][1] + c[1][1]) * ih, (c[0][2] + c[1][2]) * il, (c[0][3] + c[1][3]) * ih, sa, sb_, ll);
                    if (M_FENCE == 2) bar_arrive(BAR_V, 384);
                    send_tile<1024, 256>((c[2][0] + c[3][0]) * il, (c[2][1] + c[3][1]) * ih, (c[2][2] + c[3][2]) * il, (c[2][3] + c[3][3]) * ih, sa, sb_, ll);
                    if (M_FENCE == 3) bar_arrive(BAR_V, 384);
                }
                };
                if (a < 2) first_half(ic<0>()); else first_half(ic<1>());
                STAMP(warp);
                if (!TP_E && !V_EARLY) bar_arrive(BAR_V, 384);
                {
                    const uint4 ad = lds128(stash);
                    const uint32_t kl = lds32(stash + 512), so = SLOT_OFF(launder(s) + 1);
                    if (K_OWN == 1 && a < 2) { mbar_wait(bTOK + 8 * (par ^ 1), ((s + 1) >> 1) & 1); load_k(par ^ 1, kl, ic<0>(), ic<K_PRE>()); }
                    { int it = 0; do { asm volatile("ld.volatile.shared.u32 %0, [%1];" : "=r"(tg) : "r"(sb + SM_SG + 36) : "memory"); } while ((tg & 1u) == (uint32_t)par && ++it < SPIN_LIMIT * 16); }
                    if (!K_OWN && K_POS == 0 && a < 2) load_k(par ^ 1, kl, ic<0>(), ic<K_PRE>());
                    const uint32_t alo = (uint32_t)(uint64_t)g_acc + so;
                    const unsigned char* pm = (const unsigned char*)(((uint64_t)g_acc & ~0xffffffffull) | (ad.x + alo));
                    const unsigned char* px = (const unsigned char*)(((uint64_t)g_acc & ~0xffffffffull) | (ad.y + alo));
                    uint4 v[6]; uint32_t x[3];
                    const uint32_t md = l16 + launder(sb + SM_MEM + a * 3072);
                    STAMP(16 + a); STAMPV(30, tg);
                    wait_gtime(tg);
                    #pragma unroll
                    for (int j = 0; j < 6; j++) v[j] = ld_relaxed128((const uint4*)(pm + 2048 * j));
                    #pragma unroll
                    for (int j = 0; j < 3; j++) x[j] = ld_relaxed32((const uint32_t*)(px + 2048 * j));
                    if (K_OWN == 2) { mbar_wait(bTOK + 8 * (par ^ 1), ((s + 1) >> 1) & 1); if (a < 2) load_k(par ^ 1, kl, ic<0>(), ic<K_PRE>()); sched_fence<16>(nv); }
                    if (LD_FENCE) bar_sync(BAR_S, 96);
                    STAMP(19 + a);
                    c = ~0u;
                    #pragma unroll
                    for (int j = 0; j < 6; j++) { sts128(md + 512 * j, v[j]); c &= v[j].x; }
                    c |= ad.z;
                    #pragma unroll
                    for (int j = 0; j < 3; j++) sts16(ad.w + 1024 * j, (uint16_t)x[j]);
                    cx = x[0] & x[1] & x[2];
                    bad = __any_sync(0xffffffffu, !(c & cx & (ACC_FULL << 16)));
                    STAMP(22 + a); STAMPV(27 + a, bad);
                    bar_sync_p(BAR_MEM, MEM_N, bad);
                }
              } while (++sn < NSEG - 1 && !bad);
                {
                    if (bad) {
                        const uint32_t lq = l16 | (c & nv), so = SLOT_OFF(sn);
                        const uint4 ad = lds128(stash);
                        const unsigned char* pm = launder_p(g_acc + (ad.x + so));
                        const unsigned char* px = launder_p(g_acc + (ad.y + so));
                        int it = 0;
                        do {
                            const uint32_t again = ~(c & __shfl_xor_sync(0xffffffffu, c, 1)) & (ACC_FULL << 16);
                            uint4 u[6]; uint32_t x[3];
                            #pragma unroll
                            for (int j = 0; j < 6; j++) { u[j] = make_uint4(~0u, ~0u, ~0u, ~0u); ld_relaxed128_p(u[j], (const uint4*)(pm + 2048 * j), again); }
                            #pragma unroll
                            for (int j = 0; j < 3; j++) x[j] = ld_relaxed32((const uint32_t*)(px + 2048 * j));
                            c = ~0u;
                            #pragma unroll
                            for (int j = 0; j < 6; j++) {
                                if (again) sts128(lq + sb + SM_MEM + a * 3072 + 512 * j, u[j]);
                                c &= u[j].x;
                            }
                            __syncwarp();
                            #pragma unroll
                            for (int j = 0; j < 3; j++) sts16(ad.w + 1024 * j, (uint16_t)x[j]);
                            c |= ad.z;
                            cx = x[0] & x[1] & x[2];
                        } while (__any_sync(0xffffffffu, !(c & cx & (ACC_FULL << 16))) && ++it < SPIN_LIMIT);
                        bar_sync(BAR_MEM, MEM_N);
                    }
                }
            }
            if (TAIL && a == 2) bar_arrive(BAR_VGO, VGO_N);
        } else {
            cluster_arrive_rx();
            const uint32_t l16 = pin(lane * 16);
            bf16* dst = g_otok + h * 4096 + (r ? 1024 : 0) + (r == 2 ? 2048 : 0);
            {
                #pragma unroll
                for (int sg = 0; sg < 2; sg++) {
                    bar_sync(BAR_X0 + sg, 288);
                    if (lane == 0) {
                        mbar_expect_tx(bX + 8 * sg, XBUF);
                        #pragma unroll
                        for (int c = 0; c < 3; c++)
                            asm volatile("cp.async.bulk.tensor.3d.shared::cluster.global.mbarrier::complete_tx::bytes [%0], [%1, {%3, %4, %5}], [%2];"
                                :: "r"(sb + SM_X + sg * XBUF + c * 12288), "l"(&tmx), "r"(bX + 8 * sg), "r"(0), "r"(sg * SEG), "r"(3 * c) : "memory");
                    }
                    __syncwarp();
                }
                if (lane == 0) load_w(40, 54);
                __syncwarp();
                cluster_wait();
            }
            __syncwarp();
            auto t_loop = [&](auto mtile) {
            constexpr int MT = mtile.value;
            uint32_t q[8][4], sp[5][2], pa[5][2], bv[8][4], rng;
            code_pad<MT ? PAD_T1 : PAD_T0>(nv);
            auto issue_x = [&](int sg) {
                asm volatile("{\n.reg .pred p, q;\nelect.sync _|p, 0xffffffff;\nsetp.eq.and.u32 q, %5, 3, p;\n"
                             "@p cp.async.bulk.tensor.3d.shared::cluster.global.mbarrier::complete_tx::bytes.multicast::cluster [%0], [%1, {%3, %4, %5}], [%2], %6;\n"
                             "@q cp.async.bulk.tensor.3d.shared::cluster.global.mbarrier::complete_tx::bytes.multicast::cluster [%7], [%1, {%3, %4, %3}], [%2], %6;\n}\n"
                    :: "r"(sb + SM_X + (sg & 1) * XBUF + r * 12288), "l"(&tmx), "r"(bX + 8 * (sg & 1)), "r"(0), "r"(sg * SEG), "r"(3 * r), "h"((unsigned short)7), "r"(sb + SM_X + (sg & 1) * XBUF) : "memory");
            };
            mbar_wait(bTOK, 0);
            if (MT) { issue_x(2); issue_x(3); }
            #pragma unroll 1
            for (int s = 0; s < NSEG; s++) {
                const int par = s & 1;
                if (K_OWN) mbar_wait(bTOK + 8 * par, (s >> 1) & 1);
                const uint32_t tok = launder(sb + SM_TOK + par * TOKBUF), exl = l16 + launder(sb + SM_EX + par * EXBUF);
                const int ln = launder(l16) >> 4;
                auto announce = [&] {
                    if (s > 0) {
                        if (lane == 0) {
                            asm volatile("cp.async.bulk.wait_group 0;" ::: "memory");
                            st_relaxed32(&g_prog[blockIdx.x], epoch << 8 | s);
                        }
                        __syncwarp();
                        if (lane == 0 && blockIdx.x == 0) GT(40, s);
                    }
                };
                if (ANN_POS == 0) announce();
                tok_part1<MT>(tok, MT ? r - 1 : 0, ln, q, sp, pa, bv, rng, [&] {
                    if (ANN_POS == 3) announce();
                    if (T_HOLD) { if (s < NSEG - 1) bar_sync(T_HOLD == 1 ? BAR_PRO : BAR_VGO, T_HOLD == 1 ? PRO_N : VGO_N); else if (T_HOLD == 2) bar_arrive(BAR_VGO, VGO_N); sched_fence<6 + MT>(nv); } });
                if (ANN_POS == 1) announce();
                STAMP(25);
                mbar_wait(bEX + 8 * par, (s >> 1) & 1);
                STAMP(26);
                auto duty = [&] { if (!S_DUTY && s + 1 < NSEG) {
                    asm volatile("{\n.reg .pred p;\nelect.sync _|p, 0xffffffff;\n"
                                 "@p cp.async.bulk.shared::cluster.global.mbarrier::complete_tx::bytes [%0], [%1], 384, [%2];\n"
                                 "@p mbarrier.arrive.expect_tx.shared.b64 _, [%2], 384;\n}\n"
                        :: "r"(sb + SM_TS), "l"(g_ts), "r"(bFREE) : "memory");
                    if (X_POS == 0 && MT && s > 0 && s + 3 < NSEG) issue_x(s + 3);
                } };
                auto pace = [&] { if (s + 1 < NSEG) {
                    if (X_POS == 2 && MT && s > 0 && s + 3 < NSEG) issue_x(s + 3);
                    const uint32_t lo = min(launder(l16), 368u), b = (gtime_lo() & ~31u) - 0x01000000u + s + (lo >> 16);
                    const uint32_t c = (b & ~31u) + (G1_NS + (s == 0 ? G1_0 : 0)) + (par ^ 1);
                    if (K_OWN) mbar_wait(bFREE, par); else mbar_wait2(bFREE, par, bTOK + 8 * (par ^ 1), ((s + 1) >> 1) & 1);
                    uint4 ts = lds128(sb + SM_TS + lo);
                    int it = 0; uint32_t m;
                    while (true) {
                        m = __reduce_max_sync(0xffffffffu, max(max(__funnelshift_r(ts.x - b, ts.x - b, 5), __funnelshift_r(ts.y - b, ts.y - b, 5)), max(__funnelshift_r(ts.z - b, ts.z - b, 5), __funnelshift_r(ts.w - b, ts.w - b, 5))));
                        if (__builtin_expect(m < 0x00100000u, 1) || ++it >= 64) break;
                        ts = ld_relaxed128((const uint4*)((const char*)g_ts + lo));
                    }
                    asm volatile("st.volatile.shared.u32 [%0], %1;" :: "r"(sb + SM_SG + 36), "r"(c + (min(m, 0x00080000u) << 5)) : "memory");
                } };
                auto wait_v = [&] {
                    if (X_POS == 1 && MT && s > 0 && s + 3 < NSEG) issue_x(s + 3);
                    mbar_wait(bEV + 8 * par, (s >> 1) & 1); };
                auto wait_x = [&] { if (__builtin_expect(s == 0, 0)) mbar_wait(bX, 1); };
                tok_part2<MT>(tok, exl, sb + SM_OST, MT ? r - 1 : 0, launder(l16) >> 4, q, sp, pa, bv, rng, s < NSEG - 1, wait_v, duty, pace, wait_x);
                STAMP(11);
                fence_async_smem();
                __syncwarp();
                if (lane == 0) {
                    asm volatile("cp.async.bulk.global.shared::cta.bulk_group [%0], [%1], 2048;" :: "l"(dst), "r"(sb + SM_OST) : "memory");
                    if (!MT) asm volatile("cp.async.bulk.global.shared::cta.bulk_group [%0], [%1], 2048;" :: "l"(dst + 2048), "r"(sb + SM_OST + 2048) : "memory");
                    asm volatile("cp.async.bulk.commit_group;" ::: "memory");
                    if (__builtin_expect(s >= NSEG - 2, 0)) {
                        asm volatile("cp.async.bulk.wait_group 0;" ::: "memory");
                        st_relaxed32(&g_prog[blockIdx.x], epoch << 8 | (s + 1));
                        if (blockIdx.x == 0 && s == NSEG - 1) GT(40, NSEG);
                    }
                }
                __syncwarp();
                dst += SEG * NH * DH;
            }
            };
            if (r == 0) t_loop(ic<0>()); else t_loop(ic<1>());
        }
        cluster_arrive(); cluster_wait();
    }
}
#define SD_THREADS 384
#define SD_CTAS  36
#define BT_RS    4624
#define SD_BT    0
#define SD_STG   74752
#define SD_EF    (SD_STG + 57344)
#define SD_BC    (SD_STG)
#define KSLOTS   5
#define BC_BYTES 10240
#define BC_LBO   1280
#define SD_KP    (SD_STG + 90112)
#define SD_Q0    205824
#define SD_Q1    (SD_STG + 111616)
#define SD_OST   222720
#define SD_XCH   (SD_Q0 + 8192)
#define SD_BAR   224256
#define SD_TOTAL 224768
#define SD_SPIN  (1 << 22)
#define PART_SLOTS 8
#define SD_GO 0
#define SD_REG 200
#define SD_WAIT 6000
#define SD_P2 150
#define SD_P3 500
#define SD_GAP 0
#define SD_RUSH 44
#define SD_P1 300

__device__ uint4 g_part[SD_CTAS][PART_SLOTS][4][8][32];
__device__ __align__(16) unsigned int g_gate[S_LEN];

struct cplx { float r, i; };
__device__ __forceinline__ cplx cmul(cplx a, cplx b) { cplx c; c.r = fmaf(a.r, b.r, -a.i * b.i); c.i = fmaf(a.r, b.i, a.i * b.r); return c; }
__device__ __forceinline__ cplx cexp_(float xr, float xi) {
    const float m = ex2(xr * 1.4426950408889634f);
    const float k = rintf(xi * 0.15915494309189535f);
    const float r = fmaf(k, 1.7484555314695172e-7f, fmaf(k, -6.2831854820251465f, xi));
    cplx o; o.r = m * __cosf(r); o.i = m * __sinf(r); return o;
}
__device__ __forceinline__ void mma_f16(float (&c)[4], const uint32_t (&a)[4], uint32_t b0, uint32_t b1) {
    asm("mma.sync.aligned.m16n8k16.row.col.f32.f16.f16.f32 {%0,%1,%2,%3}, {%4,%5,%6,%7}, {%8,%9}, {%0,%1,%2,%3};"
        : "+f"(c[0]), "+f"(c[1]), "+f"(c[2]), "+f"(c[3]) : "r"(a[0]), "r"(a[1]), "r"(a[2]), "r"(a[3]), "r"(b0), "r"(b1));
}
__device__ __forceinline__ uint32_t mul_bf2(uint32_t a, uint32_t b) { uint32_t r; asm("mul.rn.bf16x2 %0, %1, %2;" : "=r"(r) : "r"(a), "r"(b)); return r; }
__device__ __forceinline__ void mbar_wait_long(uint32_t a, uint32_t parity) { int it = 0; while (!mbar_try(a, parity) && ++it < SD_SPIN) {} }
__device__ __forceinline__ uint16_t lds16(uint32_t a) { uint16_t v; asm volatile("ld.shared.u16 %0, [%1];" : "=h"(v) : "r"(a) : "memory"); return v; }
__device__ __forceinline__ void wg_wait1() { asm volatile("wgmma.wait_group.sync.aligned 1;" ::: "memory"); }
__device__ __forceinline__ void tma2d(uint32_t dst, const CUtensorMap* tm, uint32_t bar, int c0, int c1) {
    asm volatile("cp.async.bulk.tensor.2d.shared::cluster.global.mbarrier::complete_tx::bytes [%0], [%1, {%3, %4}], [%2];"
        :: "r"(dst), "l"(tm), "r"(bar), "r"(c0), "r"(c1) : "memory");
}
__device__ __forceinline__ uint32_t add_bf2(uint32_t a, uint32_t b) { uint32_t r; asm("add.rn.bf16x2 %0, %1, %2;" : "=r"(r) : "r"(a), "r"(b)); return r; }
__device__ __forceinline__ void wgmma_conv(float (&d)[32], uint32_t a0, uint32_t a1, uint32_t a2, uint32_t a3, uint64_t desc) {
    asm volatile("{\n.reg .pred p;\nsetp.ne.b32 p, 1, 0;\n"
        "wgmma.mma_async.sync.aligned.m64n64k16.f32.bf16.bf16 {%0,%1,%2,%3,%4,%5,%6,%7,%8,%9,%10,%11,%12,%13,%14,%15,%16,%17,%18,%19,%20,%21,%22,%23,%24,%25,%26,%27,%28,%29,%30,%31}, {%32,%33,%34,%35}, %36, p, 1, 1, 0;\n}\n"
        : "+f"(d[0]), "+f"(d[1]), "+f"(d[2]), "+f"(d[3]), "+f"(d[4]), "+f"(d[5]), "+f"(d[6]), "+f"(d[7]), "+f"(d[8]), "+f"(d[9]), "+f"(d[10]), "+f"(d[11]), "+f"(d[12]), "+f"(d[13]), "+f"(d[14]), "+f"(d[15]), "+f"(d[16]), "+f"(d[17]), "+f"(d[18]), "+f"(d[19]), "+f"(d[20]), "+f"(d[21]), "+f"(d[22]), "+f"(d[23]), "+f"(d[24]), "+f"(d[25]), "+f"(d[26]), "+f"(d[27]), "+f"(d[28]), "+f"(d[29]), "+f"(d[30]), "+f"(d[31])
        : "r"(a0), "r"(a1), "r"(a2), "r"(a3), "l"(desc));
}
__device__ __forceinline__ void wgmma_conv(float (&d)[24], uint32_t a0, uint32_t a1, uint32_t a2, uint32_t a3, uint64_t desc) {
    asm volatile("{\n.reg .pred p;\nsetp.ne.b32 p, 1, 0;\n"
        "wgmma.mma_async.sync.aligned.m64n48k16.f32.bf16.bf16 {%0,%1,%2,%3,%4,%5,%6,%7,%8,%9,%10,%11,%12,%13,%14,%15,%16,%17,%18,%19,%20,%21,%22,%23}, {%24,%25,%26,%27}, %28, p, 1, 1, 0;\n}\n"
        : "+f"(d[0]), "+f"(d[1]), "+f"(d[2]), "+f"(d[3]), "+f"(d[4]), "+f"(d[5]), "+f"(d[6]), "+f"(d[7]), "+f"(d[8]), "+f"(d[9]), "+f"(d[10]), "+f"(d[11]), "+f"(d[12]), "+f"(d[13]), "+f"(d[14]), "+f"(d[15]), "+f"(d[16]), "+f"(d[17]), "+f"(d[18]), "+f"(d[19]), "+f"(d[20]), "+f"(d[21]), "+f"(d[22]), "+f"(d[23])
        : "r"(a0), "r"(a1), "r"(a2), "r"(a3), "l"(desc));
}
__device__ __forceinline__ void wgmma_conv(float (&d)[16], uint32_t a0, uint32_t a1, uint32_t a2, uint32_t a3, uint64_t desc) {
    asm volatile("{\n.reg .pred p;\nsetp.ne.b32 p, 1, 0;\n"
        "wgmma.mma_async.sync.aligned.m64n32k16.f32.bf16.bf16 {%0,%1,%2,%3,%4,%5,%6,%7,%8,%9,%10,%11,%12,%13,%14,%15}, {%16,%17,%18,%19}, %20, p, 1, 1, 0;\n}\n"
        : "+f"(d[0]), "+f"(d[1]), "+f"(d[2]), "+f"(d[3]), "+f"(d[4]), "+f"(d[5]), "+f"(d[6]), "+f"(d[7]), "+f"(d[8]), "+f"(d[9]), "+f"(d[10]), "+f"(d[11]), "+f"(d[12]), "+f"(d[13]), "+f"(d[14]), "+f"(d[15])
        : "r"(a0), "r"(a1), "r"(a2), "r"(a3), "l"(desc));
}
__device__ __forceinline__ void wgmma_conv(float (&d)[8], uint32_t a0, uint32_t a1, uint32_t a2, uint32_t a3, uint64_t desc) {
    asm volatile("{\n.reg .pred p;\nsetp.ne.b32 p, 1, 0;\n"
        "wgmma.mma_async.sync.aligned.m64n16k16.f32.bf16.bf16 {%0,%1,%2,%3,%4,%5,%6,%7}, {%8,%9,%10,%11}, %12, p, 1, 1, 0;\n}\n"
        : "+f"(d[0]), "+f"(d[1]), "+f"(d[2]), "+f"(d[3]), "+f"(d[4]), "+f"(d[5]), "+f"(d[6]), "+f"(d[7])
        : "r"(a0), "r"(a1), "r"(a2), "r"(a3), "l"(desc));
}
template<int NR> __device__ __forceinline__ void conv_mma(float (&acc)[NR], const uint32_t (&R)[16], uint32_t dlo) {
    #pragma unroll
    for (int q = 0; q < 4; q++)
        wgmma_conv(acc, R[4 * q], R[4 * q + 1], R[4 * q + 2], R[4 * q + 3], (uint64_t)(dlo + (2 * (3 - q)) * (BC_LBO >> 4)) | ((uint64_t)8 << 32));
}
__device__ __forceinline__ void conv_ld(uint32_t (&R)[16], uint32_t a) {
    #pragma unroll
    for (int q = 0; q < 4; q++) { const uint2 u = lds64(a + 64 * (2 * q + 1)); R[4 * q] = u.x; R[4 * q + 1] = u.y; }
}
__device__ __forceinline__ void conv_fix(uint32_t (&R)[16], uint32_t& carry) {
    #pragma unroll
    for (int q = 0; q < 4; q++) {
        asm volatile("mov.b32 %0, %1;" : "=r"(R[4 * q + 2]) : "r"(q ? R[4 * q - 3] : carry));
        asm volatile("mov.b32 %0, %1;" : "=r"(R[4 * q + 3]) : "r"(R[4 * q]));
    }
    asm volatile("mov.b32 %0, %1;" : "=r"(carry) : "r"(R[13]));
}
template<int A> __device__ __forceinline__ void conv_group(float (&acc)[32 - 8 * A], uint32_t (&R)[4][16], uint32_t& carry, uint32_t pb, uint32_t dlo) {
    #pragma unroll
    for (int e = 0; e < 8; e += 2) {
        const int dl = 8 * A + e;
        conv_fix(R[dl & 3], carry); conv_fix(R[(dl + 1) & 3], carry);
        wg_fence(); conv_mma(acc, R[dl & 3], dlo + 16 - 2 * e); conv_mma(acc, R[(dl + 1) & 3], dlo + 14 - 2 * e); wg_commit();
        wg_wait1();
        if (dl + 2 < 32) { conv_ld(R[(dl + 2) & 3], pb + (dl + 2) * 512); conv_ld(R[(dl + 3) & 3], pb + (dl + 3) * 512); }
    }
}

__global__ void __launch_bounds__(SD_THREADS, 1)
side_kernel(const __grid_constant__ CUtensorMap tmw, const bf16* __restrict__ x,
            const bf16* __restrict__ log_A_real, const bf16* __restrict__ A_imag, const bf16* __restrict__ C_real, const bf16* __restrict__ C_imag,
            const bf16* __restrict__ log_dt, const bf16* __restrict__ D_skip, const bf16* __restrict__ gate_w, bf16* __restrict__ out) {
    extern __shared__ __align__(1024) unsigned char smem[];
    const uint32_t sb = smem_u32(smem);
    const int tid = threadIdx.x, lane = tid & 31;
    const int warp = __shfl_sync(0xffffffffu, tid >> 5, 0);
    const int g = lane >> 2, t = lane & 3, mi = lane >> 3, r8 = lane & 7;
    const bool sh = blockIdx.x < 32;
    const int d0 = blockIdx.x * 16;
    const uint32_t b0_ = sb + SD_BAR, bKF = b0_ + 384, bKE = bKF + 8 * KSLOTS, bWO = b0_ + 48, bFULL = b0_ + 56, bEMPTY = b0_ + 88, bEPI = b0_ + 120, bPRT = b0_ + 152, bGO = b0_ + 184, bCH = b0_ + 256;
    const unsigned epoch = ld_relaxed32(&g_epoch);
    if (tid == 0) GT(blockIdx.x, 0);
    if (tid == 0) {
        for (int i = 0; i < 2 * KSLOTS; i++) mbar_init(bKF + 8 * i, 128);
        mbar_init(bWO, 1);
        for (int i = 0; i < 16; i++) mbar_init(bCH + 8 * i, 1);
        for (int i = 0; i < 4; i++) { mbar_init(bFULL + 8 * i, 1); mbar_init(bEMPTY + 8 * i, sh ? 8 : 4); mbar_init(bEPI + 8 * i, 4); mbar_init(bPRT + 8 * i, 8); mbar_init(bGO + 8 * i, 1); }
        asm volatile("fence.mbarrier_init.release.cluster;" ::: "memory");
    }
    for (int i = tid; i < KSLOTS * 8 * 16; i += SD_THREADS) sts128(sb + SD_BC + (i >> 4) * BC_LBO + (i & 15) * 16, make_uint4(0, 0, 0, 0));
    if (tid < 128) sts64(sb + ((tid & 64) ? SD_Q1 : SD_Q0) + (tid & 63) * 8, 0u, 0u);
    fence_async_smem();
    __syncthreads();

    if (warp < 8) {
        asm volatile("setmaxnreg.inc.sync.aligned.u32 %0;" :: "n"(SD_REG));
        const int wg = warp >> 2, w = warp & 3, t128 = tid & 127;
        if (SD_WAIT) __nanosleep(SD_WAIT);
        {
            #pragma unroll 1
            for (int i = 0; i < 4; i++) {
                const int tp = tid + 256 * i;
                const bf16* xp = x + (size_t)(2 * tp) * DM + d0;
                const uint4 v0 = __ldg((const uint4*)xp), v1 = __ldg((const uint4*)(xp + 8)), v2 = __ldg((const uint4*)(xp + DM)), v3 = __ldg((const uint4*)(xp + DM + 8));
                const uint32_t a = sb + SD_BT + (tp >> 5) * 144 + (tp & 31) * 4;
                const uint32_t lo[8] = {v0.x, v0.y, v0.z, v0.w, v1.x, v1.y, v1.z, v1.w};
                const uint32_t hi[8] = {v2.x, v2.y, v2.z, v2.w, v3.x, v3.y, v3.z, v3.w};
                #pragma unroll
                for (int j = 0; j < 8; j++) { sts32(a + (2 * j) * BT_RS, __byte_perm(lo[j], hi[j], 0x5410)); sts32(a + (2 * j + 1) * BT_RS, __byte_perm(lo[j], hi[j], 0x7632)); }
                if (SD_GAP) __nanosleep(SD_GAP);
            }
        }
        bar_sync(1, 256);
        if (tid == 0) GT(blockIdx.x, 65);
        const uint32_t pa = sb + (wg ? SD_Q1 : SD_Q0);
        const uint32_t pb = pa + (72 + 16 * w - 56 + g - 2 * t) * 8;
        for (int c = wg; c < 16; c += 2) {
            const uint32_t bt = sb + SD_BT + c * BT_RS;
            bar_sync(2 + wg, 128);
            #pragma unroll
            for (int it = 0; it < 9; it++) {
                const int k = it < 8 ? t128 + 128 * it : t128 - 4;
                if (it < 8 || t128 < 4) {
                    auto word = [&](int j) { return j >= 0 ? lds32(bt + (j >> 5) * 144 + (j & 31) * 4) : 0u; };
                    const uint32_t c0 = word(k), p0 = word(k - 1), c1 = word(k + 4), p1 = word(k + 3);
                    sts128(pa + (72 + 2 * k) * 8, make_uint4(__byte_perm(c0, p0, 0x7610), __byte_perm(c1, p1, 0x7610), __byte_perm(c0, c0, 0x1032), __byte_perm(c1, c1, 0x1032)));
                }
            }
            bar_sync(2 + wg, 128);
            const int slot = c % KSLOTS;
            float acc[32];
            #pragma unroll
            for (int i = 0; i < 32; i++) acc[i] = 0.f;
            uint32_t R[4][16];
            uint32_t carry = lds32(pb);
            conv_ld(R[0], pb); conv_ld(R[1], pb + 512);
            const uint32_t dlo = (((sb + SD_BC + slot * BC_BYTES) & 0x3FFFF) >> 4) | ((BC_LBO >> 4) << 16);
            mbar_wait_long(bKF + 8 * slot, (c / KSLOTS) & 1);
            const float ds = bf(D_skip[d0 + c]);
            auto fin = [&](const float* a8, int q0) {
                #pragma unroll
                for (int q = 0; q < 2; q++)
                    #pragma unroll
                    for (int hh = 0; hh < 2; hh++) {
                        const uint32_t a = bt + (4 * (q0 + q) + t) * 144 + (16 * w + g + 8 * hh) * 2;
                        const float u = __uint_as_float((uint32_t)lds16(a) << 16);
                        const float y = rbf(a8[4 * q + 2 * hh] + a8[4 * q + 2 * hh + 1]);
                        sts16(a, (uint16_t)(pack_bf16(y + rbf(u * ds), 0.f) & 0xffff));
                    }
            };
            float a1[24], a2[16], a3[8];
            conv_group<0>(acc, R, carry, pb, dlo);
            wg_wait0();
            #pragma unroll
            for (int i = 0; i < 24; i++) asm volatile("mov.b32 %0, %1;" : "=f"(a1[i]) : "f"(acc[8 + i]));
            fin(acc, 0);
            conv_group<1>(a1, R, carry, pb, dlo);
            wg_wait0();
            #pragma unroll
            for (int i = 0; i < 16; i++) asm volatile("mov.b32 %0, %1;" : "=f"(a2[i]) : "f"(a1[8 + i]));
            fin(a1, 2);
            conv_group<2>(a2, R, carry, pb, dlo);
            wg_wait0();
            #pragma unroll
            for (int i = 0; i < 8; i++) asm volatile("mov.b32 %0, %1;" : "=f"(a3[i]) : "f"(a2[8 + i]));
            fin(a2, 4);
            conv_group<3>(a3, R, carry, pb, dlo);
            wg_wait0();
            mbar_arrive(bKE + 8 * slot);
            fin(a3, 6);
        }
        fence_async_smem();
        __syncthreads();
        const uint32_t stg = sb + SD_STG + wg * 65536;
        uint32_t wf[32][4];
        if (tid == 0) GT(blockIdx.x, 66);
        mbar_wait_long(bWO, 0);
        #pragma unroll
        for (int i = 0; i < 32; i++)
            ldsm_x4_t(wf[i], stg + (i * 16 + (mi >> 1) * 8 + r8) * 128 + (((2 * w + (mi & 1)) ^ r8) << 4));
        { uint32_t x = 0;
          #pragma unroll
          for (int i = 0; i < 32; i++) x |= wf[i][0];
          asm volatile("" :: "r"(x) : "memory"); }
        __syncwarp();
        if (lane == 0) {
            mbar_arrive(bEMPTY + 16 * wg); mbar_arrive(bEMPTY + 16 * wg + 8);
            if (sh) { mbar_arrive(bEMPTY + 16 * (wg ^ 1)); mbar_arrive(bEMPTY + 16 * (wg ^ 1) + 8); }
        }
        uint4* dst = sh ? &g_part[(blockIdx.x & ~7) + 4 * wg + w][0][0][blockIdx.x & 7][lane] : &g_part[32 + w][0][0][2 * (blockIdx.x - 32) + wg][lane];
        const uint32_t dl0 = (((sb + SD_STG) & 0x3FFFF) >> 4) | 0x10000u;
        auto seg = [&](int s, auto last) {
            const int bi = sh ? s & 3 : 2 * wg + (s & 1), bp = (sh ? s >> 2 : s >> 1) & 1;
            const uint32_t xd = uni(dl0 + bi * 2048);
            float acc[16];
            #pragma unroll
            for (int i = 0; i < 32; i++) {
                if (i == 0 || (last.value && (i & 7) == 0)) { mbar_wait_long(bCH + 32 * bi + i, i ? 0 : bp); wg_fence(); }
                if (i == 0) wgmma_n32<0>(acc, wf[i], desc_from(xd));
                else wgmma_n32<1>(acc, wf[i], desc_from(xd + (i >> 2) * 256 + (i & 3) * 2));
            }
            wg_commit();
            if (s >= PART_SLOTS / 2) mbar_wait_long(bEPI + 8 * (s & 3), ((s - 4) >> 2) & 1);
            const uint32_t ph = ((s / PART_SLOTS) & 1) ^ 1;
            uint4* p = dst + (s % PART_SLOTS) * (4 * 8 * 32);
            wg_wait0();
            #pragma unroll
            for (int j = 0; j < 4; j++)
                st_relaxed128(p + 256 * j, make_uint4((__float_as_uint(acc[4 * j]) & ~1u) | ph, __float_as_uint(acc[4 * j + 1]), __float_as_uint(acc[4 * j + 2]), __float_as_uint(acc[4 * j + 3])));
            if (tid == 0 && s == NSEG - 1) GT(blockIdx.x, 71);
            __syncwarp();
            if (lane == 0) { mbar_arrive(bEMPTY + 8 * bi); mbar_arrive(bPRT + 8 * (s & 3)); }
        };
        #pragma unroll 1
        for (int s = 0; s < NSEG - 1; s++) seg(s, ic<0>());
        seg(NSEG - 1, ic<1>());
    } else {
        asm volatile("setmaxnreg.dec.sync.aligned.u32 %0;" :: "n"(504 - 2 * SD_REG));
        const int w = warp - 8, n = tid - 256;
        bf16 p_la = log_A_real[d0 * NS + n], p_ai = A_imag[d0 * NS + n], p_cr = C_real[d0 * NS + n], p_ci = C_imag[d0 * NS + n], p_dt = log_dt[d0];
        const uint32_t ef = sb + SD_EF + w * 8192;
        const uint32_t efl = ef + lane * 4;
        uint32_t goff[8];
        #pragma unroll
        for (int i = 0; i < 16; i++) {
            const int l = 64 * lane + 8 * (w + 4 * (i >> 3)) + (i & 7);
            const int p = (int)rbf((float)l);
            const int a = p >> 7, b = (p >> 3) & 15, c = p & 7;
            const int row = p < 256 ? 8 * a + c : (p < 512 ? 16 + 4 * (a - 2) + (c >> 1) : (p < 1024 ? 24 + 2 * (a - 4) + (c >> 2) : 24 + a));
            const uint32_t off = row * 72 + b * 4;
            if (i & 1) goff[i >> 1] |= off << 16; else goff[i >> 1] = off;
        }
        for (int c = 0; c < 16; c++) {
            const float dt = rbf(expf(bf(p_dt)));
            const float xr = -rbf(expf(bf(p_la))) * dt, xi = bf(p_ai) * dt;
            cplx C; C.r = 2.f * bf(p_cr) * dt; C.i = 2.f * bf(p_ci) * dt;
            if (c + 1 < 16) {
                const int o = (d0 + c + 1) * NS + n;
                p_la = log_A_real[o]; p_ai = A_imag[o]; p_cr = C_real[o]; p_ci = C_imag[o]; p_dt = log_dt[d0 + c + 1];
            }
            const uint32_t mexp = min(max(__reduce_max_sync(0xffffffffu, __float_as_uint(fmaxf(fabsf(C.r), fabsf(C.i)))) & 0x7f800000u, 0x01000000u), 0x7e000000u);
            const float unsc = __uint_as_float(mexp), sc = __uint_as_float(0x7f000000u - mexp);
            C.r *= sc; C.i *= sc;
            #define EADDR(r) ((efl ^ (((r) & 7) << 4)) + (r) * 128)
            {
                cplx f[16];
                f[1] = cexp_(8.f * xr, -8.f * xi);
                f[2] = cmul(f[1], f[1]); f[3] = cmul(f[2], f[1]); f[4] = cmul(f[2], f[2]); f[5] = cmul(f[4], f[1]); f[6] = cmul(f[4], f[2]); f[7] = cmul(f[4], f[3]);
                f[8] = cmul(f[4], f[4]);
                #pragma unroll
                for (int b = 9; b < 16; b++) f[b] = cmul(f[8], f[b - 8]);
                sts32(EADDR(0) + 6144, 0x00003c00u);
                #pragma unroll
                for (int b = 1; b < 16; b++) sts32(EADDR(b) + 6144, pack_f16(f[b].r, f[b].i));
            }
            {
                cplx G[17], wc[8];
                G[1] = cexp_(128.f * xr, 128.f * xi);
                wc[1] = cexp_(xr, xi);
                G[2] = cmul(G[1], G[1]); G[4] = cmul(G[2], G[2]); G[8] = cmul(G[4], G[4]);
                wc[2] = cmul(wc[1], wc[1]); wc[3] = cmul(wc[2], wc[1]); wc[4] = cmul(wc[2], wc[2]); wc[5] = cmul(wc[4], wc[1]); wc[6] = cmul(wc[4], wc[2]); wc[7] = cmul(wc[4], wc[3]);
                cplx CG[17];
                CG[0] = C; CG[1] = cmul(C, G[1]); CG[2] = cmul(C, G[2]); CG[3] = cmul(CG[1], G[2]);
                #pragma unroll
                for (int a = 0; a < 4; a++) CG[4 + a] = cmul(CG[a], G[4]);
                #pragma unroll
                for (int a = 0; a < 9; a++) CG[8 + a] = cmul(CG[a], G[8]);
                #pragma unroll
                for (int r = 0; r < 41; r++) {
                    const int a = r < 16 ? (r >> 3) : (r < 24 ? 2 + ((r >> 2) & 1) : (r < 32 ? 4 + ((r >> 1) & 3) : r - 24));
                    const int cc = r < 16 ? (r & 7) : (r < 24 ? 2 * (r & 3) : (r < 32 ? 4 * (r & 1) : 0));
                    const cplx e = cc ? cmul(CG[a], wc[cc]) : CG[a];
                    sts32(EADDR(r), pack_f16(e.r, e.i));
                }
            }
            __syncwarp();
            float acc[3][2][4];
            #pragma unroll
            for (int i = 0; i < 3; i++)
                #pragma unroll
                for (int j = 0; j < 2; j++) { acc[i][j][0] = acc[i][j][1] = acc[i][j][2] = acc[i][j][3] = 0.f; }
            #pragma unroll
            for (int ks = 0; ks < 4; ks++) {
                uint32_t bq[4];
                ldsm_x4(bq, ef + 6144 + ((mi >> 1) * 8 + r8) * 128 + (((2 * ks + (mi & 1)) ^ r8) << 4));
                #pragma unroll
                for (int mt = 0; mt < 3; mt++) {
                    uint32_t aq[4];
                    ldsm_x4(aq, ef + (16 * mt + (mi & 1) * 8 + r8) * 128 + (((2 * ks + (mi >> 1)) ^ r8) << 4));
                    mma_f16(acc[mt][0], aq, bq[0], bq[1]);
                    mma_f16(acc[mt][1], aq, bq[2], bq[3]);
                }
            }
            const uint32_t kp = sb + SD_KP;
            #pragma unroll
            for (int mt = 0; mt < 3; mt++)
                #pragma unroll
                for (int nt = 0; nt < 2; nt++) {
                    const uint32_t a = kp + w * 3072 + (16 * mt + g) * 64 + nt * 32 + t * 8;
                    sts64(a, __float_as_uint(acc[mt][nt][0] * unsc), __float_as_uint(acc[mt][nt][1] * unsc));
                    sts64(a + 512, __float_as_uint(acc[mt][nt][2] * unsc), __float_as_uint(acc[mt][nt][3] * unsc));
                }
            bar_sync(4, 128);
            #pragma unroll
            for (int i = 0; i < 3; i++) {
                const uint32_t a = kp + (n + 128 * i) * 8;
                const uint2 v0 = lds64(a), v1 = lds64(a + 3072), v2 = lds64(a + 6144), v3 = lds64(a + 9216);
                sts64(a + 12288 + ((n >> 3) + 16 * i) * 8, __float_as_uint((__uint_as_float(v0.x) + __uint_as_float(v1.x)) + (__uint_as_float(v2.x) + __uint_as_float(v3.x))),
                                 __float_as_uint((__uint_as_float(v0.y) + __uint_as_float(v1.y)) + (__uint_as_float(v2.y) + __uint_as_float(v3.y))));
            }
            bar_sync(4, 128);
            const int slot = c % KSLOTS;
            float kv[16];
            #pragma unroll
            for (int e = 0; e < 8; e++) { kv[2 * e] = __uint_as_float(lds32(kp + 12288 + (goff[e] & 0xffff))); kv[2 * e + 1] = __uint_as_float(lds32(kp + 12288 + (goff[e] >> 16))); }
            if (c >= KSLOTS) mbar_wait_long(bKE + 8 * slot, (c / KSLOTS - 1) & 1);
            #pragma unroll
            for (int it = 0; it < 2; it++) {
                uint32_t hi[4], lo[4];
                #pragma unroll
                for (int e = 0; e < 4; e++) {
                    const float k0 = kv[8 * it + 2 * e], k1 = kv[8 * it + 2 * e + 1];
                    hi[e] = pack_bf16(k0, k1);
                    lo[e] = pack_bf16(k0 - bf_lo(hi[e]), k1 - bf_hi(hi[e]));
                }
                const uint32_t a = sb + SD_BC + slot * BC_BYTES + (w + 4 * it) * BC_LBO + (16 + 2 * lane) * 16;
                sts128(a, make_uint4(hi[0], hi[1], hi[2], hi[3]));
                sts128(a + 16, make_uint4(lo[0], lo[1], lo[2], lo[3]));
            }
            fence_async_smem();
            mbar_arrive(bKF + 8 * slot);
        }
        {
            uint32_t gw[9];
            #pragma unroll
            for (int j = 0; j < 9; j++) gw[j] = __ldg((const uint32_t*)gate_w + lane + 32 * j);
            float z = 0.f;
            #pragma unroll 1
            for (int i0 = 0; i0 < 15; i0 += 5) {
                uint32_t xv[5][9];
                #pragma unroll
                for (int i = 0; i < 5; i++) {
                    const int tk = min(blockIdx.x * 57 + w + 4 * (i0 + i), S_LEN - 1);
                    #pragma unroll
                    for (int j = 0; j < 9; j++) xv[i][j] = __ldg((const uint32_t*)(x + (size_t)tk * DM) + lane + 32 * j);
                }
                #pragma unroll
                for (int i = 0; i < 5; i++) {
                    float acc = 0.f;
                    #pragma unroll
                    for (int j = 0; j < 9; j++) { const uint32_t m = mul_bf2(xv[i][j], gw[j]); acc += bf_lo(m) + bf_hi(m); }
                    #pragma unroll
                    for (int o = 16; o; o >>= 1) acc += __shfl_xor_sync(0xffffffffu, acc, o);
                    if (lane == i0 + i) z = rbf(acc);
                }
            }
            const int li = w + 4 * lane, tk = blockIdx.x * 57 + li;
            if (li < 57 && tk < S_LEN) st_relaxed32(&g_gate[tk], pack_bf16(1.f / (1.f + expf(-z)), 0.f) | (epoch << 16));
        }
        if (tid == 256) GT(blockIdx.x, 67);
        fence_async_smem();
        __syncthreads();
            const uint32_t ost = sb + SD_OST + w * 256;
            const uint4* const pl = &g_part[blockIdx.x][0][0][0][lane];
            uint4 v[8];
            auto fetch = [&](int u, bool block) {
                const int s = u >> 2;
                uint32_t early;
                asm volatile("{\n.reg .pred p;\nmbarrier.test_wait.parity.shared::cta.b64 p, [%1], %2;\nselp.u32 %0, 1, 0, p;\n}\n" : "=r"(early) : "r"(bPRT + 8 * (s & 3)), "r"((s >> 2) & 1) : "memory");
                if (!early) {
                    if (!block) return false;
                    mbar_wait_long(bPRT + 8 * (s & 3), (s >> 2) & 1);
                    delay_clk(s < NSEG - 2 ? SD_P1 : SD_P2);
                } else if (SD_P3 && s < SD_RUSH) delay_clk(SD_P3);
                const uint4* p = pl + (u & (4 * PART_SLOTS - 1)) * 256;
                #pragma unroll
                for (int i = 0; i < 8; i++) v[i] = ld_relaxed128(p + 32 * i);
                return true;
            };
            auto units = [&](int u, int end) {
              fetch(u, true);
              #pragma unroll 1
              while (true) {
                const int s = u >> 2;
                const int t0 = 8 * u + 2 * t;
                const uint2 gt = lds64(sb + SD_Q0 + t0 * 4);
                const uint32_t ba = sb + SD_BT + g * BT_RS + (t0 >> 6) * 144 + (t0 & 63) * 2;
                const uint32_t b0 = lds32(ba), b1 = lds32(ba + 8 * BT_RS);
                const uint32_t phm = ((s / PART_SLOTS) & 1) - 1;
                int it = 0;
                while (true) {
                    uint32_t any = 0;
                    #pragma unroll
                    for (int i = 0; i < 8; i++) any |= v[i].x ^ phm;
                    if (!__any_sync(0xffffffffu, any & 1u) || ++it >= SD_SPIN) break;
                    if (it > 1 && s < NSEG - 2) __nanosleep(200);
                    const uint4* p = pl + (u & (4 * PART_SLOTS - 1)) * 256;
                    #pragma unroll
                    for (int i = 0; i < 8; i++) ld_relaxed128_p(v[i], p + 32 * i, (v[i].x ^ phm) & 1u);
                }
                if (lane == 0) mbar_arrive(bEPI + 8 * (s & 3));
                float a0 = __uint_as_float(v[0].x), a1 = __uint_as_float(v[0].y), a2 = __uint_as_float(v[0].z), a3 = __uint_as_float(v[0].w);
                #pragma unroll
                for (int i = 1; i < 8; i++) { a0 += __uint_as_float(v[i].x); a1 += __uint_as_float(v[i].y); a2 += __uint_as_float(v[i].z); a3 += __uint_as_float(v[i].w); }
                const uint32_t s01 = pack_bf16(a0, a1), s23 = pack_bf16(a2, a3);
                const int nu = u + 3;
                const bool pre = nu < end && fetch(nu, false);
                const uint32_t gg = __byte_perm(gt.x, gt.y, 0x5410), mm = pack_bf16(1.f - bf_lo(gg), 1.f - bf_hi(gg));
                const uint32_t r0 = add_bf2(mul_bf2(gg, s01), mul_bf2(mm, b0)), r1 = add_bf2(mul_bf2(gg, s23), mul_bf2(mm, b1));
                asm volatile("stmatrix.sync.aligned.m8n8.x2.trans.shared.b16 [%0], {%1,%2};" :: "r"(ost + r8 * 32 + (mi & 1) * 16), "r"(r0), "r"(r1) : "memory");
                __syncwarp();
                if (lane < 16) *(uint4*)(out + (size_t)(8 * u + (lane >> 1)) * DM + d0 + 8 * (lane & 1)) = lds128(ost + lane * 16);
                __syncwarp();
                if (lane == 0 && (u & 3) == 3) GT(blockIdx.x, 1 + s);
                if (nu >= end) break;
                if (!pre) fetch(nu, true);
                u = nu;
              }
            };
        if (w == 0) {
            if (lane == 0) {
                mbar_expect_tx(bWO, 131072);
                #pragma unroll
                for (int q = 0; q < 4; q++) tma2d(sb + SD_STG + q * 32768, &tmw, bWO, sh ? 128 * (blockIdx.x >> 3) + 64 * (q >> 1) : 512, sh ? 512 * (blockIdx.x & 7) + 256 * (q & 1) : 1024 * (blockIdx.x - 32) + 256 * q);
            }
            bar_sync(5, 128);
            const int ke0 = sh ? blockIdx.x & 7 : 2 * (blockIdx.x - 32);
            const unsigned int* f = &g_prog[12 * ke0 + (lane < (sh ? 12 : 24) ? lane : 0)];
            int avail = 0;
            #pragma unroll 1
            for (int s = 0; s < NSEG; s++) {
                if (s >= avail) {
                    int it = 0;
                    while (true) {
                        uint32_t v;
                        asm volatile("ld.acquire.gpu.global.u32 %0, [%1];" : "=r"(v) : "l"(f) : "memory");
                        avail = __reduce_min_sync(0xffffffffu, (v >> 8) == (epoch & 0xffffffu) ? v & 255u : 0u);
                        if (avail > s || ++it >= SD_SPIN) break;
                        if (s < NSEG - 1) __nanosleep(64);
                    }
                    asm volatile("fence.proxy.async.global;" ::: "memory");
                    if (lane == 0 && s == NSEG - 1) GT(blockIdx.x, 70);
                }
                if (lane == 0 && s == 2 && blockIdx.x == 0) st_relaxed32(&g_epoch, epoch + 1);
                const int b0 = sh ? s & 3 : s & 1, bp = (sh ? s >> 2 : s >> 1) & 1;
                const bf16* src = g_otok + (size_t)s * (SEG * NH * DH) + ke0 * 16384;
                mbar_wait_long(bEMPTY + 8 * b0, bp);
                if (!sh) mbar_wait_long(bEMPTY + 16 + 8 * b0, bp);
                if (s < NSEG - 1) {
                    asm volatile("{\n.reg .pred p, q;\nelect.sync _|p, 0xffffffff;\nsetp.eq.and.u32 q, %6, 0, p;\n"
                                 "@p mbarrier.arrive.expect_tx.shared.b64 _, [%2], 32768;\n"
                                 "@p cp.async.bulk.shared::cluster.global.mbarrier::complete_tx::bytes [%0], [%1], 32768, [%2];\n"
                                 "@q mbarrier.arrive.expect_tx.shared.b64 _, [%5], 32768;\n"
                                 "@q cp.async.bulk.shared::cluster.global.mbarrier::complete_tx::bytes [%3], [%4], 32768, [%5];\n}\n"
                        :: "r"(sb + SD_STG + b0 * 32768), "l"(src), "r"(bCH + 32 * b0), "r"(sb + SD_STG + (b0 + 2) * 32768), "l"(src + 16384), "r"(bCH + 32 * (b0 + 2)), "r"((uint32_t)sh) : "memory");
                } else {
                    #pragma unroll
                    for (int hc = 0; hc < 4; hc++)
                        asm volatile("{\n.reg .pred p, q;\nelect.sync _|p, 0xffffffff;\nsetp.eq.and.u32 q, %6, 0, p;\n"
                                     "@p mbarrier.arrive.expect_tx.shared.b64 _, [%2], 8192;\n"
                                     "@p cp.async.bulk.shared::cluster.global.mbarrier::complete_tx::bytes [%0], [%1], 8192, [%2];\n"
                                     "@q mbarrier.arrive.expect_tx.shared.b64 _, [%5], 8192;\n"
                                     "@q cp.async.bulk.shared::cluster.global.mbarrier::complete_tx::bytes [%3], [%4], 8192, [%5];\n}\n"
                            :: "r"(sb + SD_STG + b0 * 32768 + hc * 8192), "l"(src + hc * 4096), "r"(bCH + 32 * b0 + 8 * hc),
                               "r"(sb + SD_STG + (b0 + 2) * 32768 + hc * 8192), "l"(src + 16384 + hc * 4096), "r"(bCH + 32 * (b0 + 2) + 8 * hc), "r"((uint32_t)sh) : "memory");
                }
            }
        } else {
            if (w == 3) {
                for (int i = 0; i < 16; i += 8) {
                    uint4 v[8]; uint32_t miss = 0xffu; int it = 0;
                    const uint32_t tag = epoch & 0xffffu;
                    #pragma unroll
                    for (int j = 0; j < 8; j++) v[j] = make_uint4(0, 0, 0, 0);
                    do {
                        #pragma unroll
                        for (int j = 0; j < 8; j++) ld_relaxed128_p(v[j], (const uint4*)g_gate + (i + j) * 32 + lane, miss & (1u << j));
                        miss = 0;
                        #pragma unroll
                        for (int j = 0; j < 8; j++) miss |= (uint32_t)((v[j].x >> 16) != tag || (v[j].y >> 16) != tag || (v[j].z >> 16) != tag || (v[j].w >> 16) != tag) << j;
                    } while (__any_sync(0xffffffffu, miss) && ++it < SD_SPIN);
                    #pragma unroll
                    for (int j = 0; j < 8; j++) sts128(sb + SD_Q0 + ((i + j) * 32 + lane) * 16, v[j]);
                }
            }
            bar_sync(5, 128);
        }
        #pragma unroll 1
        for (int k = w == 0; k < 2; k++) units(k ? 4 * (NSEG - 1) + w : w - 1, k ? 0 : 4 * (NSEG - 1));
    }
    if (tid == 256) GT(blockIdx.x, 72);
}

extern "C" void kernel_launch(void* const* d_in, const int* in_sizes, int n_in, void* d_out, int out_size) {
    const bf16* x = (const bf16*)d_in[0];
    const bf16* mem0 = (const bf16*)d_in[1];
    const bf16* Wq = (const bf16*)d_in[2];
    const bf16* Wk = (const bf16*)d_in[3];
    const bf16* Wv = (const bf16*)d_in[4];
    const bf16* Wo = (const bf16*)d_in[5];
    const bf16* log_A_real = (const bf16*)d_in[8];
    const bf16* A_imag = (const bf16*)d_in[9];
    const bf16* C_real = (const bf16*)d_in[10];
    const bf16* C_imag = (const bf16*)d_in[11];
    const bf16* log_dt = (const bf16*)d_in[12];
    const bf16* D_skip = (const bf16*)d_in[13];
    const bf16* gate_w = (const bf16*)d_in[14];
    bf16* out = (bf16*)d_out;
    typedef CUresult (*EncFn)(CUtensorMap*, CUtensorMapDataType, cuuint32_t, void*, const cuuint64_t*, const cuuint64_t*, const cuuint32_t*, const cuuint32_t*,
                              CUtensorMapInterleave, CUtensorMapSwizzle, CUtensorMapL2promotion, CUtensorMapFloatOOBfill);
    static EncFn enc = nullptr;
    if (!enc) { void* fn = nullptr; cudaDriverEntryPointQueryResult qr; cudaGetDriverEntryPoint("cuTensorMapEncodeTiled", &fn, cudaEnableDefault, &qr); enc = (EncFn)fn; }
    auto mk = [&](CUtensorMap* tm, const void* ptr, uint64_t cols, uint64_t rows, uint32_t bc, uint32_t br) {
        cuuint64_t gdim[2] = {cols, rows}; cuuint64_t gstr[1] = {cols * 2}; cuuint32_t box[2] = {bc, br}; cuuint32_t estr[2] = {1, 1};
        enc(tm, CU_TENSOR_MAP_DATA_TYPE_BFLOAT16, 2, (void*)ptr, gdim, gstr, box, estr, CU_TENSOR_MAP_INTERLEAVE_NONE, bc == 64 ? CU_TENSOR_MAP_SWIZZLE_128B : CU_TENSOR_MAP_SWIZZLE_64B,
            CU_TENSOR_MAP_L2_PROMOTION_L2_256B, CU_TENSOR_MAP_FLOAT_OOB_FILL_NONE);
    };
    static bool attr_done = false;
    if (!attr_done) {
        cudaFuncSetAttribute(chain_kernel, cudaFuncAttributeMaxDynamicSharedMemorySize, SM_TOTAL);
        cudaFuncSetAttribute(side_kernel, cudaFuncAttributeMaxDynamicSharedMemorySize, SD_TOTAL);
        attr_done = true;
    }
    CUtensorMap tmx, tmw, tmq, tmk, tmv, tmo;
    {
        cuuint64_t gdim[3] = {64, S_LEN, DM / 64}; cuuint64_t gstr[2] = {DM * 2, 128}; cuuint32_t box[3] = {64, SEG, 3}; cuuint32_t estr[3] = {1, 1, 1};
        enc(&tmx, CU_TENSOR_MAP_DATA_TYPE_BFLOAT16, 3, (void*)x, gdim, gstr, box, estr, CU_TENSOR_MAP_INTERLEAVE_NONE, CU_TENSOR_MAP_SWIZZLE_128B,
            CU_TENSOR_MAP_L2_PROMOTION_L2_256B, CU_TENSOR_MAP_FLOAT_OOB_FILL_NONE);
    }
    mk(&tmw, Wo, DM, NH * DH, 64, 256);
    mk(&tmo, Wo, DM, NH * DH, 32, 128);
    mk(&tmq, Wq, NH * DH, DM, 32, 48); mk(&tmk, Wk, NH * DH, DM, 32, 48); mk(&tmv, Wv, NH * DH, DM, 32, 48);
    chain_kernel<<<96, CH_THREADS, SM_TOTAL>>>(tmx, tmq, tmk, tmv, tmo, mem0, 0u);
    cudaLaunchConfig_t cfg = {};
    cfg.gridDim = dim3(SD_CTAS); cfg.blockDim = dim3(SD_THREADS); cfg.dynamicSmemBytes = SD_TOTAL; cfg.stream = cudaStreamPerThread;
    cudaLaunchAttribute at[1];
    at[0].id = cudaLaunchAttributeProgrammaticStreamSerialization; at[0].val.programmaticStreamSerializationAllowed = 1;
    cfg.attrs = at; cfg.numAttrs = 1;
    cudaLaunchKernelEx(&cfg, side_kernel, tmw, x, log_A_real, A_imag, C_real, C_imag, log_dt, D_skip, gate_w, out);
}
```

```cpp
#include <cuda_runtime.h>
#include <cuda.h>
#include <cuda_bf16.h>
#include <stdint.h>

#define S_LEN 2048
#define DM 576
#define NH 32
#define DH 128
#define NMEM 8
#define SEG 32
#define NSEG 64
#define LQ 40
#define NS 128

typedef __nv_bfloat16 bf16;

__device__ __forceinline__ float bf(bf16 v) { return __bfloat162float(v); }
__device__ __forceinline__ bf16 tobf(float v) { return __float2bfloat16_rn(v); }
__device__ __forceinline__ float rbf(float v) { return __bfloat162float(__float2bfloat16_rn(v)); }

#define CH_THREADS 384
#define SPIN_LIMIT (1 << 17)
#define SM_X     0
#define XBUF     36864
#define SM_TOK   73728
#define TOKBUF   24576
#define SM_STASH 139264
#define SM_TS    (SM_STASH + 3072)
#define SM_WO    147456
#define SM_MEM   196608
#define SM_EX    205824
#define EXBUF    6144
#define SM_P     218112
#define SM_OST   219136
#define SM_O     223232
#define SM_BAR   228352
#define SM_IL    (SM_BAR + 128)
#define SM_SG    (SM_IL + 256)
#define SM_TOTAL (SM_SG + 64)

#define ACC_X    36864
#define ACC_FULL 0x0020u
#define SLOT_OFF(sl) ((((sl) & 1) << 7) | (((sl) & 2) << 8))
__device__ __align__(65536) unsigned char g_acc[65536];
__device__ unsigned int g_init[96];
__device__ unsigned int g_epoch = 1;
__device__ __align__(128) unsigned int g_ts[128];
__device__ __align__(1024) bf16 g_otok[S_LEN * NH * DH];
__device__ __align__(1024) unsigned char g_tokx[96][8192];
__device__ __align__(128) unsigned int g_prog[96];
#define STAMP(i)
#define STAMPV(i, v)
#define GT(b, i)
#define STAMPB(i)

__device__ __forceinline__ uint32_t smem_u32(const void* p) { return (uint32_t)__cvta_generic_to_shared(p); }
__device__ __forceinline__ void ldsm_x4(uint32_t (&r)[4], uint32_t addr) {
    asm volatile("ldmatrix.sync.aligned.m8n8.x4.shared.b16 {%0,%1,%2,%3}, [%4];" : "=r"(r[0]), "=r"(r[1]), "=r"(r[2]), "=r"(r[3]) : "r"(addr) : "memory");
}
__device__ __forceinline__ void ldsm_x4_p(uint32_t (&r)[4], uint32_t addr, uint32_t skip) {
    asm volatile("{\n.reg .pred p;\nsetp.eq.u32 p, %5, 0;\n@p ldmatrix.sync.aligned.m8n8.x4.shared.b16 {%0,%1,%2,%3}, [%4];\n}\n" : "+r"(r[0]), "+r"(r[1]), "+r"(r[2]), "+r"(r[3]) : "r"(addr), "r"(skip) : "memory");
}
__device__ __forceinline__ void ldsm_x4_t(uint32_t (&r)[4], uint32_t addr) {
    asm volatile("ldmatrix.sync.aligned.m8n8.x4.trans.shared.b16 {%0,%1,%2,%3}, [%4];" : "=r"(r[0]), "=r"(r[1]), "=r"(r[2]), "=r"(r[3]) : "r"(addr) : "memory");
}
__device__ __forceinline__ uint32_t ldsm_x1_t(uint32_t addr) {
    uint32_t r; asm volatile("ldmatrix.sync.aligned.m8n8.x1.trans.shared.b16 {%0}, [%1];" : "=r"(r) : "r"(addr) : "memory"); return r;
}
__device__ __forceinline__ void ldsm_x2_t(uint32_t& r0, uint32_t& r1, uint32_t addr) {
    asm volatile("ldmatrix.sync.aligned.m8n8.x2.trans.shared.b16 {%0,%1}, [%2];" : "=r"(r0), "=r"(r1) : "r"(addr) : "memory");
}
__device__ __forceinline__ void stsm_x4(uint32_t addr, uint32_t r0, uint32_t r1, uint32_t r2, uint32_t r3) {
    asm volatile("stmatrix.sync.aligned.m8n8.x4.shared.b16 [%0], {%1,%2,%3,%4};" :: "r"(addr), "r"(r0), "r"(r1), "r"(r2), "r"(r3) : "memory");
}
__device__ __forceinline__ void stsm_x4_t(uint32_t addr, uint32_t r0, uint32_t r1, uint32_t r2, uint32_t r3) {
    asm volatile("stmatrix.sync.aligned.m8n8.x4.trans.shared.b16 [%0], {%1,%2,%3,%4};" :: "r"(addr), "r"(r0), "r"(r1), "r"(r2), "r"(r3) : "memory");
}
__device__ __forceinline__ void mma16816(float (&c)[4], const uint32_t (&a)[4], uint32_t b0, uint32_t b1) {
    asm("mma.sync.aligned.m16n8k16.row.col.f32.bf16.bf16.f32 {%0,%1,%2,%3}, {%4,%5,%6,%7}, {%8,%9}, {%0,%1,%2,%3};"
        : "+f"(c[0]), "+f"(c[1]), "+f"(c[2]), "+f"(c[3]) : "r"(a[0]), "r"(a[1]), "r"(a[2]), "r"(a[3]), "r"(b0), "r"(b1));
}
__device__ __forceinline__ void mma16816r(float (&c)[4], uint32_t a0, uint32_t a1, uint32_t a2, uint32_t a3, uint32_t b0, uint32_t b1) {
    asm("mma.sync.aligned.m16n8k16.row.col.f32.bf16.bf16.f32 {%0,%1,%2,%3}, {%4,%5,%6,%7}, {%8,%9}, {%0,%1,%2,%3};"
        : "+f"(c[0]), "+f"(c[1]), "+f"(c[2]), "+f"(c[3]) : "r"(a0), "r"(a1), "r"(a2), "r"(a3), "r"(b0), "r"(b1));
}
__device__ __forceinline__ void mma1688(float (&c)[4], uint32_t a0, uint32_t a1, uint32_t b0) {
    asm("mma.sync.aligned.m16n8k8.row.col.f32.bf16.bf16.f32 {%0,%1,%2,%3}, {%4,%5}, {%6}, {%0,%1,%2,%3};"
        : "+f"(c[0]), "+f"(c[1]), "+f"(c[2]), "+f"(c[3]) : "r"(a0), "r"(a1), "r"(b0));
}
__device__ __forceinline__ uint32_t pack_bf16(float lo, float hi) {
    uint32_t r; asm("cvt.rn.bf16x2.f32 %0, %1, %2;" : "=r"(r) : "f"(hi), "f"(lo)); return r;
}
__device__ __forceinline__ float bf_lo(uint32_t v) { return __uint_as_float(v << 16); }
__device__ __forceinline__ float bf_hi(uint32_t v) { return __uint_as_float(v & 0xffff0000u); }
__device__ __forceinline__ uint32_t max_bf2(uint32_t a, uint32_t b) { uint32_t r; asm("max.bf16x2 %0, %1, %2;" : "=r"(r) : "r"(a), "r"(b)); return r; }
__device__ __forceinline__ uint32_t maxabs_bf2(uint32_t a, uint32_t b) { uint32_t r; asm("max.NaN.xorsign.abs.bf16x2 %0, %1, %2;" : "=r"(r) : "r"(a), "r"(b)); return r; }
__device__ __forceinline__ float ex2(float x) { float r; asm("ex2.approx.ftz.f32 %0, %1;" : "=f"(r) : "f"(x)); return r; }
__device__ __forceinline__ void ld_relaxed128_p(uint4& v, const uint4* p, uint32_t pred) {
    asm volatile("{\n.reg .pred p;\nsetp.ne.u32 p, %5, 0;\n@p ld.relaxed.gpu.global.v4.u32 {%0,%1,%2,%3}, [%4];\n}\n" : "+r"(v.x), "+r"(v.y), "+r"(v.z), "+r"(v.w) : "l"(p), "r"(pred) : "memory");
}
__device__ __forceinline__ uint4 ld_relaxed128(const uint4* p) { uint4 v; asm volatile("ld.relaxed.gpu.global.v4.u32 {%0,%1,%2,%3}, [%4];" : "=r"(v.x), "=r"(v.y), "=r"(v.z), "=r"(v.w) : "l"(p) : "memory"); return v; }
__device__ __forceinline__ uint32_t ld_relaxed32(const uint32_t* p) { uint32_t v; asm volatile("ld.relaxed.gpu.global.u32 %0, [%1];" : "=r"(v) : "l"(p) : "memory"); return v; }
__device__ __forceinline__ void st_relaxed128(uint4* p, uint4 v) { asm volatile("st.relaxed.gpu.global.v4.u32 [%0], {%1,%2,%3,%4};" :: "l"(p), "r"(v.x), "r"(v.y), "r"(v.z), "r"(v.w) : "memory"); }
__device__ __forceinline__ void st_relaxed32(uint32_t* p, uint32_t v) { asm volatile("st.relaxed.gpu.global.u32 [%0], %1;" :: "l"(p), "r"(v) : "memory"); }
__device__ __forceinline__ void st_relaxed128_p(uint4* p, uint4 v, uint32_t skip) {
    asm volatile("{\n.reg .pred p;\nsetp.eq.u32 p, %5, 0;\n@p st.relaxed.gpu.global.v4.u32 [%0], {%1,%2,%3,%4};\n}\n" :: "l"(p), "r"(v.x), "r"(v.y), "r"(v.z), "r"(v.w), "r"(skip) : "memory");
}
__device__ __forceinline__ void st_relaxed64_p(void* p, uint32_t x, uint32_t y, uint32_t skip) {
    asm volatile("{\n.reg .pred p;\n.reg .b64 v;\nsetp.eq.u32 p, %3, 0;\nmov.b64 v, {%1,%2};\n@p st.relaxed.gpu.global.b64 [%0], v;\n}\n" :: "l"(p), "r"(x), "r"(y), "r"(skip) : "memory");
}
__device__ __forceinline__ void ld_relaxed64_p(uint2& v, const void* p, uint32_t pred) {
    asm volatile("{\n.reg .pred p;\n.reg .b64 v;\nsetp.ne.u32 p, %3, 0;\nmov.b64 v, {%0,%1};\n@p ld.relaxed.gpu.global.b64 v, [%2];\nmov.b64 {%0,%1}, v;\n}\n" : "+r"(v.x), "+r"(v.y) : "l"(p), "r"(pred) : "memory");
}
__device__ __forceinline__ uint2 ld_relaxed64(const void* p) {
    uint2 v; asm volatile("{\n.reg .b64 v;\nld.relaxed.gpu.global.b64 v, [%2];\nmov.b64 {%0,%1}, v;\n}\n" : "=r"(v.x), "=r"(v.y) : "l"(p) : "memory"); return v;
}
__device__ __forceinline__ void st_relaxed32_p(void* p, uint32_t v, uint32_t skip) {
    asm volatile("{\n.reg .pred p;\nsetp.eq.u32 p, %2, 0;\n@p st.relaxed.gpu.global.u32 [%0], %1;\n}\n" :: "l"(p), "r"(v), "r"(skip) : "memory");
}
__device__ __forceinline__ void bar_arrive_p(int id, int n, uint32_t skip) {
    asm volatile("{\n.reg .pred p;\nsetp.eq.u32 p, %2, 0;\n@p bar.arrive %0, %1;\n}\n" :: "r"(id), "r"(n), "r"(skip) : "memory");
}
__device__ __forceinline__ void bar_sync_p(int id, int n, uint32_t skip) {
    asm volatile("{\n.reg .pred p;\nsetp.eq.u32 p, %2, 0;\n@p bar.sync %0, %1;\n}\n" :: "r"(id), "r"(n), "r"(skip) : "memory");
}
__device__ __forceinline__ uint32_t movm(uint32_t x) { uint32_t r; asm volatile("movmatrix.sync.aligned.m8n8.trans.b16 %0, %1;" : "=r"(r) : "r"(x)); return r; }
__device__ __forceinline__ void sts32_p(uint32_t a, uint32_t v, uint32_t doit) {
    asm volatile("{\n.reg .pred p;\nsetp.ne.u32 p, %2, 0;\n@p st.shared.u32 [%0], %1;\n}\n" :: "r"(a), "r"(v), "r"(doit) : "memory");
}
__device__ __forceinline__ uint32_t pin(uint32_t x) { return __shfl_sync(0xffffffffu, x, threadIdx.x & 31); }
__device__ __forceinline__ void ldsm16_t(uint32_t (&b)[4][4], uint32_t a) {
    asm volatile("ldmatrix.sync.aligned.m8n8.x4.trans.shared.b16 {%0,%1,%2,%3}, [%16];\n"
                 "ldmatrix.sync.aligned.m8n8.x4.trans.shared.b16 {%4,%5,%6,%7}, [%16+512];\n"
                 "ldmatrix.sync.aligned.m8n8.x4.trans.shared.b16 {%8,%9,%10,%11}, [%16+1024];\n"
                 "ldmatrix.sync.aligned.m8n8.x4.trans.shared.b16 {%12,%13,%14,%15}, [%16+1536];\n"
        : "=r"(b[0][0]), "=r"(b[0][1]), "=r"(b[0][2]), "=r"(b[0][3]), "=r"(b[1][0]), "=r"(b[1][1]), "=r"(b[1][2]), "=r"(b[1][3]),
          "=r"(b[2][0]), "=r"(b[2][1]), "=r"(b[2][2]), "=r"(b[2][3]), "=r"(b[3][0]), "=r"(b[3][1]), "=r"(b[3][2]), "=r"(b[3][3]) : "r"(a) : "memory");
}
template<int ID> __device__ __forceinline__ void sched_fence(uint32_t never) { while (never == 0x7fffff00u + ID) { asm volatile("nanosleep.u32 64;" ::: "memory"); } }
__device__ __forceinline__ uint32_t opaque_u() { uint32_t v; asm volatile("mov.u32 %0, %%nsmid;" : "=r"(v)); return v; }
__device__ __forceinline__ uint32_t bar_red_or(int id, int n, uint32_t v) {
    uint32_t r; asm volatile("{\n.reg .pred p, q;\nsetp.ne.u32 p, %3, 0;\nbar.red.or.pred q, %1, %2, p;\nselp.u32 %0, 1, 0, q;\n}\n" : "=r"(r) : "r"(id), "r"(n), "r"(v) : "memory"); return r;
}
template<class T> __device__ __forceinline__ T* launder_p(T* p) { asm volatile("" : "+l"(p)); return p; }
__device__ __forceinline__ uint32_t mapa_u32(uint32_t addr, uint32_t rank) { uint32_t d; asm("mapa.shared::cluster.u32 %0, %1, %2;" : "=r"(d) : "r"(addr), "r"(rank)); return d; }
__device__ __forceinline__ uint32_t mapa_v(uint32_t addr, uint32_t rank) { uint32_t d; asm volatile("mapa.shared::cluster.u32 %0, %1, %2;" : "=r"(d) : "r"(addr), "r"(rank)); return d; }
__device__ __forceinline__ void st_async32(uint32_t addr, uint32_t v, uint32_t mbar) { asm volatile("st.async.shared::cluster.mbarrier::complete_tx::bytes.u32 [%0], %1, [%2];" :: "r"(addr), "r"(v), "r"(mbar) : "memory"); }
__device__ __forceinline__ void cluster_arrive() { asm volatile("barrier.cluster.arrive.release.aligned;" ::: "memory"); }
__device__ __forceinline__ void cluster_wait() { asm volatile("barrier.cluster.wait.acquire.aligned;" ::: "memory"); }
__device__ __forceinline__ void cp_async16(uint32_t dst, const void* src) { asm volatile("cp.async.cg.shared.global [%0], [%1], 16;" :: "r"(dst), "l"(src) : "memory"); }
__device__ __forceinline__ void cp_async_commit() { asm volatile("cp.async.commit_group;" ::: "memory"); }
template<int N> __device__ __forceinline__ void cp_async_wait() { asm volatile("cp.async.wait_group %0;" :: "n"(N) : "memory"); }
__device__ __forceinline__ void cp_async_wait0() { asm volatile("cp.async.wait_group 0;" ::: "memory"); }
__device__ __forceinline__ void mbar_init(uint32_t a, uint32_t cnt) { asm volatile("mbarrier.init.shared.b64 [%0], %1;" :: "r"(a), "r"(cnt) : "memory"); }
__device__ __forceinline__ void mbar_expect_tx(uint32_t a, uint32_t bytes) { asm volatile("mbarrier.arrive.expect_tx.shared.b64 _, [%0], %1;" :: "r"(a), "r"(bytes) : "memory"); }
__device__ __forceinline__ bool mbar_try(uint32_t a, uint32_t parity) {
    uint32_t ok; asm volatile("{\n.reg .pred p;\nmbarrier.try_wait.parity.shared::cta.b64 p, [%1], %2;\nselp.u32 %0, 1, 0, p;\n}\n" : "=r"(ok) : "r"(a), "r"(parity) : "memory"); return ok;
}
__device__ __forceinline__ void mbar_wait(uint32_t a, uint32_t parity) { int it = 0; bool more; do { more = ++it < SPIN_LIMIT; } while (!mbar_try(a, parity) && more); }
__device__ __forceinline__ void bar_sync(int id, int n) { asm volatile("bar.sync %0, %1;" :: "r"(id), "r"(n) : "memory"); }
__device__ __forceinline__ void bar_arrive(int id, int n) { asm volatile("bar.arrive %0, %1;" :: "r"(id), "r"(n) : "memory"); }
__device__ __forceinline__ void fence_async_smem() { asm volatile("fence.proxy.async.shared::cta;" ::: "memory"); }
__device__ __forceinline__ void sts32(uint32_t a, uint32_t v) { asm volatile("st.shared.u32 [%0], %1;" :: "r"(a), "r"(v) : "memory"); }
__device__ __forceinline__ void sts128(uint32_t a, uint4 v) { asm volatile("st.shared.v4.u32 [%0], {%1,%2,%3,%4};" :: "r"(a), "r"(v.x), "r"(v.y), "r"(v.z), "r"(v.w) : "memory"); }
__device__ __forceinline__ uint4 lds128(uint32_t a) { uint4 v; asm volatile("ld.shared.v4.u32 {%0,%1,%2,%3}, [%4];" : "=r"(v.x), "=r"(v.y), "=r"(v.z), "=r"(v.w) : "r"(a) : "memory"); return v; }
__device__ __forceinline__ uint32_t lds32(uint32_t a) { uint32_t v; asm volatile("ld.shared.u32 %0, [%1];" : "=r"(v) : "r"(a) : "memory"); return v; }
__device__ __forceinline__ uint32_t gtime_lo() { uint32_t t; asm volatile("mov.u32 %0, %globaltimer_lo;" : "=r"(t)); return t; }
__device__ __forceinline__ void wait_gtime(uint32_t tg) {
    asm volatile("{\n.reg .pred p, q;\n.reg .b64 t;\n.reg .b32 lo, hi, d, n;\nmov.b32 n, 300;\n"
                 "WG_%=:\nmov.u64 t, %%globaltimer;\nmov.b64 {lo, hi}, t;\nsub.s32 d, lo, %0;\nsub.s32 n, n, 1;\n"
                 "setp.gt.s32 q, n, 0;\nsetp.lt.and.s32 p, d, 0, q;\n@p bra.uni WG_%=;\n}\n" :: "r"(tg) : "memory");
}
__device__ __forceinline__ void delay_clk(int d) { uint32_t t0 = clock(); while ((int)(clock() - t0) < d) {} }

__device__ __forceinline__ uint64_t desc128(uint32_t addr) {
    return (uint64_t)((addr & 0x3FFFF) >> 4) | ((uint64_t)1 << 16) | ((uint64_t)64 << 32) | ((uint64_t)1 << 62);
}
template<int accum> __device__ __forceinline__ void wgmma_n32(float (&d)[16], const uint32_t (&a)[4], uint64_t desc) {
    if (accum) {
        asm volatile("{\n.reg .pred p;\nsetp.ne.b32 p, 1, 0;\n"
            "wgmma.mma_async.sync.aligned.m64n32k16.f32.bf16.bf16 {%0,%1,%2,%3,%4,%5,%6,%7,%8,%9,%10,%11,%12,%13,%14,%15}, {%16,%17,%18,%19}, %20, p, 1, 1, 0;\n}\n"
            : "+f"(d[0]), "+f"(d[1]), "+f"(d[2]), "+f"(d[3]), "+f"(d[4]), "+f"(d[5]), "+f"(d[6]), "+f"(d[7]),
              "+f"(d[8]), "+f"(d[9]), "+f"(d[10]), "+f"(d[11]), "+f"(d[12]), "+f"(d[13]), "+f"(d[14]), "+f"(d[15])
            : "r"(a[0]), "r"(a[1]), "r"(a[2]), "r"(a[3]), "l"(desc));
    } else {
        asm volatile("{\n.reg .pred p;\nsetp.ne.b32 p, 0, 0;\n"
            "wgmma.mma_async.sync.aligned.m64n32k16.f32.bf16.bf16 {%0,%1,%2,%3,%4,%5,%6,%7,%8,%9,%10,%11,%12,%13,%14,%15}, {%16,%17,%18,%19}, %20, p, 1, 1, 0;\n}\n"
            : "=f"(d[0]), "=f"(d[1]), "=f"(d[2]), "=f"(d[3]), "=f"(d[4]), "=f"(d[5]), "=f"(d[6]), "=f"(d[7]),
              "=f"(d[8]), "=f"(d[9]), "=f"(d[10]), "=f"(d[11]), "=f"(d[12]), "=f"(d[13]), "=f"(d[14]), "=f"(d[15])
            : "r"(a[0]), "r"(a[1]), "r"(a[2]), "r"(a[3]), "l"(desc));
    }
}
__device__ __forceinline__ float rcp_approx(float x) { float r; asm("rcp.approx.ftz.f32 %0, %1;" : "=f"(r) : "f"(x)); return r; }
__device__ __forceinline__ void wg_fence() { asm volatile("wgmma.fence.sync.aligned;" ::: "memory"); }
__device__ __forceinline__ void wg_commit() { asm volatile("wgmma.commit_group.sync.aligned;" ::: "memory"); }
__device__ __forceinline__ void wg_wait0() { asm volatile("wgmma.wait_group.sync.aligned 0;" ::: "memory"); }

#define SCALE_HI 0x3db53db5u
#define SCALE_LO 0x371e371eu
#define LOG2E 1.4426950408889634f
#define NEG_BIG2 0xce6ece6eu
__device__ __forceinline__ uint32_t scale_bf2(uint32_t x) {
    uint32_t t, r;
    asm("mul.rn.bf16x2 %0, %1, %2;" : "=r"(t) : "r"(x), "r"(SCALE_LO));
    asm("fma.rn.bf16x2 %0, %1, %2, %3;" : "=r"(r) : "r"(x), "r"(SCALE_HI), "r"(t));
    return r;
}
__device__ __forceinline__ void cluster_arrive_rx() { asm volatile("barrier.cluster.arrive.relaxed.aligned;" ::: "memory"); }
__device__ __forceinline__ uint32_t launder(uint32_t x) { asm volatile("" : "+r"(x)); return x; }
__device__ __forceinline__ void mbar_arrive(uint32_t a) { asm volatile("mbarrier.arrive.shared.b64 _, [%0];" :: "r"(a) : "memory"); }
__device__ __forceinline__ void mbar_wait_cl(uint32_t a, uint32_t parity) {
    int it = 0; uint32_t ok;
    do { asm volatile("{\n.reg .pred p;\nmbarrier.try_wait.parity.acquire.cluster.shared::cta.b64 p, [%1], %2;\nselp.u32 %0, 1, 0, p;\n}\n" : "=r"(ok) : "r"(a), "r"(parity) : "memory"); } while (!ok && ++it < SPIN_LIMIT);
}
__device__ __forceinline__ uint64_t desc_from(uint32_t lo) { return (uint64_t)lo | ((uint64_t)0x40000040u << 32); }
#define SB_OFF 1024u
#define DESC_LO(off) ((((SB_OFF + (uint32_t)(off)) & 0x3FFFFu) >> 4) | 0x10000u)
template<int N> struct ic { static constexpr int value = N; };
__device__ __forceinline__ uint32_t uni(uint32_t x) { return __shfl_sync(0xffffffffu, x, 0); }

__device__ __forceinline__ uint32_t pack_f16(float lo, float hi) { uint32_t r; asm("cvt.rn.f16x2.f32 %0, %1, %2;" : "=r"(r) : "f"(hi), "f"(lo)); return r; }
__device__ __forceinline__ void sts16(uint32_t a, uint16_t v) { asm volatile("st.shared.u16 [%0], %1;" :: "r"(a), "h"(v) : "memory"); }
__device__ __forceinline__ void sts64(uint32_t a, uint32_t x, uint32_t y) { asm volatile("st.shared.v2.u32 [%0], {%1,%2};" :: "r"(a), "r"(x), "r"(y) : "memory"); }
__device__ __forceinline__ void ld_relaxed32_p(uint32_t& v, const void* p, uint32_t pred) {
    asm volatile("{\n.reg .pred p;\nsetp.ne.u32 p, %2, 0;\n@p ld.relaxed.gpu.global.u32 %0, [%1];\n}\n" : "+r"(v) : "l"(p), "r"(pred) : "memory");
}
__device__ __forceinline__ uint2 lds64(uint32_t a) { uint2 v; asm volatile("ld.shared.v2.u32 {%0,%1}, [%2];" : "=r"(v.x), "=r"(v.y) : "r"(a) : "memory"); return v; }
__device__ __forceinline__ void mbar_wait2(uint32_t a, uint32_t pa, uint32_t b, uint32_t pb) {
    int it = 0; uint32_t ok;
    do { asm volatile("{\n.reg .pred p, q;\nmbarrier.try_wait.parity.shared::cta.b64 p, [%1], %2;\nmbarrier.try_wait.parity.shared::cta.b64 q, [%3], %4;\nand.pred p, p, q;\nselp.u32 %0, 1, 0, p;\n}\n"
                      : "=r"(ok) : "r"(a), "r"(pa), "r"(b), "r"(pb) : "memory"); } while (!ok && ++it < SPIN_LIMIT);
}
__device__ __forceinline__ float exd(float s, float m) { return ex2(__fmul_rn(__fsub_rn(s, m), LOG2E)); }
__device__ __forceinline__ uint32_t gtime_after(uint32_t z) {
    uint32_t t = 0; asm volatile("{\n.reg .pred p;\nsetp.eq.u32 p, %1, 0;\n@p mov.u32 %0, %%globaltimer_lo;\n}\n" : "+r"(t) : "r"(z)); return t;
}
#define T_HOLD 0
#define T_KPRE 3
#define BLK_Q(p) (((p) < 3 ? (p) : 8) * 2048)
#define BLK_K(p) (((p) < 3 ? 4 + (p) : 9) * 2048)
#define BLK_V(p) (((p) < 2 ? 3 + 4 * (p) : 8 + (p)) * 2048)
__device__ __forceinline__ uint32_t exp_bf2(uint32_t s) { return pack_bf16(ex2(bf_lo(s) * LOG2E), ex2(bf_hi(s) * LOG2E)); }
template<int MT, int LO, int HI>
__device__ __forceinline__ void tok_loadv(uint32_t tok, int eh, int lane, uint32_t (&bv)[8][4]) {
    const int r8 = lane & 7;
    const uint32_t va = MT ? tok + lane * 64 + ((r8 >> 1) << 4) : tok + (lane & 15) * 64 + (((lane >> 4) ^ (r8 >> 1)) << 4);
    const uint32_t o0 = eh ? BLK_V(2) : BLK_V(0), o1 = eh ? BLK_V(3) : BLK_V(1);
    #pragma unroll
    for (int n = LO; n < HI; n++) { if (MT) ldsm_x4_t(bv[n], (va ^ ((n & 3) << 4)) + (n < 4 ? o0 : o1)); else ldsm_x4_t(bv[n], (va ^ ((n & 1) << 5)) + BLK_V(n >> 1)); }
}
#define T_VPRE 4
template<int MT, class F>
__device__ __forceinline__ void tok_part1(uint32_t tok, int eh, int lane, uint32_t (&q)[8][4], uint32_t (&sp)[5][2], uint32_t (&pa)[5][2], uint32_t (&bv)[8][4], uint32_t& rng, F&& hold) {
    float e[5][4];
    constexpr int NK = MT ? 5 : 3;
    const int g = lane >> 2, t = lane & 3, mi = lane >> 3, r8 = lane & 7;
    #pragma unroll
    for (int nt = 1; nt < NK; nt++) { e[nt][0] = e[nt][1] = e[nt][2] = e[nt][3] = 0.f; }
    const uint32_t qa = tok + (16 * MT + (mi & 1) * 8 + r8) * 64 + (((mi >> 1) ^ (r8 >> 1)) << 4);
    const uint32_t ka = tok + r8 * 64 + ((mi ^ (r8 >> 1)) << 4);
    uint32_t b[4][NK][4];
    constexpr int PRE = T_HOLD == 3 ? (MT ? T_KPRE : 4) : 0;
    #pragma unroll
    for (int k2 = 0; k2 < 4; k2++) {
        if (T_HOLD == 3) { ldsm_x4(q[2 * k2], qa + BLK_Q(k2)); ldsm_x4(q[2 * k2 + 1], (qa ^ 32) + BLK_Q(k2)); }
        if (k2 < PRE) {
            #pragma unroll
            for (int nt = 1; nt < NK; nt++) ldsm_x4(b[k2][nt], ka + BLK_K(k2) + (nt - 1) * 512);
        }
    }
    if (T_HOLD == 3) hold();
    #pragma unroll
    for (int k2 = 0; k2 < 4; k2++) {
        if (T_HOLD != 3) { ldsm_x4(q[2 * k2], qa + BLK_Q(k2)); ldsm_x4(q[2 * k2 + 1], (qa ^ 32) + BLK_Q(k2)); }
        if (k2 >= PRE) {
            #pragma unroll
            for (int nt = 1; nt < NK; nt++) ldsm_x4(b[k2][nt], ka + BLK_K(k2) + (nt - 1) * 512);
        }
        #pragma unroll
        for (int nt = 1; nt < NK; nt++) mma16816(e[nt], q[2 * k2], b[k2][nt][0], b[k2][nt][1]);
        #pragma unroll
        for (int nt = 1; nt < NK; nt++) mma16816(e[nt], q[2 * k2 + 1], b[k2][nt][2], b[k2][nt][3]);
    }
    #pragma unroll
    for (int nt = 1; nt < NK; nt++) asm volatile("" : "+f"(e[nt][0]), "+f"(e[nt][1]), "+f"(e[nt][2]), "+f"(e[nt][3]));
    if (T_HOLD != 3) hold();
    #pragma unroll
    for (int nt = 1; nt < NK; nt++) {
        sp[nt][0] = nt < NK - 1 ? scale_bf2(pack_bf16(e[nt][0], e[nt][1])) : NEG_BIG2; sp[nt][1] = scale_bf2(pack_bf16(e[nt][2], e[nt][3]));
        rng = maxabs_bf2(nt == 1 ? sp[1][0] : (nt < NK - 1 ? maxabs_bf2(rng, sp[nt][0]) : rng), sp[nt][1]);
    }
    const uint32_t keep = (2 * t <= g ? 0x0000ffffu : 0u) | (2 * t + 1 <= g ? 0xffff0000u : 0u);
    sp[NK - 2][0] = (sp[NK - 2][0] & keep) | (NEG_BIG2 & ~keep);
    sp[NK - 1][1] = (sp[NK - 1][1] & keep) | (NEG_BIG2 & ~keep);
    #pragma unroll
    for (int nt = 1; nt < NK; nt++) { pa[nt][0] = nt < NK - 1 ? exp_bf2(sp[nt][0]) : 0u; pa[nt][1] = exp_bf2(sp[nt][1]); }
    tok_loadv<MT, 0, MT ? T_VPRE : 8>(tok, eh, lane, bv);
}
template<int MT, class F, class G, class H, class I>
__device__ __forceinline__ void tok_part2(uint32_t tok, uint32_t exl, uint32_t ost, int eh, int lane, const uint32_t (&q)[8][4], uint32_t (&sp)[5][2], uint32_t (&pa)[5][2], uint32_t (&bv)[8][4], uint32_t rng, bool vb,
                                          F&& wait_v, G&& duty, H&& pace, I&& wait_x) {
    constexpr int NK = MT ? 5 : 3;
    const int mi = lane >> 3, r8 = lane & 7;
    {
        float c[4][4];
        uint32_t b[4][4];
        ldsm16_t(b, exl + 2048);
        duty();
        #pragma unroll
        for (int j = 0; j < 4; j++) { c[j][0] = c[j][1] = c[j][2] = c[j][3] = 0.f; }
        #pragma unroll
        for (int k2 = 0; k2 < 4; k2++) { mma16816(c[(2 * k2) & 3], q[2 * k2], b[k2][0], b[k2][1]); mma16816(c[(2 * k2 + 1) & 3], q[2 * k2 + 1], b[k2][2], b[k2][3]); }
        sp[0][0] = scale_bf2(pack_bf16((c[0][0] + c[1][0]) + (c[2][0] + c[3][0]), (c[0][1] + c[1][1]) + (c[2][1] + c[3][1])));
        sp[0][1] = scale_bf2(pack_bf16((c[0][2] + c[1][2]) + (c[2][2] + c[3][2]), (c[0][3] + c[1][3]) + (c[2][3] + c[3][3])));
    }
    pa[0][0] = exp_bf2(sp[0][0]); pa[0][1] = exp_bf2(sp[0][1]);
    rng = maxabs_bf2(maxabs_bf2(rng, sp[0][0]), sp[0][1]);
    if (__builtin_expect(__any_sync(0xffffffffu, ((rng & 0x7fff7fffu) + 0x3ddf3ddfu) & 0x80008000u), 0)) {
        uint32_t m0 = sp[0][0], m1 = sp[0][1];
        #pragma unroll
        for (int nt = 1; nt < NK; nt++) { if (nt < NK - 1) m0 = max_bf2(m0, sp[nt][0]); m1 = max_bf2(m1, sp[nt][1]); }
        uint32_t mm = max_bf2(__byte_perm(m0, m1, 0x5410), __byte_perm(m0, m1, 0x7632));
        mm = max_bf2(mm, __shfl_xor_sync(0xffffffffu, mm, 1));
        mm = max_bf2(mm, __shfl_xor_sync(0xffffffffu, mm, 2));
        #pragma unroll
        for (int nt = 0; nt < NK; nt++) {
            if (nt < NK - 1) pa[nt][0] = pack_bf16(exd(bf_lo(sp[nt][0]), bf_lo(mm)), exd(bf_hi(sp[nt][0]), bf_lo(mm)));
            pa[nt][1] = pack_bf16(exd(bf_lo(sp[nt][1]), bf_hi(mm)), exd(bf_hi(sp[nt][1]), bf_hi(mm)));
        }
    }
    tok_loadv<MT, MT ? T_VPRE : 8, 8>(tok, eh, lane, bv);
    wait_v();
    constexpr int NQ = MT ? 2 : 4;
    float o[NQ][4][4], l[4] = {0.f, 0.f, 0.f, 0.f};
    const uint32_t ONE = 0x3F803F80u;
    mma16816r(l, pa[1][0], pa[1][1], pa[2][0], pa[2][1], ONE, ONE);
    if (MT) mma16816r(l, pa[3 % NK][0], pa[3 % NK][1], pa[4 % NK][0], pa[4 % NK][1], ONE, ONE);
    mma1688(l, pa[0][0], pa[0][1], ONE);
    #pragma unroll
    for (int j = 0; j < NQ; j++) {
        uint32_t bm[4];
        ldsm_x4(bm, exl + 4096 + (MT ? eh * 1024 : 0) + 512 * j);
        #pragma unroll
        for (int n = 0; n < 4; n++) {
            o[j][n][0] = o[j][n][1] = o[j][n][2] = o[j][n][3] = 0.f;
            if (MT) mma16816r(o[j][n], pa[1][0], pa[1][1], pa[2][0], pa[2][1], bv[4 * j + n][0], bv[4 * j + n][1]);
            else mma16816r(o[j][n], pa[1][0], pa[1][1], pa[2][0], pa[2][1], bv[2 * j + (n >> 1)][2 * (n & 1)], bv[2 * j + (n >> 1)][2 * (n & 1) + 1]);
        }
        if (MT) {
            #pragma unroll
            for (int n = 0; n < 4; n++) mma16816r(o[j][n], pa[3 % NK][0], pa[3 % NK][1], pa[4 % NK][0], pa[4 % NK][1], bv[4 * j + n][2], bv[4 * j + n][3]);
        }
        #pragma unroll
        for (int n = 0; n < 4; n++) mma1688(o[j][n], pa[0][0], pa[0][1], bm[n]);
    }
    #pragma unroll
    for (int j = 0; j < NQ; j++) asm volatile("" : "+f"(o[j][0][0]), "+f"(o[j][1][0]), "+f"(o[j][2][0]), "+f"(o[j][3][0]));
    asm volatile("" : "+f"(l[0]), "+f"(l[2]));
    wait_x();
    bar_arrive_p(12, 384, !vb);
    pace();
    const float i0 = rcp_approx(l[0]), i1 = rcp_approx(l[2]);
    const uint32_t oa = ost + ((mi & 1) * 8 + r8) * 128 + (((mi >> 1) ^ r8) << 4);
    #pragma unroll
    for (int j = 0; j < NQ; j++) {
        stsm_x4((oa ^ ((j & 1) << 6)) + (j >> 1) * 2048, pack_bf16(o[j][0][0] * i0, o[j][0][1] * i0), pack_bf16(o[j][0][2] * i1, o[j][0][3] * i1), pack_bf16(o[j][1][0] * i0, o[j][1][1] * i0), pack_bf16(o[j][1][2] * i1, o[j][1][3] * i1));
        stsm_x4((oa ^ (((j & 1) << 6) | 32)) + (j >> 1) * 2048, pack_bf16(o[j][2][0] * i0, o[j][2][1] * i0), pack_bf16(o[j][2][2] * i1, o[j][2][3] * i1), pack_bf16(o[j][3][0] * i0, o[j][3][1] * i0), pack_bf16(o[j][3][2] * i1, o[j][3][3] * i1));
    }
}

#define SEND_LANE(ll) ((ll) >> 2)
#define TP_E 0
#define V_EARLY 1
#ifndef M_SF
#define M_SF 0
#endif
#ifndef M_F2
#define M_F2 0
#endif
#ifndef M_FENCE
#define M_FENCE 0
#endif
#define SW_FENCE 0
#define PV_FENCE 1
#define IL_AT 3
#define TAIL 0
#define MP_PRE 4
#define VF_EARLY 1
__device__ __forceinline__ void stsm2_p(uint32_t a, const uint32_t (&v)[8], uint32_t skip) {
    asm volatile("{\n.reg .pred p;\nsetp.eq.u32 p, %9, 0;\n@p stmatrix.sync.aligned.m8n8.x4.trans.shared.b16 [%0], {%1,%2,%3,%4};\n"
                 "@p stmatrix.sync.aligned.m8n8.x4.trans.shared.b16 [%0+1024], {%5,%6,%7,%8};\n}\n"
        :: "r"(a), "r"(v[0]), "r"(v[1]), "r"(v[2]), "r"(v[3]), "r"(v[4]), "r"(v[5]), "r"(v[6]), "r"(v[7]), "r"(skip) : "memory");
}
template<int OA, int OB>
__device__ __forceinline__ void send_tile(float c0, float c1, float c2, float c3, uint32_t a, uint32_t b, uint32_t l16) {
    const uint32_t hi = (uint32_t)((uint64_t)g_acc >> 32);
    asm volatile("{\n.reg .pred q, pl, ph;\n.reg .b64 pa, pb;\n.reg .b32 t, w0, w1, w2;\n.reg .f32 x, y, z;\n"
                 "and.b32 t, %7, 0x30;\nsetp.eq.u32 q, t, 0;\nand.b32 t, %7, 0x70;\nsetp.eq.u32 ph, t, 0;\nxor.pred pl, q, ph;\n"
                 "selp.f32 x, 0f00010000, %4, pl;\nselp.f32 y, 0f00010000, %6, ph;\nselp.f32 z, %6, %4, ph;\n"
                 "cvt.rn.bf16x2.f32 w0, x, %3;\ncvt.rn.bf16x2.f32 w1, y, %5;\ncvt.rn.bf16x2.f32 w2, 0f00010000, z;\n"
                 "mov.b64 pa, {%0, %2};\nmov.b64 pb, {%1, %2};\n"
                 "red.relaxed.gpu.global.add.noftz.bf16x2 [pa+%8], w0;\nred.relaxed.gpu.global.add.noftz.bf16x2 [pa+%10], w1;\n@q red.relaxed.gpu.global.add.noftz.bf16x2 [pb+%9], w2;\n}\n"
        :: "r"(a), "r"(b), "r"(hi), "f"(c0), "f"(c1), "f"(c2), "f"(c3), "r"(l16), "n"(OA), "n"(OB), "n"(OA + 256) : "memory");
}
__device__ __forceinline__ uint32_t send_ua(uint32_t tile) { return (uint32_t)(uint64_t)g_acc + tile * 1024; }
__device__ __forceinline__ uint32_t send_ub(uint32_t tile) { return (uint32_t)(uint64_t)g_acc + ACC_X + (tile >> 1) * 1024 + (tile & 1) * 256; }
__device__ __forceinline__ void lds_il(float& il, float& ih, uint32_t a) {
    uint32_t x, y; asm volatile("ldmatrix.sync.aligned.m8n8.x2.shared.b16 {%0,%1}, [%2];" : "=r"(x), "=r"(y) : "r"(a) : "memory");
    il = __uint_as_float(x); ih = __uint_as_float(y);
}
template<bool OWN, class F>
__device__ __forceinline__ void stage_w(const uint32_t (&wo)[8][4], uint32_t ol, uint32_t tile, uint32_t so, uint32_t l16, uint32_t nv, uint32_t ila, float il, float ih, F&& issued) {
    uint32_t b[4][4], sa, sb_, ll;
    float c[2][4];
    auto addr = [&] {
        ll = OWN ? l16 : l16 | (__float_as_uint(c[0][0]) & nv);
        sa = SEND_LANE(ll) + (send_ua(tile) + so); sb_ = (ll >> 4) + (send_ub(tile) + so);
    };
    bar_sync(11, 352);
    ldsm16_t(b, ol);
    if (!OWN) lds_il(il, ih, ila);
    if (OWN) addr();
    if (!OWN || SW_FENCE) sched_fence<0>(nv);
    #pragma unroll
    for (int i = 0; i < 2; i++) c[i][0] = c[i][1] = c[i][2] = c[i][3] = 0.f;
    #pragma unroll
    for (int j = 0; j < 4; j++) {
        if (!OWN && j == 3) addr();
        mma16816(c[0], wo[2 * j], b[j][0], b[j][1]); mma16816(c[1], wo[2 * j + 1], b[j][2], b[j][3]);
    }
    if (TP_E || (OWN && V_EARLY)) { asm volatile("" : "+f"(c[0][0]), "+f"(c[1][0])); sched_fence<OWN ? 4 : 5>(nv); }
    issued();
    send_tile<0, 0>((c[0][0] + c[1][0]) * il, (c[0][1] + c[1][1]) * ih, (c[0][2] + c[1][2]) * il, (c[0][3] + c[1][3]) * ih, sa, sb_, l16);
}

template<int N> __device__ __forceinline__ void code_pad(uint32_t nv) {
    if (N && nv == 0x7fffffe0u + N % 16) {
        float v = __uint_as_float(nv);
        #pragma unroll
        for (int i = 0; i < N; i++) asm volatile("fma.rn.f32 %0, %0, %0, %0;" : "+f"(v));
        sts32_p(0u, __float_as_uint(v), nv);
    }
}
#define PAD_T0 0
#define PAD_T1 0
#define PAD_S 0
#define PAD_P 0
#define BAR_PRO 1
#define BAR_MEM 2
#define BAR_P   3
#define BAR_PRJ 4
#define BAR_VGO 7
#define BAR_X0  7
#define BAR_S   9
#define BAR_P2  10
#define BAR_O   11
#define BAR_O2  14
#define BAR_TP  15
#define BAR_V   12
#define BAR_FB  13
#define VGO_AT 9
#define TP_N 36
#define TP_N1 24
#define REG_P 200
#define W_FENCE 1
#define WO_PRE 4
#define WO_MID 8
#define WO_EX 8
#define WO_REP 2
#define TP_DELAY 0
#define PRE_W 4
#ifndef M_RES
#define M_RES 5
#endif
#define K_PRE 6
#define K_POS 0
#define LD_FENCE 0
#define CV_FENCE 4
#define ANN_POS 3
#define PRO_V 0
#define PUB_W 0
#define ST_AT 4
#define MEM_N 352
#define VGO_N (256 + (T_HOLD == 2 ? 32 : 0) + (TAIL ? 32 : 0))
#define PRO_N ((PRO_V ? 256 : 32 * nqk) + (K_PRE < 8 ? 64 : 0) + ((T_HOLD & 1) ? 32 : 0))
#define S_DUTY 0
#define X_POS 1
#define K_OWN 1
#define TM_PF 1
#define TS_CAP 64
#define G1_MIN 128
#define G1_0 256
#define G1_NS 1216

__global__ void __cluster_dims__(3, 1, 1) __launch_bounds__(CH_THREADS, 1)
chain_kernel(const __grid_constant__ CUtensorMap tmx, const __grid_constant__ CUtensorMap tmq, const __grid_constant__ CUtensorMap tmk,
             const __grid_constant__ CUtensorMap tmv, const __grid_constant__ CUtensorMap tmo, const bf16* __restrict__ mem0, const uint32_t nv_) {
    extern __shared__ __align__(1024) unsigned char smem[];
    const uint32_t sb = smem_u32(smem);
    const int tid = threadIdx.x, lane = tid & 31;
    const int warp = __shfl_sync(0xffffffffu, tid >> 5, 0);
    const uint32_t nv = __shfl_sync(0xffffffffu, nv_ * tid, 0);
    const int h = blockIdx.x / 3, r = blockIdx.x % 3;
    const int mi = lane >> 3, r8 = lane & 7;
    const uint32_t bX = sb + SM_BAR, bTOK = bX + 16, bEX = bX + 40, bW = bX + 64, bEV = bX + 104, bFREE = bX + 32;
    const int nqk = r < 2 ? 6 : 4;
    if ((sb & 0xFFFFFFu) != SB_OFF) __trap();
    asm volatile("griddepcontrol.launch_dependents;");
    if (tid == 0 && blockIdx.x == 0) GT(40, 0);

    auto load_w = [&](int lo, int hi) {
        #pragma unroll 1
        for (int i = lo; i < hi; i++) {
            const int blk = i >> 2, j = i & 3;
            if (i < 48) {
                const int m = r < 2 ? (j < 3 ? r : 2) : (j < 2 ? j : 2), p = r < 2 ? (j < 3 ? j : r) : (j < 2 ? 3 : j);
                asm volatile("cp.async.bulk.tensor.2d.shared::cluster.global.mbarrier::complete_tx::bytes [%0], [%1, {%3, %4}], [%2];"
                    :: "r"(sb + i * 3072), "l"(m == 0 ? &tmq : (m == 1 ? &tmk : &tmv)), "r"(bW + (blk < 3 ? 0 : (blk < 6 ? 8 : (blk < 10 ? 16 : 24)))), "r"(h * DH + p * 32), "r"(blk * 48) : "memory");
            } else asm volatile("cp.async.bulk.tensor.2d.shared::cluster.global.mbarrier::complete_tx::bytes [%0], [%1, {%3, %4}], [%2];"
                :: "r"(sb + SM_WO + (i - 48) * 8192), "l"(&tmo), "r"(bW + 32), "r"(192 * r + 32 * (i - 48)), "r"(h * DH) : "memory");
        }
    };
    if (tid == 352) {
        #pragma unroll
        for (int i = 0; i < 15; i++) mbar_init(bX + 8 * i, (i == 5 || i == 6) ? 1 + nqk : (i >= 13 ? 9 - nqk : 1));
        asm volatile("fence.mbarrier_init.release.cluster;" ::: "memory");
        mbar_expect_tx(bW, 36864); mbar_expect_tx(bW + 8, 36864); mbar_expect_tx(bW + 16, 49152); mbar_expect_tx(bW + 24, 24576); mbar_expect_tx(bW + 32, 49152);
        load_w(0, 2 * PRE_W);
    }
    if (TM_PF && tid < 2) asm volatile("prefetch.param.tensormap [%0];" :: "l"(__cvta_generic_to_grid_constant(tid ? &tmo : &tmx)) : "memory");
    const unsigned epoch = ld_relaxed32(&g_epoch);
    __syncthreads();
    const uint32_t pw0 = ((mi >> 1) * 8 + r8) * 64 + (((2 * (warp & 1) + (mi & 1)) ^ (r8 >> 1)) << 4);
    auto tok_publish = [&](int tb, int k) {
        const uint32_t src = sb + SM_TOK + tb * TOKBUF + r * 8192, bar = bTOK + 8 * tb;
        if (k == 1) asm volatile("{\n.reg .pred p;\nelect.sync _|p, 0xffffffff;\n@p mbarrier.arrive.expect_tx.shared.b64 _, [%0], 16384;\n}\n" :: "r"(bar) : "memory");
        asm volatile("{\n.reg .pred p;\nelect.sync _|p, 0xffffffff;\n"
                     "@p cp.async.bulk.shared::cluster.shared::cta.mbarrier::complete_tx::bytes [%0], [%1], 8192, [%2];\n}\n"
            :: "r"(mapa_u32(src, (r + k) % 3)), "r"(src), "r"(mapa_u32(bar, (r + k) % 3)) : "memory");
    };
    if (warp < 8) {
        asm volatile("setmaxnreg.inc.sync.aligned.u32 %0;" :: "n"(REG_P));
        uint32_t wf[36][4];
        const uint32_t wl = sb + (warp >> 1) * 3072 + pw0;
        float ta0[16], ta1[16];
        auto tp_part = [&](auto lo, auto hi) {
            wg_fence();
            #pragma unroll
            for (int i = lo.value; i < hi.value; i++) {
                if (i == 0) wgmma_n32<0>(ta0, wf[0], desc_from(DESC_LO(SM_X))); else wgmma_n32<1>(ta0, wf[i], desc_from(DESC_LO(SM_X) + (i >> 2) * 256 + (i & 3) * 2));
            }
            #pragma unroll
            for (int i = lo.value; i < hi.value; i++) {
                if (i == 0) wgmma_n32<0>(ta1, wf[0], desc_from(DESC_LO(SM_X + XBUF))); else wgmma_n32<1>(ta1, wf[i], desc_from(DESC_LO(SM_X + XBUF) + (i >> 2) * 256 + (i & 3) * 2));
            }
            wg_commit();
        };
        if (tid == 32) load_w(2 * PRE_W, 40);
        if (tid == 0) GT(41 + blockIdx.x % 3, 7);
        code_pad<PAD_P>(nv);
        mbar_wait(bW, 0);
        #pragma unroll
        for (int i = 0; i < 9; i++) ldsm_x4_t(wf[i], wl + (i / 3) * 12288 + (i % 3) * 1024);
        fence_async_smem(); bar_arrive(BAR_X0, 288);
        mbar_wait(bW + 8, 0);
        #pragma unroll
        for (int i = 9; i < 18; i++) ldsm_x4_t(wf[i], wl + (i / 3) * 12288 + (i % 3) * 1024);
        fence_async_smem(); bar_arrive(BAR_X0 + 1, 288);
        mbar_wait(bX, 0); mbar_wait(bX + 8, 0);
        tp_part(ic<0>(), ic<18>());
        wg_wait0();
        sts128(sb + SM_OST + tid * 16, make_uint4(wf[0][0], wf[0][1], wf[0][2], wf[0][3]));
        mbar_wait(bW + 16, 0);
        #pragma unroll
        for (int i = 18; i < 30; i++) ldsm_x4_t(wf[i], wl + (i / 3) * 12288 + (i % 3) * 1024);
        tp_part(ic<18>(), ic<30>());
        mbar_wait(bW + 24, 0);
        if (tid == 0) GT(41 + blockIdx.x % 3, 0);
        wg_wait0();
        #pragma unroll
        for (int i = 30; i < 36; i++) ldsm_x4_t(wf[i], wl + (i / 3) * 12288 + (i % 3) * 1024);
        fence_async_smem();
        cluster_arrive_rx();
        tp_part(ic<30>(), ic<36>());
        if (tid == 0) GT(41 + blockIdx.x % 3, 2);
        const uint32_t pw = pin(pw0);
        auto tp_store = [&](const float (&acc)[16], uint32_t off) {
            const uint32_t ta = pw + launder(sb + off + (warp >> 1) * 2048);
            stsm_x4_t(ta, pack_bf16(acc[0], acc[1]), pack_bf16(acc[2], acc[3]), pack_bf16(acc[4], acc[5]), pack_bf16(acc[6], acc[7]));
            stsm_x4_t(ta + 1024, pack_bf16(acc[8], acc[9]), pack_bf16(acc[10], acc[11]), pack_bf16(acc[12], acc[13]), pack_bf16(acc[14], acc[15]));
        };
        cluster_wait();
        wg_wait0();
        tp_store(ta0, SM_TOK + r * 8192);
        if (warp == 0) { bar_sync(BAR_PRJ, 256); fence_async_smem(); tok_publish(0, 1); tok_publish(0, 2); } else bar_arrive(BAR_PRJ, 256);
        if (!TAIL) { tp_store(ta1, SM_TOK + TOKBUF + r * 8192); }
        { const uint4 v = lds128(sb + SM_OST + tid * 16); wf[0][0] = v.x; wf[0][1] = v.y; wf[0][2] = v.z; wf[0][3] = v.w; }
        if (tid == 0) GT(41 + blockIdx.x % 3, 4);
        const uint32_t l16 = pin(lane * 16), sbl = sb + l16, l4w = pin(sb + warp * 256 + lane * 4);
        uint32_t wo[8][4];
        const int exo = r < 2 ? (warp < 6 ? r * 2048 : 4096 + (2 * r - 6) * 256) : (warp < 2 ? 6 * 256 : (warp < 4 ? 2048 + 4 * 256 : 4096));
        const bool isqk = warp < nqk;
        const uint32_t exbar = isqk ? bEX : bEV;
        uint32_t vf[2][4];
        auto prep = [&](int s) {
            const uint32_t va = pw + launder(sb + SM_TOK + (s & 1) * TOKBUF + BLK_V(warp >> 1));
            mbar_wait(bTOK + 8 * (s & 1), (s >> 1) & 1);
            if (VF_EARLY) { ldsm_x4_t(vf[0], va); ldsm_x4_t(vf[1], va + 1024); }
        };
        prep(0);
        for (int s = 0; ; s++) {
            const int par = s & 1;
            const uint32_t va = pw + launder(sb + SM_TOK + par * TOKBUF + BLK_V(warp >> 1)), wa = pw + launder(sb + SM_WO + (warp >> 1) * 8192);
            const uint32_t exu = launder(SM_EX + par * EXBUF);
            {
                float acc[4][4];
                #pragma unroll
                for (int i = 0; i < 4; i++) { acc[i][0] = acc[i][1] = acc[i][2] = acc[i][3] = 0.f; }
                uint32_t b[18][4];
                if (!isqk) { bar_arrive(BAR_MEM, MEM_N); bar_sync(BAR_VGO, VGO_N); } else bar_sync(BAR_MEM, MEM_N);
                #pragma unroll
                for (int i2 = 0; i2 < 18; i2++) {
                    if (!TAIL || i2 >= MP_PRE) ldsm_x4_t(b[i2], sbl + SM_MEM + i2 * 512);
                    if (i2 == VGO_AT) bar_arrive_p(BAR_VGO, VGO_N, !isqk);
                    if (PRO_V && i2 == PRO_V) bar_arrive_p(BAR_PRO, PRO_N, isqk || s == NSEG - 1);
                    mma16816(acc[(2 * i2) & 3], wf[2 * i2], b[i2][0], b[i2][1]);
                    mma16816(acc[(2 * i2 + 1) & 3], wf[2 * i2 + 1], b[i2][2], b[i2][3]);
                }
                float q[4];
                #pragma unroll
                for (int i = 0; i < 4; i++) q[i] = (acc[0][i] + acc[1][i]) + (acc[2][i] + acc[3][i]);
                const uint32_t lo = pack_bf16(q[0], q[1]), hi = pack_bf16(q[2], q[3]);
                const uint32_t exl = l4w + launder(exu + exo), bar = exbar + par * 8;
                #pragma unroll
                for (int k = 1; k < 3; k++) {
                    const uint32_t exd = mapa_u32(exl, (r + k) % 3), exb = mapa_u32(bar, (r + k) % 3);
                    st_async32(exd, lo, exb); st_async32(exd + 128, hi, exb);
                }
                sts32(exl, lo); sts32(exl + 128, hi);
                __syncwarp();
                asm volatile("{\n.reg .pred p;\nelect.sync _|p, 0xffffffff;\n@p mbarrier.arrive.shared.b64 _, [%0];\n}\n" :: "r"(bar) : "memory");
                if (s < NSEG - 1) bar_sync_p(BAR_PRO, PRO_N, !isqk);
            }
            if (s == 0) mbar_wait(bW + 32, 0);
            if (s == NSEG - 1) break;
            {
                if (!VF_EARLY) { ldsm_x4_t(vf[0], va); ldsm_x4_t(vf[1], va + 1024); }
                #pragma unroll
                for (int i = 0; i < WO_PRE; i++) ldsm_x4_t(wo[i], wa + i * 1024);
                if (WO_PRE < 8) {
                    #pragma unroll
                    for (int k = 0; k < WO_REP; k++) mbar_wait(bEX + 8 * par, (s >> 1) & 1);
                    #pragma unroll
                    for (int i = WO_PRE; i < 8; i++) ldsm_x4_t(wo[i], wa + i * 1024);
                }
                mbar_wait(bEV + 8 * par, (s >> 1) & 1);
                const uint32_t vm0 = lds32(l4w + exu + 4096), vm1 = lds32(l4w + exu + 4096 + 128);
                const uint32_t big = bar_red_or(BAR_P, 352, 0u);
                uint32_t pb[4]; ldsm_x4_t(pb, sbl + SM_P);
                uint32_t pm = ldsm_x1_t(sbl + SM_P + 512);
                float o0[4] = {0.f, 0.f, 0.f, 0.f}, o1[4] = {0.f, 0.f, 0.f, 0.f}, o2[4] = {0.f, 0.f, 0.f, 0.f};
                if (__builtin_expect(big, 0)) {
                    bar_sync(BAR_P2, 352);
                    ldsm_x4_t(pb, sbl + SM_P); pm = ldsm_x1_t(sbl + SM_P + 512);
                }
                mma16816(o0, vf[0], pb[0], pb[1]);
                mma16816(o1, vf[1], pb[2], pb[3]);
                mma1688(o2, vm0, vm1, pm);
                uint32_t oa = pm;
                #pragma unroll
                for (int i = 0; i < 8; i++) oa ^= wo[i][0];
                oa = l4w | (oa & nv);
                sts32(oa + SM_O, pack_bf16((o0[0] + o1[0]) + o2[0], (o0[1] + o1[1]) + o2[1]));
                sts32(oa + SM_O + 128, pack_bf16((o0[2] + o1[2]) + o2[2], (o0[3] + o1[3]) + o2[3]));
                const uint32_t xd = uni(DESC_LO(SM_X) + par * (XBUF >> 4));
                auto tp = [&](auto lo, auto hi) {
                    #pragma unroll
                    for (int i = lo.value; i < hi.value; i++) {
                        if (i == 0) wgmma_n32<0>(ta1, wf[0], desc_from(xd));
                        else wgmma_n32<1>(ta1, wf[i], desc_from(xd + (i >> 2) * 256 + (i & 3) * 2));
                    }
                };
                stage_w<false>(wo, sbl + SM_O, 12 * r + warp, SLOT_OFF(s + 1), l16, nv, sbl + SM_IL, 0.f, 0.f, [&] {
                    if (TP_E) { bar_sync(BAR_V, 384); wg_fence(); tp(ic<0>(), ic<TP_E>()); } });
                STAMP(warp);
                if (!TP_E) { bar_sync(BAR_V, 384); wg_fence(); }
                STAMP(12);
                tp(ic<TP_E>(), ic<TP_N>());
                wg_commit();
                prep(s + 1);
                if (!TAIL) { wg_wait0(); tp_store(ta1, SM_TOK + par * TOKBUF + r * 8192); STAMP(13 + (warp >> 2)); }
            }
        }
        cluster_arrive(); cluster_wait();
    } else {
        asm volatile("setmaxnreg.dec.sync.aligned.u32 %0;" :: "n"(504 - 2 * REG_P));
        const int a = warp - 8;
        const uint32_t sbl = sb + lane * 16;
        if (a < 3) {
            const uint32_t zs = 3 * blockIdx.x + (r8 >> 1);
            const uint32_t zoff = (r8 < 6 ? (zs >> 3) * 1024 + ((zs >> 2) & 1) * 256 + (zs & 3) * 32 : ACC_X + (blockIdx.x >> 1) * 1024 + (blockIdx.x & 1) * 256) + (lane & 1) * 16;
            const uint32_t zskip = r8 >= 6 && blockIdx.x >= 36;
            if (a == 1) {
                st_relaxed128_p((uint4*)(g_acc + zoff + SLOT_OFF(mi)), make_uint4(0, 0, 0, 0), zskip);
                __threadfence();
                __syncwarp();
                if (lane == 0) st_relaxed32(&g_init[blockIdx.x], epoch);
            }
            {
                #pragma unroll
                for (int i = 0; i < 6; i++) {
                    const int c = tid - 256 + 96 * i;
                    const unsigned short* m = (const unsigned short*)mem0 + c;
                    uint4 v;
                    v.x = m[0] | ((uint32_t)m[DM] << 16); v.y = m[2 * DM] | ((uint32_t)m[3 * DM] << 16);
                    v.z = m[4 * DM] | ((uint32_t)m[5 * DM] << 16); v.w = m[6 * DM] | ((uint32_t)m[7 * DM] << 16);
                    sts128(sb + SM_MEM + c * 16, v);
                }
                sts32(sb + SM_SG + 36, 0u);
            }
            asm volatile("barrier.cluster.arrive.release.aligned;" ::: "memory");
            { int it = 0; while (__any_sync(0xffffffffu, ld_relaxed32(&g_init[a * 32 + lane]) != epoch) && ++it < SPIN_LIMIT) {} }
            __threadfence();
            const uint32_t kl0 = (a < 2 ? SM_TOK + (16 * a + (mi & 1) * 8 + r8) * 64 + (((mi >> 1) ^ (r8 >> 1)) << 4) : SM_EX + 2048 + ((((mi & 1) << 1) | (mi >> 1)) * 8 + r8) * 16);
            const uint32_t l16 = pin(lane * 16);
            uint32_t kf[8][4], wo[8][4];
            auto load_k = [&](int tb, uint32_t kl, auto lo, auto hi) {
                const uint32_t ka = kl + launder(sb + tb * TOKBUF);
                #pragma unroll
                for (int kk = lo.value; kk < hi.value; kk++) ldsm_x4(kf[kk], (ka ^ ((kk & 1) << 5)) + BLK_K(kk >> 1));
            };
            code_pad<PAD_S>(nv);
            cluster_wait();
            if (a == 0 && lane == 0) { mbar_expect_tx(bEX, 4096 - 256 * nqk); mbar_expect_tx(bEV, 256 * nqk); }
            if (a < 2) bar_arrive(BAR_MEM, MEM_N); else bar_sync(BAR_MEM, MEM_N);
            mbar_wait(bW + 32, 0);
            #pragma unroll
            for (int i = 0; i < 8; i++) ldsm_x4_t(wo[i], pw0 + sb + SM_WO + (warp >> 1) * 8192 + i * 1024);
            sts128(sbl + SM_STASH + a * 1024 + 512, make_uint4(kl0, (pw0 ^ 32) + sb + SM_WO + 5 * 8192, zoff | ((zskip || lane >= 8) << 31), 0u));
            sts128(sbl + SM_STASH + a * 1024, make_uint4(a * 12288 + (lane >> 4) * 1024 + (mi & 1) * 256 + r8 * 16, ACC_X + a * 6144 + (lane >> 4) * 1024 + (mi & 1) * 256 + r8 * 4,
                                                         ((lane ^ mi) & 1) ? 0u : ~0u, sb + SM_MEM + a * 3072 + mi * 256 + r8 * 16 + (r8 & 1 ? 2 : 130)));
            const uint32_t stash = l16 + uni(sb + SM_STASH + a * 1024);
            #pragma unroll
            for (int i = 0; i < 8; i++) ldsm_x4_t(kf[i], (pw0 ^ 32) + sb + SM_WO + 5 * 8192 + i * 1024);
            if (a < 2) { mbar_wait(bTOK, 0); load_k(0, kl0, ic<0>(), ic<K_PRE>()); }
            __syncwarp();
            int sn = 0;
            #pragma unroll 1
            while (sn < NSEG - 1) {
              uint32_t bad, c, cx;
              #pragma unroll 1
              do {
                const int s = sn, par = s & 1;
                const uint32_t exu = launder(sb + par * EXBUF);
                const uint32_t exl = l16 + exu + SM_EX;
                const uint32_t t0 = gtime_lo();
                STAMP(15); STAMPV(31, t0);
                if (!TAIL && a == 2) st_relaxed32_p(&g_ts[blockIdx.x], (t0 & ~31u) | (s & 31), l16);
                if (a == 1) {
                    const uint32_t z = lds32(stash + 520);
                    st_relaxed128_p((uint4*)(g_acc + (z + SLOT_OFF(s + 3))), make_uint4(0, 0, 0, 0), z >> 31);
                }
                if (a == 0 && l16 == 0) { mbar_expect_tx(bEX + 8 * (par ^ 1), 4096 - 256 * nqk); mbar_expect_tx(bEV + 8 * (par ^ 1), 256 * nqk); }
                uint32_t tg;
                auto first_half = [&](auto role) {
                constexpr bool M = role.value;
                auto publish = [&] {
                    asm volatile("{\n.reg .pred p;\nelect.sync _|p, 0xffffffff;\n"
                                 "@p cp.async.bulk.shared::cluster.global.mbarrier::complete_tx::bytes.multicast::cluster [%0], [%1], 8192, [%2], %3;\n}\n"
                        :: "r"(sb + SM_TOK + (par ^ 1) * TOKBUF + r * 8192), "l"(g_tokx[blockIdx.x]), "r"(bTOK + 8 * (par ^ 1)), "h"((unsigned short)(7 ^ (1 << r))) : "memory");
                };
                uint32_t sl, sh, kl = 0, w2 = 0;
                if (M) {
                    if (TAIL) { bar_sync(BAR_VGO, VGO_N); __syncwarp(); st_relaxed32_p(&g_ts[blockIdx.x], (gtime_after(lds32(stash + 524)) & ~31u) | (s & 31), l16); }
                    fence_async_smem();
                    if (l16 == 0) {
                        asm volatile("cp.async.bulk.global.shared::cta.bulk_group [%0], [%1], 8192;\ncp.async.bulk.commit_group;"
                            :: "l"(g_tokx[blockIdx.x]), "r"(sb + SM_TOK + (par ^ 1) * TOKBUF + r * 8192) : "memory");
                        mbar_expect_tx(bTOK + 8 * (par ^ 1), 16384);
                        if (s == 0) mbar_expect_tx(bX, XBUF);
                        if (s + 3 < NSEG) mbar_expect_tx(bX + 8 * (par ^ 1), XBUF);
                    }
                    __syncwarp();
                    if (s > 0 && s + 2 < NSEG) mbar_wait(bX + 8 * par, ((s >> 1) & 1) ^ 1);
                    if (PUB_W == 0) asm volatile("cp.async.bulk.wait_group 0;" ::: "memory");
                    kl = lds32(stash + 512);
                }
                if (!M && K_PRE < 8) {
                    const uint32_t kl = lds32(stash + 512);
                    bar_sync(BAR_PRO, PRO_N);
                    load_k(par, kl, ic<K_PRE>(), ic<8>());
                }
                const uint32_t pst = (launder(l16) >> 2) + launder(sb + SM_P + a * 256);
                mbar_wait(bEX + 8 * par, (s >> 1) & 1);
                if (!M) {
                    uint32_t b[4][4];
                    ldsm16_t(b, exl);
                    float c[4][4];
                    #pragma unroll
                    for (int j = 0; j < 4; j++) { c[j][0] = c[j][1] = c[j][2] = c[j][3] = 0.f; }
                    #pragma unroll
                    for (int j = 0; j < 4; j++) { mma16816(c[(2 * j) & 3], kf[2 * j], b[j][0], b[j][1]); mma16816(c[(2 * j + 1) & 3], kf[2 * j + 1], b[j][2], b[j][3]); }
                    sl = scale_bf2(pack_bf16((c[0][0] + c[1][0]) + (c[2][0] + c[3][0]), (c[0][1] + c[1][1]) + (c[2][1] + c[3][1])));
                    sh = scale_bf2(pack_bf16((c[0][2] + c[1][2]) + (c[2][2] + c[3][2]), (c[0][3] + c[1][3]) + (c[2][3] + c[3][3])));
                } else {
                    float c[4][4];
                    #pragma unroll
                    for (int j = 0; j < 4; j++) { c[j][0] = c[j][1] = c[j][2] = c[j][3] = 0.f; }
                    uint32_t k[4][4], b[4][4];
                    #pragma unroll
                    for (int j = 0; j < 4; j++) { ldsm_x4_t(k[j], kl + exu + 512 * j); ldsm_x4_t(b[j], exl + 512 * j); }
                    if (M_SF) sched_fence<9>(nv);
                    #pragma unroll
                    for (int j = 0; j < 4; j++) { mma16816(c[2 * (j & 1)], k[j], b[j][0], b[j][1]); mma16816(c[2 * (j & 1) + 1], k[j], b[j][2], b[j][3]); }
                    if (PUB_W == 0) publish();
                    sh = sl = scale_bf2(pack_bf16((c[0][0] + c[1][2]) + (c[2][0] + c[3][2]), (c[0][1] + c[1][3]) + (c[2][1] + c[3][3])));
                }
                sts32(pst, pack_bf16(ex2(bf_lo(sl) * LOG2E), ex2(bf_hi(sl) * LOG2E)));
                if (!M) sts32(pst + 128, pack_bf16(ex2(bf_lo(sh) * LOG2E), ex2(bf_hi(sh) * LOG2E)));
                if (S_DUTY && !M) {
                    if (a == 0)
                        asm volatile("{\n.reg .pred p;\nelect.sync _|p, 0xffffffff;\n"
                                     "@p cp.async.bulk.shared::cluster.global.mbarrier::complete_tx::bytes [%0], [%1], 384, [%2];\n"
                                     "@p mbarrier.arrive.expect_tx.shared.b64 _, [%2], 384;\n}\n"
                            :: "r"(sb + SM_TS), "l"(g_ts), "r"(bFREE) : "memory");
                    else if (s > 0 && s + 3 < NSEG)
                        asm volatile("{\n.reg .pred p;\nelect.sync _|p, 0xffffffff;\n"
                                     "@p cp.async.bulk.tensor.3d.shared::cluster.global.mbarrier::complete_tx::bytes.multicast::cluster [%0], [%1, {%3, %4, %5}], [%2], %6;\n}\n"
                            :: "r"(sb + SM_X + (par ^ 1) * XBUF + r * 12288), "l"(&tmx), "r"(bX + 8 * (par ^ 1)), "r"(0), "r"((s + 3) * SEG), "r"(3 * r), "h"((unsigned short)7) : "memory");
                }
                const uint32_t big = bar_red_or(BAR_P, 352, ((maxabs_bf2(sl, sh) & 0x7fff7fffu) + 0x3ddf3ddfu) & 0x80008000u);
                float l0[4], l1[4], l2[4];
                uint32_t pb[4], pm;
                if (!M) { ldsm_x4_t(pb, l16 + sb + SM_P); pm = ldsm_x1_t(l16 + sb + SM_P + 512); }
                if (__builtin_expect(big, 0)) {
                    uint32_t m2 = max_bf2(sl, sh);
                    m2 = max_bf2(m2, __shfl_xor_sync(0xffffffffu, m2, 4));
                    m2 = max_bf2(m2, __shfl_xor_sync(0xffffffffu, m2, 8));
                    m2 = max_bf2(m2, __shfl_xor_sync(0xffffffffu, m2, 16));
                    const uint32_t lq = l16 | (m2 & nv);
                    if (lq < 64) sts32(lq + sb + SM_P + 768 + a * 4, m2);
                    bar_sync(BAR_S, 96);
                    const uint4 m = lds128(sb + SM_P + 768 + (lq & 0x30));
                    m2 = max_bf2(max_bf2(m.x, m.y), m.z);
                    const float ml = bf_lo(m2), mh = bf_hi(m2);
                    sts32(pst, pack_bf16(exd(bf_lo(sl), ml), exd(bf_hi(sl), mh)));
                    if (!M) sts32(pst + 128, pack_bf16(exd(bf_lo(sh), ml), exd(bf_hi(sh), mh)));
                    bar_sync(BAR_P2, 352);
                    if (!M) { ldsm_x4_t(pb, l16 + sb + SM_P); pm = ldsm_x1_t(l16 + sb + SM_P + 512); }
                }
                if (!M) {
                    const uint32_t ONE = 0x3F803F80u;
                    #pragma unroll
                    for (int i = 0; i < 4; i++) l0[i] = l1[i] = l2[i] = 0.f;
                    mma16816r(l0, ONE, ONE, ONE, ONE, pb[0], pb[1]);
                    mma16816r(l1, ONE, ONE, ONE, ONE, pb[2], pb[3]);
                    mma1688(l2, ONE, ONE, pm);
                }
                const uint32_t ll = launder(l16), ila = sb + SM_IL + (ll >> 2), so = SLOT_OFF(launder(s) + 1);
                if (!M) {
                    const float dl = (l0[0] + l1[0]) + l2[0], dh = (l0[1] + l1[1]) + l2[1], mine = rcp_approx(a ? dh : dl);
                    sts32(ila + a * 128, __float_as_uint(mine));
                    const float other = rcp_approx(a ? dl : dh), sil = a ? other : mine, sih = a ? mine : other;
                    stage_w<true>(wo, l16 + sb + SM_O, 12 * r + warp, so, ll, nv, 0u, sil, sih, [&] { if (TP_E || V_EARLY) bar_arrive(BAR_V, 384); });
                } else {
                    w2 = lds32(stash + 516);
                    #pragma unroll
                    for (int i = M_RES; i < 8; i++) ldsm_x4_t(kf[i], w2 + i * 1024);
                    if (PUB_W == 1) { asm volatile("cp.async.bulk.wait_group 0;" ::: "memory"); publish(); }
                    const uint32_t sa = launder(SEND_LANE(ll) + (send_ua(12 * r + 10) + so)), sb_ = launder((ll >> 4) + (send_ub(12 * r + 10) + so));
                    bar_sync_p(BAR_O, 352, (kf[5][0] ^ kf[6][0] ^ kf[7][0] ^ sa ^ sb_) & nv);
                    float c[4][4], il, ih;
                    #pragma unroll
                    for (int i = 0; i < 4; i++) c[i][0] = c[i][1] = c[i][2] = c[i][3] = 0.f;
                    uint32_t b[4][4];
                    #pragma unroll
                    for (int j = 0; j < 4; j++) ldsm_x4_t(b[j], l16 + sb + SM_O + 512 * (3 - j));
                    lds_il(il, ih, l16 + sb + SM_IL);
                    sched_fence<11>(nv);
                    #pragma unroll
                    for (int j = 0; j < 4; j++) {
                        if (j == 2) { if (M_F2) sched_fence<10>(nv); }
                        mma16816(c[0], wo[6 - 2 * j], b[j][0], b[j][1]); mma16816(c[2], kf[6 - 2 * j], b[j][0], b[j][1]);
                        mma16816(c[1], wo[7 - 2 * j], b[j][2], b[j][3]); mma16816(c[3], kf[7 - 2 * j], b[j][2], b[j][3]);
                    }
                    asm volatile("" : "+f"(c[0][0]), "+f"(c[1][0]), "+f"(c[2][0]), "+f"(c[3][0]));
                    if (TP_E || V_EARLY) { if (M_FENCE == 1) sched_fence<8>(nv); else asm volatile("" : "+f"(il) : "f"(c[0][0] + c[1][0]), "f"(c[2][0] + c[3][0])); if (M_FENCE < 2) bar_arrive(BAR_V, 384); }
                    send_tile<0, 0>((c[0][0] + c[1][0]) * il, (c[0][1] + c[1][1]) * ih, (c[0][2] + c[1][2]) * il, (c[0][3] + c[1][3]) * ih, sa, sb_, ll);
                    if (M_FENCE == 2) bar_arrive(BAR_V, 384);
                    send_tile<1024, 256>((c[2][0] + c[3][0]) * il, (c[2][1] + c[3][1]) * ih, (c[2][2] + c[3][2]) * il, (c[2][3] + c[3][3]) * ih, sa, sb_, ll);
                    if (M_FENCE == 3) bar_arrive(BAR_V, 384);
                }
                };
                if (a < 2) first_half(ic<0>()); else first_half(ic<1>());
                STAMP(warp);
                if (!TP_E && !V_EARLY) bar_arrive(BAR_V, 384);
                {
                    const uint4 ad = lds128(stash);
                    const uint32_t kl = lds32(stash + 512), so = SLOT_OFF(launder(s) + 1);
                    if (K_OWN == 1 && a < 2) { mbar_wait(bTOK + 8 * (par ^ 1), ((s + 1) >> 1) & 1); load_k(par ^ 1, kl, ic<0>(), ic<K_PRE>()); }
                    { int it = 0; do { asm volatile("ld.volatile.shared.u32 %0, [%1];" : "=r"(tg) : "r"(sb + SM_SG + 36) : "memory"); } while ((tg & 1u) == (uint32_t)par && ++it < SPIN_LIMIT * 16); }
                    if (!K_OWN && K_POS == 0 && a < 2) load_k(par ^ 1, kl, ic<0>(), ic<K_PRE>());
                    const uint32_t alo = (uint32_t)(uint64_t)g_acc + so;
                    const unsigned char* pm = (const unsigned char*)(((uint64_t)g_acc & ~0xffffffffull) | (ad.x + alo));
                    const unsigned char* px = (const unsigned char*)(((uint64_t)g_acc & ~0xffffffffull) | (ad.y + alo));
                    uint4 v[6]; uint32_t x[3];
                    const uint32_t md = l16 + launder(sb + SM_MEM + a * 3072);
                    STAMP(16 + a); STAMPV(30, tg);
                    wait_gtime(tg);
                    #pragma unroll
                    for (int j = 0; j < 6; j++) v[j] = ld_relaxed128((const uint4*)(pm + 2048 * j));
                    #pragma unroll
                    for (int j = 0; j < 3; j++) x[j] = ld_relaxed32((const uint32_t*)(px + 2048 * j));
                    if (K_OWN == 2) { mbar_wait(bTOK + 8 * (par ^ 1), ((s + 1) >> 1) & 1); if (a < 2) load_k(par ^ 1, kl, ic<0>(), ic<K_PRE>()); sched_fence<16>(nv); }
                    if (LD_FENCE) bar_sync(BAR_S, 96);
                    STAMP(19 + a);
                    c = ~0u;
                    #pragma unroll
                    for (int j = 0; j < 6; j++) { sts128(md + 512 * j, v[j]); c &= v[j].x; }
                    c |= ad.z;
                    #pragma unroll
                    for (int j = 0; j < 3; j++) sts16(ad.w + 1024 * j, (uint16_t)x[j]);
                    cx = x[0] & x[1] & x[2];
                    bad = __any_sync(0xffffffffu, !(c & cx & (ACC_FULL << 16)));
                    STAMP(22 + a); STAMPV(27 + a, bad);
                    bar_sync_p(BAR_MEM, MEM_N, bad);
                }
              } while (++sn < NSEG - 1 && !bad);
                {
                    if (bad) {
                        const uint32_t lq = l16 | (c & nv), so = SLOT_OFF(sn);
                        const uint4 ad = lds128(stash);
                        const unsigned char* pm = launder_p(g_acc + (ad.x + so));
                        const unsigned char* px = launder_p(g_acc + (ad.y + so));
                        int it = 0;
                        do {
                            const uint32_t again = ~(c & __shfl_xor_sync(0xffffffffu, c, 1)) & (ACC_FULL << 16);
                            uint4 u[6]; uint32_t x[3];
                            #pragma unroll
                            for (int j = 0; j < 6; j++) { u[j] = make_uint4(~0u, ~0u, ~0u, ~0u); ld_relaxed128_p(u[j], (const uint4*)(pm + 2048 * j), again); }
                            #pragma unroll
                            for (int j = 0; j < 3; j++) x[j] = ld_relaxed32((const uint32_t*)(px + 2048 * j));
                            c = ~0u;
                            #pragma unroll
                            for (int j = 0; j < 6; j++) {
                                if (again) sts128(lq + sb + SM_MEM + a * 3072 + 512 * j, u[j]);
                                c &= u[j].x;
                            }
                            __syncwarp();
                            #pragma unroll
                            for (int j = 0; j < 3; j++) sts16(ad.w + 1024 * j, (uint16_t)x[j]);
                            c |= ad.z;
                            cx = x[0] & x[1] & x[2];
                        } while (__any_sync(0xffffffffu, !(c & cx & (ACC_FULL << 16))) && ++it < SPIN_LIMIT);
                        bar_sync(BAR_MEM, MEM_N);
                    }
                }
            }
            if (TAIL && a == 2) bar_arrive(BAR_VGO, VGO_N);
        } else {
            cluster_arrive_rx();
            const uint32_t l16 = pin(lane * 16);
            bf16* dst = g_otok + h * 4096 + (r ? 1024 : 0) + (r == 2 ? 2048 : 0);
            {
                #pragma unroll
                for (int sg = 0; sg < 2; sg++) {
                    bar_sync(BAR_X0 + sg, 288);
                    if (lane == 0) {
                        mbar_expect_tx(bX + 8 * sg, XBUF);
                        #pragma unroll
                        for (int c = 0; c < 3; c++)
                            asm volatile("cp.async.bulk.tensor.3d.shared::cluster.global.mbarrier::complete_tx::bytes [%0], [%1, {%3, %4, %5}], [%2];"
                                :: "r"(sb + SM_X + sg * XBUF + c * 12288), "l"(&tmx), "r"(bX + 8 * sg), "r"(0), "r"(sg * SEG), "r"(3 * c) : "memory");
                    }
                    __syncwarp();
                }
                if (lane == 0) load_w(40, 54);
                __syncwarp();
                cluster_wait();
            }
            __syncwarp();
            auto t_loop = [&](auto mtile) {
            constexpr int MT = mtile.value;
            uint32_t q[8][4], sp[5][2], pa[5][2], bv[8][4], rng;
            code_pad<MT ? PAD_T1 : PAD_T0>(nv);
            auto issue_x = [&](int sg) {
                asm volatile("{\n.reg .pred p, q;\nelect.sync _|p, 0xffffffff;\nsetp.eq.and.u32 q, %5, 3, p;\n"
                             "@p cp.async.bulk.tensor.3d.shared::cluster.global.mbarrier::complete_tx::bytes.multicast::cluster [%0], [%1, {%3, %4, %5}], [%2], %6;\n"
                             "@q cp.async.bulk.tensor.3d.shared::cluster.global.mbarrier::complete_tx::bytes.multicast::cluster [%7], [%1, {%3, %4, %3}], [%2], %6;\n}\n"
                    :: "r"(sb + SM_X + (sg & 1) * XBUF + r * 12288), "l"(&tmx), "r"(bX + 8 * (sg & 1)), "r"(0), "r"(sg * SEG), "r"(3 * r), "h"((unsigned short)7), "r"(sb + SM_X + (sg & 1) * XBUF) : "memory");
            };
            mbar_wait(bTOK, 0);
            if (MT) { issue_x(2); issue_x(3); }
            #pragma unroll 1
            for (int s = 0; s < NSEG; s++) {
                const int par = s & 1;
                if (K_OWN) mbar_wait(bTOK + 8 * par, (s >> 1) & 1);
                const uint32_t tok = launder(sb + SM_TOK + par * TOKBUF), exl = l16 + launder(sb + SM_EX + par * EXBUF);
                const int ln = launder(l16) >> 4;
                auto announce = [&] {
                    if (s > 0) {
                        if (lane == 0) {
                            asm volatile("cp.async.bulk.wait_group 0;" ::: "memory");
                            st_relaxed32(&g_prog[blockIdx.x], epoch << 8 | s);
                        }
                        __syncwarp();
                        if (lane == 0 && blockIdx.x == 0) GT(40, s);
                    }
                };
                if (ANN_POS == 0) announce();
                tok_part1<MT>(tok, MT ? r - 1 : 0, ln, q, sp, pa, bv, rng, [&] {
                    if (ANN_POS == 3) announce();
                    if (T_HOLD) { if (s < NSEG - 1) bar_sync((T_HOLD & 1) ? BAR_PRO : BAR_VGO, (T_HOLD & 1) ? PRO_N : VGO_N); else if (T_HOLD == 2) bar_arrive(BAR_VGO, VGO_N); sched_fence<6 + MT>(nv); } });
                if (ANN_POS == 1) announce();
                STAMP(25);
                mbar_wait(bEX + 8 * par, (s >> 1) & 1);
                STAMP(26);
                auto duty = [&] { if (!S_DUTY && s + 1 < NSEG) {
                    asm volatile("{\n.reg .pred p;\nelect.sync _|p, 0xffffffff;\n"
                                 "@p cp.async.bulk.shared::cluster.global.mbarrier::complete_tx::bytes [%0], [%1], 384, [%2];\n"
                                 "@p mbarrier.arrive.expect_tx.shared.b64 _, [%2], 384;\n}\n"
                        :: "r"(sb + SM_TS), "l"(g_ts), "r"(bFREE) : "memory");
                    if (X_POS == 0 && MT && s > 0 && s + 3 < NSEG) issue_x(s + 3);
                } };
                auto pace = [&] { if (s + 1 < NSEG) {
                    if (X_POS == 2 && MT && s > 0 && s + 3 < NSEG) issue_x(s + 3);
                    const uint32_t lo = min(launder(l16), 368u), b = (gtime_lo() & ~31u) - 0x01000000u + s + (lo >> 16);
                    const uint32_t c = (b & ~31u) + (G1_NS + (s == 0 ? G1_0 : 0)) + (par ^ 1);
                    if (K_OWN) mbar_wait(bFREE, par); else mbar_wait2(bFREE, par, bTOK + 8 * (par ^ 1), ((s + 1) >> 1) & 1);
                    uint4 ts = lds128(sb + SM_TS + lo);
                    int it = 0; uint32_t m;
                    while (true) {
                        m = __reduce_max_sync(0xffffffffu, max(max(__funnelshift_r(ts.x - b, ts.x - b, 5), __funnelshift_r(ts.y - b, ts.y - b, 5)), max(__funnelshift_r(ts.z - b, ts.z - b, 5), __funnelshift_r(ts.w - b, ts.w - b, 5))));
                        if (__builtin_expect(m < 0x00100000u, 1) || ++it >= 64) break;
                        ts = ld_relaxed128((const uint4*)((const char*)g_ts + lo));
                    }
                    asm volatile("st.volatile.shared.u32 [%0], %1;" :: "r"(sb + SM_SG + 36), "r"(c + (min(m, 0x00080000u) << 5)) : "memory");
                } };
                auto wait_v = [&] {
                    if (X_POS == 1 && MT && s > 0 && s + 3 < NSEG) issue_x(s + 3);
                    mbar_wait(bEV + 8 * par, (s >> 1) & 1); };
                auto wait_x = [&] { if (__builtin_expect(s == 0, 0)) mbar_wait(bX, 1); };
                tok_part2<MT>(tok, exl, sb + SM_OST, MT ? r - 1 : 0, launder(l16) >> 4, q, sp, pa, bv, rng, s < NSEG - 1, wait_v, duty, pace, wait_x);
                STAMP(11);
                fence_async_smem();
                __syncwarp();
                if (lane == 0) {
                    asm volatile("cp.async.bulk.global.shared::cta.bulk_group [%0], [%1], 2048;" :: "l"(dst), "r"(sb + SM_OST) : "memory");
                    if (!MT) asm volatile("cp.async.bulk.global.shared::cta.bulk_group [%0], [%1], 2048;" :: "l"(dst + 2048), "r"(sb + SM_OST + 2048) : "memory");
                    asm volatile("cp.async.bulk.commit_group;" ::: "memory");
                    if (__builtin_expect(s >= NSEG - 2, 0)) {
                        asm volatile("cp.async.bulk.wait_group 0;" ::: "memory");
                        st_relaxed32(&g_prog[blockIdx.x], epoch << 8 | (s + 1));
                        if (blockIdx.x == 0 && s == NSEG - 1) GT(40, NSEG);
                    }
                }
                __syncwarp();
                dst += SEG * NH * DH;
            }
            };
            if (r == 0) t_loop(ic<0>()); else t_loop(ic<1>());
        }
        cluster_arrive(); cluster_wait();
    }
}
#define SD_THREADS 384
#define SD_CTAS  36
#define BT_RS    4624
#define SD_BT    0
#define SD_STG   74752
#define SD_EF    (SD_STG + 57344)
#define SD_BC    (SD_STG)
#define KSLOTS   5
#define BC_BYTES 10240
#define BC_LBO   1280
#define SD_KP    (SD_STG + 90112)
#define SD_Q0    205824
#define SD_Q1    (SD_STG + 111616)
#define SD_OST   222720
#define SD_XCH   (SD_Q0 + 8192)
#define SD_BAR   224256
#define SD_TOTAL 224768
#define SD_SPIN  (1 << 22)
#define PART_SLOTS 8
#define SD_GO 0
#define SD_REG 200
#define SD_WAIT 6000
#define SD_P2 150
#define SD_P3 500
#define SD_GAP 0
#define SD_RUSH 44
#define SD_P1 300

__device__ uint4 g_part[SD_CTAS][PART_SLOTS][4][8][32];
__device__ __align__(16) unsigned int g_gate[S_LEN];

struct cplx { float r, i; };
__device__ __forceinline__ cplx cmul(cplx a, cplx b) { cplx c; c.r = fmaf(a.r, b.r, -a.i * b.i); c.i = fmaf(a.r, b.i, a.i * b.r); return c; }
__device__ __forceinline__ cplx cexp_(float xr, float xi) {
    const float m = ex2(xr * 1.4426950408889634f);
    const float k = rintf(xi * 0.15915494309189535f);
    const float r = fmaf(k, 1.7484555314695172e-7f, fmaf(k, -6.2831854820251465f, xi));
    cplx o; o.r = m * __cosf(r); o.i = m * __sinf(r); return o;
}
__device__ __forceinline__ void mma_f16(float (&c)[4], const uint32_t (&a)[4], uint32_t b0, uint32_t b1) {
    asm("mma.sync.aligned.m16n8k16.row.col.f32.f16.f16.f32 {%0,%1,%2,%3}, {%4,%5,%6,%7}, {%8,%9}, {%0,%1,%2,%3};"
        : "+f"(c[0]), "+f"(c[1]), "+f"(c[2]), "+f"(c[3]) : "r"(a[0]), "r"(a[1]), "r"(a[2]), "r"(a[3]), "r"(b0), "r"(b1));
}
__device__ __forceinline__ uint32_t mul_bf2(uint32_t a, uint32_t b) { uint32_t r; asm("mul.rn.bf16x2 %0, %1, %2;" : "=r"(r) : "r"(a), "r"(b)); return r; }
__device__ __forceinline__ void mbar_wait_long(uint32_t a, uint32_t parity) { int it = 0; while (!mbar_try(a, parity) && ++it < SD_SPIN) {} }
__device__ __forceinline__ uint16_t lds16(uint32_t a) { uint16_t v; asm volatile("ld.shared.u16 %0, [%1];" : "=h"(v) : "r"(a) : "memory"); return v; }
__device__ __forceinline__ void wg_wait1() { asm volatile("wgmma.wait_group.sync.aligned 1;" ::: "memory"); }
__device__ __forceinline__ void tma2d(uint32_t dst, const CUtensorMap* tm, uint32_t bar, int c0, int c1) {
    asm volatile("cp.async.bulk.tensor.2d.shared::cluster.global.mbarrier::complete_tx::bytes [%0], [%1, {%3, %4}], [%2];"
        :: "r"(dst), "l"(tm), "r"(bar), "r"(c0), "r"(c1) : "memory");
}
__device__ __forceinline__ uint32_t add_bf2(uint32_t a, uint32_t b) { uint32_t r; asm("add.rn.bf16x2 %0, %1, %2;" : "=r"(r) : "r"(a), "r"(b)); return r; }
__device__ __forceinline__ void wgmma_conv(float (&d)[32], uint32_t a0, uint32_t a1, uint32_t a2, uint32_t a3, uint64_t desc) {
    asm volatile("{\n.reg .pred p;\nsetp.ne.b32 p, 1, 0;\n"
        "wgmma.mma_async.sync.aligned.m64n64k16.f32.bf16.bf16 {%0,%1,%2,%3,%4,%5,%6,%7,%8,%9,%10,%11,%12,%13,%14,%15,%16,%17,%18,%19,%20,%21,%22,%23,%24,%25,%26,%27,%28,%29,%30,%31}, {%32,%33,%34,%35}, %36, p, 1, 1, 0;\n}\n"
        : "+f"(d[0]), "+f"(d[1]), "+f"(d[2]), "+f"(d[3]), "+f"(d[4]), "+f"(d[5]), "+f"(d[6]), "+f"(d[7]), "+f"(d[8]), "+f"(d[9]), "+f"(d[10]), "+f"(d[11]), "+f"(d[12]), "+f"(d[13]), "+f"(d[14]), "+f"(d[15]), "+f"(d[16]), "+f"(d[17]), "+f"(d[18]), "+f"(d[19]), "+f"(d[20]), "+f"(d[21]), "+f"(d[22]), "+f"(d[23]), "+f"(d[24]), "+f"(d[25]), "+f"(d[26]), "+f"(d[27]), "+f"(d[28]), "+f"(d[29]), "+f"(d[30]), "+f"(d[31])
        : "r"(a0), "r"(a1), "r"(a2), "r"(a3), "l"(desc));
}
__device__ __forceinline__ void wgmma_conv(float (&d)[24], uint32_t a0, uint32_t a1, uint32_t a2, uint32_t a3, uint64_t desc) {
    asm volatile("{\n.reg .pred p;\nsetp.ne.b32 p, 1, 0;\n"
        "wgmma.mma_async.sync.aligned.m64n48k16.f32.bf16.bf16 {%0,%1,%2,%3,%4,%5,%6,%7,%8,%9,%10,%11,%12,%13,%14,%15,%16,%17,%18,%19,%20,%21,%22,%23}, {%24,%25,%26,%27}, %28, p, 1, 1, 0;\n}\n"
        : "+f"(d[0]), "+f"(d[1]), "+f"(d[2]), "+f"(d[3]), "+f"(d[4]), "+f"(d[5]), "+f"(d[6]), "+f"(d[7]), "+f"(d[8]), "+f"(d[9]), "+f"(d[10]), "+f"(d[11]), "+f"(d[12]), "+f"(d[13]), "+f"(d[14]), "+f"(d[15]), "+f"(d[16]), "+f"(d[17]), "+f"(d[18]), "+f"(d[19]), "+f"(d[20]), "+f"(d[21]), "+f"(d[22]), "+f"(d[23])
        : "r"(a0), "r"(a1), "r"(a2), "r"(a3), "l"(desc));
}
__device__ __forceinline__ void wgmma_conv(float (&d)[16], uint32_t a0, uint32_t a1, uint32_t a2, uint32_t a3, uint64_t desc) {
    asm volatile("{\n.reg .pred p;\nsetp.ne.b32 p, 1, 0;\n"
        "wgmma.mma_async.sync.aligned.m64n32k16.f32.bf16.bf16 {%0,%1,%2,%3,%4,%5,%6,%7,%8,%9,%10,%11,%12,%13,%14,%15}, {%16,%17,%18,%19}, %20, p, 1, 1, 0;\n}\n"
        : "+f"(d[0]), "+f"(d[1]), "+f"(d[2]), "+f"(d[3]), "+f"(d[4]), "+f"(d[5]), "+f"(d[6]), "+f"(d[7]), "+f"(d[8]), "+f"(d[9]), "+f"(d[10]), "+f"(d[11]), "+f"(d[12]), "+f"(d[13]), "+f"(d[14]), "+f"(d[15])
        : "r"(a0), "r"(a1), "r"(a2), "r"(a3), "l"(desc));
}
__device__ __forceinline__ void wgmma_conv(float (&d)[8], uint32_t a0, uint32_t a1, uint32_t a2, uint32_t a3, uint64_t desc) {
    asm volatile("{\n.reg .pred p;\nsetp.ne.b32 p, 1, 0;\n"
        "wgmma.mma_async.sync.aligned.m64n16k16.f32.bf16.bf16 {%0,%1,%2,%3,%4,%5,%6,%7}, {%8,%9,%10,%11}, %12, p, 1, 1, 0;\n}\n"
        : "+f"(d[0]), "+f"(d[1]), "+f"(d[2]), "+f"(d[3]), "+f"(d[4]), "+f"(d[5]), "+f"(d[6]), "+f"(d[7])
        : "r"(a0), "r"(a1), "r"(a2), "r"(a3), "l"(desc));
}
template<int NR> __device__ __forceinline__ void conv_mma(float (&acc)[NR], const uint32_t (&R)[16], uint32_t dlo) {
    #pragma unroll
    for (int q = 0; q < 4; q++)
        wgmma_conv(acc, R[4 * q], R[4 * q + 1], R[4 * q + 2], R[4 * q + 3], (uint64_t)(dlo + (2 * (3 - q)) * (BC_LBO >> 4)) | ((uint64_t)8 << 32));
}
__device__ __forceinline__ void conv_ld(uint32_t (&R)[16], uint32_t a) {
    #pragma unroll
    for (int q = 0; q < 4; q++) { const uint2 u = lds64(a + 64 * (2 * q + 1)); R[4 * q] = u.x; R[4 * q + 1] = u.y; }
}
__device__ __forceinline__ void conv_fix(uint32_t (&R)[16], uint32_t& carry) {
    #pragma unroll
    for (int q = 0; q < 4; q++) {
        asm volatile("mov.b32 %0, %1;" : "=r"(R[4 * q + 2]) : "r"(q ? R[4 * q - 3] : carry));
        asm volatile("mov.b32 %0, %1;" : "=r"(R[4 * q + 3]) : "r"(R[4 * q]));
    }
    asm volatile("mov.b32 %0, %1;" : "=r"(carry) : "r"(R[13]));
}
template<int A> __device__ __forceinline__ void conv_group(float (&acc)[32 - 8 * A], uint32_t (&R)[4][16], uint32_t& carry, uint32_t pb, uint32_t dlo) {
    #pragma unroll
    for (int e = 0; e < 8; e += 2) {
        const int dl = 8 * A + e;
        conv_fix(R[dl & 3], carry); conv_fix(R[(dl + 1) & 3], carry);
        wg_fence(); conv_mma(acc, R[dl & 3], dlo + 16 - 2 * e); conv_mma(acc, R[(dl + 1) & 3], dlo + 14 - 2 * e); wg_commit();
        wg_wait1();
        if (dl + 2 < 32) { conv_ld(R[(dl + 2) & 3], pb + (dl + 2) * 512); conv_ld(R[(dl + 3) & 3], pb + (dl + 3) * 512); }
    }
}

__global__ void __launch_bounds__(SD_THREADS, 1)
side_kernel(const __grid_constant__ CUtensorMap tmw, const bf16* __restrict__ x,
            const bf16* __restrict__ log_A_real, const bf16* __restrict__ A_imag, const bf16* __restrict__ C_real, const bf16* __restrict__ C_imag,
            const bf16* __restrict__ log_dt, const bf16* __restrict__ D_skip, const bf16* __restrict__ gate_w, bf16* __restrict__ out) {
    extern __shared__ __align__(1024) unsigned char smem[];
    const uint32_t sb = smem_u32(smem);
    const int tid = threadIdx.x, lane = tid & 31;
    const int warp = __shfl_sync(0xffffffffu, tid >> 5, 0);
    const int g = lane >> 2, t = lane & 3, mi = lane >> 3, r8 = lane & 7;
    const bool sh = blockIdx.x < 32;
    const int d0 = blockIdx.x * 16;
    const uint32_t b0_ = sb + SD_BAR, bKF = b0_ + 384, bKE = bKF + 8 * KSLOTS, bWO = b0_ + 48, bFULL = b0_ + 56, bEMPTY = b0_ + 88, bEPI = b0_ + 120, bPRT = b0_ + 152, bGO = b0_ + 184, bCH = b0_ + 256;
    const unsigned epoch = ld_relaxed32(&g_epoch);
    if (tid == 0) GT(blockIdx.x, 0);
    if (tid == 0) {
        for (int i = 0; i < 2 * KSLOTS; i++) mbar_init(bKF + 8 * i, 128);
        mbar_init(bWO, 1);
        for (int i = 0; i < 16; i++) mbar_init(bCH + 8 * i, 1);
        for (int i = 0; i < 4; i++) { mbar_init(bFULL + 8 * i, 1); mbar_init(bEMPTY + 8 * i, sh ? 8 : 4); mbar_init(bEPI + 8 * i, 4); mbar_init(bPRT + 8 * i, 8); mbar_init(bGO + 8 * i, 1); }
        asm volatile("fence.mbarrier_init.release.cluster;" ::: "memory");
    }
    for (int i = tid; i < KSLOTS * 8 * 16; i += SD_THREADS) sts128(sb + SD_BC + (i >> 4) * BC_LBO + (i & 15) * 16, make_uint4(0, 0, 0, 0));
    if (tid < 128) sts64(sb + ((tid & 64) ? SD_Q1 : SD_Q0) + (tid & 63) * 8, 0u, 0u);
    fence_async_smem();
    __syncthreads();

    if (warp < 8) {
        asm volatile("setmaxnreg.inc.sync.aligned.u32 %0;" :: "n"(SD_REG));
        const int wg = warp >> 2, w = warp & 3, t128 = tid & 127;
        if (SD_WAIT) __nanosleep(SD_WAIT);
        {
            #pragma unroll 1
            for (int i = 0; i < 4; i++) {
                const int tp = tid + 256 * i;
                const bf16* xp = x + (size_t)(2 * tp) * DM + d0;
                const uint4 v0 = __ldg((const uint4*)xp), v1 = __ldg((const uint4*)(xp + 8)), v2 = __ldg((const uint4*)(xp + DM)), v3 = __ldg((const uint4*)(xp + DM + 8));
                const uint32_t a = sb + SD_BT + (tp >> 5) * 144 + (tp & 31) * 4;
                const uint32_t lo[8] = {v0.x, v0.y, v0.z, v0.w, v1.x, v1.y, v1.z, v1.w};
                const uint32_t hi[8] = {v2.x, v2.y, v2.z, v2.w, v3.x, v3.y, v3.z, v3.w};
                #pragma unroll
                for (int j = 0; j < 8; j++) { sts32(a + (2 * j) * BT_RS, __byte_perm(lo[j], hi[j], 0x5410)); sts32(a + (2 * j + 1) * BT_RS, __byte_perm(lo[j], hi[j], 0x7632)); }
                if (SD_GAP) __nanosleep(SD_GAP);
            }
        }
        bar_sync(1, 256);
        if (tid == 0) GT(blockIdx.x, 65);
        const uint32_t pa = sb + (wg ? SD_Q1 : SD_Q0);
        const uint32_t pb = pa + (72 + 16 * w - 56 + g - 2 * t) * 8;
        for (int c = wg; c < 16; c += 2) {
            const uint32_t bt = sb + SD_BT + c * BT_RS;
            bar_sync(2 + wg, 128);
            #pragma unroll
            for (int it = 0; it < 9; it++) {
                const int k = it < 8 ? t128 + 128 * it : t128 - 4;
                if (it < 8 || t128 < 4) {
                    auto word = [&](int j) { return j >= 0 ? lds32(bt + (j >> 5) * 144 + (j & 31) * 4) : 0u; };
                    const uint32_t c0 = word(k), p0 = word(k - 1), c1 = word(k + 4), p1 = word(k + 3);
                    sts128(pa + (72 + 2 * k) * 8, make_uint4(__byte_perm(c0, p0, 0x7610), __byte_perm(c1, p1, 0x7610), __byte_perm(c0, c0, 0x1032), __byte_perm(c1, c1, 0x1032)));
                }
            }
            bar_sync(2 + wg, 128);
            const int slot = c % KSLOTS;
            float acc[32];
            #pragma unroll
            for (int i = 0; i < 32; i++) acc[i] = 0.f;
            uint32_t R[4][16];
            uint32_t carry = lds32(pb);
            conv_ld(R[0], pb); conv_ld(R[1], pb + 512);
            const uint32_t dlo = (((sb + SD_BC + slot * BC_BYTES) & 0x3FFFF) >> 4) | ((BC_LBO >> 4) << 16);
            mbar_wait_long(bKF + 8 * slot, (c / KSLOTS) & 1);
            const float ds = bf(D_skip[d0 + c]);
            auto fin = [&](const float* a8, int q0) {
                #pragma unroll
                for (int q = 0; q < 2; q++)
                    #pragma unroll
                    for (int hh = 0; hh < 2; hh++) {
                        const uint32_t a = bt + (4 * (q0 + q) + t) * 144 + (16 * w + g + 8 * hh) * 2;
                        const float u = __uint_as_float((uint32_t)lds16(a) << 16);
                        const float y = rbf(a8[4 * q + 2 * hh] + a8[4 * q + 2 * hh + 1]);
                        sts16(a, (uint16_t)(pack_bf16(y + rbf(u * ds), 0.f) & 0xffff));
                    }
            };
            float a1[24], a2[16], a3[8];
            conv_group<0>(acc, R, carry, pb, dlo);
            wg_wait0();
            #pragma unroll
            for (int i = 0; i < 24; i++) asm volatile("mov.b32 %0, %1;" : "=f"(a1[i]) : "f"(acc[8 + i]));
            fin(acc, 0);
            conv_group<1>(a1, R, carry, pb, dlo);
            wg_wait0();
            #pragma unroll
            for (int i = 0; i < 16; i++) asm volatile("mov.b32 %0, %1;" : "=f"(a2[i]) : "f"(a1[8 + i]));
            fin(a1, 2);
            conv_group<2>(a2, R, carry, pb, dlo);
            wg_wait0();
            #pragma unroll
            for (int i = 0; i < 8; i++) asm volatile("mov.b32 %0, %1;" : "=f"(a3[i]) : "f"(a2[8 + i]));
            fin(a2, 4);
            conv_group<3>(a3, R, carry, pb, dlo);
            wg_wait0();
            mbar_arrive(bKE + 8 * slot);
            fin(a3, 6);
        }
        fence_async_smem();
        __syncthreads();
        const uint32_t stg = sb + SD_STG + wg * 65536;
        uint32_t wf[32][4];
        if (tid == 0) GT(blockIdx.x, 66);
        mbar_wait_long(bWO, 0);
        #pragma unroll
        for (int i = 0; i < 32; i++)
            ldsm_x4_t(wf[i], stg + (i * 16 + (mi >> 1) * 8 + r8) * 128 + (((2 * w + (mi & 1)) ^ r8) << 4));
        { uint32_t x = 0;
          #pragma unroll
          for (int i = 0; i < 32; i++) x |= wf[i][0];
          asm volatile("" :: "r"(x) : "memory"); }
        __syncwarp();
        if (lane == 0) {
            mbar_arrive(bEMPTY + 16 * wg); mbar_arrive(bEMPTY + 16 * wg + 8);
            if (sh) { mbar_arrive(bEMPTY + 16 * (wg ^ 1)); mbar_arrive(bEMPTY + 16 * (wg ^ 1) + 8); }
        }
        uint4* dst = sh ? &g_part[(blockIdx.x & ~7) + 4 * wg + w][0][0][blockIdx.x & 7][lane] : &g_part[32 + w][0][0][2 * (blockIdx.x - 32) + wg][lane];
        const uint32_t dl0 = (((sb + SD_STG) & 0x3FFFF) >> 4) | 0x10000u;
        auto seg = [&](int s, auto last) {
            const int bi = sh ? s & 3 : 2 * wg + (s & 1), bp = (sh ? s >> 2 : s >> 1) & 1;
            const uint32_t xd = uni(dl0 + bi * 2048);
            float acc[16];
            #pragma unroll
            for (int i = 0; i < 32; i++) {
                if (i == 0 || (last.value && (i & 7) == 0)) { mbar_wait_long(bCH + 32 * bi + i, i ? 0 : bp); wg_fence(); }
                if (i == 0) wgmma_n32<0>(acc, wf[i], desc_from(xd));
                else wgmma_n32<1>(acc, wf[i], desc_from(xd + (i >> 2) * 256 + (i & 3) * 2));
            }
            wg_commit();
            if (s >= PART_SLOTS / 2) mbar_wait_long(bEPI + 8 * (s & 3), ((s - 4) >> 2) & 1);
            const uint32_t ph = ((s / PART_SLOTS) & 1) ^ 1;
            uint4* p = dst + (s % PART_SLOTS) * (4 * 8 * 32);
            wg_wait0();
            #pragma unroll
            for (int j = 0; j < 4; j++)
                st_relaxed128(p + 256 * j, make_uint4((__float_as_uint(acc[4 * j]) & ~1u) | ph, __float_as_uint(acc[4 * j + 1]), __float_as_uint(acc[4 * j + 2]), __float_as_uint(acc[4 * j + 3])));
            if (tid == 0 && s == NSEG - 1) GT(blockIdx.x, 71);
            __syncwarp();
            if (lane == 0) { mbar_arrive(bEMPTY + 8 * bi); mbar_arrive(bPRT + 8 * (s & 3)); }
        };
        #pragma unroll 1
        for (int s = 0; s < NSEG - 1; s++) seg(s, ic<0>());
        seg(NSEG - 1, ic<1>());
    } else {
        asm volatile("setmaxnreg.dec.sync.aligned.u32 %0;" :: "n"(504 - 2 * SD_REG));
        const int w = warp - 8, n = tid - 256;
        bf16 p_la = log_A_real[d0 * NS + n], p_ai = A_imag[d0 * NS + n], p_cr = C_real[d0 * NS + n], p_ci = C_imag[d0 * NS + n], p_dt = log_dt[d0];
        const uint32_t ef = sb + SD_EF + w * 8192;
        const uint32_t efl = ef + lane * 4;
        uint32_t goff[8];
        #pragma unroll
        for (int i = 0; i < 16; i++) {
            const int l = 64 * lane + 8 * (w + 4 * (i >> 3)) + (i & 7);
            const int p = (int)rbf((float)l);
            const int a = p >> 7, b = (p >> 3) & 15, c = p & 7;
            const int row = p < 256 ? 8 * a + c : (p < 512 ? 16 + 4 * (a - 2) + (c >> 1) : (p < 1024 ? 24 + 2 * (a - 4) + (c >> 2) : 24 + a));
            const uint32_t off = row * 72 + b * 4;
            if (i & 1) goff[i >> 1] |= off << 16; else goff[i >> 1] = off;
        }
        for (int c = 0; c < 16; c++) {
            const float dt = rbf(expf(bf(p_dt)));
            const float xr = -rbf(expf(bf(p_la))) * dt, xi = bf(p_ai) * dt;
            cplx C; C.r = 2.f * bf(p_cr) * dt; C.i = 2.f * bf(p_ci) * dt;
            if (c + 1 < 16) {
                const int o = (d0 + c + 1) * NS + n;
                p_la = log_A_real[o]; p_ai = A_imag[o]; p_cr = C_real[o]; p_ci = C_imag[o]; p_dt = log_dt[d0 + c + 1];
            }
            const uint32_t mexp = min(max(__reduce_max_sync(0xffffffffu, __float_as_uint(fmaxf(fabsf(C.r), fabsf(C.i)))) & 0x7f800000u, 0x01000000u), 0x7e000000u);
            const float unsc = __uint_as_float(mexp), sc = __uint_as_float(0x7f000000u - mexp);
            C.r *= sc; C.i *= sc;
            #define EADDR(r) ((efl ^ (((r) & 7) << 4)) + (r) * 128)
            {
                cplx f[16];
                f[1] = cexp_(8.f * xr, -8.f * xi);
                f[2] = cmul(f[1], f[1]); f[3] = cmul(f[2], f[1]); f[4] = cmul(f[2], f[2]); f[5] = cmul(f[4], f[1]); f[6] = cmul(f[4], f[2]); f[7] = cmul(f[4], f[3]);
                f[8] = cmul(f[4], f[4]);
                #pragma unroll
                for (int b = 9; b < 16; b++) f[b] = cmul(f[8], f[b - 8]);
                sts32(EADDR(0) + 6144, 0x00003c00u);
                #pragma unroll
                for (int b = 1; b < 16; b++) sts32(EADDR(b) + 6144, pack_f16(f[b].r, f[b].i));
            }
            {
                cplx G[17], wc[8];
                G[1] = cexp_(128.f * xr, 128.f * xi);
                wc[1] = cexp_(xr, xi);
                G[2] = cmul(G[1], G[1]); G[4] = cmul(G[2], G[2]); G[8] = cmul(G[4], G[4]);
                wc[2] = cmul(wc[1], wc[1]); wc[3] = cmul(wc[2], wc[1]); wc[4] = cmul(wc[2], wc[2]); wc[5] = cmul(wc[4], wc[1]); wc[6] = cmul(wc[4], wc[2]); wc[7] = cmul(wc[4], wc[3]);
                cplx CG[17];
                CG[0] = C; CG[1] = cmul(C, G[1]); CG[2] = cmul(C, G[2]); CG[3] = cmul(CG[1], G[2]);
                #pragma unroll
                for (int a = 0; a < 4; a++) CG[4 + a] = cmul(CG[a], G[4]);
                #pragma unroll
                for (int a = 0; a < 9; a++) CG[8 + a] = cmul(CG[a], G[8]);
                #pragma unroll
                for (int r = 0; r < 41; r++) {
                    const int a = r < 16 ? (r >> 3) : (r < 24 ? 2 + ((r >> 2) & 1) : (r < 32 ? 4 + ((r >> 1) & 3) : r - 24));
                    const int cc = r < 16 ? (r & 7) : (r < 24 ? 2 * (r & 3) : (r < 32 ? 4 * (r & 1) : 0));
                    const cplx e = cc ? cmul(CG[a], wc[cc]) : CG[a];
                    sts32(EADDR(r), pack_f16(e.r, e.i));
                }
            }
            __syncwarp();
            float acc[3][2][4];
            #pragma unroll
            for (int i = 0; i < 3; i++)
                #pragma unroll
                for (int j = 0; j < 2; j++) { acc[i][j][0] = acc[i][j][1] = acc[i][j][2] = acc[i][j][3] = 0.f; }
            #pragma unroll
            for (int ks = 0; ks < 4; ks++) {
                uint32_t bq[4];
                ldsm_x4(bq, ef + 6144 + ((mi >> 1) * 8 + r8) * 128 + (((2 * ks + (mi & 1)) ^ r8) << 4));
                #pragma unroll
                for (int mt = 0; mt < 3; mt++) {
                    uint32_t aq[4];
                    ldsm_x4(aq, ef + (16 * mt + (mi & 1) * 8 + r8) * 128 + (((2 * ks + (mi >> 1)) ^ r8) << 4));
                    mma_f16(acc[mt][0], aq, bq[0], bq[1]);
                    mma_f16(acc[mt][1], aq, bq[2], bq[3]);
                }
            }
            const uint32_t kp = sb + SD_KP;
            #pragma unroll
            for (int mt = 0; mt < 3; mt++)
                #pragma unroll
                for (int nt = 0; nt < 2; nt++) {
                    const uint32_t a = kp + w * 3072 + (16 * mt + g) * 64 + nt * 32 + t * 8;
                    sts64(a, __float_as_uint(acc[mt][nt][0] * unsc), __float_as_uint(acc[mt][nt][1] * unsc));
                    sts64(a + 512, __float_as_uint(acc[mt][nt][2] * unsc), __float_as_uint(acc[mt][nt][3] * unsc));
                }
            bar_sync(4, 128);
            #pragma unroll
            for (int i = 0; i < 3; i++) {
                const uint32_t a = kp + (n + 128 * i) * 8;
                const uint2 v0 = lds64(a), v1 = lds64(a + 3072), v2 = lds64(a + 6144), v3 = lds64(a + 9216);
                sts64(a + 12288 + ((n >> 3) + 16 * i) * 8, __float_as_uint((__uint_as_float(v0.x) + __uint_as_float(v1.x)) + (__uint_as_float(v2.x) + __uint_as_float(v3.x))),
                                 __float_as_uint((__uint_as_float(v0.y) + __uint_as_float(v1.y)) + (__uint_as_float(v2.y) + __uint_as_float(v3.y))));
            }
            bar_sync(4, 128);
            const int slot = c % KSLOTS;
            float kv[16];
            #pragma unroll
            for (int e = 0; e < 8; e++) { kv[2 * e] = __uint_as_float(lds32(kp + 12288 + (goff[e] & 0xffff))); kv[2 * e + 1] = __uint_as_float(lds32(kp + 12288 + (goff[e] >> 16))); }
            if (c >= KSLOTS) mbar_wait_long(bKE + 8 * slot, (c / KSLOTS - 1) & 1);
            #pragma unroll
            for (int it = 0; it < 2; it++) {
                uint32_t hi[4], lo[4];
                #pragma unroll
                for (int e = 0; e < 4; e++) {
                    const float k0 = kv[8 * it + 2 * e], k1 = kv[8 * it + 2 * e + 1];
                    hi[e] = pack_bf16(k0, k1);
                    lo[e] = pack_bf16(k0 - bf_lo(hi[e]), k1 - bf_hi(hi[e]));
                }
                const uint32_t a = sb + SD_BC + slot * BC_BYTES + (w + 4 * it) * BC_LBO + (16 + 2 * lane) * 16;
                sts128(a, make_uint4(hi[0], hi[1], hi[2], hi[3]));
                sts128(a + 16, make_uint4(lo[0], lo[1], lo[2], lo[3]));
            }
            fence_async_smem();
            mbar_arrive(bKF + 8 * slot);
        }
        {
            uint32_t gw[9];
            #pragma unroll
            for (int j = 0; j < 9; j++) gw[j] = __ldg((const uint32_t*)gate_w + lane + 32 * j);
            float z = 0.f;
            #pragma unroll 1
            for (int i0 = 0; i0 < 15; i0 += 5) {
                uint32_t xv[5][9];
                #pragma unroll
                for (int i = 0; i < 5; i++) {
                    const int tk = min(blockIdx.x * 57 + w + 4 * (i0 + i), S_LEN - 1);
                    #pragma unroll
                    for (int j = 0; j < 9; j++) xv[i][j] = __ldg((const uint32_t*)(x + (size_t)tk * DM) + lane + 32 * j);
                }
                #pragma unroll
                for (int i = 0; i < 5; i++) {
                    float acc = 0.f;
                    #pragma unroll
                    for (int j = 0; j < 9; j++) { const uint32_t m = mul_bf2(xv[i][j], gw[j]); acc += bf_lo(m) + bf_hi(m); }
                    #pragma unroll
                    for (int o = 16; o; o >>= 1) acc += __shfl_xor_sync(0xffffffffu, acc, o);
                    if (lane == i0 + i) z = rbf(acc);
                }
            }
            const int li = w + 4 * lane, tk = blockIdx.x * 57 + li;
            if (li < 57 && tk < S_LEN) st_relaxed32(&g_gate[tk], pack_bf16(1.f / (1.f + expf(-z)), 0.f) | (epoch << 16));
        }
        if (tid == 256) GT(blockIdx.x, 67);
        fence_async_smem();
        __syncthreads();
            const uint32_t ost = sb + SD_OST + w * 256;
            const uint4* const pl = &g_part[blockIdx.x][0][0][0][lane];
            uint4 v[8];
            auto fetch = [&](int u, bool block) {
                const int s = u >> 2;
                uint32_t early;
                asm volatile("{\n.reg .pred p;\nmbarrier.test_wait.parity.shared::cta.b64 p, [%1], %2;\nselp.u32 %0, 1, 0, p;\n}\n" : "=r"(early) : "r"(bPRT + 8 * (s & 3)), "r"((s >> 2) & 1) : "memory");
                if (!early) {
                    if (!block) return false;
                    mbar_wait_long(bPRT + 8 * (s & 3), (s >> 2) & 1);
                    delay_clk(s < NSEG - 2 ? SD_P1 : SD_P2);
                } else if (SD_P3 && s < SD_RUSH) delay_clk(SD_P3);
                const uint4* p = pl + (u & (4 * PART_SLOTS - 1)) * 256;
                #pragma unroll
                for (int i = 0; i < 8; i++) v[i] = ld_relaxed128(p + 32 * i);
                return true;
            };
            auto units = [&](int u, int end) {
              fetch(u, true);
              #pragma unroll 1
              while (true) {
                const int s = u >> 2;
                const int t0 = 8 * u + 2 * t;
                const uint2 gt = lds64(sb + SD_Q0 + t0 * 4);
                const uint32_t ba = sb + SD_BT + g * BT_RS + (t0 >> 6) * 144 + (t0 & 63) * 2;
                const uint32_t b0 = lds32(ba), b1 = lds32(ba + 8 * BT_RS);
                const uint32_t phm = ((s / PART_SLOTS) & 1) - 1;
                int it = 0;
                while (true) {
                    uint32_t any = 0;
                    #pragma unroll
                    for (int i = 0; i < 8; i++) any |= v[i].x ^ phm;
                    if (!__any_sync(0xffffffffu, any & 1u) || ++it >= SD_SPIN) break;
                    if (it > 1 && s < NSEG - 2) __nanosleep(200);
                    const uint4* p = pl + (u & (4 * PART_SLOTS - 1)) * 256;
                    #pragma unroll
                    for (int i = 0; i < 8; i++) ld_relaxed128_p(v[i], p + 32 * i, (v[i].x ^ phm) & 1u);
                }
                if (lane == 0) mbar_arrive(bEPI + 8 * (s & 3));
                float a0 = __uint_as_float(v[0].x), a1 = __uint_as_float(v[0].y), a2 = __uint_as_float(v[0].z), a3 = __uint_as_float(v[0].w);
                #pragma unroll
                for (int i = 1; i < 8; i++) { a0 += __uint_as_float(v[i].x); a1 += __uint_as_float(v[i].y); a2 += __uint_as_float(v[i].z); a3 += __uint_as_float(v[i].w); }
                const uint32_t s01 = pack_bf16(a0, a1), s23 = pack_bf16(a2, a3);
                const int nu = u + 3;
                const bool pre = nu < end && fetch(nu, false);
                const uint32_t gg = __byte_perm(gt.x, gt.y, 0x5410), mm = pack_bf16(1.f - bf_lo(gg), 1.f - bf_hi(gg));
                const uint32_t r0 = add_bf2(mul_bf2(gg, s01), mul_bf2(mm, b0)), r1 = add_bf2(mul_bf2(gg, s23), mul_bf2(mm, b1));
                asm volatile("stmatrix.sync.aligned.m8n8.x2.trans.shared.b16 [%0], {%1,%2};" :: "r"(ost + r8 * 32 + (mi & 1) * 16), "r"(r0), "r"(r1) : "memory");
                __syncwarp();
                if (lane < 16) *(uint4*)(out + (size_t)(8 * u + (lane >> 1)) * DM + d0 + 8 * (lane & 1)) = lds128(ost + lane * 16);
                __syncwarp();
                if (lane == 0 && (u & 3) == 3) GT(blockIdx.x, 1 + s);
                if (nu >= end) break;
                if (!pre) fetch(nu, true);
                u = nu;
              }
            };
        if (w == 0) {
            if (lane == 0) {
                mbar_expect_tx(bWO, 131072);
                #pragma unroll
                for (int q = 0; q < 4; q++) tma2d(sb + SD_STG + q * 32768, &tmw, bWO, sh ? 128 * (blockIdx.x >> 3) + 64 * (q >> 1) : 512, sh ? 512 * (blockIdx.x & 7) + 256 * (q & 1) : 1024 * (blockIdx.x - 32) + 256 * q);
            }
            bar_sync(5, 128);
            const int ke0 = sh ? blockIdx.x & 7 : 2 * (blockIdx.x - 32);
            const unsigned int* f = &g_prog[12 * ke0 + (lane < (sh ? 12 : 24) ? lane : 0)];
            int avail = 0;
            #pragma unroll 1
            for (int s = 0; s < NSEG; s++) {
                if (s >= avail) {
                    int it = 0;
                    while (true) {
                        uint32_t v;
                        asm volatile("ld.acquire.gpu.global.u32 %0, [%1];" : "=r"(v) : "l"(f) : "memory");
                        avail = __reduce_min_sync(0xffffffffu, (v >> 8) == (epoch & 0xffffffu) ? v & 255u : 0u);
                        if (avail > s || ++it >= SD_SPIN) break;
                        if (s < NSEG - 1) __nanosleep(64);
                    }
                    asm volatile("fence.proxy.async.global;" ::: "memory");
                    if (lane == 0 && s == NSEG - 1) GT(blockIdx.x, 70);
                }
                if (lane == 0 && s == 2 && blockIdx.x == 0) st_relaxed32(&g_epoch, epoch + 1);
                const int b0 = sh ? s & 3 : s & 1, bp = (sh ? s >> 2 : s >> 1) & 1;
                const bf16* src = g_otok + (size_t)s * (SEG * NH * DH) + ke0 * 16384;
                mbar_wait_long(bEMPTY + 8 * b0, bp);
                if (!sh) mbar_wait_long(bEMPTY + 16 + 8 * b0, bp);
                if (s < NSEG - 1) {
                    asm volatile("{\n.reg .pred p, q;\nelect.sync _|p, 0xffffffff;\nsetp.eq.and.u32 q, %6, 0, p;\n"
                                 "@p mbarrier.arrive.expect_tx.shared.b64 _, [%2], 32768;\n"
                                 "@p cp.async.bulk.shared::cluster.global.mbarrier::complete_tx::bytes [%0], [%1], 32768, [%2];\n"
                                 "@q mbarrier.arrive.expect_tx.shared.b64 _, [%5], 32768;\n"
                                 "@q cp.async.bulk.shared::cluster.global.mbarrier::complete_tx::bytes [%3], [%4], 32768, [%5];\n}\n"
                        :: "r"(sb + SD_STG + b0 * 32768), "l"(src), "r"(bCH + 32 * b0), "r"(sb + SD_STG + (b0 + 2) * 32768), "l"(src + 16384), "r"(bCH + 32 * (b0 + 2)), "r"((uint32_t)sh) : "memory");
                } else {
                    #pragma unroll
                    for (int hc = 0; hc < 4; hc++)
                        asm volatile("{\n.reg .pred p, q;\nelect.sync _|p, 0xffffffff;\nsetp.eq.and.u32 q, %6, 0, p;\n"
                                     "@p mbarrier.arrive.expect_tx.shared.b64 _, [%2], 8192;\n"
                                     "@p cp.async.bulk.shared::cluster.global.mbarrier::complete_tx::bytes [%0], [%1], 8192, [%2];\n"
                                     "@q mbarrier.arrive.expect_tx.shared.b64 _, [%5], 8192;\n"
                                     "@q cp.async.bulk.shared::cluster.global.mbarrier::complete_tx::bytes [%3], [%4], 8192, [%5];\n}\n"
                            :: "r"(sb + SD_STG + b0 * 32768 + hc * 8192), "l"(src + hc * 4096), "r"(bCH + 32 * b0 + 8 * hc),
                               "r"(sb + SD_STG + (b0 + 2) * 32768 + hc * 8192), "l"(src + 16384 + hc * 4096), "r"(bCH + 32 * (b0 + 2) + 8 * hc), "r"((uint32_t)sh) : "memory");
                }
            }
        } else {
            if (w == 3) {
                for (int i = 0; i < 16; i += 8) {
                    uint4 v[8]; uint32_t miss = 0xffu; int it = 0;
                    const uint32_t tag = epoch & 0xffffu;
                    #pragma unroll
                    for (int j = 0; j < 8; j++) v[j] = make_uint4(0, 0, 0, 0);
                    do {
                        #pragma unroll
                        for (int j = 0; j < 8; j++) ld_relaxed128_p(v[j], (const uint4*)g_gate + (i + j) * 32 + lane, miss & (1u << j));
                        miss = 0;
                        #pragma unroll
                        for (int j = 0; j < 8; j++) miss |= (uint32_t)((v[j].x >> 16) != tag || (v[j].y >> 16) != tag || (v[j].z >> 16) != tag || (v[j].w >> 16) != tag) << j;
                    } while (__any_sync(0xffffffffu, miss) && ++it < SD_SPIN);
                    #pragma unroll
                    for (int j = 0; j < 8; j++) sts128(sb + SD_Q0 + ((i + j) * 32 + lane) * 16, v[j]);
                }
            }
            bar_sync(5, 128);
        }
        #pragma unroll 1
        for (int k = w == 0; k < 2; k++) units(k ? 4 * (NSEG - 1) + w : w - 1, k ? 0 : 4 * (NSEG - 1));
    }
    if (tid == 256) GT(blockIdx.x, 72);
}

extern "C" void kernel_launch(void* const* d_in, const int* in_sizes, int n_in, void* d_out, int out_size) {
    const bf16* x = (const bf16*)d_in[0];
    const bf16* mem0 = (const bf16*)d_in[1];
    const bf16* Wq = (const bf16*)d_in[2];
    const bf16* Wk = (const bf16*)d_in[3];
    const bf16* Wv = (const bf16*)d_in[4];
    const bf16* Wo = (const bf16*)d_in[5];
    const bf16* log_A_real = (const bf16*)d_in[8];
    const bf16* A_imag = (const bf16*)d_in[9];
    const bf16* C_real = (const bf16*)d_in[10];
    const bf16* C_imag = (const bf16*)d_in[11];
    const bf16* log_dt = (const bf16*)d_in[12];
    const bf16* D_skip = (const bf16*)d_in[13];
    const bf16* gate_w = (const bf16*)d_in[14];
    bf16* out = (bf16*)d_out;
    typedef CUresult (*EncFn)(CUtensorMap*, CUtensorMapDataType, cuuint32_t, void*, const cuuint64_t*, const cuuint64_t*, const cuuint32_t*, const cuuint32_t*,
                              CUtensorMapInterleave, CUtensorMapSwizzle, CUtensorMapL2promotion, CUtensorMapFloatOOBfill);
    static EncFn enc = nullptr;
    if (!enc) { void* fn = nullptr; cudaDriverEntryPointQueryResult qr; cudaGetDriverEntryPoint("cuTensorMapEncodeTiled", &fn, cudaEnableDefault, &qr); enc = (EncFn)fn; }
    auto mk = [&](CUtensorMap* tm, const void* ptr, uint64_t cols, uint64_t rows, uint32_t bc, uint32_t br) {
        cuuint64_t gdim[2] = {cols, rows}; cuuint64_t gstr[1] = {cols * 2}; cuuint32_t box[2] = {bc, br}; cuuint32_t estr[2] = {1, 1};
        enc(tm, CU_TENSOR_MAP_DATA_TYPE_BFLOAT16, 2, (void*)ptr, gdim, gstr, box, estr, CU_TENSOR_MAP_INTERLEAVE_NONE, bc == 64 ? CU_TENSOR_MAP_SWIZZLE_128B : CU_TENSOR_MAP_SWIZZLE_64B,
            CU_TENSOR_MAP_L2_PROMOTION_L2_256B, CU_TENSOR_MAP_FLOAT_OOB_FILL_NONE);
    };
    static bool attr_done = false;
    if (!attr_done) {
        cudaFuncSetAttribute(chain_kernel, cudaFuncAttributeMaxDynamicSharedMemorySize, SM_TOTAL);
        cudaFuncSetAttribute(side_kernel, cudaFuncAttributeMaxDynamicSharedMemorySize, SD_TOTAL);
        attr_done = true;
    }
    CUtensorMap tmx, tmw, tmq, tmk, tmv, tmo;
    {
        cuuint64_t gdim[3] = {64, S_LEN, DM / 64}; cuuint64_t gstr[2] = {DM * 2, 128}; cuuint32_t box[3] = {64, SEG, 3}; cuuint32_t estr[3] = {1, 1, 1};
        enc(&tmx, CU_TENSOR_MAP_DATA_TYPE_BFLOAT16, 3, (void*)x, gdim, gstr, box, estr, CU_TENSOR_MAP_INTERLEAVE_NONE, CU_TENSOR_MAP_SWIZZLE_128B,
            CU_TENSOR_MAP_L2_PROMOTION_L2_256B, CU_TENSOR_MAP_FLOAT_OOB_FILL_NONE);
    }
    mk(&tmw, Wo, DM, NH * DH, 64, 256);
    mk(&tmo, Wo, DM, NH * DH, 32, 128);
    mk(&tmq, Wq, NH * DH, DM, 32, 48); mk(&tmk, Wk, NH * DH, DM, 32, 48); mk(&tmv, Wv, NH * DH, DM, 32, 48);
    chain_kernel<<<96, CH_THREADS, SM_TOTAL>>>(tmx, tmq, tmk, tmv, tmo, mem0, 0u);
    cudaLaunchConfig_t cfg = {};
    cfg.gridDim = dim3(SD_CTAS); cfg.blockDim = dim3(SD_THREADS); cfg.dynamicSmemBytes = SD_TOTAL; cfg.stream = cudaStreamPerThread;
    cudaLaunchAttribute at[1];
    at[0].id = cudaLaunchAttributeProgrammaticStreamSerialization; at[0].val.programmaticStreamSerializationAllowed = 1;
    cfg.attrs = at; cfg.numAttrs = 1;
    cudaLaunchKernelEx(&cfg, side_kernel, tmw, x, log_A_real, A_imag, C_real, C_imag, log_dt, D_skip, gate_w, out);
}
```

```cpp
#include <cuda_runtime.h>
#include <cuda.h>
#include <cuda_bf16.h>
#include <stdint.h>

#define S_LEN 2048
#define DM 576
#define NH 32
#define DH 128
#define NMEM 8
#define SEG 32
#define NSEG 64
#define LQ 40
#define NS 128

typedef __nv_bfloat16 bf16;

__device__ __forceinline__ float bf(bf16 v) { return __bfloat162float(v); }
__device__ __forceinline__ bf16 tobf(float v) { return __float2bfloat16_rn(v); }
__device__ __forceinline__ float rbf(float v) { return __bfloat162float(__float2bfloat16_rn(v)); }

#define CH_THREADS 384
#define SPIN_LIMIT (1 << 17)
#define SM_X     0
#define XBUF     36864
#define SM_TOK   73728
#define TOKBUF   24576
#define SM_STASH 139264
#define SM_TS    (SM_STASH + 3072)
#define SM_WO    147456
#define SM_MEM   196608
#define SM_EX    205824
#define EXBUF    6144
#define SM_P     218112
#define SM_OST   219136
#define SM_O     223232
#define SM_BAR   228352
#define SM_IL    (SM_BAR + 128)
#define SM_SG    (SM_IL + 256)
#define SM_TOTAL (SM_SG + 64)

#define ACC_X    36864
#define ACC_FULL 0x0020u
#define SLOT_OFF(sl) ((((sl) & 1) << 7) | (((sl) & 2) << 8))
__device__ __align__(65536) unsigned char g_acc[65536];
__device__ unsigned int g_init[96];
__device__ unsigned int g_epoch = 1;
__device__ __align__(128) unsigned int g_ts[128];
__device__ __align__(1024) bf16 g_otok[S_LEN * NH * DH];
__device__ __align__(1024) unsigned char g_tokx[96][8192];
__device__ __align__(128) unsigned int g_prog[96];
#define STAMP(i)
#define STAMPV(i, v)
#define GT(b, i)
#define STAMPB(i)

__device__ __forceinline__ uint32_t smem_u32(const void* p) { return (uint32_t)__cvta_generic_to_shared(p); }
__device__ __forceinline__ void ldsm_x4(uint32_t (&r)[4], uint32_t addr) {
    asm volatile("ldmatrix.sync.aligned.m8n8.x4.shared.b16 {%0,%1,%2,%3}, [%4];" : "=r"(r[0]), "=r"(r[1]), "=r"(r[2]), "=r"(r[3]) : "r"(addr) : "memory");
}
__device__ __forceinline__ void ldsm_x4_p(uint32_t (&r)[4], uint32_t addr, uint32_t skip) {
    asm volatile("{\n.reg .pred p;\nsetp.eq.u32 p, %5, 0;\n@p ldmatrix.sync.aligned.m8n8.x4.shared.b16 {%0,%1,%2,%3}, [%4];\n}\n" : "+r"(r[0]), "+r"(r[1]), "+r"(r[2]), "+r"(r[3]) : "r"(addr), "r"(skip) : "memory");
}
__device__ __forceinline__ void ldsm_x4_t(uint32_t (&r)[4], uint32_t addr) {
    asm volatile("ldmatrix.sync.aligned.m8n8.x4.trans.shared.b16 {%0,%1,%2,%3}, [%4];" : "=r"(r[0]), "=r"(r[1]), "=r"(r[2]), "=r"(r[3]) : "r"(addr) : "memory");
}
__device__ __forceinline__ uint32_t ldsm_x1_t(uint32_t addr) {
    uint32_t r; asm volatile("ldmatrix.sync.aligned.m8n8.x1.trans.shared.b16 {%0}, [%1];" : "=r"(r) : "r"(addr) : "memory"); return r;
}
__device__ __forceinline__ void ldsm_x2_t(uint32_t& r0, uint32_t& r1, uint32_t addr) {
    asm volatile("ldmatrix.sync.aligned.m8n8.x2.trans.shared.b16 {%0,%1}, [%2];" : "=r"(r0), "=r"(r1) : "r"(addr) : "memory");
}
__device__ __forceinline__ void stsm_x4(uint32_t addr, uint32_t r0, uint32_t r1, uint32_t r2, uint32_t r3) {
    asm volatile("stmatrix.sync.aligned.m8n8.x4.shared.b16 [%0], {%1,%2,%3,%4};" :: "r"(addr), "r"(r0), "r"(r1), "r"(r2), "r"(r3) : "memory");
}
__device__ __forceinline__ void stsm_x4_t(uint32_t addr, uint32_t r0, uint32_t r1, uint32_t r2, uint32_t r3) {
    asm volatile("stmatrix.sync.aligned.m8n8.x4.trans.shared.b16 [%0], {%1,%2,%3,%4};" :: "r"(addr), "r"(r0), "r"(r1), "r"(r2), "r"(r3) : "memory");
}
__device__ __forceinline__ void mma16816(float (&c)[4], const uint32_t (&a)[4], uint32_t b0, uint32_t b1) {
    asm("mma.sync.aligned.m16n8k16.row.col.f32.bf16.bf16.f32 {%0,%1,%2,%3}, {%4,%5,%6,%7}, {%8,%9}, {%0,%1,%2,%3};"
        : "+f"(c[0]), "+f"(c[1]), "+f"(c[2]), "+f"(c[3]) : "r"(a[0]), "r"(a[1]), "r"(a[2]), "r"(a[3]), "r"(b0), "r"(b1));
}
__device__ __forceinline__ void mma16816r(float (&c)[4], uint32_t a0, uint32_t a1, uint32_t a2, uint32_t a3, uint32_t b0, uint32_t b1) {
    asm("mma.sync.aligned.m16n8k16.row.col.f32.bf16.bf16.f32 {%0,%1,%2,%3}, {%4,%5,%6,%7}, {%8,%9}, {%0,%1,%2,%3};"
        : "+f"(c[0]), "+f"(c[1]), "+f"(c[2]), "+f"(c[3]) : "r"(a0), "r"(a1), "r"(a2), "r"(a3), "r"(b0), "r"(b1));
}
__device__ __forceinline__ void mma1688(float (&c)[4], uint32_t a0, uint32_t a1, uint32_t b0) {
    asm("mma.sync.aligned.m16n8k8.row.col.f32.bf16.bf16.f32 {%0,%1,%2,%3}, {%4,%5}, {%6}, {%0,%1,%2,%3};"
        : "+f"(c[0]), "+f"(c[1]), "+f"(c[2]), "+f"(c[3]) : "r"(a0), "r"(a1), "r"(b0));
}
__device__ __forceinline__ uint32_t pack_bf16(float lo, float hi) {
    uint32_t r; asm("cvt.rn.bf16x2.f32 %0, %1, %2;" : "=r"(r) : "f"(hi), "f"(lo)); return r;
}
__device__ __forceinline__ float bf_lo(uint32_t v) { return __uint_as_float(v << 16); }
__device__ __forceinline__ float bf_hi(uint32_t v) { return __uint_as_float(v & 0xffff0000u); }
__device__ __forceinline__ uint32_t max_bf2(uint32_t a, uint32_t b) { uint32_t r; asm("max.bf16x2 %0, %1, %2;" : "=r"(r) : "r"(a), "r"(b)); return r; }
__device__ __forceinline__ uint32_t maxabs_bf2(uint32_t a, uint32_t b) { uint32_t r; asm("max.NaN.xorsign.abs.bf16x2 %0, %1, %2;" : "=r"(r) : "r"(a), "r"(b)); return r; }
__device__ __forceinline__ float ex2(float x) { float r; asm("ex2.approx.ftz.f32 %0, %1;" : "=f"(r) : "f"(x)); return r; }
__device__ __forceinline__ void ld_relaxed128_p(uint4& v, const uint4* p, uint32_t pred) {
    asm volatile("{\n.reg .pred p;\nsetp.ne.u32 p, %5, 0;\n@p ld.relaxed.gpu.global.v4.u32 {%0,%1,%2,%3}, [%4];\n}\n" : "+r"(v.x), "+r"(v.y), "+r"(v.z), "+r"(v.w) : "l"(p), "r"(pred) : "memory");
}
__device__ __forceinline__ uint4 ld_relaxed128(const uint4* p) { uint4 v; asm volatile("ld.relaxed.gpu.global.v4.u32 {%0,%1,%2,%3}, [%4];" : "=r"(v.x), "=r"(v.y), "=r"(v.z), "=r"(v.w) : "l"(p) : "memory"); return v; }
__device__ __forceinline__ uint32_t ld_relaxed32(const uint32_t* p) { uint32_t v; asm volatile("ld.relaxed.gpu.global.u32 %0, [%1];" : "=r"(v) : "l"(p) : "memory"); return v; }
__device__ __forceinline__ void st_relaxed128(uint4* p, uint4 v) { asm volatile("st.relaxed.gpu.global.v4.u32 [%0], {%1,%2,%3,%4};" :: "l"(p), "r"(v.x), "r"(v.y), "r"(v.z), "r"(v.w) : "memory"); }
__device__ __forceinline__ void st_relaxed32(uint32_t* p, uint32_t v) { asm volatile("st.relaxed.gpu.global.u32 [%0], %1;" :: "l"(p), "r"(v) : "memory"); }
__device__ __forceinline__ void st_relaxed128_p(uint4* p, uint4 v, uint32_t skip) {
    asm volatile("{\n.reg .pred p;\nsetp.eq.u32 p, %5, 0;\n@p st.relaxed.gpu.global.v4.u32 [%0], {%1,%2,%3,%4};\n}\n" :: "l"(p), "r"(v.x), "r"(v.y), "r"(v.z), "r"(v.w), "r"(skip) : "memory");
}
__device__ __forceinline__ void st_relaxed64_p(void* p, uint32_t x, uint32_t y, uint32_t skip) {
    asm volatile("{\n.reg .pred p;\n.reg .b64 v;\nsetp.eq.u32 p, %3, 0;\nmov.b64 v, {%1,%2};\n@p st.relaxed.gpu.global.b64 [%0], v;\n}\n" :: "l"(p), "r"(x), "r"(y), "r"(skip) : "memory");
}
__device__ __forceinline__ void ld_relaxed64_p(uint2& v, const void* p, uint32_t pred) {
    asm volatile("{\n.reg .pred p;\n.reg .b64 v;\nsetp.ne.u32 p, %3, 0;\nmov.b64 v, {%0,%1};\n@p ld.relaxed.gpu.global.b64 v, [%2];\nmov.b64 {%0,%1}, v;\n}\n" : "+r"(v.x), "+r"(v.y) : "l"(p), "r"(pred) : "memory");
}
__device__ __forceinline__ uint2 ld_relaxed64(const void* p) {
    uint2 v; asm volatile("{\n.reg .b64 v;\nld.relaxed.gpu.global.b64 v, [%2];\nmov.b64 {%0,%1}, v;\n}\n" : "=r"(v.x), "=r"(v.y) : "l"(p) : "memory"); return v;
}
__device__ __forceinline__ void st_relaxed32_p(void* p, uint32_t v, uint32_t skip) {
    asm volatile("{\n.reg .pred p;\nsetp.eq.u32 p, %2, 0;\n@p st.relaxed.gpu.global.u32 [%0], %1;\n}\n" :: "l"(p), "r"(v), "r"(skip) : "memory");
}
__device__ __forceinline__ void bar_arrive_p(int id, int n, uint32_t skip) {
    asm volatile("{\n.reg .pred p;\nsetp.eq.u32 p, %2, 0;\n@p bar.arrive %0, %1;\n}\n" :: "r"(id), "r"(n), "r"(skip) : "memory");
}
__device__ __forceinline__ void bar_sync_p(int id, int n, uint32_t skip) {
    asm volatile("{\n.reg .pred p;\nsetp.eq.u32 p, %2, 0;\n@p bar.sync %0, %1;\n}\n" :: "r"(id), "r"(n), "r"(skip) : "memory");
}
__device__ __forceinline__ uint32_t movm(uint32_t x) { uint32_t r; asm volatile("movmatrix.sync.aligned.m8n8.trans.b16 %0, %1;" : "=r"(r) : "r"(x)); return r; }
__device__ __forceinline__ void sts32_p(uint32_t a, uint32_t v, uint32_t doit) {
    asm volatile("{\n.reg .pred p;\nsetp.ne.u32 p, %2, 0;\n@p st.shared.u32 [%0], %1;\n}\n" :: "r"(a), "r"(v), "r"(doit) : "memory");
}
__device__ __forceinline__ uint32_t pin(uint32_t x) { return __shfl_sync(0xffffffffu, x, threadIdx.x & 31); }
__device__ __forceinline__ void ldsm16_t(uint32_t (&b)[4][4], uint32_t a) {
    asm volatile("ldmatrix.sync.aligned.m8n8.x4.trans.shared.b16 {%0,%1,%2,%3}, [%16];\n"
                 "ldmatrix.sync.aligned.m8n8.x4.trans.shared.b16 {%4,%5,%6,%7}, [%16+512];\n"
                 "ldmatrix.sync.aligned.m8n8.x4.trans.shared.b16 {%8,%9,%10,%11}, [%16+1024];\n"
                 "ldmatrix.sync.aligned.m8n8.x4.trans.shared.b16 {%12,%13,%14,%15}, [%16+1536];\n"
        : "=r"(b[0][0]), "=r"(b[0][1]), "=r"(b[0][2]), "=r"(b[0][3]), "=r"(b[1][0]), "=r"(b[1][1]), "=r"(b[1][2]), "=r"(b[1][3]),
          "=r"(b[2][0]), "=r"(b[2][1]), "=r"(b[2][2]), "=r"(b[2][3]), "=r"(b[3][0]), "=r"(b[3][1]), "=r"(b[3][2]), "=r"(b[3][3]) : "r"(a) : "memory");
}
template<int ID> __device__ __forceinline__ void sched_fence(uint32_t never) { while (never == 0x7fffff00u + ID) { asm volatile("nanosleep.u32 64;" ::: "memory"); } }
__device__ __forceinline__ uint32_t opaque_u() { uint32_t v; asm volatile("mov.u32 %0, %%nsmid;" : "=r"(v)); return v; }
__device__ __forceinline__ uint32_t bar_red_or(int id, int n, uint32_t v) {
    uint32_t r; asm volatile("{\n.reg .pred p, q;\nsetp.ne.u32 p, %3, 0;\nbar.red.or.pred q, %1, %2, p;\nselp.u32 %0, 1, 0, q;\n}\n" : "=r"(r) : "r"(id), "r"(n), "r"(v) : "memory"); return r;
}
template<class T> __device__ __forceinline__ T* launder_p(T* p) { asm volatile("" : "+l"(p)); return p; }
__device__ __forceinline__ uint32_t mapa_u32(uint32_t addr, uint32_t rank) { uint32_t d; asm("mapa.shared::cluster.u32 %0, %1, %2;" : "=r"(d) : "r"(addr), "r"(rank)); return d; }
__device__ __forceinline__ uint32_t mapa_v(uint32_t addr, uint32_t rank) { uint32_t d; asm volatile("mapa.shared::cluster.u32 %0, %1, %2;" : "=r"(d) : "r"(addr), "r"(rank)); return d; }
__device__ __forceinline__ void st_async32(uint32_t addr, uint32_t v, uint32_t mbar) { asm volatile("st.async.shared::cluster.mbarrier::complete_tx::bytes.u32 [%0], %1, [%2];" :: "r"(addr), "r"(v), "r"(mbar) : "memory"); }
__device__ __forceinline__ void cluster_arrive() { asm volatile("barrier.cluster.arrive.release.aligned;" ::: "memory"); }
__device__ __forceinline__ void cluster_wait() { asm volatile("barrier.cluster.wait.acquire.aligned;" ::: "memory"); }
__device__ __forceinline__ void cp_async16(uint32_t dst, const void* src) { asm volatile("cp.async.cg.shared.global [%0], [%1], 16;" :: "r"(dst), "l"(src) : "memory"); }
__device__ __forceinline__ void cp_async_commit() { asm volatile("cp.async.commit_group;" ::: "memory"); }
template<int N> __device__ __forceinline__ void cp_async_wait() { asm volatile("cp.async.wait_group %0;" :: "n"(N) : "memory"); }
__device__ __forceinline__ void cp_async_wait0() { asm volatile("cp.async.wait_group 0;" ::: "memory"); }
__device__ __forceinline__ void mbar_init(uint32_t a, uint32_t cnt) { asm volatile("mbarrier.init.shared.b64 [%0], %1;" :: "r"(a), "r"(cnt) : "memory"); }
__device__ __forceinline__ void mbar_expect_tx(uint32_t a, uint32_t bytes) { asm volatile("mbarrier.arrive.expect_tx.shared.b64 _, [%0], %1;" :: "r"(a), "r"(bytes) : "memory"); }
__device__ __forceinline__ bool mbar_try(uint32_t a, uint32_t parity) {
    uint32_t ok; asm volatile("{\n.reg .pred p;\nmbarrier.try_wait.parity.shared::cta.b64 p, [%1], %2;\nselp.u32 %0, 1, 0, p;\n}\n" : "=r"(ok) : "r"(a), "r"(parity) : "memory"); return ok;
}
__device__ __forceinline__ void mbar_wait(uint32_t a, uint32_t parity) { int it = 0; bool more; do { more = ++it < SPIN_LIMIT; } while (!mbar_try(a, parity) && more); }
__device__ __forceinline__ void bar_sync(int id, int n) { asm volatile("bar.sync %0, %1;" :: "r"(id), "r"(n) : "memory"); }
__device__ __forceinline__ void bar_arrive(int id, int n) { asm volatile("bar.arrive %0, %1;" :: "r"(id), "r"(n) : "memory"); }
__device__ __forceinline__ void fence_async_smem() { asm volatile("fence.proxy.async.shared::cta;" ::: "memory"); }
__device__ __forceinline__ void sts32(uint32_t a, uint32_t v) { asm volatile("st.shared.u32 [%0], %1;" :: "r"(a), "r"(v) : "memory"); }
__device__ __forceinline__ void sts128(uint32_t a, uint4 v) { asm volatile("st.shared.v4.u32 [%0], {%1,%2,%3,%4};" :: "r"(a), "r"(v.x), "r"(v.y), "r"(v.z), "r"(v.w) : "memory"); }
__device__ __forceinline__ uint4 lds128(uint32_t a) { uint4 v; asm volatile("ld.shared.v4.u32 {%0,%1,%2,%3}, [%4];" : "=r"(v.x), "=r"(v.y), "=r"(v.z), "=r"(v.w) : "r"(a) : "memory"); return v; }
__device__ __forceinline__ uint32_t lds32(uint32_t a) { uint32_t v; asm volatile("ld.shared.u32 %0, [%1];" : "=r"(v) : "r"(a) : "memory"); return v; }
__device__ __forceinline__ uint32_t gtime_lo() { uint32_t t; asm volatile("mov.u32 %0, %globaltimer_lo;" : "=r"(t)); return t; }
__device__ __forceinline__ void wait_gtime(uint32_t tg) {
    asm volatile("{\n.reg .pred p, q;\n.reg .b64 t;\n.reg .b32 lo, hi, d, n;\nmov.b32 n, 300;\n"
                 "WG_%=:\nmov.u64 t, %%globaltimer;\nmov.b64 {lo, hi}, t;\nsub.s32 d, lo, %0;\nsub.s32 n, n, 1;\n"
                 "setp.gt.s32 q, n, 0;\nsetp.lt.and.s32 p, d, 0, q;\n@p bra.uni WG_%=;\n}\n" :: "r"(tg) : "memory");
}
__device__ __forceinline__ void delay_clk(int d) { uint32_t t0 = clock(); while ((int)(clock() - t0) < d) {} }

__device__ __forceinline__ uint64_t desc128(uint32_t addr) {
    return (uint64_t)((addr & 0x3FFFF) >> 4) | ((uint64_t)1 << 16) | ((uint64_t)64 << 32) | ((uint64_t)1 << 62);
}
template<int accum> __device__ __forceinline__ void wgmma_n32(float (&d)[16], const uint32_t (&a)[4], uint64_t desc) {
    if (accum) {
        asm volatile("{\n.reg .pred p;\nsetp.ne.b32 p, 1, 0;\n"
            "wgmma.mma_async.sync.aligned.m64n32k16.f32.bf16.bf16 {%0,%1,%2,%3,%4,%5,%6,%7,%8,%9,%10,%11,%12,%13,%14,%15}, {%16,%17,%18,%19}, %20, p, 1, 1, 0;\n}\n"
            : "+f"(d[0]), "+f"(d[1]), "+f"(d[2]), "+f"(d[3]), "+f"(d[4]), "+f"(d[5]), "+f"(d[6]), "+f"(d[7]),
              "+f"(d[8]), "+f"(d[9]), "+f"(d[10]), "+f"(d[11]), "+f"(d[12]), "+f"(d[13]), "+f"(d[14]), "+f"(d[15])
            : "r"(a[0]), "r"(a[1]), "r"(a[2]), "r"(a[3]), "l"(desc));
    } else {
        asm volatile("{\n.reg .pred p;\nsetp.ne.b32 p, 0, 0;\n"
            "wgmma.mma_async.sync.aligned.m64n32k16.f32.bf16.bf16 {%0,%1,%2,%3,%4,%5,%6,%7,%8,%9,%10,%11,%12,%13,%14,%15}, {%16,%17,%18,%19}, %20, p, 1, 1, 0;\n}\n"
            : "=f"(d[0]), "=f"(d[1]), "=f"(d[2]), "=f"(d[3]), "=f"(d[4]), "=f"(d[5]), "=f"(d[6]), "=f"(d[7]),
              "=f"(d[8]), "=f"(d[9]), "=f"(d[10]), "=f"(d[11]), "=f"(d[12]), "=f"(d[13]), "=f"(d[14]), "=f"(d[15])
            : "r"(a[0]), "r"(a[1]), "r"(a[2]), "r"(a[3]), "l"(desc));
    }
}
__device__ __forceinline__ float rcp_approx(float x) { float r; asm("rcp.approx.ftz.f32 %0, %1;" : "=f"(r) : "f"(x)); return r; }
__device__ __forceinline__ void wg_fence() { asm volatile("wgmma.fence.sync.aligned;" ::: "memory"); }
__device__ __forceinline__ void wg_commit() { asm volatile("wgmma.commit_group.sync.aligned;" ::: "memory"); }
__device__ __forceinline__ void wg_wait0() { asm volatile("wgmma.wait_group.sync.aligned 0;" ::: "memory"); }

#define SCALE_HI 0x3db53db5u
#define SCALE_LO 0x371e371eu
#define LOG2E 1.4426950408889634f
#define NEG_BIG2 0xce6ece6eu
__device__ __forceinline__ uint32_t scale_bf2(uint32_t x) {
    uint32_t t, r;
    asm("mul.rn.bf16x2 %0, %1, %2;" : "=r"(t) : "r"(x), "r"(SCALE_LO));
    asm("fma.rn.bf16x2 %0, %1, %2, %3;" : "=r"(r) : "r"(x), "r"(SCALE_HI), "r"(t));
    return r;
}
__device__ __forceinline__ void cluster_arrive_rx() { asm volatile("barrier.cluster.arrive.relaxed.aligned;" ::: "memory"); }
__device__ __forceinline__ uint32_t launder(uint32_t x) { asm volatile("" : "+r"(x)); return x; }
__device__ __forceinline__ void mbar_arrive(uint32_t a) { asm volatile("mbarrier.arrive.shared.b64 _, [%0];" :: "r"(a) : "memory"); }
__device__ __forceinline__ void mbar_wait_cl(uint32_t a, uint32_t parity) {
    int it = 0; uint32_t ok;
    do { asm volatile("{\n.reg .pred p;\nmbarrier.try_wait.parity.acquire.cluster.shared::cta.b64 p, [%1], %2;\nselp.u32 %0, 1, 0, p;\n}\n" : "=r"(ok) : "r"(a), "r"(parity) : "memory"); } while (!ok && ++it < SPIN_LIMIT);
}
__device__ __forceinline__ uint64_t desc_from(uint32_t lo) { return (uint64_t)lo | ((uint64_t)0x40000040u << 32); }
#define SB_OFF 1024u
#define DESC_LO(off) ((((SB_OFF + (uint32_t)(off)) & 0x3FFFFu) >> 4) | 0x10000u)
template<int N> struct ic { static constexpr int value = N; };
__device__ __forceinline__ uint32_t uni(uint32_t x) { return __shfl_sync(0xffffffffu, x, 0); }

__device__ __forceinline__ uint32_t pack_f16(float lo, float hi) { uint32_t r; asm("cvt.rn.f16x2.f32 %0, %1, %2;" : "=r"(r) : "f"(hi), "f"(lo)); return r; }
__device__ __forceinline__ void sts16(uint32_t a, uint16_t v) { asm volatile("st.shared.u16 [%0], %1;" :: "r"(a), "h"(v) : "memory"); }
__device__ __forceinline__ void sts64(uint32_t a, uint32_t x, uint32_t y) { asm volatile("st.shared.v2.u32 [%0], {%1,%2};" :: "r"(a), "r"(x), "r"(y) : "memory"); }
__device__ __forceinline__ void ld_relaxed32_p(uint32_t& v, const void* p, uint32_t pred) {
    asm volatile("{\n.reg .pred p;\nsetp.ne.u32 p, %2, 0;\n@p ld.relaxed.gpu.global.u32 %0, [%1];\n}\n" : "+r"(v) : "l"(p), "r"(pred) : "memory");
}
__device__ __forceinline__ uint2 lds64(uint32_t a) { uint2 v; asm volatile("ld.shared.v2.u32 {%0,%1}, [%2];" : "=r"(v.x), "=r"(v.y) : "r"(a) : "memory"); return v; }
__device__ __forceinline__ void mbar_wait2(uint32_t a, uint32_t pa, uint32_t b, uint32_t pb) {
    int it = 0; uint32_t ok;
    do { asm volatile("{\n.reg .pred p, q;\nmbarrier.try_wait.parity.shared::cta.b64 p, [%1], %2;\nmbarrier.try_wait.parity.shared::cta.b64 q, [%3], %4;\nand.pred p, p, q;\nselp.u32 %0, 1, 0, p;\n}\n"
                      : "=r"(ok) : "r"(a), "r"(pa), "r"(b), "r"(pb) : "memory"); } while (!ok && ++it < SPIN_LIMIT);
}
__device__ __forceinline__ float exd(float s, float m) { return ex2(__fmul_rn(__fsub_rn(s, m), LOG2E)); }
__device__ __forceinline__ uint32_t gtime_after(uint32_t z) {
    uint32_t t = 0; asm volatile("{\n.reg .pred p;\nsetp.eq.u32 p, %1, 0;\n@p mov.u32 %0, %%globaltimer_lo;\n}\n" : "+r"(t) : "r"(z)); return t;
}
#define T_HOLD 0
#define T_KPRE 3
#define BLK_Q(p) (((p) < 3 ? (p) : 8) * 2048)
#define BLK_K(p) (((p) < 3 ? 4 + (p) : 9) * 2048)
#define BLK_V(p) (((p) < 2 ? 3 + 4 * (p) : 8 + (p)) * 2048)
__device__ __forceinline__ uint32_t exp_bf2(uint32_t s) { return pack_bf16(ex2(bf_lo(s) * LOG2E), ex2(bf_hi(s) * LOG2E)); }
template<int MT, int LO, int HI>
__device__ __forceinline__ void tok_loadv(uint32_t tok, int eh, int lane, uint32_t (&bv)[8][4]) {
    const int r8 = lane & 7;
    const uint32_t va = MT ? tok + lane * 64 + ((r8 >> 1) << 4) : tok + (lane & 15) * 64 + (((lane >> 4) ^ (r8 >> 1)) << 4);
    const uint32_t o0 = eh ? BLK_V(2) : BLK_V(0), o1 = eh ? BLK_V(3) : BLK_V(1);
    #pragma unroll
    for (int n = LO; n < HI; n++) { if (MT) ldsm_x4_t(bv[n], (va ^ ((n & 3) << 4)) + (n < 4 ? o0 : o1)); else ldsm_x4_t(bv[n], (va ^ ((n & 1) << 5)) + BLK_V(n >> 1)); }
}
#define T_VPRE 4
template<int MT, class F>
__device__ __forceinline__ void tok_part1(uint32_t tok, int eh, int lane, uint32_t (&q)[8][4], uint32_t (&sp)[5][2], uint32_t (&pa)[5][2], uint32_t (&bv)[8][4], uint32_t& rng, F&& hold) {
    float e[5][4];
    constexpr int NK = MT ? 5 : 3;
    const int g = lane >> 2, t = lane & 3, mi = lane >> 3, r8 = lane & 7;
    #pragma unroll
    for (int nt = 1; nt < NK; nt++) { e[nt][0] = e[nt][1] = e[nt][2] = e[nt][3] = 0.f; }
    const uint32_t qa = tok + (16 * MT + (mi & 1) * 8 + r8) * 64 + (((mi >> 1) ^ (r8 >> 1)) << 4);
    const uint32_t ka = tok + r8 * 64 + ((mi ^ (r8 >> 1)) << 4);
    uint32_t b[4][NK][4];
    constexpr int PRE = T_HOLD == 3 ? (MT ? T_KPRE : 4) : 0;
    #pragma unroll
    for (int k2 = 0; k2 < 4; k2++) {
        if (T_HOLD == 3) { ldsm_x4(q[2 * k2], qa + BLK_Q(k2)); ldsm_x4(q[2 * k2 + 1], (qa ^ 32) + BLK_Q(k2)); }
        if (k2 < PRE) {
            #pragma unroll
            for (int nt = 1; nt < NK; nt++) ldsm_x4(b[k2][nt], ka + BLK_K(k2) + (nt - 1) * 512);
        }
    }
    if (T_HOLD == 3) hold();
    #pragma unroll
    for (int k2 = 0; k2 < 4; k2++) {
        if (T_HOLD != 3) { ldsm_x4(q[2 * k2], qa + BLK_Q(k2)); ldsm_x4(q[2 * k2 + 1], (qa ^ 32) + BLK_Q(k2)); }
        if (k2 >= PRE) {
            #pragma unroll
            for (int nt = 1; nt < NK; nt++) ldsm_x4(b[k2][nt], ka + BLK_K(k2) + (nt - 1) * 512);
        }
        #pragma unroll
        for (int nt = 1; nt < NK; nt++) mma16816(e[nt], q[2 * k2], b[k2][nt][0], b[k2][nt][1]);
        #pragma unroll
        for (int nt = 1; nt < NK; nt++) mma16816(e[nt], q[2 * k2 + 1], b[k2][nt][2], b[k2][nt][3]);
    }
    #pragma unroll
    for (int nt = 1; nt < NK; nt++) asm volatile("" : "+f"(e[nt][0]), "+f"(e[nt][1]), "+f"(e[nt][2]), "+f"(e[nt][3]));
    if (T_HOLD != 3) hold();
    #pragma unroll
    for (int nt = 1; nt < NK; nt++) {
        sp[nt][0] = nt < NK - 1 ? scale_bf2(pack_bf16(e[nt][0], e[nt][1])) : NEG_BIG2; sp[nt][1] = scale_bf2(pack_bf16(e[nt][2], e[nt][3]));
        rng = maxabs_bf2(nt == 1 ? sp[1][0] : (nt < NK - 1 ? maxabs_bf2(rng, sp[nt][0]) : rng), sp[nt][1]);
    }
    const uint32_t keep = (2 * t <= g ? 0x0000ffffu : 0u) | (2 * t + 1 <= g ? 0xffff0000u : 0u);
    sp[NK - 2][0] = (sp[NK - 2][0] & keep) | (NEG_BIG2 & ~keep);
    sp[NK - 1][1] = (sp[NK - 1][1] & keep) | (NEG_BIG2 & ~keep);
    #pragma unroll
    for (int nt = 1; nt < NK; nt++) { pa[nt][0] = nt < NK - 1 ? exp_bf2(sp[nt][0]) : 0u; pa[nt][1] = exp_bf2(sp[nt][1]); }
    tok_loadv<MT, 0, MT ? T_VPRE : 8>(tok, eh, lane, bv);
}
template<int MT, class F, class G, class H, class I>
__device__ __forceinline__ void tok_part2(uint32_t tok, uint32_t exl, uint32_t ost, int eh, int lane, const uint32_t (&q)[8][4], uint32_t (&sp)[5][2], uint32_t (&pa)[5][2], uint32_t (&bv)[8][4], uint32_t rng, bool vb,
                                          F&& wait_v, G&& duty, H&& pace, I&& wait_x) {
    constexpr int NK = MT ? 5 : 3;
    const int mi = lane >> 3, r8 = lane & 7;
    {
        float c[4][4];
        uint32_t b[4][4];
        ldsm16_t(b, exl + 2048);
        duty();
        #pragma unroll
        for (int j = 0; j < 4; j++) { c[j][0] = c[j][1] = c[j][2] = c[j][3] = 0.f; }
        #pragma unroll
        for (int k2 = 0; k2 < 4; k2++) { mma16816(c[(2 * k2) & 3], q[2 * k2], b[k2][0], b[k2][1]); mma16816(c[(2 * k2 + 1) & 3], q[2 * k2 + 1], b[k2][2], b[k2][3]); }
        sp[0][0] = scale_bf2(pack_bf16((c[0][0] + c[1][0]) + (c[2][0] + c[3][0]), (c[0][1] + c[1][1]) + (c[2][1] + c[3][1])));
        sp[0][1] = scale_bf2(pack_bf16((c[0][2] + c[1][2]) + (c[2][2] + c[3][2]), (c[0][3] + c[1][3]) + (c[2][3] + c[3][3])));
    }
    pa[0][0] = exp_bf2(sp[0][0]); pa[0][1] = exp_bf2(sp[0][1]);
    rng = maxabs_bf2(maxabs_bf2(rng, sp[0][0]), sp[0][1]);
    if (__builtin_expect(__any_sync(0xffffffffu, ((rng & 0x7fff7fffu) + 0x3ddf3ddfu) & 0x80008000u), 0)) {
        uint32_t m0 = sp[0][0], m1 = sp[0][1];
        #pragma unroll
        for (int nt = 1; nt < NK; nt++) { if (nt < NK - 1) m0 = max_bf2(m0, sp[nt][0]); m1 = max_bf2(m1, sp[nt][1]); }
        uint32_t mm = max_bf2(__byte_perm(m0, m1, 0x5410), __byte_perm(m0, m1, 0x7632));
        mm = max_bf2(mm, __shfl_xor_sync(0xffffffffu, mm, 1));
        mm = max_bf2(mm, __shfl_xor_sync(0xffffffffu, mm, 2));
        #pragma unroll
        for (int nt = 0; nt < NK; nt++) {
            if (nt < NK - 1) pa[nt][0] = pack_bf16(exd(bf_lo(sp[nt][0]), bf_lo(mm)), exd(bf_hi(sp[nt][0]), bf_lo(mm)));
            pa[nt][1] = pack_bf16(exd(bf_lo(sp[nt][1]), bf_hi(mm)), exd(bf_hi(sp[nt][1]), bf_hi(mm)));
        }
    }
    tok_loadv<MT, MT ? T_VPRE : 8, 8>(tok, eh, lane, bv);
    wait_v();
    constexpr int NQ = MT ? 2 : 4;
    float o[NQ][4][4], l[4] = {0.f, 0.f, 0.f, 0.f};
    const uint32_t ONE = 0x3F803F80u;
    mma16816r(l, pa[1][0], pa[1][1], pa[2][0], pa[2][1], ONE, ONE);
    if (MT) mma16816r(l, pa[3 % NK][0], pa[3 % NK][1], pa[4 % NK][0], pa[4 % NK][1], ONE, ONE);
    mma1688(l, pa[0][0], pa[0][1], ONE);
    #pragma unroll
    for (int j = 0; j < NQ; j++) {
        uint32_t bm[4];
        ldsm_x4(bm, exl + 4096 + (MT ? eh * 1024 : 0) + 512 * j);
        #pragma unroll
        for (int n = 0; n < 4; n++) {
            o[j][n][0] = o[j][n][1] = o[j][n][2] = o[j][n][3] = 0.f;
            if (MT) mma16816r(o[j][n], pa[1][0], pa[1][1], pa[2][0], pa[2][1], bv[4 * j + n][0], bv[4 * j + n][1]);
            else mma16816r(o[j][n], pa[1][0], pa[1][1], pa[2][0], pa[2][1], bv[2 * j + (n >> 1)][2 * (n & 1)], bv[2 * j + (n >> 1)][2 * (n & 1) + 1]);
        }
        if (MT) {
            #pragma unroll
            for (int n = 0; n < 4; n++) mma16816r(o[j][n], pa[3 % NK][0], pa[3 % NK][1], pa[4 % NK][0], pa[4 % NK][1], bv[4 * j + n][2], bv[4 * j + n][3]);
        }
        #pragma unroll
        for (int n = 0; n < 4; n++) mma1688(o[j][n], pa[0][0], pa[0][1], bm[n]);
    }
    #pragma unroll
    for (int j = 0; j < NQ; j++) asm volatile("" : "+f"(o[j][0][0]), "+f"(o[j][1][0]), "+f"(o[j][2][0]), "+f"(o[j][3][0]));
    asm volatile("" : "+f"(l[0]), "+f"(l[2]));
    wait_x();
    bar_arrive_p(12, 384, !vb);
    pace();
    const float i0 = rcp_approx(l[0]), i1 = rcp_approx(l[2]);
    const uint32_t oa = ost + ((mi & 1) * 8 + r8) * 128 + (((mi >> 1) ^ r8) << 4);
    #pragma unroll
    for (int j = 0; j < NQ; j++) {
        stsm_x4((oa ^ ((j & 1) << 6)) + (j >> 1) * 2048, pack_bf16(o[j][0][0] * i0, o[j][0][1] * i0), pack_bf16(o[j][0][2] * i1, o[j][0][3] * i1), pack_bf16(o[j][1][0] * i0, o[j][1][1] * i0), pack_bf16(o[j][1][2] * i1, o[j][1][3] * i1));
        stsm_x4((oa ^ (((j & 1) << 6) | 32)) + (j >> 1) * 2048, pack_bf16(o[j][2][0] * i0, o[j][2][1] * i0), pack_bf16(o[j][2][2] * i1, o[j][2][3] * i1), pack_bf16(o[j][3][0] * i0, o[j][3][1] * i0), pack_bf16(o[j][3][2] * i1, o[j][3][3] * i1));
    }
}

#define X_PRED "@q "
#define X_LANE(ll) ((ll) >> 4)
#define SEND_LANE(ll) ((ll) >> 2)
#define TP_E 0
#define V_EARLY 1
#ifndef M_SF
#define M_SF 0
#endif
#ifndef M_F2
#define M_F2 0
#endif
#ifndef M_FENCE
#define M_FENCE 0
#endif
#define SW_FENCE 0
#define PV_FENCE 1
#define IL_AT 3
#define TAIL 0
#define MP_PRE 4
#define VF_EARLY 1
__device__ __forceinline__ void stsm2_p(uint32_t a, const uint32_t (&v)[8], uint32_t skip) {
    asm volatile("{\n.reg .pred p;\nsetp.eq.u32 p, %9, 0;\n@p stmatrix.sync.aligned.m8n8.x4.trans.shared.b16 [%0], {%1,%2,%3,%4};\n"
                 "@p stmatrix.sync.aligned.m8n8.x4.trans.shared.b16 [%0+1024], {%5,%6,%7,%8};\n}\n"
        :: "r"(a), "r"(v[0]), "r"(v[1]), "r"(v[2]), "r"(v[3]), "r"(v[4]), "r"(v[5]), "r"(v[6]), "r"(v[7]), "r"(skip) : "memory");
}
template<int OA, int OB>
__device__ __forceinline__ void send_tile(float c0, float c1, float c2, float c3, uint32_t a, uint32_t b, uint32_t l16) {
    const uint32_t hi = (uint32_t)((uint64_t)g_acc >> 32);
    asm volatile("{\n.reg .pred q, pl, ph;\n.reg .b64 pa, pb;\n.reg .b32 t, w0, w1, w2;\n.reg .f32 x, y, z;\n"
                 "and.b32 t, %7, 0x30;\nsetp.eq.u32 q, t, 0;\nand.b32 t, %7, 0x70;\nsetp.eq.u32 ph, t, 0;\nxor.pred pl, q, ph;\n"
                 "selp.f32 x, 0f00010000, %4, pl;\nselp.f32 y, 0f00010000, %6, ph;\nselp.f32 z, %6, %4, ph;\n"
                 "cvt.rn.bf16x2.f32 w0, x, %3;\ncvt.rn.bf16x2.f32 w1, y, %5;\ncvt.rn.bf16x2.f32 w2, 0f00010000, z;\n"
                 "mov.b64 pa, {%0, %2};\nmov.b64 pb, {%1, %2};\n"
                 "red.relaxed.gpu.global.add.noftz.bf16x2 [pa+%8], w0;\nred.relaxed.gpu.global.add.noftz.bf16x2 [pa+%10], w1;\n" X_PRED "red.relaxed.gpu.global.add.noftz.bf16x2 [pb+%9], w2;\n}\n"
        :: "r"(a), "r"(b), "r"(hi), "f"(c0), "f"(c1), "f"(c2), "f"(c3), "r"(l16), "n"(OA), "n"(OB), "n"(OA + 256) : "memory");
}
__device__ __forceinline__ uint32_t send_ua(uint32_t tile) { return (uint32_t)(uint64_t)g_acc + tile * 1024; }
__device__ __forceinline__ uint32_t send_ub(uint32_t tile) { return (uint32_t)(uint64_t)g_acc + ACC_X + (tile >> 1) * 1024 + (tile & 1) * 256; }
__device__ __forceinline__ void lds_il(float& il, float& ih, uint32_t a) {
    uint32_t x, y; asm volatile("ldmatrix.sync.aligned.m8n8.x2.shared.b16 {%0,%1}, [%2];" : "=r"(x), "=r"(y) : "r"(a) : "memory");
    il = __uint_as_float(x); ih = __uint_as_float(y);
}
template<bool OWN, class F>
__device__ __forceinline__ void stage_w(const uint32_t (&wo)[8][4], uint32_t ol, uint32_t tile, uint32_t so, uint32_t l16, uint32_t nv, uint32_t ila, F&& issued) {
    float il, ih;
    uint32_t b[4][4], sa, sb_, ll;
    float c[2][4];
    auto addr = [&] {
        ll = OWN ? l16 : l16 | (__float_as_uint(c[0][0]) & nv);
        sa = SEND_LANE(ll) + (send_ua(tile) + so); sb_ = X_LANE(ll) + (send_ub(tile) + so);
    };
    ldsm16_t(b, ol);
    lds_il(il, ih, ila);
    if (OWN) addr();
    if (!OWN || SW_FENCE) sched_fence<0>(nv);
    #pragma unroll
    for (int i = 0; i < 2; i++) c[i][0] = c[i][1] = c[i][2] = c[i][3] = 0.f;
    #pragma unroll
    for (int j = 0; j < 4; j++) {
        if (!OWN && j == 3) addr();
        mma16816(c[0], wo[2 * j], b[j][0], b[j][1]); mma16816(c[1], wo[2 * j + 1], b[j][2], b[j][3]);
    }
    if (TP_E || (OWN && V_EARLY)) { asm volatile("" : "+f"(c[0][0]), "+f"(c[1][0])); sched_fence<OWN ? 4 : 5>(nv); }
    issued();
    send_tile<0, 0>((c[0][0] + c[1][0]) * il, (c[0][1] + c[1][1]) * ih, (c[0][2] + c[1][2]) * il, (c[0][3] + c[1][3]) * ih, sa, sb_, l16);
}

template<int N> __device__ __forceinline__ void code_pad(uint32_t nv) {
    if (N && nv == 0x7fffffe0u + N % 16) {
        float v = __uint_as_float(nv);
        #pragma unroll
        for (int i = 0; i < N; i++) asm volatile("fma.rn.f32 %0, %0, %0, %0;" : "+f"(v));
        sts32_p(0u, __float_as_uint(v), nv);
    }
}
#define PAD_T0 0
#define PAD_T1 0
#define PAD_S 0
#define PAD_P 0
#define BAR_PRO 1
#define BAR_MEM 2
#define BAR_P   3
#define BAR_PRJ 4
#define BAR_VGO 7
#define BAR_X0  7
#define BAR_S   9
#define BAR_P2  10
#define BAR_O   11
#define BAR_O2  14
#define BAR_TP  15
#define BAR_V   12
#define BAR_FB  13
#define VGO_AT 9
#define TP_N 36
#define TP_N1 24
#define REG_P 200
#define W_FENCE 1
#define WO_PRE 3
#define WO_MID 8
#define WO_EX 8
#define WO_REP 2
#define TP_DELAY 0
#define PRE_W 4
#ifndef M_RES
#define M_RES 5
#endif
#define K_PRE 6
#define K_POS 0
#define LD_FENCE 0
#define CV_FENCE 4
#define ANN_POS 3
#define PRO_V 0
#define PUB_W 0
#define ST_AT 4
#define MEM_N 352
#define VGO_N (256 + (T_HOLD == 2 ? 32 : 0) + (TAIL ? 32 : 0))
#define PRO_N ((PRO_V ? 256 : 32 * nqk) + (K_PRE < 8 ? 64 : 0) + ((T_HOLD & 1) ? 32 : 0))
#define S_DUTY 0
#define X_POS 1
#define K_OWN 1
#define TM_PF 1
#define TS_CAP 64
#define G1_MIN 128
#define G1_0 256
#define G1_NS 1216

__global__ void __cluster_dims__(3, 1, 1) __launch_bounds__(CH_THREADS, 1)
chain_kernel(const __grid_constant__ CUtensorMap tmx, const __grid_constant__ CUtensorMap tmq, const __grid_constant__ CUtensorMap tmk,
             const __grid_constant__ CUtensorMap tmv, const __grid_constant__ CUtensorMap tmo, const bf16* __restrict__ mem0, const uint32_t nv_) {
    extern __shared__ __align__(1024) unsigned char smem[];
    const uint32_t sb = smem_u32(smem);
    const int tid = threadIdx.x, lane = tid & 31;
    const int warp = __shfl_sync(0xffffffffu, tid >> 5, 0);
    const uint32_t nv = __shfl_sync(0xffffffffu, nv_ * tid, 0);
    const int h = blockIdx.x / 3, r = blockIdx.x % 3;
    const int mi = lane >> 3, r8 = lane & 7;
    const uint32_t bX = sb + SM_BAR, bTOK = bX + 16, bEX = bX + 40, bW = bX + 64, bEV = bX + 104, bFREE = bX + 32;
    const int nqk = r < 2 ? 6 : 4;
    if ((sb & 0xFFFFFFu) != SB_OFF) __trap();
    asm volatile("griddepcontrol.launch_dependents;");
    if (tid == 0 && blockIdx.x == 0) GT(40, 0);

    auto load_w = [&](int lo, int hi) {
        #pragma unroll 1
        for (int i = lo; i < hi; i++) {
            const int blk = i >> 2, j = i & 3;
            if (i < 48) {
                const int m = r < 2 ? (j < 3 ? r : 2) : (j < 2 ? j : 2), p = r < 2 ? (j < 3 ? j : r) : (j < 2 ? 3 : j);
                asm volatile("cp.async.bulk.tensor.2d.shared::cluster.global.mbarrier::complete_tx::bytes [%0], [%1, {%3, %4}], [%2];"
                    :: "r"(sb + i * 3072), "l"(m == 0 ? &tmq : (m == 1 ? &tmk : &tmv)), "r"(bW + (blk < 3 ? 0 : (blk < 6 ? 8 : (blk < 10 ? 16 : 24)))), "r"(h * DH + p * 32), "r"(blk * 48) : "memory");
            } else asm volatile("cp.async.bulk.tensor.2d.shared::cluster.global.mbarrier::complete_tx::bytes [%0], [%1, {%3, %4}], [%2];"
                :: "r"(sb + SM_WO + (i - 48) * 8192), "l"(&tmo), "r"(bW + 32), "r"(192 * r + 32 * (i - 48)), "r"(h * DH) : "memory");
        }
    };
    if (tid == 352) {
        #pragma unroll
        for (int i = 0; i < 15; i++) mbar_init(bX + 8 * i, (i == 5 || i == 6) ? 1 + nqk : (i >= 13 ? 9 - nqk : 1));
        asm volatile("fence.mbarrier_init.release.cluster;" ::: "memory");
        mbar_expect_tx(bW, 36864); mbar_expect_tx(bW + 8, 36864); mbar_expect_tx(bW + 16, 49152); mbar_expect_tx(bW + 24, 24576); mbar_expect_tx(bW + 32, 49152);
        load_w(0, 2 * PRE_W);
    }
    if (TM_PF && tid < 2) asm volatile("prefetch.param.tensormap [%0];" :: "l"(__cvta_generic_to_grid_constant(tid ? &tmo : &tmx)) : "memory");
    const unsigned epoch = ld_relaxed32(&g_epoch);
    __syncthreads();
    const uint32_t pw0 = ((mi >> 1) * 8 + r8) * 64 + (((2 * (warp & 1) + (mi & 1)) ^ (r8 >> 1)) << 4);
    auto tok_publish = [&](int tb, int k) {
        const uint32_t src = sb + SM_TOK + tb * TOKBUF + r * 8192, bar = bTOK + 8 * tb;
        if (k == 1) asm volatile("{\n.reg .pred p;\nelect.sync _|p, 0xffffffff;\n@p mbarrier.arrive.expect_tx.shared.b64 _, [%0], 16384;\n}\n" :: "r"(bar) : "memory");
        asm volatile("{\n.reg .pred p;\nelect.sync _|p, 0xffffffff;\n"
                     "@p cp.async.bulk.shared::cluster.shared::cta.mbarrier::complete_tx::bytes [%0], [%1], 8192, [%2];\n}\n"
            :: "r"(mapa_u32(src, (r + k) % 3)), "r"(src), "r"(mapa_u32(bar, (r + k) % 3)) : "memory");
    };
    if (warp < 8) {
        asm volatile("setmaxnreg.inc.sync.aligned.u32 %0;" :: "n"(REG_P));
        uint32_t wf[36][4];
        const uint32_t wl = sb + (warp >> 1) * 3072 + pw0;
        float ta0[16], ta1[16];
        auto tp_part = [&](auto lo, auto hi) {
            wg_fence();
            #pragma unroll
            for (int i = lo.value; i < hi.value; i++) {
                if (i == 0) wgmma_n32<0>(ta0, wf[0], desc_from(DESC_LO(SM_X))); else wgmma_n32<1>(ta0, wf[i], desc_from(DESC_LO(SM_X) + (i >> 2) * 256 + (i & 3) * 2));
            }
            #pragma unroll
            for (int i = lo.value; i < hi.value; i++) {
                if (i == 0) wgmma_n32<0>(ta1, wf[0], desc_from(DESC_LO(SM_X + XBUF))); else wgmma_n32<1>(ta1, wf[i], desc_from(DESC_LO(SM_X + XBUF) + (i >> 2) * 256 + (i & 3) * 2));
            }
            wg_commit();
        };
        if (tid == 32) load_w(2 * PRE_W, 40);
        if (tid == 0) GT(41 + blockIdx.x % 3, 7);
        code_pad<PAD_P>(nv);
        mbar_wait(bW, 0);
        #pragma unroll
        for (int i = 0; i < 9; i++) ldsm_x4_t(wf[i], wl + (i / 3) * 12288 + (i % 3) * 1024);
        fence_async_smem(); bar_arrive(BAR_X0, 288);
        mbar_wait(bW + 8, 0);
        #pragma unroll
        for (int i = 9; i < 18; i++) ldsm_x4_t(wf[i], wl + (i / 3) * 12288 + (i % 3) * 1024);
        fence_async_smem(); bar_arrive(BAR_X0 + 1, 288);
        mbar_wait(bX, 0); mbar_wait(bX + 8, 0);
        tp_part(ic<0>(), ic<18>());
        wg_wait0();
        sts128(sb + SM_OST + tid * 16, make_uint4(wf[0][0], wf[0][1], wf[0][2], wf[0][3]));
        mbar_wait(bW + 16, 0);
        #pragma unroll
        for (int i = 18; i < 30; i++) ldsm_x4_t(wf[i], wl + (i / 3) * 12288 + (i % 3) * 1024);
        tp_part(ic<18>(), ic<30>());
        mbar_wait(bW + 24, 0);
        if (tid == 0) GT(41 + blockIdx.x % 3, 0);
        wg_wait0();
        #pragma unroll
        for (int i = 30; i < 36; i++) ldsm_x4_t(wf[i], wl + (i / 3) * 12288 + (i % 3) * 1024);
        fence_async_smem();
        cluster_arrive_rx();
        tp_part(ic<30>(), ic<36>());
        if (tid == 0) GT(41 + blockIdx.x % 3, 2);
        const uint32_t pw = pin(pw0);
        auto tp_store = [&](const float (&acc)[16], uint32_t off) {
            const uint32_t ta = pw + launder(sb + off + (warp >> 1) * 2048);
            stsm_x4_t(ta, pack_bf16(acc[0], acc[1]), pack_bf16(acc[2], acc[3]), pack_bf16(acc[4], acc[5]), pack_bf16(acc[6], acc[7]));
            stsm_x4_t(ta + 1024, pack_bf16(acc[8], acc[9]), pack_bf16(acc[10], acc[11]), pack_bf16(acc[12], acc[13]), pack_bf16(acc[14], acc[15]));
        };
        cluster_wait();
        wg_wait0();
        tp_store(ta0, SM_TOK + r * 8192);
        if (warp == 0) { bar_sync(BAR_PRJ, 256); fence_async_smem(); tok_publish(0, 1); tok_publish(0, 2); } else bar_arrive(BAR_PRJ, 256);
        if (!TAIL) { tp_store(ta1, SM_TOK + TOKBUF + r * 8192); }
        { const uint4 v = lds128(sb + SM_OST + tid * 16); wf[0][0] = v.x; wf[0][1] = v.y; wf[0][2] = v.z; wf[0][3] = v.w; }
        if (tid == 0) GT(41 + blockIdx.x % 3, 4);
        const uint32_t l16 = pin(lane * 16), sbl = sb + l16, l4w = pin(sb + warp * 256 + lane * 4);
        uint32_t wo[8][4];
        const int exo = r < 2 ? (warp < 6 ? r * 2048 : 4096 + (2 * r - 6) * 256) : (warp < 2 ? 6 * 256 : (warp < 4 ? 2048 + 4 * 256 : 4096));
        const bool isqk = warp < nqk;
        const uint32_t exbar = isqk ? bEX : bEV;
        uint32_t vf[2][4];
        auto prep = [&](int s) {
            const uint32_t va = pw + launder(sb + SM_TOK + (s & 1) * TOKBUF + BLK_V(warp >> 1));
            mbar_wait(bTOK + 8 * (s & 1), (s >> 1) & 1);
            if (VF_EARLY) { ldsm_x4_t(vf[0], va); ldsm_x4_t(vf[1], va + 1024); }
        };
        prep(0);
        for (int s = 0; ; s++) {
            const int par = s & 1;
            const uint32_t va = pw + launder(sb + SM_TOK + par * TOKBUF + BLK_V(warp >> 1)), wa = pw + launder(sb + SM_WO + (warp >> 1) * 8192);
            const uint32_t exu = launder(SM_EX + par * EXBUF);
            {
                float acc[4][4];
                #pragma unroll
                for (int i = 0; i < 4; i++) { acc[i][0] = acc[i][1] = acc[i][2] = acc[i][3] = 0.f; }
                uint32_t b[18][4];
                if (!isqk) { bar_arrive(BAR_MEM, MEM_N); bar_sync(BAR_VGO, VGO_N); } else bar_sync(BAR_MEM, MEM_N);
                #pragma unroll
                for (int i2 = 0; i2 < 18; i2++) {
                    if (!TAIL || i2 >= MP_PRE) ldsm_x4_t(b[i2], sbl + SM_MEM + i2 * 512);
                    if (i2 == VGO_AT) bar_arrive_p(BAR_VGO, VGO_N, !isqk);
                    if (PRO_V && i2 == PRO_V) bar_arrive_p(BAR_PRO, PRO_N, isqk || s == NSEG - 1);
                    mma16816(acc[(2 * i2) & 3], wf[2 * i2], b[i2][0], b[i2][1]);
                    mma16816(acc[(2 * i2 + 1) & 3], wf[2 * i2 + 1], b[i2][2], b[i2][3]);
                }
                float q[4];
                #pragma unroll
                for (int i = 0; i < 4; i++) q[i] = (acc[0][i] + acc[1][i]) + (acc[2][i] + acc[3][i]);
                const uint32_t lo = pack_bf16(q[0], q[1]), hi = pack_bf16(q[2], q[3]);
                const uint32_t exl = l4w + launder(exu + exo), bar = exbar + par * 8;
                #pragma unroll
                for (int k = 1; k < 3; k++) {
                    const uint32_t exd = mapa_u32(exl, (r + k) % 3), exb = mapa_u32(bar, (r + k) % 3);
                    st_async32(exd, lo, exb); st_async32(exd + 128, hi, exb);
                }
                sts32(exl, lo); sts32(exl + 128, hi);
                __syncwarp();
                asm volatile("{\n.reg .pred p;\nelect.sync _|p, 0xffffffff;\n@p mbarrier.arrive.shared.b64 _, [%0];\n}\n" :: "r"(bar) : "memory");
                if (s < NSEG - 1) bar_sync_p(BAR_PRO, PRO_N, !isqk);
            }
            if (s == 0) mbar_wait(bW + 32, 0);
            if (s == NSEG - 1) break;
            {
                if (!VF_EARLY) { ldsm_x4_t(vf[0], va); ldsm_x4_t(vf[1], va + 1024); }
                #pragma unroll
                for (int i = 0; i < WO_PRE; i++) ldsm_x4_t(wo[i], wa + i * 1024);
                if (WO_PRE < 8) {
                    #pragma unroll
                    for (int k = 0; k < WO_REP; k++) mbar_wait(bEX + 8 * par, (s >> 1) & 1);
                    #pragma unroll
                    for (int i = WO_PRE; i < 8; i++) ldsm_x4_t(wo[i], wa + i * 1024);
                }
                mbar_wait(bEV + 8 * par, (s >> 1) & 1);
                const uint32_t vm0 = lds32(l4w + exu + 4096), vm1 = lds32(l4w + exu + 4096 + 128);
                const uint32_t big = bar_red_or(BAR_P, 352, 0u);
                uint32_t pb[4]; ldsm_x4_t(pb, sbl + SM_P);
                uint32_t pm = ldsm_x1_t(sbl + SM_P + 512);
                float o0[4] = {0.f, 0.f, 0.f, 0.f}, o1[4] = {0.f, 0.f, 0.f, 0.f}, o2[4] = {0.f, 0.f, 0.f, 0.f};
                if (__builtin_expect(big, 0)) {
                    bar_sync(BAR_P2, 352);
                    ldsm_x4_t(pb, sbl + SM_P); pm = ldsm_x1_t(sbl + SM_P + 512);
                }
                mma16816(o0, vf[0], pb[0], pb[1]);
                mma16816(o1, vf[1], pb[2], pb[3]);
                mma1688(o2, vm0, vm1, pm);
                uint32_t oa = pm;
                #pragma unroll
                for (int i = 0; i < 8; i++) oa ^= wo[i][0];
                oa = l4w | (oa & nv);
                sts32(oa + SM_O, pack_bf16((o0[0] + o1[0]) + o2[0], (o0[1] + o1[1]) + o2[1]));
                sts32(oa + SM_O + 128, pack_bf16((o0[2] + o1[2]) + o2[2], (o0[3] + o1[3]) + o2[3]));
                const uint32_t xd = uni(DESC_LO(SM_X) + par * (XBUF >> 4));
                auto tp = [&](auto lo, auto hi) {
                    #pragma unroll
                    for (int i = lo.value; i < hi.value; i++) {
                        if (i == 0) wgmma_n32<0>(ta1, wf[0], desc_from(xd));
                        else wgmma_n32<1>(ta1, wf[i], desc_from(xd + (i >> 2) * 256 + (i & 3) * 2));
                    }
                };
                bar_sync(BAR_O, 352);
                stage_w<false>(wo, sbl + SM_O, 12 * r + warp, SLOT_OFF(s + 1), l16, nv, sbl + SM_IL, [&] {
                    if (TP_E) { bar_sync(BAR_V, 384); wg_fence(); tp(ic<0>(), ic<TP_E>()); } });
                STAMP(warp);
                if (!TP_E) { bar_sync(BAR_V, 384); wg_fence(); }
                STAMP(12);
                tp(ic<TP_E>(), ic<TP_N>());
                wg_commit();
                prep(s + 1);
                if (!TAIL) { wg_wait0(); tp_store(ta1, SM_TOK + par * TOKBUF + r * 8192); STAMP(13 + (warp >> 2)); }
            }
        }
        cluster_arrive(); cluster_wait();
    } else {
        asm volatile("setmaxnreg.dec.sync.aligned.u32 %0;" :: "n"(504 - 2 * REG_P));
        const int a = warp - 8;
        const uint32_t sbl = sb + lane * 16;
        if (a < 3) {
            const uint32_t zs = 3 * blockIdx.x + (r8 >> 1);
            const uint32_t zoff = (r8 < 6 ? (zs >> 3) * 1024 + ((zs >> 2) & 1) * 256 + (zs & 3) * 32 : ACC_X + (blockIdx.x >> 1) * 1024 + (blockIdx.x & 1) * 256) + (lane & 1) * 16;
            const uint32_t zskip = r8 >= 6 && blockIdx.x >= 36;
            if (a == 1) {
                st_relaxed128_p((uint4*)(g_acc + zoff + SLOT_OFF(mi)), make_uint4(0, 0, 0, 0), zskip);
                __threadfence();
                __syncwarp();
                if (lane == 0) st_relaxed32(&g_init[blockIdx.x], epoch);
            }
            {
                #pragma unroll
                for (int i = 0; i < 6; i++) {
                    const int c = tid - 256 + 96 * i;
                    const unsigned short* m = (const unsigned short*)mem0 + c;
                    uint4 v;
                    v.x = m[0] | ((uint32_t)m[DM] << 16); v.y = m[2 * DM] | ((uint32_t)m[3 * DM] << 16);
                    v.z = m[4 * DM] | ((uint32_t)m[5 * DM] << 16); v.w = m[6 * DM] | ((uint32_t)m[7 * DM] << 16);
                    sts128(sb + SM_MEM + c * 16, v);
                }
                sts32(sb + SM_SG + 36, 0u);
            }
            asm volatile("barrier.cluster.arrive.release.aligned;" ::: "memory");
            { int it = 0; while (__any_sync(0xffffffffu, ld_relaxed32(&g_init[a * 32 + lane]) != epoch) && ++it < SPIN_LIMIT) {} }
            __threadfence();
            const uint32_t kl0 = (a < 2 ? SM_TOK + (16 * a + (mi & 1) * 8 + r8) * 64 + (((mi >> 1) ^ (r8 >> 1)) << 4) : SM_EX + 2048 + ((((mi & 1) << 1) | (mi >> 1)) * 8 + r8) * 16);
            const uint32_t l16 = pin(lane * 16);
            uint32_t kf[8][4], wo[8][4];
            auto load_k = [&](int tb, uint32_t kl, auto lo, auto hi) {
                const uint32_t ka = kl + launder(sb + tb * TOKBUF);
                #pragma unroll
                for (int kk = lo.value; kk < hi.value; kk++) ldsm_x4(kf[kk], (ka ^ ((kk & 1) << 5)) + BLK_K(kk >> 1));
            };
            code_pad<PAD_S>(nv);
            cluster_wait();
            if (a == 0 && lane == 0) { mbar_expect_tx(bEX, 4096 - 256 * nqk); mbar_expect_tx(bEV, 256 * nqk); }
            if (a < 2) bar_arrive(BAR_MEM, MEM_N); else bar_sync(BAR_MEM, MEM_N);
            mbar_wait(bW + 32, 0);
            #pragma unroll
            for (int i = 0; i < 8; i++) ldsm_x4_t(wo[i], pw0 + sb + SM_WO + (warp >> 1) * 8192 + i * 1024);
            sts128(sbl + SM_STASH + a * 1024 + 512, make_uint4(kl0, (pw0 ^ 32) + sb + SM_WO + 5 * 8192, zoff | ((zskip || lane >= 8) << 31), 0u));
            sts128(sbl + SM_STASH + a * 1024, make_uint4(a * 12288 + (lane >> 4) * 1024 + (mi & 1) * 256 + r8 * 16, ACC_X + a * 6144 + (lane >> 4) * 1024 + (mi & 1) * 256 + r8 * 4,
                                                         ((lane ^ mi) & 1) ? 0u : ~0u, sb + SM_MEM + a * 3072 + mi * 256 + r8 * 16 + (r8 & 1 ? 2 : 130)));
            const uint32_t stash = l16 + uni(sb + SM_STASH + a * 1024);
            #pragma unroll
            for (int i = 0; i < 8; i++) ldsm_x4_t(kf[i], (pw0 ^ 32) + sb + SM_WO + 5 * 8192 + i * 1024);
            if (a < 2) { mbar_wait(bTOK, 0); load_k(0, kl0, ic<0>(), ic<K_PRE>()); }
            __syncwarp();
            int sn = 0;
            #pragma unroll 1
            while (sn < NSEG - 1) {
              uint32_t bad, c, cx;
              #pragma unroll 1
              do {
                const int s = sn, par = s & 1;
                const uint32_t exu = launder(sb + par * EXBUF);
                const uint32_t exl = l16 + exu + SM_EX;
                const uint32_t t0 = gtime_lo();
                STAMP(15); STAMPV(31, t0);
                if (!TAIL && a == 2) st_relaxed32_p(&g_ts[blockIdx.x], (t0 & ~31u) | (s & 31), l16);
                if (a == 1) {
                    const uint32_t z = lds32(stash + 520);
                    st_relaxed128_p((uint4*)(g_acc + (z + SLOT_OFF(s + 3))), make_uint4(0, 0, 0, 0), z >> 31);
                }
                if (a == 0 && l16 == 0) { mbar_expect_tx(bEX + 8 * (par ^ 1), 4096 - 256 * nqk); mbar_expect_tx(bEV + 8 * (par ^ 1), 256 * nqk); }
                uint32_t tg;
                auto first_half = [&](auto role) {
                constexpr bool M = role.value;
                auto publish = [&] {
                    asm volatile("{\n.reg .pred p;\nelect.sync _|p, 0xffffffff;\n"
                                 "@p cp.async.bulk.shared::cluster.global.mbarrier::complete_tx::bytes.multicast::cluster [%0], [%1], 8192, [%2], %3;\n}\n"
                        :: "r"(sb + SM_TOK + (par ^ 1) * TOKBUF + r * 8192), "l"(g_tokx[blockIdx.x]), "r"(bTOK + 8 * (par ^ 1)), "h"((unsigned short)(7 ^ (1 << r))) : "memory");
                };
                uint32_t sl, sh, kl = 0, w2 = 0;
                if (M) {
                    if (TAIL) { bar_sync(BAR_VGO, VGO_N); __syncwarp(); st_relaxed32_p(&g_ts[blockIdx.x], (gtime_after(lds32(stash + 524)) & ~31u) | (s & 31), l16); }
                    fence_async_smem();
                    if (l16 == 0) {
                        asm volatile("cp.async.bulk.global.shared::cta.bulk_group [%0], [%1], 8192;\ncp.async.bulk.commit_group;"
                            :: "l"(g_tokx[blockIdx.x]), "r"(sb + SM_TOK + (par ^ 1) * TOKBUF + r * 8192) : "memory");
                        mbar_expect_tx(bTOK + 8 * (par ^ 1), 16384);
                        if (s == 0) mbar_expect_tx(bX, XBUF);
                        if (s + 3 < NSEG) mbar_expect_tx(bX + 8 * (par ^ 1), XBUF);
                    }
                    __syncwarp();
                    if (s > 0 && s + 2 < NSEG) mbar_wait(bX + 8 * par, ((s >> 1) & 1) ^ 1);
                    if (PUB_W == 0) asm volatile("cp.async.bulk.wait_group 0;" ::: "memory");
                    kl = lds32(stash + 512);
                }
                if (!M && K_PRE < 8) {
                    const uint32_t kl = lds32(stash + 512);
                    bar_sync(BAR_PRO, PRO_N);
                    load_k(par, kl, ic<K_PRE>(), ic<8>());
                }
                uint32_t pst = (launder(l16) >> 2) + launder(sb + SM_P + a * 256);
                if (!M) {
                    uint32_t x = kf[0][0];
                    #pragma unroll
                    for (int i = 1; i < 8; i++) x ^= kf[i][0];
                    sts32_p(pst, x, nv);
                }
                mbar_wait(bEX + 8 * par, (s >> 1) & 1);
                if (!M) {
                    uint32_t b[4][4];
                    ldsm16_t(b, exl);
                    float c[4][4];
                    #pragma unroll
                    for (int j = 0; j < 4; j++) { c[j][0] = c[j][1] = c[j][2] = c[j][3] = 0.f; }
                    #pragma unroll
                    for (int j = 0; j < 4; j++) { mma16816(c[(2 * j) & 3], kf[2 * j], b[j][0], b[j][1]); mma16816(c[(2 * j + 1) & 3], kf[2 * j + 1], b[j][2], b[j][3]); }
                    sl = scale_bf2(pack_bf16((c[0][0] + c[1][0]) + (c[2][0] + c[3][0]), (c[0][1] + c[1][1]) + (c[2][1] + c[3][1])));
                    sh = scale_bf2(pack_bf16((c[0][2] + c[1][2]) + (c[2][2] + c[3][2]), (c[0][3] + c[1][3]) + (c[2][3] + c[3][3])));
                } else {
                    float c[4][4];
                    #pragma unroll
                    for (int j = 0; j < 4; j++) { c[j][0] = c[j][1] = c[j][2] = c[j][3] = 0.f; }
                    uint32_t k[4][4], b[4][4];
                    #pragma unroll
                    for (int j = 0; j < 4; j++) { ldsm_x4_t(k[j], kl + exu + 512 * j); ldsm_x4_t(b[j], exl + 512 * j); }
                    if (M_SF) sched_fence<9>(nv);
                    #pragma unroll
                    for (int j = 0; j < 4; j++) { mma16816(c[2 * (j & 1)], k[j], b[j][0], b[j][1]); mma16816(c[2 * (j & 1) + 1], k[j], b[j][2], b[j][3]); }
                    if (PUB_W == 0) publish();
                    sh = sl = scale_bf2(pack_bf16((c[0][0] + c[1][2]) + (c[2][0] + c[3][2]), (c[0][1] + c[1][3]) + (c[2][1] + c[3][3])));
                }
                sts32(pst, pack_bf16(ex2(bf_lo(sl) * LOG2E), ex2(bf_hi(sl) * LOG2E)));
                if (!M) sts32(pst + 128, pack_bf16(ex2(bf_lo(sh) * LOG2E), ex2(bf_hi(sh) * LOG2E)));
                if (S_DUTY && !M) {
                    if (a == 0)
                        asm volatile("{\n.reg .pred p;\nelect.sync _|p, 0xffffffff;\n"
                                     "@p cp.async.bulk.shared::cluster.global.mbarrier::complete_tx::bytes [%0], [%1], 384, [%2];\n"
                                     "@p mbarrier.arrive.expect_tx.shared.b64 _, [%2], 384;\n}\n"
                            :: "r"(sb + SM_TS), "l"(g_ts), "r"(bFREE) : "memory");
                    else if (s > 0 && s + 3 < NSEG)
                        asm volatile("{\n.reg .pred p;\nelect.sync _|p, 0xffffffff;\n"
                                     "@p cp.async.bulk.tensor.3d.shared::cluster.global.mbarrier::complete_tx::bytes.multicast::cluster [%0], [%1, {%3, %4, %5}], [%2], %6;\n}\n"
                            :: "r"(sb + SM_X + (par ^ 1) * XBUF + r * 12288), "l"(&tmx), "r"(bX + 8 * (par ^ 1)), "r"(0), "r"((s + 3) * SEG), "r"(3 * r), "h"((unsigned short)7) : "memory");
                }
                const uint32_t big = bar_red_or(BAR_P, 352, ((maxabs_bf2(sl, sh) & 0x7fff7fffu) + 0x3ddf3ddfu) & 0x80008000u);
                auto denom = [&] {
                    uint32_t pb[4]; ldsm_x4_t(pb, l16 + sb + SM_P);
                    const uint32_t pm = ldsm_x1_t(l16 + sb + SM_P + 512), ONE = 0x3F803F80u;
                    float l0[4] = {0.f, 0.f, 0.f, 0.f}, l1[4] = {0.f, 0.f, 0.f, 0.f}, l2[4] = {0.f, 0.f, 0.f, 0.f};
                    mma16816r(l0, ONE, ONE, ONE, ONE, pb[0], pb[1]);
                    mma16816r(l1, ONE, ONE, ONE, ONE, pb[2], pb[3]);
                    mma1688(l2, ONE, ONE, pm);
                    const float dl = (l0[0] + l1[0]) + l2[0], dh = (l0[1] + l1[1]) + l2[1];
                    sts32(pst + (SM_IL - SM_P) - a * 128, __float_as_uint(rcp_approx(a ? dh : dl)));
                };
                if (!M) { denom(); bar_sync_p(BAR_O, 352, big); }
                if (__builtin_expect(big, 0)) {
                    uint32_t m2 = max_bf2(sl, sh);
                    m2 = max_bf2(m2, __shfl_xor_sync(0xffffffffu, m2, 4));
                    m2 = max_bf2(m2, __shfl_xor_sync(0xffffffffu, m2, 8));
                    m2 = max_bf2(m2, __shfl_xor_sync(0xffffffffu, m2, 16));
                    const uint32_t lq = l16 | (m2 & nv);
                    if (lq < 64) sts32(lq + sb + SM_P + 768 + a * 4, m2);
                    bar_sync(BAR_S, 96);
                    const uint4 m = lds128(sb + SM_P + 768 + (lq & 0x30));
                    m2 = max_bf2(max_bf2(m.x, m.y), m.z);
                    const float ml = bf_lo(m2), mh = bf_hi(m2);
                    sts32(pst, pack_bf16(exd(bf_lo(sl), ml), exd(bf_hi(sl), mh)));
                    if (!M) sts32(pst + 128, pack_bf16(exd(bf_lo(sh), ml), exd(bf_hi(sh), mh)));
                    bar_sync(BAR_P2, 352);
                    if (!M) { denom(); bar_sync(BAR_O, 352); }
                }
                const uint32_t ll = launder(l16), so = SLOT_OFF(launder(s) + 1);
                if (!M) {
                    stage_w<true>(wo, l16 + sb + SM_O, 12 * r + warp, so, ll, nv, l16 + sb + SM_IL, [&] { if (TP_E || V_EARLY) bar_arrive(BAR_V, 384); });
                } else {
                    w2 = lds32(stash + 516);
                    #pragma unroll
                    for (int i = M_RES; i < 8; i++) ldsm_x4_t(kf[i], w2 + i * 1024);
                    if (PUB_W == 1) { asm volatile("cp.async.bulk.wait_group 0;" ::: "memory"); publish(); }
                    const uint32_t sa = launder(SEND_LANE(ll) + (send_ua(12 * r + 10) + so)), sb_ = launder(X_LANE(ll) + (send_ub(12 * r + 10) + so));
                    bar_sync_p(BAR_O, 352, (kf[5][0] ^ kf[6][0] ^ kf[7][0] ^ sa ^ sb_) & nv);
                    float c[4][4], il, ih;
                    #pragma unroll
                    for (int i = 0; i < 4; i++) c[i][0] = c[i][1] = c[i][2] = c[i][3] = 0.f;
                    uint32_t b[4][4];
                    #pragma unroll
                    for (int j = 0; j < 4; j++) ldsm_x4_t(b[j], l16 + sb + SM_O + 512 * (3 - j));
                    lds_il(il, ih, l16 + sb + SM_IL);
                    sched_fence<11>(nv);
                                    #pragma unroll
                    for (int j = 0; j < 4; j++) {
                        if (j == 2) { if (M_F2) sched_fence<10>(nv); }
                        mma16816(c[0], wo[6 - 2 * j], b[j][0], b[j][1]); mma16816(c[2], kf[6 - 2 * j], b[j][0], b[j][1]);
                        mma16816(c[1], wo[7 - 2 * j], b[j][2], b[j][3]); mma16816(c[3], kf[7 - 2 * j], b[j][2], b[j][3]);
                    }
                    asm volatile("" : "+f"(c[0][0]), "+f"(c[1][0]), "+f"(c[2][0]), "+f"(c[3][0]));
                    if (TP_E || V_EARLY) { if (M_FENCE == 1) sched_fence<8>(nv); else asm volatile("" : "+f"(il) : "f"(c[0][0] + c[1][0]), "f"(c[2][0] + c[3][0])); if (M_FENCE < 2) bar_arrive(BAR_V, 384); }
                    send_tile<0, 0>((c[0][0] + c[1][0]) * il, (c[0][1] + c[1][1]) * ih, (c[0][2] + c[1][2]) * il, (c[0][3] + c[1][3]) * ih, sa, sb_, ll);
                    if (M_FENCE == 2) bar_arrive(BAR_V, 384);
                    send_tile<1024, 256>((c[2][0] + c[3][0]) * il, (c[2][1] + c[3][1]) * ih, (c[2][2] + c[3][2]) * il, (c[2][3] + c[3][3]) * ih, sa, sb_, ll);
                    if (M_FENCE == 3) bar_arrive(BAR_V, 384);
                }
                };
                if (a < 2) first_half(ic<0>()); else first_half(ic<1>());
                STAMP(warp);
                if (!TP_E && !V_EARLY) bar_arrive(BAR_V, 384);
                {
                    const uint4 ad = lds128(stash);
                    const uint32_t kl = lds32(stash + 512), so = SLOT_OFF(launder(s) + 1);
                    if (K_OWN == 1 && a < 2) { mbar_wait(bTOK + 8 * (par ^ 1), ((s + 1) >> 1) & 1); load_k(par ^ 1, kl, ic<0>(), ic<K_PRE>()); }
                    { int it = 0; do { asm volatile("ld.volatile.shared.u32 %0, [%1];" : "=r"(tg) : "r"(sb + SM_SG + 36) : "memory"); } while ((tg & 1u) == (uint32_t)par && ++it < SPIN_LIMIT * 16); }
                    if (!K_OWN && K_POS == 0 && a < 2) load_k(par ^ 1, kl, ic<0>(), ic<K_PRE>());
                    const uint32_t alo = (uint32_t)(uint64_t)g_acc + so;
                    const unsigned char* pm = (const unsigned char*)(((uint64_t)g_acc & ~0xffffffffull) | (ad.x + alo));
                    const unsigned char* px = (const unsigned char*)(((uint64_t)g_acc & ~0xffffffffull) | (ad.y + alo));
                    uint4 v[6]; uint32_t x[3];
                    const uint32_t md = l16 + launder(sb + SM_MEM + a * 3072);
                    STAMP(16 + a); STAMPV(30, tg);
                    wait_gtime(tg);
                    #pragma unroll
                    for (int j = 0; j < 6; j++) v[j] = ld_relaxed128((const uint4*)(pm + 2048 * j));
                    #pragma unroll
                    for (int j = 0; j < 3; j++) x[j] = ld_relaxed32((const uint32_t*)(px + 2048 * j));
                    if (K_OWN == 2) { mbar_wait(bTOK + 8 * (par ^ 1), ((s + 1) >> 1) & 1); if (a < 2) load_k(par ^ 1, kl, ic<0>(), ic<K_PRE>()); sched_fence<16>(nv); }
                    if (LD_FENCE) bar_sync(BAR_S, 96);
                    STAMP(19 + a);
                    c = ~0u;
                    #pragma unroll
                    for (int j = 0; j < 6; j++) { sts128(md + 512 * j, v[j]); c &= v[j].x; }
                    c |= ad.z;
                    #pragma unroll
                    for (int j = 0; j < 3; j++) sts16(ad.w + 1024 * j, (uint16_t)x[j]);
                    cx = x[0] & x[1] & x[2];
                    bad = __any_sync(0xffffffffu, !(c & cx & (ACC_FULL << 16)));
                    STAMP(22 + a); STAMPV(27 + a, bad);
                    bar_sync_p(BAR_MEM, MEM_N, bad);
                }
              } while (++sn < NSEG - 1 && !bad);
                {
                    if (bad) {
                        const uint32_t lq = l16 | (c & nv), so = SLOT_OFF(sn);
                        const uint4 ad = lds128(stash);
                        const unsigned char* pm = launder_p(g_acc + (ad.x + so));
                        const unsigned char* px = launder_p(g_acc + (ad.y + so));
                        int it = 0;
                        do {
                            const uint32_t again = ~(c & __shfl_xor_sync(0xffffffffu, c, 1)) & (ACC_FULL << 16);
                            uint4 u[6]; uint32_t x[3];
                            #pragma unroll
                            for (int j = 0; j < 6; j++) { u[j] = make_uint4(~0u, ~0u, ~0u, ~0u); ld_relaxed128_p(u[j], (const uint4*)(pm + 2048 * j), again); }
                            #pragma unroll
                            for (int j = 0; j < 3; j++) x[j] = ld_relaxed32((const uint32_t*)(px + 2048 * j));
                            c = ~0u;
                            #pragma unroll
                            for (int j = 0; j < 6; j++) {
                                if (again) sts128(lq + sb + SM_MEM + a * 3072 + 512 * j, u[j]);
                                c &= u[j].x;
                            }
                            __syncwarp();
                            #pragma unroll
                            for (int j = 0; j < 3; j++) sts16(ad.w + 1024 * j, (uint16_t)x[j]);
                            c |= ad.z;
                            cx = x[0] & x[1] & x[2];
                        } while (__any_sync(0xffffffffu, !(c & cx & (ACC_FULL << 16))) && ++it < SPIN_LIMIT);
                        bar_sync(BAR_MEM, MEM_N);
                    }
                }
            }
            if (TAIL && a == 2) bar_arrive(BAR_VGO, VGO_N);
        } else {
            cluster_arrive_rx();
            const uint32_t l16 = pin(lane * 16);
            bf16* dst = g_otok + h * 4096 + (r ? 1024 : 0) + (r == 2 ? 2048 : 0);
            {
                #pragma unroll
                for (int sg = 0; sg < 2; sg++) {
                    bar_sync(BAR_X0 + sg, 288);
                    if (lane == 0) {
                        mbar_expect_tx(bX + 8 * sg, XBUF);
                        #pragma unroll
                        for (int c = 0; c < 3; c++)
                            asm volatile("cp.async.bulk.tensor.3d.shared::cluster.global.mbarrier::complete_tx::bytes [%0], [%1, {%3, %4, %5}], [%2];"
                                :: "r"(sb + SM_X + sg * XBUF + c * 12288), "l"(&tmx), "r"(bX + 8 * sg), "r"(0), "r"(sg * SEG), "r"(3 * c) : "memory");
                    }
                    __syncwarp();
                }
                if (lane == 0) load_w(40, 54);
                __syncwarp();
                cluster_wait();
            }
            __syncwarp();
            auto t_loop = [&](auto mtile) {
            constexpr int MT = mtile.value;
            uint32_t q[8][4], sp[5][2], pa[5][2], bv[8][4], rng;
            code_pad<MT ? PAD_T1 : PAD_T0>(nv);
            auto issue_x = [&](int sg) {
                asm volatile("{\n.reg .pred p, q;\nelect.sync _|p, 0xffffffff;\nsetp.eq.and.u32 q, %5, 3, p;\n"
                             "@p cp.async.bulk.tensor.3d.shared::cluster.global.mbarrier::complete_tx::bytes.multicast::cluster [%0], [%1, {%3, %4, %5}], [%2], %6;\n"
                             "@q cp.async.bulk.tensor.3d.shared::cluster.global.mbarrier::complete_tx::bytes.multicast::cluster [%7], [%1, {%3, %4, %3}], [%2], %6;\n}\n"
                    :: "r"(sb + SM_X + (sg & 1) * XBUF + r * 12288), "l"(&tmx), "r"(bX + 8 * (sg & 1)), "r"(0), "r"(sg * SEG), "r"(3 * r), "h"((unsigned short)7), "r"(sb + SM_X + (sg & 1) * XBUF) : "memory");
            };
            mbar_wait(bTOK, 0);
            if (MT) { issue_x(2); issue_x(3); }
            #pragma unroll 1
            for (int s = 0; s < NSEG; s++) {
                const int par = s & 1;
                if (K_OWN) mbar_wait(bTOK + 8 * par, (s >> 1) & 1);
                const uint32_t tok = launder(sb + SM_TOK + par * TOKBUF), exl = l16 + launder(sb + SM_EX + par * EXBUF);
                const int ln = launder(l16) >> 4;
                auto announce = [&] {
                    if (s > 0) {
                        if (lane == 0) {
                            asm volatile("cp.async.bulk.wait_group 0;" ::: "memory");
                            st_relaxed32(&g_prog[blockIdx.x], epoch << 8 | s);
                        }
                        __syncwarp();
                        if (lane == 0 && blockIdx.x == 0) GT(40, s);
                    }
                };
                if (ANN_POS == 0) announce();
                tok_part1<MT>(tok, MT ? r - 1 : 0, ln, q, sp, pa, bv, rng, [&] {
                    if (ANN_POS == 3) announce();
                    if (T_HOLD) { if (s < NSEG - 1) bar_sync((T_HOLD & 1) ? BAR_PRO : BAR_VGO, (T_HOLD & 1) ? PRO_N : VGO_N); else if (T_HOLD == 2) bar_arrive(BAR_VGO, VGO_N); sched_fence<6 + MT>(nv); } });
                if (ANN_POS == 1) announce();
                STAMP(25);
                mbar_wait(bEX + 8 * par, (s >> 1) & 1);
                STAMP(26);
                auto duty = [&] { if (!S_DUTY && s + 1 < NSEG) {
                    asm volatile("{\n.reg .pred p;\nelect.sync _|p, 0xffffffff;\n"
                                 "@p cp.async.bulk.shared::cluster.global.mbarrier::complete_tx::bytes [%0], [%1], 384, [%2];\n"
                                 "@p mbarrier.arrive.expect_tx.shared.b64 _, [%2], 384;\n}\n"
                        :: "r"(sb + SM_TS), "l"(g_ts), "r"(bFREE) : "memory");
                    if (X_POS == 0 && MT && s > 0 && s + 3 < NSEG) issue_x(s + 3);
                } };
                auto pace = [&] { if (s + 1 < NSEG) {
                    if (X_POS == 2 && MT && s > 0 && s + 3 < NSEG) issue_x(s + 3);
                    const uint32_t lo = min(launder(l16), 368u), b = (gtime_lo() & ~31u) - 0x01000000u + s + (lo >> 16);
                    const uint32_t c = (b & ~31u) + (G1_NS + (s == 0 ? G1_0 : 0)) + (par ^ 1);
                    if (K_OWN) mbar_wait(bFREE, par); else mbar_wait2(bFREE, par, bTOK + 8 * (par ^ 1), ((s + 1) >> 1) & 1);
                    uint4 ts = lds128(sb + SM_TS + lo);
                    int it = 0; uint32_t m;
                    while (true) {
                        m = __reduce_max_sync(0xffffffffu, max(max(__funnelshift_r(ts.x - b, ts.x - b, 5), __funnelshift_r(ts.y - b, ts.y - b, 5)), max(__funnelshift_r(ts.z - b, ts.z - b, 5), __funnelshift_r(ts.w - b, ts.w - b, 5))));
                        if (__builtin_expect(m < 0x00100000u, 1) || ++it >= 64) break;
                        ts = ld_relaxed128((const uint4*)((const char*)g_ts + lo));
                    }
                    asm volatile("st.volatile.shared.u32 [%0], %1;" :: "r"(sb + SM_SG + 36), "r"(c + (min(m, 0x00080000u) << 5)) : "memory");
                } };
                auto wait_v = [&] {
                    if (X_POS == 1 && MT && s > 0 && s + 3 < NSEG) issue_x(s + 3);
                    mbar_wait(bEV + 8 * par, (s >> 1) & 1); };
                auto wait_x = [&] { if (__builtin_expect(s == 0, 0)) mbar_wait(bX, 1); };
                tok_part2<MT>(tok, exl, sb + SM_OST, MT ? r - 1 : 0, launder(l16) >> 4, q, sp, pa, bv, rng, s < NSEG - 1, wait_v, duty, pace, wait_x);
                STAMP(11);
                fence_async_smem();
                __syncwarp();
                if (lane == 0) {
                    asm volatile("cp.async.bulk.global.shared::cta.bulk_group [%0], [%1], 2048;" :: "l"(dst), "r"(sb + SM_OST) : "memory");
                    if (!MT) asm volatile("cp.async.bulk.global.shared::cta.bulk_group [%0], [%1], 2048;" :: "l"(dst + 2048), "r"(sb + SM_OST + 2048) : "memory");
                    asm volatile("cp.async.bulk.commit_group;" ::: "memory");
                    if (__builtin_expect(s >= NSEG - 2, 0)) {
                        asm volatile("cp.async.bulk.wait_group 0;" ::: "memory");
                        st_relaxed32(&g_prog[blockIdx.x], epoch << 8 | (s + 1));
                        if (blockIdx.x == 0 && s == NSEG - 1) GT(40, NSEG);
                    }
                }
                __syncwarp();
                dst += SEG * NH * DH;
            }
            };
            if (r == 0) t_loop(ic<0>()); else t_loop(ic<1>());
        }
        cluster_arrive(); cluster_wait();
    }
}
#define SD_THREADS 384
#define SD_CTAS  36
#define BT_RS    4624
#define SD_BT    0
#define SD_STG   74752
#define SD_EF    (SD_STG + 57344)
#define SD_BC    (SD_STG)
#define KSLOTS   5
#define BC_BYTES 10240
#define BC_LBO   1280
#define SD_KP    (SD_STG + 90112)
#define SD_Q0    205824
#define SD_Q1    (SD_STG + 111616)
#define SD_OST   222720
#define SD_XCH   (SD_Q0 + 8192)
#define SD_BAR   224256
#define SD_TOTAL 224768
#define SD_SPIN  (1 << 22)
#define PART_SLOTS 8
#define SD_GO 0
#define SD_REG 200
#define SD_WAIT 6000
#define SD_P2 150
#define SD_P3 500
#define SD_GAP 0
#define SD_RUSH 44
#define SD_P1 300

__device__ uint4 g_part[SD_CTAS][PART_SLOTS][4][8][32];
__device__ __align__(16) unsigned int g_gate[S_LEN];

struct cplx { float r, i; };
__device__ __forceinline__ cplx cmul(cplx a, cplx b) { cplx c; c.r = fmaf(a.r, b.r, -a.i * b.i); c.i = fmaf(a.r, b.i, a.i * b.r); return c; }
__device__ __forceinline__ cplx cexp_(float xr, float xi) {
    const float m = ex2(xr * 1.4426950408889634f);
    const float k = rintf(xi * 0.15915494309189535f);
    const float r = fmaf(k, 1.7484555314695172e-7f, fmaf(k, -6.2831854820251465f, xi));
    cplx o; o.r = m * __cosf(r); o.i = m * __sinf(r); return o;
}
__device__ __forceinline__ void mma_f16(float (&c)[4], const uint32_t (&a)[4], uint32_t b0, uint32_t b1) {
    asm("mma.sync.aligned.m16n8k16.row.col.f32.f16.f16.f32 {%0,%1,%2,%3}, {%4,%5,%6,%7}, {%8,%9}, {%0,%1,%2,%3};"
        : "+f"(c[0]), "+f"(c[1]), "+f"(c[2]), "+f"(c[3]) : "r"(a[0]), "r"(a[1]), "r"(a[2]), "r"(a[3]), "r"(b0), "r"(b1));
}
__device__ __forceinline__ uint32_t mul_bf2(uint32_t a, uint32_t b) { uint32_t r; asm("mul.rn.bf16x2 %0, %1, %2;" : "=r"(r) : "r"(a), "r"(b)); return r; }
__device__ __forceinline__ void mbar_wait_long(uint32_t a, uint32_t parity) { int it = 0; while (!mbar_try(a, parity) && ++it < SD_SPIN) {} }
__device__ __forceinline__ uint16_t lds16(uint32_t a) { uint16_t v; asm volatile("ld.shared.u16 %0, [%1];" : "=h"(v) : "r"(a) : "memory"); return v; }
__device__ __forceinline__ void wg_wait1() { asm volatile("wgmma.wait_group.sync.aligned 1;" ::: "memory"); }
__device__ __forceinline__ void tma2d(uint32_t dst, const CUtensorMap* tm, uint32_t bar, int c0, int c1) {
    asm volatile("cp.async.bulk.tensor.2d.shared::cluster.global.mbarrier::complete_tx::bytes [%0], [%1, {%3, %4}], [%2];"
        :: "r"(dst), "l"(tm), "r"(bar), "r"(c0), "r"(c1) : "memory");
}
__device__ __forceinline__ uint32_t add_bf2(uint32_t a, uint32_t b) { uint32_t r; asm("add.rn.bf16x2 %0, %1, %2;" : "=r"(r) : "r"(a), "r"(b)); return r; }
__device__ __forceinline__ void wgmma_conv(float (&d)[32], uint32_t a0, uint32_t a1, uint32_t a2, uint32_t a3, uint64_t desc) {
    asm volatile("{\n.reg .pred p;\nsetp.ne.b32 p, 1, 0;\n"
        "wgmma.mma_async.sync.aligned.m64n64k16.f32.bf16.bf16 {%0,%1,%2,%3,%4,%5,%6,%7,%8,%9,%10,%11,%12,%13,%14,%15,%16,%17,%18,%19,%20,%21,%22,%23,%24,%25,%26,%27,%28,%29,%30,%31}, {%32,%33,%34,%35}, %36, p, 1, 1, 0;\n}\n"
        : "+f"(d[0]), "+f"(d[1]), "+f"(d[2]), "+f"(d[3]), "+f"(d[4]), "+f"(d[5]), "+f"(d[6]), "+f"(d[7]), "+f"(d[8]), "+f"(d[9]), "+f"(d[10]), "+f"(d[11]), "+f"(d[12]), "+f"(d[13]), "+f"(d[14]), "+f"(d[15]), "+f"(d[16]), "+f"(d[17]), "+f"(d[18]), "+f"(d[19]), "+f"(d[20]), "+f"(d[21]), "+f"(d[22]), "+f"(d[23]), "+f"(d[24]), "+f"(d[25]), "+f"(d[26]), "+f"(d[27]), "+f"(d[28]), "+f"(d[29]), "+f"(d[30]), "+f"(d[31])
        : "r"(a0), "r"(a1), "r"(a2), "r"(a3), "l"(desc));
}
__device__ __forceinline__ void wgmma_conv(float (&d)[24], uint32_t a0, uint32_t a1, uint32_t a2, uint32_t a3, uint64_t desc) {
    asm volatile("{\n.reg .pred p;\nsetp.ne.b32 p, 1, 0;\n"
        "wgmma.mma_async.sync.aligned.m64n48k16.f32.bf16.bf16 {%0,%1,%2,%3,%4,%5,%6,%7,%8,%9,%10,%11,%12,%13,%14,%15,%16,%17,%18,%19,%20,%21,%22,%23}, {%24,%25,%26,%27}, %28, p, 1, 1, 0;\n}\n"
        : "+f"(d[0]), "+f"(d[1]), "+f"(d[2]), "+f"(d[3]), "+f"(d[4]), "+f"(d[5]), "+f"(d[6]), "+f"(d[7]), "+f"(d[8]), "+f"(d[9]), "+f"(d[10]), "+f"(d[11]), "+f"(d[12]), "+f"(d[13]), "+f"(d[14]), "+f"(d[15]), "+f"(d[16]), "+f"(d[17]), "+f"(d[18]), "+f"(d[19]), "+f"(d[20]), "+f"(d[21]), "+f"(d[22]), "+f"(d[23])
        : "r"(a0), "r"(a1), "r"(a2), "r"(a3), "l"(desc));
}
__device__ __forceinline__ void wgmma_conv(float (&d)[16], uint32_t a0, uint32_t a1, uint32_t a2, uint32_t a3, uint64_t desc) {
    asm volatile("{\n.reg .pred p;\nsetp.ne.b32 p, 1, 0;\n"
        "wgmma.mma_async.sync.aligned.m64n32k16.f32.bf16.bf16 {%0,%1,%2,%3,%4,%5,%6,%7,%8,%9,%10,%11,%12,%13,%14,%15}, {%16,%17,%18,%19}, %20, p, 1, 1, 0;\n}\n"
        : "+f"(d[0]), "+f"(d[1]), "+f"(d[2]), "+f"(d[3]), "+f"(d[4]), "+f"(d[5]), "+f"(d[6]), "+f"(d[7]), "+f"(d[8]), "+f"(d[9]), "+f"(d[10]), "+f"(d[11]), "+f"(d[12]), "+f"(d[13]), "+f"(d[14]), "+f"(d[15])
        : "r"(a0), "r"(a1), "r"(a2), "r"(a3), "l"(desc));
}
__device__ __forceinline__ void wgmma_conv(float (&d)[8], uint32_t a0, uint32_t a1, uint32_t a2, uint32_t a3, uint64_t desc) {
    asm volatile("{\n.reg .pred p;\nsetp.ne.b32 p, 1, 0;\n"
        "wgmma.mma_async.sync.aligned.m64n16k16.f32.bf16.bf16 {%0,%1,%2,%3,%4,%5,%6,%7}, {%8,%9,%10,%11}, %12, p, 1, 1, 0;\n}\n"
        : "+f"(d[0]), "+f"(d[1]), "+f"(d[2]), "+f"(d[3]), "+f"(d[4]), "+f"(d[5]), "+f"(d[6]), "+f"(d[7])
        : "r"(a0), "r"(a1), "r"(a2), "r"(a3), "l"(desc));
}
template<int NR> __device__ __forceinline__ void conv_mma(float (&acc)[NR], const uint32_t (&R)[16], uint32_t dlo) {
    #pragma unroll
    for (int q = 0; q < 4; q++)
        wgmma_conv(acc, R[4 * q], R[4 * q + 1], R[4 * q + 2], R[4 * q + 3], (uint64_t)(dlo + (2 * (3 - q)) * (BC_LBO >> 4)) | ((uint64_t)8 << 32));
}
__device__ __forceinline__ void conv_ld(uint32_t (&R)[16], uint32_t a) {
    #pragma unroll
    for (int q = 0; q < 4; q++) { const uint2 u = lds64(a + 64 * (2 * q + 1)); R[4 * q] = u.x; R[4 * q + 1] = u.y; }
}
__device__ __forceinline__ void conv_fix(uint32_t (&R)[16], uint32_t& carry) {
    #pragma unroll
    for (int q = 0; q < 4; q++) {
        asm volatile("mov.b32 %0, %1;" : "=r"(R[4 * q + 2]) : "r"(q ? R[4 * q - 3] : carry));
        asm volatile("mov.b32 %0, %1;" : "=r"(R[4 * q + 3]) : "r"(R[4 * q]));
    }
    asm volatile("mov.b32 %0, %1;" : "=r"(carry) : "r"(R[13]));
}
template<int A> __device__ __forceinline__ void conv_group(float (&acc)[32 - 8 * A], uint32_t (&R)[4][16], uint32_t& carry, uint32_t pb, uint32_t dlo) {
    #pragma unroll
    for (int e = 0; e < 8; e += 2) {
        const int dl = 8 * A + e;
        conv_fix(R[dl & 3], carry); conv_fix(R[(dl + 1) & 3], carry);
        wg_fence(); conv_mma(acc, R[dl & 3], dlo + 16 - 2 * e); conv_mma(acc, R[(dl + 1) & 3], dlo + 14 - 2 * e); wg_commit();
        wg_wait1();
        if (dl + 2 < 32) { conv_ld(R[(dl + 2) & 3], pb + (dl + 2) * 512); conv_ld(R[(dl + 3) & 3], pb + (dl + 3) * 512); }
    }
}

__global__ void __launch_bounds__(SD_THREADS, 1)
side_kernel(const __grid_constant__ CUtensorMap tmw, const bf16* __restrict__ x,
            const bf16* __restrict__ log_A_real, const bf16* __restrict__ A_imag, const bf16* __restrict__ C_real, const bf16* __restrict__ C_imag,
            const bf16* __restrict__ log_dt, const bf16* __restrict__ D_skip, const bf16* __restrict__ gate_w, bf16* __restrict__ out) {
    extern __shared__ __align__(1024) unsigned char smem[];
    const uint32_t sb = smem_u32(smem);
    const int tid = threadIdx.x, lane = tid & 31;
    const int warp = __shfl_sync(0xffffffffu, tid >> 5, 0);
    const int g = lane >> 2, t = lane & 3, mi = lane >> 3, r8 = lane & 7;
    const bool sh = blockIdx.x < 32;
    const int d0 = blockIdx.x * 16;
    const uint32_t b0_ = sb + SD_BAR, bKF = b0_ + 384, bKE = bKF + 8 * KSLOTS, bWO = b0_ + 48, bFULL = b0_ + 56, bEMPTY = b0_ + 88, bEPI = b0_ + 120, bPRT = b0_ + 152, bGO = b0_ + 184, bCH = b0_ + 256;
    const unsigned epoch = ld_relaxed32(&g_epoch);
    if (tid == 0) GT(blockIdx.x, 0);
    if (tid == 0) {
        for (int i = 0; i < 2 * KSLOTS; i++) mbar_init(bKF + 8 * i, 128);
        mbar_init(bWO, 1);
        for (int i = 0; i < 16; i++) mbar_init(bCH + 8 * i, 1);
        for (int i = 0; i < 4; i++) { mbar_init(bFULL + 8 * i, 1); mbar_init(bEMPTY + 8 * i, sh ? 8 : 4); mbar_init(bEPI + 8 * i, 4); mbar_init(bPRT + 8 * i, 8); mbar_init(bGO + 8 * i, 1); }
        asm volatile("fence.mbarrier_init.release.cluster;" ::: "memory");
    }
    for (int i = tid; i < KSLOTS * 8 * 16; i += SD_THREADS) sts128(sb + SD_BC + (i >> 4) * BC_LBO + (i & 15) * 16, make_uint4(0, 0, 0, 0));
    if (tid < 128) sts64(sb + ((tid & 64) ? SD_Q1 : SD_Q0) + (tid & 63) * 8, 0u, 0u);
    fence_async_smem();
    __syncthreads();

    if (warp < 8) {
        asm volatile("setmaxnreg.inc.sync.aligned.u32 %0;" :: "n"(SD_REG));
        const int wg = warp >> 2, w = warp & 3, t128 = tid & 127;
        if (SD_WAIT) __nanosleep(SD_WAIT);
        {
            #pragma unroll 1
            for (int i = 0; i < 4; i++) {
                const int tp = tid + 256 * i;
                const bf16* xp = x + (size_t)(2 * tp) * DM + d0;
                const uint4 v0 = __ldg((const uint4*)xp), v1 = __ldg((const uint4*)(xp + 8)), v2 = __ldg((const uint4*)(xp + DM)), v3 = __ldg((const uint4*)(xp + DM + 8));
                const uint32_t a = sb + SD_BT + (tp >> 5) * 144 + (tp & 31) * 4;
                const uint32_t lo[8] = {v0.x, v0.y, v0.z, v0.w, v1.x, v1.y, v1.z, v1.w};
                const uint32_t hi[8] = {v2.x, v2.y, v2.z, v2.w, v3.x, v3.y, v3.z, v3.w};
                #pragma unroll
                for (int j = 0; j < 8; j++) { sts32(a + (2 * j) * BT_RS, __byte_perm(lo[j], hi[j], 0x5410)); sts32(a + (2 * j + 1) * BT_RS, __byte_perm(lo[j], hi[j], 0x7632)); }
                if (SD_GAP) __nanosleep(SD_GAP);
            }
        }
        bar_sync(1, 256);
        if (tid == 0) GT(blockIdx.x, 65);
        const uint32_t pa = sb + (wg ? SD_Q1 : SD_Q0);
        const uint32_t pb = pa + (72 + 16 * w - 56 + g - 2 * t) * 8;
        for (int c = wg; c < 16; c += 2) {
            const uint32_t bt = sb + SD_BT + c * BT_RS;
            bar_sync(2 + wg, 128);
            #pragma unroll
            for (int it = 0; it < 9; it++) {
                const int k = it < 8 ? t128 + 128 * it : t128 - 4;
                if (it < 8 || t128 < 4) {
                    auto word = [&](int j) { return j >= 0 ? lds32(bt + (j >> 5) * 144 + (j & 31) * 4) : 0u; };
                    const uint32_t c0 = word(k), p0 = word(k - 1), c1 = word(k + 4), p1 = word(k + 3);
                    sts128(pa + (72 + 2 * k) * 8, make_uint4(__byte_perm(c0, p0, 0x7610), __byte_perm(c1, p1, 0x7610), __byte_perm(c0, c0, 0x1032), __byte_perm(c1, c1, 0x1032)));
                }
            }
            bar_sync(2 + wg, 128);
            const int slot = c % KSLOTS;
            float acc[32];
            #pragma unroll
            for (int i = 0; i < 32; i++) acc[i] = 0.f;
            uint32_t R[4][16];
            uint32_t carry = lds32(pb);
            conv_ld(R[0], pb); conv_ld(R[1], pb + 512);
            const uint32_t dlo = (((sb + SD_BC + slot * BC_BYTES) & 0x3FFFF) >> 4) | ((BC_LBO >> 4) << 16);
            mbar_wait_long(bKF + 8 * slot, (c / KSLOTS) & 1);
            const float ds = bf(D_skip[d0 + c]);
            auto fin = [&](const float* a8, int q0) {
                #pragma unroll
                for (int q = 0; q < 2; q++)
                    #pragma unroll
                    for (int hh = 0; hh < 2; hh++) {
                        const uint32_t a = bt + (4 * (q0 + q) + t) * 144 + (16 * w + g + 8 * hh) * 2;
                        const float u = __uint_as_float((uint32_t)lds16(a) << 16);
                        const float y = rbf(a8[4 * q + 2 * hh] + a8[4 * q + 2 * hh + 1]);
                        sts16(a, (uint16_t)(pack_bf16(y + rbf(u * ds), 0.f) & 0xffff));
                    }
            };
            float a1[24], a2[16], a3[8];
            conv_group<0>(acc, R, carry, pb, dlo);
            wg_wait0();
            #pragma unroll
            for (int i = 0; i < 24; i++) asm volatile("mov.b32 %0, %1;" : "=f"(a1[i]) : "f"(acc[8 + i]));
            fin(acc, 0);
            conv_group<1>(a1, R, carry, pb, dlo);
            wg_wait0();
            #pragma unroll
            for (int i = 0; i < 16; i++) asm volatile("mov.b32 %0, %1;" : "=f"(a2[i]) : "f"(a1[8 + i]));
            fin(a1, 2);
            conv_group<2>(a2, R, carry, pb, dlo);
            wg_wait0();
            #pragma unroll
            for (int i = 0; i < 8; i++) asm volatile("mov.b32 %0, %1;" : "=f"(a3[i]) : "f"(a2[8 + i]));
            fin(a2, 4);
            conv_group<3>(a3, R, carry, pb, dlo);
            wg_wait0();
            mbar_arrive(bKE + 8 * slot);
            fin(a3, 6);
        }
        fence_async_smem();
        __syncthreads();
        const uint32_t stg = sb + SD_STG + wg * 65536;
        uint32_t wf[32][4];
        if (tid == 0) GT(blockIdx.x, 66);
        mbar_wait_long(bWO, 0);
        #pragma unroll
        for (int i = 0; i < 32; i++)
            ldsm_x4_t(wf[i], stg + (i * 16 + (mi >> 1) * 8 + r8) * 128 + (((2 * w + (mi & 1)) ^ r8) << 4));
        { uint32_t x = 0;
          #pragma unroll
          for (int i = 0; i < 32; i++) x |= wf[i][0];
          asm volatile("" :: "r"(x) : "memory"); }
        __syncwarp();
        if (lane == 0) {
            mbar_arrive(bEMPTY + 16 * wg); mbar_arrive(bEMPTY + 16 * wg + 8);
            if (sh) { mbar_arrive(bEMPTY + 16 * (wg ^ 1)); mbar_arrive(bEMPTY + 16 * (wg ^ 1) + 8); }
        }
        uint4* dst = sh ? &g_part[(blockIdx.x & ~7) + 4 * wg + w][0][0][blockIdx.x & 7][lane] : &g_part[32 + w][0][0][2 * (blockIdx.x - 32) + wg][lane];
        const uint32_t dl0 = (((sb + SD_STG) & 0x3FFFF) >> 4) | 0x10000u;
        auto seg = [&](int s, auto last) {
            const int bi = sh ? s & 3 : 2 * wg + (s & 1), bp = (sh ? s >> 2 : s >> 1) & 1;
            const uint32_t xd = uni(dl0 + bi * 2048);
            float acc[16];
            #pragma unroll
            for (int i = 0; i < 32; i++) {
                if (i == 0 || (last.value && (i & 7) == 0)) { mbar_wait_long(bCH + 32 * bi + i, i ? 0 : bp); wg_fence(); }
                if (i == 0) wgmma_n32<0>(acc, wf[i], desc_from(xd));
                else wgmma_n32<1>(acc, wf[i], desc_from(xd + (i >> 2) * 256 + (i & 3) * 2));
            }
            wg_commit();
            if (s >= PART_SLOTS / 2) mbar_wait_long(bEPI + 8 * (s & 3), ((s - 4) >> 2) & 1);
            const uint32_t ph = ((s / PART_SLOTS) & 1) ^ 1;
            uint4* p = dst + (s % PART_SLOTS) * (4 * 8 * 32);
            wg_wait0();
            #pragma unroll
            for (int j = 0; j < 4; j++)
                st_relaxed128(p + 256 * j, make_uint4((__float_as_uint(acc[4 * j]) & ~1u) | ph, __float_as_uint(acc[4 * j + 1]), __float_as_uint(acc[4 * j + 2]), __float_as_uint(acc[4 * j + 3])));
            if (tid == 0 && s == NSEG - 1) GT(blockIdx.x, 71);
            __syncwarp();
            if (lane == 0) { mbar_arrive(bEMPTY + 8 * bi); mbar_arrive(bPRT + 8 * (s & 3)); }
        };
        #pragma unroll 1
        for (int s = 0; s < NSEG - 1; s++) seg(s, ic<0>());
        seg(NSEG - 1, ic<1>());
    } else {
        asm volatile("setmaxnreg.dec.sync.aligned.u32 %0;" :: "n"(504 - 2 * SD_REG));
        const int w = warp - 8, n = tid - 256;
        bf16 p_la = log_A_real[d0 * NS + n], p_ai = A_imag[d0 * NS + n], p_cr = C_real[d0 * NS + n], p_ci = C_imag[d0 * NS + n], p_dt = log_dt[d0];
        const uint32_t ef = sb + SD_EF + w * 8192;
        const uint32_t efl = ef + lane * 4;
        uint32_t goff[8];
        #pragma unroll
        for (int i = 0; i < 16; i++) {
            const int l = 64 * lane + 8 * (w + 4 * (i >> 3)) + (i & 7);
            const int p = (int)rbf((float)l);
            const int a = p >> 7, b = (p >> 3) & 15, c = p & 7;
            const int row = p < 256 ? 8 * a + c : (p < 512 ? 16 + 4 * (a - 2) + (c >> 1) : (p < 1024 ? 24 + 2 * (a - 4) + (c >> 2) : 24 + a));
            const uint32_t off = row * 72 + b * 4;
            if (i & 1) goff[i >> 1] |= off << 16; else goff[i >> 1] = off;
        }
        for (int c = 0; c < 16; c++) {
            const float dt = rbf(expf(bf(p_dt)));
            const float xr = -rbf(expf(bf(p_la))) * dt, xi = bf(p_ai) * dt;
            cplx C; C.r = 2.f * bf(p_cr) * dt; C.i = 2.f * bf(p_ci) * dt;
            if (c + 1 < 16) {
                const int o = (d0 + c + 1) * NS + n;
                p_la = log_A_real[o]; p_ai = A_imag[o]; p_cr = C_real[o]; p_ci = C_imag[o]; p_dt = log_dt[d0 + c + 1];
            }
            const uint32_t mexp = min(max(__reduce_max_sync(0xffffffffu, __float_as_uint(fmaxf(fabsf(C.r), fabsf(C.i)))) & 0x7f800000u, 0x01000000u), 0x7e000000u);
            const float unsc = __uint_as_float(mexp), sc = __uint_as_float(0x7f000000u - mexp);
            C.r *= sc; C.i *= sc;
            #define EADDR(r) ((efl ^ (((r) & 7) << 4)) + (r) * 128)
            {
                cplx f[16];
                f[1] = cexp_(8.f * xr, -8.f * xi);
                f[2] = cmul(f[1], f[1]); f[3] = cmul(f[2], f[1]); f[4] = cmul(f[2], f[2]); f[5] = cmul(f[4], f[1]); f[6] = cmul(f[4], f[2]); f[7] = cmul(f[4], f[3]);
                f[8] = cmul(f[4], f[4]);
                #pragma unroll
                for (int b = 9; b < 16; b++) f[b] = cmul(f[8], f[b - 8]);
                sts32(EADDR(0) + 6144, 0x00003c00u);
                #pragma unroll
                for (int b = 1; b < 16; b++) sts32(EADDR(b) + 6144, pack_f16(f[b].r, f[b].i));
            }
            {
                cplx G[17], wc[8];
                G[1] = cexp_(128.f * xr, 128.f * xi);
                wc[1] = cexp_(xr, xi);
                G[2] = cmul(G[1], G[1]); G[4] = cmul(G[2], G[2]); G[8] = cmul(G[4], G[4]);
                wc[2] = cmul(wc[1], wc[1]); wc[3] = cmul(wc[2], wc[1]); wc[4] = cmul(wc[2], wc[2]); wc[5] = cmul(wc[4], wc[1]); wc[6] = cmul(wc[4], wc[2]); wc[7] = cmul(wc[4], wc[3]);
                cplx CG[17];
                CG[0] = C; CG[1] = cmul(C, G[1]); CG[2] = cmul(C, G[2]); CG[3] = cmul(CG[1], G[2]);
                #pragma unroll
                for (int a = 0; a < 4; a++) CG[4 + a] = cmul(CG[a], G[4]);
                #pragma unroll
                for (int a = 0; a < 9; a++) CG[8 + a] = cmul(CG[a], G[8]);
                #pragma unroll
                for (int r = 0; r < 41; r++) {
                    const int a = r < 16 ? (r >> 3) : (r < 24 ? 2 + ((r >> 2) & 1) : (r < 32 ? 4 + ((r >> 1) & 3) : r - 24));
                    const int cc = r < 16 ? (r & 7) : (r < 24 ? 2 * (r & 3) : (r < 32 ? 4 * (r & 1) : 0));
                    const cplx e = cc ? cmul(CG[a], wc[cc]) : CG[a];
                    sts32(EADDR(r), pack_f16(e.r, e.i));
                }
            }
            __syncwarp();
            float acc[3][2][4];
            #pragma unroll
            for (int i = 0; i < 3; i++)
                #pragma unroll
                for (int j = 0; j < 2; j++) { acc[i][j][0] = acc[i][j][1] = acc[i][j][2] = acc[i][j][3] = 0.f; }
            #pragma unroll
            for (int ks = 0; ks < 4; ks++) {
                uint32_t bq[4];
                ldsm_x4(bq, ef + 6144 + ((mi >> 1) * 8 + r8) * 128 + (((2 * ks + (mi & 1)) ^ r8) << 4));
                #pragma unroll
                for (int mt = 0; mt < 3; mt++) {
                    uint32_t aq[4];
                    ldsm_x4(aq, ef + (16 * mt + (mi & 1) * 8 + r8) * 128 + (((2 * ks + (mi >> 1)) ^ r8) << 4));
                    mma_f16(acc[mt][0], aq, bq[0], bq[1]);
                    mma_f16(acc[mt][1], aq, bq[2], bq[3]);
                }
            }
            const uint32_t kp = sb + SD_KP;
            #pragma unroll
            for (int mt = 0; mt < 3; mt++)
                #pragma unroll
                for (int nt = 0; nt < 2; nt++) {
                    const uint32_t a = kp + w * 3072 + (16 * mt + g) * 64 + nt * 32 + t * 8;
                    sts64(a, __float_as_uint(acc[mt][nt][0] * unsc), __float_as_uint(acc[mt][nt][1] * unsc));
                    sts64(a + 512, __float_as_uint(acc[mt][nt][2] * unsc), __float_as_uint(acc[mt][nt][3] * unsc));
                }
            bar_sync(4, 128);
            #pragma unroll
            for (int i = 0; i < 3; i++) {
                const uint32_t a = kp + (n + 128 * i) * 8;
                const uint2 v0 = lds64(a), v1 = lds64(a + 3072), v2 = lds64(a + 6144), v3 = lds64(a + 9216);
                sts64(a + 12288 + ((n >> 3) + 16 * i) * 8, __float_as_uint((__uint_as_float(v0.x) + __uint_as_float(v1.x)) + (__uint_as_float(v2.x) + __uint_as_float(v3.x))),
                                 __float_as_uint((__uint_as_float(v0.y) + __uint_as_float(v1.y)) + (__uint_as_float(v2.y) + __uint_as_float(v3.y))));
            }
            bar_sync(4, 128);
            const int slot = c % KSLOTS;
            float kv[16];
            #pragma unroll
            for (int e = 0; e < 8; e++) { kv[2 * e] = __uint_as_float(lds32(kp + 12288 + (goff[e] & 0xffff))); kv[2 * e + 1] = __uint_as_float(lds32(kp + 12288 + (goff[e] >> 16))); }
            if (c >= KSLOTS) mbar_wait_long(bKE + 8 * slot, (c / KSLOTS - 1) & 1);
            #pragma unroll
            for (int it = 0; it < 2; it++) {
                uint32_t hi[4], lo[4];
                #pragma unroll
                for (int e = 0; e < 4; e++) {
                    const float k0 = kv[8 * it + 2 * e], k1 = kv[8 * it + 2 * e + 1];
                    hi[e] = pack_bf16(k0, k1);
                    lo[e] = pack_bf16(k0 - bf_lo(hi[e]), k1 - bf_hi(hi[e]));
                }
                const uint32_t a = sb + SD_BC + slot * BC_BYTES + (w + 4 * it) * BC_LBO + (16 + 2 * lane) * 16;
                sts128(a, make_uint4(hi[0], hi[1], hi[2], hi[3]));
                sts128(a + 16, make_uint4(lo[0], lo[1], lo[2], lo[3]));
            }
            fence_async_smem();
            mbar_arrive(bKF + 8 * slot);
        }
        {
            uint32_t gw[9];
            #pragma unroll
            for (int j = 0; j < 9; j++) gw[j] = __ldg((const uint32_t*)gate_w + lane + 32 * j);
            float z = 0.f;
            #pragma unroll 1
            for (int i0 = 0; i0 < 15; i0 += 5) {
                uint32_t xv[5][9];
                #pragma unroll
                for (int i = 0; i < 5; i++) {
                    const int tk = min(blockIdx.x * 57 + w + 4 * (i0 + i), S_LEN - 1);
                    #pragma unroll
                    for (int j = 0; j < 9; j++) xv[i][j] = __ldg((const uint32_t*)(x + (size_t)tk * DM) + lane + 32 * j);
                }
                #pragma unroll
                for (int i = 0; i < 5; i++) {
                    float acc = 0.f;
                    #pragma unroll
                    for (int j = 0; j < 9; j++) { const uint32_t m = mul_bf2(xv[i][j], gw[j]); acc += bf_lo(m) + bf_hi(m); }
                    #pragma unroll
                    for (int o = 16; o; o >>= 1) acc += __shfl_xor_sync(0xffffffffu, acc, o);
                    if (lane == i0 + i) z = rbf(acc);
                }
            }
            const int li = w + 4 * lane, tk = blockIdx.x * 57 + li;
            if (li < 57 && tk < S_LEN) st_relaxed32(&g_gate[tk], pack_bf16(1.f / (1.f + expf(-z)), 0.f) | (epoch << 16));
        }
        if (tid == 256) GT(blockIdx.x, 67);
        fence_async_smem();
        __syncthreads();
            const uint32_t ost = sb + SD_OST + w * 256;
            const uint4* const pl = &g_part[blockIdx.x][0][0][0][lane];
            uint4 v[8];
            auto fetch = [&](int u, bool block) {
                const int s = u >> 2;
                uint32_t early;
                asm volatile("{\n.reg .pred p;\nmbarrier.test_wait.parity.shared::cta.b64 p, [%1], %2;\nselp.u32 %0, 1, 0, p;\n}\n" : "=r"(early) : "r"(bPRT + 8 * (s & 3)), "r"((s >> 2) & 1) : "memory");
                if (!early) {
                    if (!block) return false;
                    mbar_wait_long(bPRT + 8 * (s & 3), (s >> 2) & 1);
                    delay_clk(s < NSEG - 2 ? SD_P1 : SD_P2);
                } else if (SD_P3 && s < SD_RUSH) delay_clk(SD_P3);
                const uint4* p = pl + (u & (4 * PART_SLOTS - 1)) * 256;
                #pragma unroll
                for (int i = 0; i < 8; i++) v[i] = ld_relaxed128(p + 32 * i);
                return true;
            };
            auto units = [&](int u, int end) {
              fetch(u, true);
              #pragma unroll 1
              while (true) {
                const int s = u >> 2;
                const int t0 = 8 * u + 2 * t;
                const uint2 gt = lds64(sb + SD_Q0 + t0 * 4);
                const uint32_t ba = sb + SD_BT + g * BT_RS + (t0 >> 6) * 144 + (t0 & 63) * 2;
                const uint32_t b0 = lds32(ba), b1 = lds32(ba + 8 * BT_RS);
                const uint32_t phm = ((s / PART_SLOTS) & 1) - 1;
                int it = 0;
                while (true) {
                    uint32_t any = 0;
                    #pragma unroll
                    for (int i = 0; i < 8; i++) any |= v[i].x ^ phm;
                    if (!__any_sync(0xffffffffu, any & 1u) || ++it >= SD_SPIN) break;
                    if (it > 1 && s < NSEG - 2) __nanosleep(200);
                    const uint4* p = pl + (u & (4 * PART_SLOTS - 1)) * 256;
                    #pragma unroll
                    for (int i = 0; i < 8; i++) ld_relaxed128_p(v[i], p + 32 * i, (v[i].x ^ phm) & 1u);
                }
                if (lane == 0) mbar_arrive(bEPI + 8 * (s & 3));
                float a0 = __uint_as_float(v[0].x), a1 = __uint_as_float(v[0].y), a2 = __uint_as_float(v[0].z), a3 = __uint_as_float(v[0].w);
                #pragma unroll
                for (int i = 1; i < 8; i++) { a0 += __uint_as_float(v[i].x); a1 += __uint_as_float(v[i].y); a2 += __uint_as_float(v[i].z); a3 += __uint_as_float(v[i].w); }
                const uint32_t s01 = pack_bf16(a0, a1), s23 = pack_bf16(a2, a3);
                const int nu = u + 3;
                const bool pre = nu < end && fetch(nu, false);
                const uint32_t gg = __byte_perm(gt.x, gt.y, 0x5410), mm = pack_bf16(1.f - bf_lo(gg), 1.f - bf_hi(gg));
                const uint32_t r0 = add_bf2(mul_bf2(gg, s01), mul_bf2(mm, b0)), r1 = add_bf2(mul_bf2(gg, s23), mul_bf2(mm, b1));
                asm volatile("stmatrix.sync.aligned.m8n8.x2.trans.shared.b16 [%0], {%1,%2};" :: "r"(ost + r8 * 32 + (mi & 1) * 16), "r"(r0), "r"(r1) : "memory");
                __syncwarp();
                if (lane < 16) *(uint4*)(out + (size_t)(8 * u + (lane >> 1)) * DM + d0 + 8 * (lane & 1)) = lds128(ost + lane * 16);
                __syncwarp();
                if (lane == 0 && (u & 3) == 3) GT(blockIdx.x, 1 + s);
                if (nu >= end) break;
                if (!pre) fetch(nu, true);
                u = nu;
              }
            };
        if (w == 0) {
            if (lane == 0) {
                mbar_expect_tx(bWO, 131072);
                #pragma unroll
                for (int q = 0; q < 4; q++) tma2d(sb + SD_STG + q * 32768, &tmw, bWO, sh ? 128 * (blockIdx.x >> 3) + 64 * (q >> 1) : 512, sh ? 512 * (blockIdx.x & 7) + 256 * (q & 1) : 1024 * (blockIdx.x - 32) + 256 * q);
            }
            bar_sync(5, 128);
            const int ke0 = sh ? blockIdx.x & 7 : 2 * (blockIdx.x - 32);
            const unsigned int* f = &g_prog[12 * ke0 + (lane < (sh ? 12 : 24) ? lane : 0)];
            int avail = 0;
            #pragma unroll 1
            for (int s = 0; s < NSEG; s++) {
                if (s >= avail) {
                    int it = 0;
                    while (true) {
                        uint32_t v;
                        asm volatile("ld.acquire.gpu.global.u32 %0, [%1];" : "=r"(v) : "l"(f) : "memory");
                        avail = __reduce_min_sync(0xffffffffu, (v >> 8) == (epoch & 0xffffffu) ? v & 255u : 0u);
                        if (avail > s || ++it >= SD_SPIN) break;
                        if (s < NSEG - 1) __nanosleep(64);
                    }
                    asm volatile("fence.proxy.async.global;" ::: "memory");
                    if (lane == 0 && s == NSEG - 1) GT(blockIdx.x, 70);
                }
                if (lane == 0 && s == 2 && blockIdx.x == 0) st_relaxed32(&g_epoch, epoch + 1);
                const int b0 = sh ? s & 3 : s & 1, bp = (sh ? s >> 2 : s >> 1) & 1;
                const bf16* src = g_otok + (size_t)s * (SEG * NH * DH) + ke0 * 16384;
                mbar_wait_long(bEMPTY + 8 * b0, bp);
                if (!sh) mbar_wait_long(bEMPTY + 16 + 8 * b0, bp);
                if (s < NSEG - 1) {
                    asm volatile("{\n.reg .pred p, q;\nelect.sync _|p, 0xffffffff;\nsetp.eq.and.u32 q, %6, 0, p;\n"
                                 "@p mbarrier.arrive.expect_tx.shared.b64 _, [%2], 32768;\n"
                                 "@p cp.async.bulk.shared::cluster.global.mbarrier::complete_tx::bytes [%0], [%1], 32768, [%2];\n"
                                 "@q mbarrier.arrive.expect_tx.shared.b64 _, [%5], 32768;\n"
                                 "@q cp.async.bulk.shared::cluster.global.mbarrier::complete_tx::bytes [%3], [%4], 32768, [%5];\n}\n"
                        :: "r"(sb + SD_STG + b0 * 32768), "l"(src), "r"(bCH + 32 * b0), "r"(sb + SD_STG + (b0 + 2) * 32768), "l"(src + 16384), "r"(bCH + 32 * (b0 + 2)), "r"((uint32_t)sh) : "memory");
                } else {
                    #pragma unroll
                    for (int hc = 0; hc < 4; hc++)
                        asm volatile("{\n.reg .pred p, q;\nelect.sync _|p, 0xffffffff;\nsetp.eq.and.u32 q, %6, 0, p;\n"
                                     "@p mbarrier.arrive.expect_tx.shared.b64 _, [%2], 8192;\n"
                                     "@p cp.async.bulk.shared::cluster.global.mbarrier::complete_tx::bytes [%0], [%1], 8192, [%2];\n"
                                     "@q mbarrier.arrive.expect_tx.shared.b64 _, [%5], 8192;\n"
                                     "@q cp.async.bulk.shared::cluster.global.mbarrier::complete_tx::bytes [%3], [%4], 8192, [%5];\n}\n"
                            :: "r"(sb + SD_STG + b0 * 32768 + hc * 8192), "l"(src + hc * 4096), "r"(bCH + 32 * b0 + 8 * hc),
                               "r"(sb + SD_STG + (b0 + 2) * 32768 + hc * 8192), "l"(src + 16384 + hc * 4096), "r"(bCH + 32 * (b0 + 2) + 8 * hc), "r"((uint32_t)sh) : "memory");
                }
            }
        } else {
            if (w == 3) {
                for (int i = 0; i < 16; i += 8) {
                    uint4 v[8]; uint32_t miss = 0xffu; int it = 0;
                    const uint32_t tag = epoch & 0xffffu;
                    #pragma unroll
                    for (int j = 0; j < 8; j++) v[j] = make_uint4(0, 0, 0, 0);
                    do {
                        #pragma unroll
                        for (int j = 0; j < 8; j++) ld_relaxed128_p(v[j], (const uint4*)g_gate + (i + j) * 32 + lane, miss & (1u << j));
                        miss = 0;
                        #pragma unroll
                        for (int j = 0; j < 8; j++) miss |= (uint32_t)((v[j].x >> 16) != tag || (v[j].y >> 16) != tag || (v[j].z >> 16) != tag || (v[j].w >> 16) != tag) << j;
                    } while (__any_sync(0xffffffffu, miss) && ++it < SD_SPIN);
                    #pragma unroll
                    for (int j = 0; j < 8; j++) sts128(sb + SD_Q0 + ((i + j) * 32 + lane) * 16, v[j]);
                }
            }
            bar_sync(5, 128);
        }
        #pragma unroll 1
        for (int k = w == 0; k < 2; k++) units(k ? 4 * (NSEG - 1) + w : w - 1, k ? 0 : 4 * (NSEG - 1));
    }
    if (tid == 256) GT(blockIdx.x, 72);
}

extern "C" void kernel_launch(void* const* d_in, const int* in_sizes, int n_in, void* d_out, int out_size) {
    const bf16* x = (const bf16*)d_in[0];
    const bf16* mem0 = (const bf16*)d_in[1];
    const bf16* Wq = (const bf16*)d_in[2];
    const bf16* Wk = (const bf16*)d_in[3];
    const bf16* Wv = (const bf16*)d_in[4];
    const bf16* Wo = (const bf16*)d_in[5];
    const bf16* log_A_real = (const bf16*)d_in[8];
    const bf16* A_imag = (const bf16*)d_in[9];
    const bf16* C_real = (const bf16*)d_in[10];
    const bf16* C_imag = (const bf16*)d_in[11];
    const bf16* log_dt = (const bf16*)d_in[12];
    const bf16* D_skip = (const bf16*)d_in[13];
    const bf16* gate_w = (const bf16*)d_in[14];
    bf16* out = (bf16*)d_out;
    typedef CUresult (*EncFn)(CUtensorMap*, CUtensorMapDataType, cuuint32_t, void*, const cuuint64_t*, const cuuint64_t*, const cuuint32_t*, const cuuint32_t*,
                              CUtensorMapInterleave, CUtensorMapSwizzle, CUtensorMapL2promotion, CUtensorMapFloatOOBfill);
    static EncFn enc = nullptr;
    if (!enc) { void* fn = nullptr; cudaDriverEntryPointQueryResult qr; cudaGetDriverEntryPoint("cuTensorMapEncodeTiled", &fn, cudaEnableDefault, &qr); enc = (EncFn)fn; }
    auto mk = [&](CUtensorMap* tm, const void* ptr, uint64_t cols, uint64_t rows, uint32_t bc, uint32_t br) {
        cuuint64_t gdim[2] = {cols, rows}; cuuint64_t gstr[1] = {cols * 2}; cuuint32_t box[2] = {bc, br}; cuuint32_t estr[2] = {1, 1};
        enc(tm, CU_TENSOR_MAP_DATA_TYPE_BFLOAT16, 2, (void*)ptr, gdim, gstr, box, estr, CU_TENSOR_MAP_INTERLEAVE_NONE, bc == 64 ? CU_TENSOR_MAP_SWIZZLE_128B : CU_TENSOR_MAP_SWIZZLE_64B,
            CU_TENSOR_MAP_L2_PROMOTION_L2_256B, CU_TENSOR_MAP_FLOAT_OOB_FILL_NONE);
    };
    static bool attr_done = false;
    if (!attr_done) {
        cudaFuncSetAttribute(chain_kernel, cudaFuncAttributeMaxDynamicSharedMemorySize, SM_TOTAL);
        cudaFuncSetAttribute(side_kernel, cudaFuncAttributeMaxDynamicSharedMemorySize, SD_TOTAL);
        attr_done = true;
    }
    CUtensorMap tmx, tmw, tmq, tmk, tmv, tmo;
    {
        cuuint64_t gdim[3] = {64, S_LEN, DM / 64}; cuuint64_t gstr[2] = {DM * 2, 128}; cuuint32_t box[3] = {64, SEG, 3}; cuuint32_t estr[3] = {1, 1, 1};
        enc(&tmx, CU_TENSOR_MAP_DATA_TYPE_BFLOAT16, 3, (void*)x, gdim, gstr, box, estr, CU_TENSOR_MAP_INTERLEAVE_NONE, CU_TENSOR_MAP_SWIZZLE_128B,
            CU_TENSOR_MAP_L2_PROMOTION_L2_256B, CU_TENSOR_MAP_FLOAT_OOB_FILL_NONE);
    }
    mk(&tmw, Wo, DM, NH * DH, 64, 256);
    mk(&tmo, Wo, DM, NH * DH, 32, 128);
    mk(&tmq, Wq, NH * DH, DM, 32, 48); mk(&tmk, Wk, NH * DH, DM, 32, 48); mk(&tmv, Wv, NH * DH, DM, 32, 48);
    chain_kernel<<<96, CH_THREADS, SM_TOTAL>>>(tmx, tmq, tmk, tmv, tmo, mem0, 0u);
    cudaLaunchConfig_t cfg = {};
    cfg.gridDim = dim3(SD_CTAS); cfg.blockDim = dim3(SD_THREADS); cfg.dynamicSmemBytes = SD_TOTAL; cfg.stream = cudaStreamPerThread;
    cudaLaunchAttribute at[1];
    at[0].id = cudaLaunchAttributeProgrammaticStreamSerialization; at[0].val.programmaticStreamSerializationAllowed = 1;
    cfg.attrs = at; cfg.numAttrs = 1;
    cudaLaunchKernelEx(&cfg, side_kernel, tmw, x, log_A_real, A_imag, C_real, C_imag, log_dt, D_skip, gate_w, out);
}
```

```cpp
#include <cuda_runtime.h>
#include <cuda.h>
#include <cuda_bf16.h>
#include <stdint.h>

#define S_LEN 2048
#define DM 576
#define NH 32
#define DH 128
#define NMEM 8
#define SEG 32
#define NSEG 64
#define LQ 40
#define NS 128

typedef __nv_bfloat16 bf16;

__device__ __forceinline__ float bf(bf16 v) { return __bfloat162float(v); }
__device__ __forceinline__ bf16 tobf(float v) { return __float2bfloat16_rn(v); }
__device__ __forceinline__ float rbf(float v) { return __bfloat162float(__float2bfloat16_rn(v)); }

#define CH_THREADS 384
#define SPIN_LIMIT (1 << 17)
#define SM_X     0
#define XBUF     36864
#define SM_TOK   73728
#define TOKBUF   24576
#define SM_STASH 139264
#define SM_TS    (SM_STASH + 3072)
#define SM_WO    147456
#define SM_MEM   196608
#define SM_EX    205824
#define EXBUF    6144
#define SM_P     218112
#define SM_OST   219136
#define SM_O     223232
#define SM_BAR   228352
#define SM_IL    (SM_BAR + 128)
#define SM_SG    (SM_IL + 256)
#define SM_TOTAL (SM_SG + 64)

#define ACC_X    36864
#define ACC_FULL 0x0020u
#define SLOT_OFF(sl) ((((sl) & 1) << 7) | (((sl) & 2) << 8))
__device__ __align__(65536) unsigned char g_acc[65536];
__device__ unsigned int g_init[96];
__device__ unsigned int g_epoch = 1;
__device__ __align__(128) unsigned int g_ts[128];
__device__ __align__(1024) bf16 g_otok[S_LEN * NH * DH];
__device__ __align__(1024) unsigned char g_tokx[96][8192];
__device__ __align__(128) unsigned int g_prog[96];
#define STAMP(i)
#define STAMPV(i, v)
#define GT(b, i)
#define STAMPB(i)

__device__ __forceinline__ uint32_t smem_u32(const void* p) { return (uint32_t)__cvta_generic_to_shared(p); }
__device__ __forceinline__ void ldsm_x4(uint32_t (&r)[4], uint32_t addr) {
    asm volatile("ldmatrix.sync.aligned.m8n8.x4.shared.b16 {%0,%1,%2,%3}, [%4];" : "=r"(r[0]), "=r"(r[1]), "=r"(r[2]), "=r"(r[3]) : "r"(addr) : "memory");
}
__device__ __forceinline__ void ldsm_x4_p(uint32_t (&r)[4], uint32_t addr, uint32_t skip) {
    asm volatile("{\n.reg .pred p;\nsetp.eq.u32 p, %5, 0;\n@p ldmatrix.sync.aligned.m8n8.x4.shared.b16 {%0,%1,%2,%3}, [%4];\n}\n" : "+r"(r[0]), "+r"(r[1]), "+r"(r[2]), "+r"(r[3]) : "r"(addr), "r"(skip) : "memory");
}
__device__ __forceinline__ void ldsm_x4_t(uint32_t (&r)[4], uint32_t addr) {
    asm volatile("ldmatrix.sync.aligned.m8n8.x4.trans.shared.b16 {%0,%1,%2,%3}, [%4];" : "=r"(r[0]), "=r"(r[1]), "=r"(r[2]), "=r"(r[3]) : "r"(addr) : "memory");
}
__device__ __forceinline__ uint32_t ldsm_x1_t(uint32_t addr) {
    uint32_t r; asm volatile("ldmatrix.sync.aligned.m8n8.x1.trans.shared.b16 {%0}, [%1];" : "=r"(r) : "r"(addr) : "memory"); return r;
}
__device__ __forceinline__ void ldsm_x2_t(uint32_t& r0, uint32_t& r1, uint32_t addr) {
    asm volatile("ldmatrix.sync.aligned.m8n8.x2.trans.shared.b16 {%0,%1}, [%2];" : "=r"(r0), "=r"(r1) : "r"(addr) : "memory");
}
__device__ __forceinline__ void stsm_x4(uint32_t addr, uint32_t r0, uint32_t r1, uint32_t r2, uint32_t r3) {
    asm volatile("stmatrix.sync.aligned.m8n8.x4.shared.b16 [%0], {%1,%2,%3,%4};" :: "r"(addr), "r"(r0), "r"(r1), "r"(r2), "r"(r3) : "memory");
}
__device__ __forceinline__ void stsm_x4_t(uint32_t addr, uint32_t r0, uint32_t r1, uint32_t r2, uint32_t r3) {
    asm volatile("stmatrix.sync.aligned.m8n8.x4.trans.shared.b16 [%0], {%1,%2,%3,%4};" :: "r"(addr), "r"(r0), "r"(r1), "r"(r2), "r"(r3) : "memory");
}
__device__ __forceinline__ void mma16816(float (&c)[4], const uint32_t (&a)[4], uint32_t b0, uint32_t b1) {
    asm("mma.sync.aligned.m16n8k16.row.col.f32.bf16.bf16.f32 {%0,%1,%2,%3}, {%4,%5,%6,%7}, {%8,%9}, {%0,%1,%2,%3};"
        : "+f"(c[0]), "+f"(c[1]), "+f"(c[2]), "+f"(c[3]) : "r"(a[0]), "r"(a[1]), "r"(a[2]), "r"(a[3]), "r"(b0), "r"(b1));
}
__device__ __forceinline__ void mma16816r(float (&c)[4], uint32_t a0, uint32_t a1, uint32_t a2, uint32_t a3, uint32_t b0, uint32_t b1) {
    asm("mma.sync.aligned.m16n8k16.row.col.f32.bf16.bf16.f32 {%0,%1,%2,%3}, {%4,%5,%6,%7}, {%8,%9}, {%0,%1,%2,%3};"
        : "+f"(c[0]), "+f"(c[1]), "+f"(c[2]), "+f"(c[3]) : "r"(a0), "r"(a1), "r"(a2), "r"(a3), "r"(b0), "r"(b1));
}
__device__ __forceinline__ void mma1688(float (&c)[4], uint32_t a0, uint32_t a1, uint32_t b0) {
    asm("mma.sync.aligned.m16n8k8.row.col.f32.bf16.bf16.f32 {%0,%1,%2,%3}, {%4,%5}, {%6}, {%0,%1,%2,%3};"
        : "+f"(c[0]), "+f"(c[1]), "+f"(c[2]), "+f"(c[3]) : "r"(a0), "r"(a1), "r"(b0));
}
__device__ __forceinline__ uint32_t pack_bf16(float lo, float hi) {
    uint32_t r; asm("cvt.rn.bf16x2.f32 %0, %1, %2;" : "=r"(r) : "f"(hi), "f"(lo)); return r;
}
__device__ __forceinline__ float bf_lo(uint32_t v) { return __uint_as_float(v << 16); }
__device__ __forceinline__ float bf_hi(uint32_t v) { return __uint_as_float(v & 0xffff0000u); }
__device__ __forceinline__ uint32_t max_bf2(uint32_t a, uint32_t b) { uint32_t r; asm("max.bf16x2 %0, %1, %2;" : "=r"(r) : "r"(a), "r"(b)); return r; }
__device__ __forceinline__ uint32_t maxabs_bf2(uint32_t a, uint32_t b) { uint32_t r; asm("max.NaN.xorsign.abs.bf16x2 %0, %1, %2;" : "=r"(r) : "r"(a), "r"(b)); return r; }
__device__ __forceinline__ float ex2(float x) { float r; asm("ex2.approx.ftz.f32 %0, %1;" : "=f"(r) : "f"(x)); return r; }
__device__ __forceinline__ void ld_relaxed128_p(uint4& v, const uint4* p, uint32_t pred) {
    asm volatile("{\n.reg .pred p;\nsetp.ne.u32 p, %5, 0;\n@p ld.relaxed.gpu.global.v4.u32 {%0,%1,%2,%3}, [%4];\n}\n" : "+r"(v.x), "+r"(v.y), "+r"(v.z), "+r"(v.w) : "l"(p), "r"(pred) : "memory");
}
__device__ __forceinline__ uint4 ld_relaxed128(const uint4* p) { uint4 v; asm volatile("ld.relaxed.gpu.global.v4.u32 {%0,%1,%2,%3}, [%4];" : "=r"(v.x), "=r"(v.y), "=r"(v.z), "=r"(v.w) : "l"(p) : "memory"); return v; }
__device__ __forceinline__ uint32_t ld_relaxed32(const uint32_t* p) { uint32_t v; asm volatile("ld.relaxed.gpu.global.u32 %0, [%1];" : "=r"(v) : "l"(p) : "memory"); return v; }
__device__ __forceinline__ void st_relaxed128(uint4* p, uint4 v) { asm volatile("st.relaxed.gpu.global.v4.u32 [%0], {%1,%2,%3,%4};" :: "l"(p), "r"(v.x), "r"(v.y), "r"(v.z), "r"(v.w) : "memory"); }
__device__ __forceinline__ void st_relaxed32(uint32_t* p, uint32_t v) { asm volatile("st.relaxed.gpu.global.u32 [%0], %1;" :: "l"(p), "r"(v) : "memory"); }
__device__ __forceinline__ void st_relaxed128_p(uint4* p, uint4 v, uint32_t skip) {
    asm volatile("{\n.reg .pred p;\nsetp.eq.u32 p, %5, 0;\n@p st.relaxed.gpu.global.v4.u32 [%0], {%1,%2,%3,%4};\n}\n" :: "l"(p), "r"(v.x), "r"(v.y), "r"(v.z), "r"(v.w), "r"(skip) : "memory");
}
__device__ __forceinline__ void st_relaxed64_p(void* p, uint32_t x, uint32_t y, uint32_t skip) {
    asm volatile("{\n.reg .pred p;\n.reg .b64 v;\nsetp.eq.u32 p, %3, 0;\nmov.b64 v, {%1,%2};\n@p st.relaxed.gpu.global.b64 [%0], v;\n}\n" :: "l"(p), "r"(x), "r"(y), "r"(skip) : "memory");
}
__device__ __forceinline__ void ld_relaxed64_p(uint2& v, const void* p, uint32_t pred) {
    asm volatile("{\n.reg .pred p;\n.reg .b64 v;\nsetp.ne.u32 p, %3, 0;\nmov.b64 v, {%0,%1};\n@p ld.relaxed.gpu.global.b64 v, [%2];\nmov.b64 {%0,%1}, v;\n}\n" : "+r"(v.x), "+r"(v.y) : "l"(p), "r"(pred) : "memory");
}
__device__ __forceinline__ uint2 ld_relaxed64(const void* p) {
    uint2 v; asm volatile("{\n.reg .b64 v;\nld.relaxed.gpu.global.b64 v, [%2];\nmov.b64 {%0,%1}, v;\n}\n" : "=r"(v.x), "=r"(v.y) : "l"(p) : "memory"); return v;
}
__device__ __forceinline__ void st_relaxed32_p(void* p, uint32_t v, uint32_t skip) {
    asm volatile("{\n.reg .pred p;\nsetp.eq.u32 p, %2, 0;\n@p st.relaxed.gpu.global.u32 [%0], %1;\n}\n" :: "l"(p), "r"(v), "r"(skip) : "memory");
}
__device__ __forceinline__ void bar_arrive_p(int id, int n, uint32_t skip) {
    asm volatile("{\n.reg .pred p;\nsetp.eq.u32 p, %2, 0;\n@p bar.arrive %0, %1;\n}\n" :: "r"(id), "r"(n), "r"(skip) : "memory");
}
__device__ __forceinline__ void bar_sync_p(int id, int n, uint32_t skip) {
    asm volatile("{\n.reg .pred p;\nsetp.eq.u32 p, %2, 0;\n@p bar.sync %0, %1;\n}\n" :: "r"(id), "r"(n), "r"(skip) : "memory");
}
__device__ __forceinline__ uint32_t movm(uint32_t x) { uint32_t r; asm volatile("movmatrix.sync.aligned.m8n8.trans.b16 %0, %1;" : "=r"(r) : "r"(x)); return r; }
__device__ __forceinline__ void sts32_p(uint32_t a, uint32_t v, uint32_t doit) {
    asm volatile("{\n.reg .pred p;\nsetp.ne.u32 p, %2, 0;\n@p st.shared.u32 [%0], %1;\n}\n" :: "r"(a), "r"(v), "r"(doit) : "memory");
}
__device__ __forceinline__ uint32_t pin(uint32_t x) { return __shfl_sync(0xffffffffu, x, threadIdx.x & 31); }
__device__ __forceinline__ void ldsm16_t(uint32_t (&b)[4][4], uint32_t a) {
    asm volatile("ldmatrix.sync.aligned.m8n8.x4.trans.shared.b16 {%0,%1,%2,%3}, [%16];\n"
                 "ldmatrix.sync.aligned.m8n8.x4.trans.shared.b16 {%4,%5,%6,%7}, [%16+512];\n"
                 "ldmatrix.sync.aligned.m8n8.x4.trans.shared.b16 {%8,%9,%10,%11}, [%16+1024];\n"
                 "ldmatrix.sync.aligned.m8n8.x4.trans.shared.b16 {%12,%13,%14,%15}, [%16+1536];\n"
        : "=r"(b[0][0]), "=r"(b[0][1]), "=r"(b[0][2]), "=r"(b[0][3]), "=r"(b[1][0]), "=r"(b[1][1]), "=r"(b[1][2]), "=r"(b[1][3]),
          "=r"(b[2][0]), "=r"(b[2][1]), "=r"(b[2][2]), "=r"(b[2][3]), "=r"(b[3][0]), "=r"(b[3][1]), "=r"(b[3][2]), "=r"(b[3][3]) : "r"(a) : "memory");
}
template<int ID> __device__ __forceinline__ void sched_fence(uint32_t never) { while (never == 0x7fffff00u + ID) { asm volatile("nanosleep.u32 64;" ::: "memory"); } }
__device__ __forceinline__ uint32_t opaque_u() { uint32_t v; asm volatile("mov.u32 %0, %%nsmid;" : "=r"(v)); return v; }
__device__ __forceinline__ uint32_t bar_red_or(int id, int n, uint32_t v) {
    uint32_t r; asm volatile("{\n.reg .pred p, q;\nsetp.ne.u32 p, %3, 0;\nbar.red.or.pred q, %1, %2, p;\nselp.u32 %0, 1, 0, q;\n}\n" : "=r"(r) : "r"(id), "r"(n), "r"(v) : "memory"); return r;
}
template<class T> __device__ __forceinline__ T* launder_p(T* p) { asm volatile("" : "+l"(p)); return p; }
__device__ __forceinline__ uint32_t mapa_u32(uint32_t addr, uint32_t rank) { uint32_t d; asm("mapa.shared::cluster.u32 %0, %1, %2;" : "=r"(d) : "r"(addr), "r"(rank)); return d; }
__device__ __forceinline__ uint32_t mapa_v(uint32_t addr, uint32_t rank) { uint32_t d; asm volatile("mapa.shared::cluster.u32 %0, %1, %2;" : "=r"(d) : "r"(addr), "r"(rank)); return d; }
__device__ __forceinline__ void st_async32(uint32_t addr, uint32_t v, uint32_t mbar) { asm volatile("st.async.shared::cluster.mbarrier::complete_tx::bytes.u32 [%0], %1, [%2];" :: "r"(addr), "r"(v), "r"(mbar) : "memory"); }
__device__ __forceinline__ void cluster_arrive() { asm volatile("barrier.cluster.arrive.release.aligned;" ::: "memory"); }
__device__ __forceinline__ void cluster_wait() { asm volatile("barrier.cluster.wait.acquire.aligned;" ::: "memory"); }
__device__ __forceinline__ void cp_async16(uint32_t dst, const void* src) { asm volatile("cp.async.cg.shared.global [%0], [%1], 16;" :: "r"(dst), "l"(src) : "memory"); }
__device__ __forceinline__ void cp_async_commit() { asm volatile("cp.async.commit_group;" ::: "memory"); }
template<int N> __device__ __forceinline__ void cp_async_wait() { asm volatile("cp.async.wait_group %0;" :: "n"(N) : "memory"); }
__device__ __forceinline__ void cp_async_wait0() { asm volatile("cp.async.wait_group 0;" ::: "memory"); }
__device__ __forceinline__ void mbar_init(uint32_t a, uint32_t cnt) { asm volatile("mbarrier.init.shared.b64 [%0], %1;" :: "r"(a), "r"(cnt) : "memory"); }
__device__ __forceinline__ void mbar_expect_tx(uint32_t a, uint32_t bytes) { asm volatile("mbarrier.arrive.expect_tx.shared.b64 _, [%0], %1;" :: "r"(a), "r"(bytes) : "memory"); }
__device__ __forceinline__ bool mbar_try(uint32_t a, uint32_t parity) {
    uint32_t ok; asm volatile("{\n.reg .pred p;\nmbarrier.try_wait.parity.shared::cta.b64 p, [%1], %2;\nselp.u32 %0, 1, 0, p;\n}\n" : "=r"(ok) : "r"(a), "r"(parity) : "memory"); return ok;
}
__device__ __forceinline__ void mbar_wait(uint32_t a, uint32_t parity) { int it = 0; bool more; do { more = ++it < SPIN_LIMIT; } while (!mbar_try(a, parity) && more); }
__device__ __forceinline__ void bar_sync(int id, int n) { asm volatile("bar.sync %0, %1;" :: "r"(id), "r"(n) : "memory"); }
__device__ __forceinline__ void bar_arrive(int id, int n) { asm volatile("bar.arrive %0, %1;" :: "r"(id), "r"(n) : "memory"); }
__device__ __forceinline__ void fence_async_smem() { asm volatile("fence.proxy.async.shared::cta;" ::: "memory"); }
__device__ __forceinline__ void sts32(uint32_t a, uint32_t v) { asm volatile("st.shared.u32 [%0], %1;" :: "r"(a), "r"(v) : "memory"); }
__device__ __forceinline__ void sts128(uint32_t a, uint4 v) { asm volatile("st.shared.v4.u32 [%0], {%1,%2,%3,%4};" :: "r"(a), "r"(v.x), "r"(v.y), "r"(v.z), "r"(v.w) : "memory"); }
__device__ __forceinline__ uint4 lds128(uint32_t a) { uint4 v; asm volatile("ld.shared.v4.u32 {%0,%1,%2,%3}, [%4];" : "=r"(v.x), "=r"(v.y), "=r"(v.z), "=r"(v.w) : "r"(a) : "memory"); return v; }
__device__ __forceinline__ uint32_t lds32(uint32_t a) { uint32_t v; asm volatile("ld.shared.u32 %0, [%1];" : "=r"(v) : "r"(a) : "memory"); return v; }
__device__ __forceinline__ uint32_t gtime_lo() { uint32_t t; asm volatile("mov.u32 %0, %globaltimer_lo;" : "=r"(t)); return t; }
__device__ __forceinline__ void wait_gtime(uint32_t tg) {
    asm volatile("{\n.reg .pred p, q;\n.reg .b64 t;\n.reg .b32 lo, hi, d, n;\nmov.b32 n, 300;\n"
                 "WG_%=:\nmov.u64 t, %%globaltimer;\nmov.b64 {lo, hi}, t;\nsub.s32 d, lo, %0;\nsub.s32 n, n, 1;\n"
                 "setp.gt.s32 q, n, 0;\nsetp.lt.and.s32 p, d, 0, q;\n@p bra.uni WG_%=;\n}\n" :: "r"(tg) : "memory");
}
__device__ __forceinline__ void delay_clk(int d) { uint32_t t0 = clock(); while ((int)(clock() - t0) < d) {} }

__device__ __forceinline__ uint64_t desc128(uint32_t addr) {
    return (uint64_t)((addr & 0x3FFFF) >> 4) | ((uint64_t)1 << 16) | ((uint64_t)64 << 32) | ((uint64_t)1 << 62);
}
template<int accum> __device__ __forceinline__ void wgmma_n32(float (&d)[16], const uint32_t (&a)[4], uint64_t desc) {
    if (accum) {
        asm volatile("{\n.reg .pred p;\nsetp.ne.b32 p, 1, 0;\n"
            "wgmma.mma_async.sync.aligned.m64n32k16.f32.bf16.bf16 {%0,%1,%2,%3,%4,%5,%6,%7,%8,%9,%10,%11,%12,%13,%14,%15}, {%16,%17,%18,%19}, %20, p, 1, 1, 0;\n}\n"
            : "+f"(d[0]), "+f"(d[1]), "+f"(d[2]), "+f"(d[3]), "+f"(d[4]), "+f"(d[5]), "+f"(d[6]), "+f"(d[7]),
              "+f"(d[8]), "+f"(d[9]), "+f"(d[10]), "+f"(d[11]), "+f"(d[12]), "+f"(d[13]), "+f"(d[14]), "+f"(d[15])
            : "r"(a[0]), "r"(a[1]), "r"(a[2]), "r"(a[3]), "l"(desc));
    } else {
        asm volatile("{\n.reg .pred p;\nsetp.ne.b32 p, 0, 0;\n"
            "wgmma.mma_async.sync.aligned.m64n32k16.f32.bf16.bf16 {%0,%1,%2,%3,%4,%5,%6,%7,%8,%9,%10,%11,%12,%13,%14,%15}, {%16,%17,%18,%19}, %20, p, 1, 1, 0;\n}\n"
            : "=f"(d[0]), "=f"(d[1]), "=f"(d[2]), "=f"(d[3]), "=f"(d[4]), "=f"(d[5]), "=f"(d[6]), "=f"(d[7]),
              "=f"(d[8]), "=f"(d[9]), "=f"(d[10]), "=f"(d[11]), "=f"(d[12]), "=f"(d[13]), "=f"(d[14]), "=f"(d[15])
            : "r"(a[0]), "r"(a[1]), "r"(a[2]), "r"(a[3]), "l"(desc));
    }
}
__device__ __forceinline__ float rcp_approx(float x) { float r; asm("rcp.approx.ftz.f32 %0, %1;" : "=f"(r) : "f"(x)); return r; }
__device__ __forceinline__ void wg_fence() { asm volatile("wgmma.fence.sync.aligned;" ::: "memory"); }
__device__ __forceinline__ void wg_commit() { asm volatile("wgmma.commit_group.sync.aligned;" ::: "memory"); }
__device__ __forceinline__ void wg_wait0() { asm volatile("wgmma.wait_group.sync.aligned 0;" ::: "memory"); }

#define SCALE_HI 0x3db53db5u
#define SCALE_LO 0x371e371eu
#define LOG2E 1.4426950408889634f
#define NEG_BIG2 0xce6ece6eu
__device__ __forceinline__ uint32_t scale_bf2(uint32_t x) {
    uint32_t t, r;
    asm("mul.rn.bf16x2 %0, %1, %2;" : "=r"(t) : "r"(x), "r"(SCALE_LO));
    asm("fma.rn.bf16x2 %0, %1, %2, %3;" : "=r"(r) : "r"(x), "r"(SCALE_HI), "r"(t));
    return r;
}
__device__ __forceinline__ void cluster_arrive_rx() { asm volatile("barrier.cluster.arrive.relaxed.aligned;" ::: "memory"); }
__device__ __forceinline__ uint32_t launder(uint32_t x) { asm volatile("" : "+r"(x)); return x; }
__device__ __forceinline__ void mbar_arrive(uint32_t a) { asm volatile("mbarrier.arrive.shared.b64 _, [%0];" :: "r"(a) : "memory"); }
__device__ __forceinline__ void mbar_wait_cl(uint32_t a, uint32_t parity) {
    int it = 0; uint32_t ok;
    do { asm volatile("{\n.reg .pred p;\nmbarrier.try_wait.parity.acquire.cluster.shared::cta.b64 p, [%1], %2;\nselp.u32 %0, 1, 0, p;\n}\n" : "=r"(ok) : "r"(a), "r"(parity) : "memory"); } while (!ok && ++it < SPIN_LIMIT);
}
__device__ __forceinline__ uint64_t desc_from(uint32_t lo) { return (uint64_t)lo | ((uint64_t)0x40000040u << 32); }
#define SB_OFF 1024u
#define DESC_LO(off) ((((SB_OFF + (uint32_t)(off)) & 0x3FFFFu) >> 4) | 0x10000u)
template<int N> struct ic { static constexpr int value = N; };
__device__ __forceinline__ uint32_t uni(uint32_t x) { return __shfl_sync(0xffffffffu, x, 0); }

__device__ __forceinline__ uint32_t pack_f16(float lo, float hi) { uint32_t r; asm("cvt.rn.f16x2.f32 %0, %1, %2;" : "=r"(r) : "f"(hi), "f"(lo)); return r; }
__device__ __forceinline__ void sts16(uint32_t a, uint16_t v) { asm volatile("st.shared.u16 [%0], %1;" :: "r"(a), "h"(v) : "memory"); }
__device__ __forceinline__ void sts64(uint32_t a, uint32_t x, uint32_t y) { asm volatile("st.shared.v2.u32 [%0], {%1,%2};" :: "r"(a), "r"(x), "r"(y) : "memory"); }
__device__ __forceinline__ void ld_relaxed32_p(uint32_t& v, const void* p, uint32_t pred) {
    asm volatile("{\n.reg .pred p;\nsetp.ne.u32 p, %2, 0;\n@p ld.relaxed.gpu.global.u32 %0, [%1];\n}\n" : "+r"(v) : "l"(p), "r"(pred) : "memory");
}
__device__ __forceinline__ uint2 lds64(uint32_t a) { uint2 v; asm volatile("ld.shared.v2.u32 {%0,%1}, [%2];" : "=r"(v.x), "=r"(v.y) : "r"(a) : "memory"); return v; }
__device__ __forceinline__ void mbar_wait2(uint32_t a, uint32_t pa, uint32_t b, uint32_t pb) {
    int it = 0; uint32_t ok;
    do { asm volatile("{\n.reg .pred p, q;\nmbarrier.try_wait.parity.shared::cta.b64 p, [%1], %2;\nmbarrier.try_wait.parity.shared::cta.b64 q, [%3], %4;\nand.pred p, p, q;\nselp.u32 %0, 1, 0, p;\n}\n"
                      : "=r"(ok) : "r"(a), "r"(pa), "r"(b), "r"(pb) : "memory"); } while (!ok && ++it < SPIN_LIMIT);
}
__device__ __forceinline__ float exd(float s, float m) { return ex2(__fmul_rn(__fsub_rn(s, m), LOG2E)); }
__device__ __forceinline__ uint32_t gtime_after(uint32_t z) {
    uint32_t t = 0; asm volatile("{\n.reg .pred p;\nsetp.eq.u32 p, %1, 0;\n@p mov.u32 %0, %%globaltimer_lo;\n}\n" : "+r"(t) : "r"(z)); return t;
}
#define T_HOLD 4
#define T_KPRE 3
#define BLK_Q(p) (((p) < 3 ? (p) : 8) * 2048)
#define BLK_K(p) (((p) < 3 ? 4 + (p) : 9) * 2048)
#define BLK_V(p) (((p) < 2 ? 3 + 4 * (p) : 8 + (p)) * 2048)
__device__ __forceinline__ uint32_t exp_bf2(uint32_t s) { return pack_bf16(ex2(bf_lo(s) * LOG2E), ex2(bf_hi(s) * LOG2E)); }
template<int MT, int LO, int HI>
__device__ __forceinline__ void tok_loadv(uint32_t tok, int eh, int lane, uint32_t (&bv)[8][4]) {
    const int r8 = lane & 7;
    const uint32_t va = MT ? tok + lane * 64 + ((r8 >> 1) << 4) : tok + (lane & 15) * 64 + (((lane >> 4) ^ (r8 >> 1)) << 4);
    const uint32_t o0 = eh ? BLK_V(2) : BLK_V(0), o1 = eh ? BLK_V(3) : BLK_V(1);
    #pragma unroll
    for (int n = LO; n < HI; n++) { if (MT) ldsm_x4_t(bv[n], (va ^ ((n & 3) << 4)) + (n < 4 ? o0 : o1)); else ldsm_x4_t(bv[n], (va ^ ((n & 1) << 5)) + BLK_V(n >> 1)); }
}
#define T_VPRE 4
template<int MT, class F>
__device__ __forceinline__ void tok_part1(uint32_t tok, int eh, int lane, uint32_t (&q)[8][4], uint32_t (&sp)[5][2], uint32_t (&pa)[5][2], uint32_t (&bv)[8][4], uint32_t& rng, F&& hold) {
    float e[5][4];
    constexpr int NK = MT ? 5 : 3;
    const int g = lane >> 2, t = lane & 3, mi = lane >> 3, r8 = lane & 7;
    #pragma unroll
    for (int nt = 1; nt < NK; nt++) { e[nt][0] = e[nt][1] = e[nt][2] = e[nt][3] = 0.f; }
    const uint32_t qa = tok + (16 * MT + (mi & 1) * 8 + r8) * 64 + (((mi >> 1) ^ (r8 >> 1)) << 4);
    const uint32_t ka = tok + r8 * 64 + ((mi ^ (r8 >> 1)) << 4);
    uint32_t b[4][NK][4];
    constexpr int PRE = T_HOLD >= 3 ? (MT ? T_KPRE : 4) : 0;
    #pragma unroll
    for (int k2 = 0; k2 < 4; k2++) {
        if (T_HOLD >= 3) { ldsm_x4(q[2 * k2], qa + BLK_Q(k2)); ldsm_x4(q[2 * k2 + 1], (qa ^ 32) + BLK_Q(k2)); }
        if (k2 < PRE) {
            #pragma unroll
            for (int nt = 1; nt < NK; nt++) ldsm_x4(b[k2][nt], ka + BLK_K(k2) + (nt - 1) * 512);
        }
    }
    if (T_HOLD >= 3) hold();
    #pragma unroll
    for (int k2 = 0; k2 < 4; k2++) {
        if (T_HOLD < 3) { ldsm_x4(q[2 * k2], qa + BLK_Q(k2)); ldsm_x4(q[2 * k2 + 1], (qa ^ 32) + BLK_Q(k2)); }
        if (k2 >= PRE) {
            #pragma unroll
            for (int nt = 1; nt < NK; nt++) ldsm_x4(b[k2][nt], ka + BLK_K(k2) + (nt - 1) * 512);
        }
        #pragma unroll
        for (int nt = 1; nt < NK; nt++) mma16816(e[nt], q[2 * k2], b[k2][nt][0], b[k2][nt][1]);
        #pragma unroll
        for (int nt = 1; nt < NK; nt++) mma16816(e[nt], q[2 * k2 + 1], b[k2][nt][2], b[k2][nt][3]);
    }
    #pragma unroll
    for (int nt = 1; nt < NK; nt++) asm volatile("" : "+f"(e[nt][0]), "+f"(e[nt][1]), "+f"(e[nt][2]), "+f"(e[nt][3]));
    if (T_HOLD < 3) hold();
    #pragma unroll
    for (int nt = 1; nt < NK; nt++) {
        sp[nt][0] = nt < NK - 1 ? scale_bf2(pack_bf16(e[nt][0], e[nt][1])) : NEG_BIG2; sp[nt][1] = scale_bf2(pack_bf16(e[nt][2], e[nt][3]));
        rng = maxabs_bf2(nt == 1 ? sp[1][0] : (nt < NK - 1 ? maxabs_bf2(rng, sp[nt][0]) : rng), sp[nt][1]);
    }
    const uint32_t keep = (2 * t <= g ? 0x0000ffffu : 0u) | (2 * t + 1 <= g ? 0xffff0000u : 0u);
    sp[NK - 2][0] = (sp[NK - 2][0] & keep) | (NEG_BIG2 & ~keep);
    sp[NK - 1][1] = (sp[NK - 1][1] & keep) | (NEG_BIG2 & ~keep);
    #pragma unroll
    for (int nt = 1; nt < NK; nt++) { pa[nt][0] = nt < NK - 1 ? exp_bf2(sp[nt][0]) : 0u; pa[nt][1] = exp_bf2(sp[nt][1]); }
    tok_loadv<MT, 0, MT ? T_VPRE : 8>(tok, eh, lane, bv);
}
template<int MT, class F, class G, class H, class I>
__device__ __forceinline__ void tok_part2(uint32_t tok, uint32_t exl, uint32_t ost, int eh, int lane, const uint32_t (&q)[8][4], uint32_t (&sp)[5][2], uint32_t (&pa)[5][2], uint32_t (&bv)[8][4], uint32_t rng, bool vb,
                                          F&& wait_v, G&& duty, H&& pace, I&& wait_x) {
    constexpr int NK = MT ? 5 : 3;
    const int mi = lane >> 3, r8 = lane & 7;
    {
        float c[4][4];
        uint32_t b[4][4];
        ldsm16_t(b, exl + 2048);
        duty();
        #pragma unroll
        for (int j = 0; j < 4; j++) { c[j][0] = c[j][1] = c[j][2] = c[j][3] = 0.f; }
        #pragma unroll
        for (int k2 = 0; k2 < 4; k2++) { mma16816(c[(2 * k2) & 3], q[2 * k2], b[k2][0], b[k2][1]); mma16816(c[(2 * k2 + 1) & 3], q[2 * k2 + 1], b[k2][2], b[k2][3]); }
        sp[0][0] = scale_bf2(pack_bf16((c[0][0] + c[1][0]) + (c[2][0] + c[3][0]), (c[0][1] + c[1][1]) + (c[2][1] + c[3][1])));
        sp[0][1] = scale_bf2(pack_bf16((c[0][2] + c[1][2]) + (c[2][2] + c[3][2]), (c[0][3] + c[1][3]) + (c[2][3] + c[3][3])));
    }
    pa[0][0] = exp_bf2(sp[0][0]); pa[0][1] = exp_bf2(sp[0][1]);
    rng = maxabs_bf2(maxabs_bf2(rng, sp[0][0]), sp[0][1]);
    if (__builtin_expect(__any_sync(0xffffffffu, ((rng & 0x7fff7fffu) + 0x3ddf3ddfu) & 0x80008000u), 0)) {
        uint32_t m0 = sp[0][0], m1 = sp[0][1];
        #pragma unroll
        for (int nt = 1; nt < NK; nt++) { if (nt < NK - 1) m0 = max_bf2(m0, sp[nt][0]); m1 = max_bf2(m1, sp[nt][1]); }
        uint32_t mm = max_bf2(__byte_perm(m0, m1, 0x5410), __byte_perm(m0, m1, 0x7632));
        mm = max_bf2(mm, __shfl_xor_sync(0xffffffffu, mm, 1));
        mm = max_bf2(mm, __shfl_xor_sync(0xffffffffu, mm, 2));
        #pragma unroll
        for (int nt = 0; nt < NK; nt++) {
            if (nt < NK - 1) pa[nt][0] = pack_bf16(exd(bf_lo(sp[nt][0]), bf_lo(mm)), exd(bf_hi(sp[nt][0]), bf_lo(mm)));
            pa[nt][1] = pack_bf16(exd(bf_lo(sp[nt][1]), bf_hi(mm)), exd(bf_hi(sp[nt][1]), bf_hi(mm)));
        }
    }
    tok_loadv<MT, MT ? T_VPRE : 8, 8>(tok, eh, lane, bv);
    wait_v();
    constexpr int NQ = MT ? 2 : 4;
    float o[NQ][4][4], l[4] = {0.f, 0.f, 0.f, 0.f};
    const uint32_t ONE = 0x3F803F80u;
    mma16816r(l, pa[1][0], pa[1][1], pa[2][0], pa[2][1], ONE, ONE);
    if (MT) mma16816r(l, pa[3 % NK][0], pa[3 % NK][1], pa[4 % NK][0], pa[4 % NK][1], ONE, ONE);
    mma1688(l, pa[0][0], pa[0][1], ONE);
    #pragma unroll
    for (int j = 0; j < NQ; j++) {
        uint32_t bm[4];
        ldsm_x4(bm, exl + 4096 + (MT ? eh * 1024 : 0) + 512 * j);
        #pragma unroll
        for (int n = 0; n < 4; n++) {
            o[j][n][0] = o[j][n][1] = o[j][n][2] = o[j][n][3] = 0.f;
            if (MT) mma16816r(o[j][n], pa[1][0], pa[1][1], pa[2][0], pa[2][1], bv[4 * j + n][0], bv[4 * j + n][1]);
            else mma16816r(o[j][n], pa[1][0], pa[1][1], pa[2][0], pa[2][1], bv[2 * j + (n >> 1)][2 * (n & 1)], bv[2 * j + (n >> 1)][2 * (n & 1) + 1]);
        }
        if (MT) {
            #pragma unroll
            for (int n = 0; n < 4; n++) mma16816r(o[j][n], pa[3 % NK][0], pa[3 % NK][1], pa[4 % NK][0], pa[4 % NK][1], bv[4 * j + n][2], bv[4 * j + n][3]);
        }
        #pragma unroll
        for (int n = 0; n < 4; n++) mma1688(o[j][n], pa[0][0], pa[0][1], bm[n]);
    }
    #pragma unroll
    for (int j = 0; j < NQ; j++) asm volatile("" : "+f"(o[j][0][0]), "+f"(o[j][1][0]), "+f"(o[j][2][0]), "+f"(o[j][3][0]));
    asm volatile("" : "+f"(l[0]), "+f"(l[2]));
    wait_x();
    bar_arrive_p(12, 384, !vb);
    pace();
    const float i0 = rcp_approx(l[0]), i1 = rcp_approx(l[2]);
    const uint32_t oa = ost + ((mi & 1) * 8 + r8) * 128 + (((mi >> 1) ^ r8) << 4);
    #pragma unroll
    for (int j = 0; j < NQ; j++) {
        stsm_x4((oa ^ ((j & 1) << 6)) + (j >> 1) * 2048, pack_bf16(o[j][0][0] * i0, o[j][0][1] * i0), pack_bf16(o[j][0][2] * i1, o[j][0][3] * i1), pack_bf16(o[j][1][0] * i0, o[j][1][1] * i0), pack_bf16(o[j][1][2] * i1, o[j][1][3] * i1));
        stsm_x4((oa ^ (((j & 1) << 6) | 32)) + (j >> 1) * 2048, pack_bf16(o[j][2][0] * i0, o[j][2][1] * i0), pack_bf16(o[j][2][2] * i1, o[j][2][3] * i1), pack_bf16(o[j][3][0] * i0, o[j][3][1] * i0), pack_bf16(o[j][3][2] * i1, o[j][3][3] * i1));
    }
}

#define X_PRED "@q "
#define X_LANE(ll) ((ll) >> 4)
#define SEND_LANE(ll) ((ll) >> 2)
#define TP_E 0
#define V_EARLY 1
#ifndef M_SF
#define M_SF 0
#endif
#ifndef M_F2
#define M_F2 0
#endif
#ifndef M_FENCE
#define M_FENCE 1
#endif
#define SW_FENCE 0
#define PV_FENCE 1
#define IL_AT 3
#define TAIL 0
#define MP_PRE 4
#define VF_EARLY 1
__device__ __forceinline__ void stsm2_p(uint32_t a, const uint32_t (&v)[8], uint32_t skip) {
    asm volatile("{\n.reg .pred p;\nsetp.eq.u32 p, %9, 0;\n@p stmatrix.sync.aligned.m8n8.x4.trans.shared.b16 [%0], {%1,%2,%3,%4};\n"
                 "@p stmatrix.sync.aligned.m8n8.x4.trans.shared.b16 [%0+1024], {%5,%6,%7,%8};\n}\n"
        :: "r"(a), "r"(v[0]), "r"(v[1]), "r"(v[2]), "r"(v[3]), "r"(v[4]), "r"(v[5]), "r"(v[6]), "r"(v[7]), "r"(skip) : "memory");
}
template<int OA, int OB>
__device__ __forceinline__ void send_tile(float c0, float c1, float c2, float c3, uint32_t a, uint32_t b, uint32_t l16) {
    const uint32_t hi = (uint32_t)((uint64_t)g_acc >> 32);
    asm volatile("{\n.reg .pred q, pl, ph;\n.reg .b64 pa, pb;\n.reg .b32 t, w0, w1, w2;\n.reg .f32 x, y, z;\n"
                 "and.b32 t, %7, 0x30;\nsetp.eq.u32 q, t, 0;\nand.b32 t, %7, 0x70;\nsetp.eq.u32 ph, t, 0;\nxor.pred pl, q, ph;\n"
                 "selp.f32 x, 0f00010000, %4, pl;\nselp.f32 y, 0f00010000, %6, ph;\nselp.f32 z, %6, %4, ph;\n"
                 "cvt.rn.bf16x2.f32 w0, x, %3;\ncvt.rn.bf16x2.f32 w1, y, %5;\ncvt.rn.bf16x2.f32 w2, 0f00010000, z;\n"
                 "mov.b64 pa, {%0, %2};\nmov.b64 pb, {%1, %2};\n"
                 "red.relaxed.gpu.global.add.noftz.bf16x2 [pa+%8], w0;\nred.relaxed.gpu.global.add.noftz.bf16x2 [pa+%10], w1;\n" X_PRED "red.relaxed.gpu.global.add.noftz.bf16x2 [pb+%9], w2;\n}\n"
        :: "r"(a), "r"(b), "r"(hi), "f"(c0), "f"(c1), "f"(c2), "f"(c3), "r"(l16), "n"(OA), "n"(OB), "n"(OA + 256) : "memory");
}
__device__ __forceinline__ uint32_t send_ua(uint32_t tile) { return (uint32_t)(uint64_t)g_acc + tile * 1024; }
__device__ __forceinline__ uint32_t send_ub(uint32_t tile) { return (uint32_t)(uint64_t)g_acc + ACC_X + (tile >> 1) * 1024 + (tile & 1) * 256; }
__device__ __forceinline__ void lds_il(float& il, float& ih, uint32_t a) {
    uint32_t x, y; asm volatile("ldmatrix.sync.aligned.m8n8.x2.shared.b16 {%0,%1}, [%2];" : "=r"(x), "=r"(y) : "r"(a) : "memory");
    il = __uint_as_float(x); ih = __uint_as_float(y);
}
template<bool OWN, class F>
__device__ __forceinline__ void stage_w(const uint32_t (&wo)[8][4], uint32_t ol, uint32_t tile, uint32_t so, uint32_t l16, uint32_t nv, uint32_t ila, F&& issued) {
    float il, ih;
    uint32_t b[4][4], sa, sb_, ll;
    float c[2][4];
    auto addr = [&] {
        ll = OWN ? l16 : l16 | (__float_as_uint(c[0][0]) & nv);
        sa = SEND_LANE(ll) + (send_ua(tile) + so); sb_ = X_LANE(ll) + (send_ub(tile) + so);
    };
    ldsm16_t(b, ol);
    lds_il(il, ih, ila);
    if (OWN) addr();
    if (!OWN || SW_FENCE) sched_fence<0>(nv);
    #pragma unroll
    for (int i = 0; i < 2; i++) c[i][0] = c[i][1] = c[i][2] = c[i][3] = 0.f;
    #pragma unroll
    for (int j = 0; j < 4; j++) {
        if (!OWN && j == 3) addr();
        mma16816(c[0], wo[2 * j], b[j][0], b[j][1]); mma16816(c[1], wo[2 * j + 1], b[j][2], b[j][3]);
    }
    if (TP_E || (OWN && V_EARLY)) { asm volatile("" : "+f"(c[0][0]), "+f"(c[1][0])); sched_fence<OWN ? 4 : 5>(nv); }
    issued();
    send_tile<0, 0>((c[0][0] + c[1][0]) * il, (c[0][1] + c[1][1]) * ih, (c[0][2] + c[1][2]) * il, (c[0][3] + c[1][3]) * ih, sa, sb_, l16);
}

template<int N> __device__ __forceinline__ void code_pad(uint32_t nv) {
    if (N && nv == 0x7fffffe0u + N % 16) {
        float v = __uint_as_float(nv);
        #pragma unroll
        for (int i = 0; i < N; i++) asm volatile("fma.rn.f32 %0, %0, %0, %0;" : "+f"(v));
        sts32_p(0u, __float_as_uint(v), nv);
    }
}
#define PAD_T0 0
#define PAD_T1 0
#define PAD_S 0
#define PAD_P 0
#define BAR_PRO 1
#define BAR_MEM 2
#define BAR_P   3
#define BAR_PRJ 4
#define BAR_VGO 7
#define BAR_X0  7
#define BAR_S   9
#define BAR_P2  10
#define BAR_O   11
#define BAR_O2  14
#define BAR_TP  15
#define BAR_V   12
#define BAR_FB  13
#define VGO_AT 9
#define TP_N 36
#define TP_N1 24
#define REG_P 200
#define W_FENCE 1
#define WO_PRE 3
#define WO_MID 8
#define WO_EX 8
#define WO_REP 2
#define TP_DELAY 0
#define PRE_W 4
#ifndef M_RES
#define M_RES 5
#endif
#define K_PRE 6
#define K_POS 0
#define LD_FENCE 0
#define CV_FENCE 4
#define ANN_POS 1
#define PRO_V 0
#define PUB_W 0
#define ST_AT 4
#define MEM_N 352
#define VGO_N (256 + (T_HOLD == 2 ? 32 : 0))
#define PRO_N ((PRO_V ? 256 : 32 * nqk) + (K_PRE < 8 ? 64 : 0) + ((T_HOLD & 1) ? 32 : 0))
#define S_DUTY 0
#define X_POS 0
#define K_OWN 1
#define TG_MERGE 1
#define K_TOP 0
#define TM_PF 1
#define TS_CAP 64
#define G1_MIN 128
#define G1_0 256
#define G1_NS 1184

__global__ void __cluster_dims__(3, 1, 1) __launch_bounds__(CH_THREADS, 1)
chain_kernel(const __grid_constant__ CUtensorMap tmx, const __grid_constant__ CUtensorMap tmq, const __grid_constant__ CUtensorMap tmk,
             const __grid_constant__ CUtensorMap tmv, const __grid_constant__ CUtensorMap tmo, const bf16* __restrict__ mem0, const uint32_t nv_) {
    extern __shared__ __align__(1024) unsigned char smem[];
    const uint32_t sb = smem_u32(smem);
    const int tid = threadIdx.x, lane = tid & 31;
    const int warp = __shfl_sync(0xffffffffu, tid >> 5, 0);
    const uint32_t nv = __shfl_sync(0xffffffffu, nv_ * tid, 0);
    const int h = blockIdx.x / 3, r = blockIdx.x % 3;
    const int mi = lane >> 3, r8 = lane & 7;
    const uint32_t bX = sb + SM_BAR, bTOK = bX + 16, bEX = bX + 40, bW = bX + 64, bEV = bX + 104, bFREE = bX + 32;
    const int nqk = r < 2 ? 6 : 4;
    if ((sb & 0xFFFFFFu) != SB_OFF) __trap();
    asm volatile("griddepcontrol.launch_dependents;");
    if (tid == 0 && blockIdx.x == 0) GT(40, 0);

    auto load_w = [&](int lo, int hi) {
        #pragma unroll 1
        for (int i = lo; i < hi; i++) {
            const int blk = i >> 2, j = i & 3;
            if (i < 48) {
                const int m = r < 2 ? (j < 3 ? r : 2) : (j < 2 ? j : 2), p = r < 2 ? (j < 3 ? j : r) : (j < 2 ? 3 : j);
                asm volatile("cp.async.bulk.tensor.2d.shared::cluster.global.mbarrier::complete_tx::bytes [%0], [%1, {%3, %4}], [%2];"
                    :: "r"(sb + i * 3072), "l"(m == 0 ? &tmq : (m == 1 ? &tmk : &tmv)), "r"(bW + (blk < 3 ? 0 : (blk < 6 ? 8 : (blk < 10 ? 16 : 24)))), "r"(h * DH + p * 32), "r"(blk * 48) : "memory");
            } else asm volatile("cp.async.bulk.tensor.2d.shared::cluster.global.mbarrier::complete_tx::bytes [%0], [%1, {%3, %4}], [%2];"
                :: "r"(sb + SM_WO + (i - 48) * 8192), "l"(&tmo), "r"(bW + 32), "r"(192 * r + 32 * (i - 48)), "r"(h * DH) : "memory");
        }
    };
    if (tid == 352) {
        #pragma unroll
        for (int i = 0; i < 15; i++) mbar_init(bX + 8 * i, (i == 5 || i == 6) ? 1 + nqk : (i >= 13 ? 9 - nqk : 1));
        asm volatile("fence.mbarrier_init.release.cluster;" ::: "memory");
        mbar_expect_tx(bW, 36864); mbar_expect_tx(bW + 8, 36864); mbar_expect_tx(bW + 16, 49152); mbar_expect_tx(bW + 24, 24576); mbar_expect_tx(bW + 32, 49152);
        load_w(0, 2 * PRE_W);
    }
    if (TM_PF && tid < 2) asm volatile("prefetch.param.tensormap [%0];" :: "l"(__cvta_generic_to_grid_constant(tid ? &tmo : &tmx)) : "memory");
    const unsigned epoch = ld_relaxed32(&g_epoch);
    __syncthreads();
    const uint32_t pw0 = ((mi >> 1) * 8 + r8) * 64 + (((2 * (warp & 1) + (mi & 1)) ^ (r8 >> 1)) << 4);
    auto tok_publish = [&](int tb, int k) {
        const uint32_t src = sb + SM_TOK + tb * TOKBUF + r * 8192, bar = bTOK + 8 * tb;
        if (k == 1) asm volatile("{\n.reg .pred p;\nelect.sync _|p, 0xffffffff;\n@p mbarrier.arrive.expect_tx.shared.b64 _, [%0], 16384;\n}\n" :: "r"(bar) : "memory");
        asm volatile("{\n.reg .pred p;\nelect.sync _|p, 0xffffffff;\n"
                     "@p cp.async.bulk.shared::cluster.shared::cta.mbarrier::complete_tx::bytes [%0], [%1], 8192, [%2];\n}\n"
            :: "r"(mapa_u32(src, (r + k) % 3)), "r"(src), "r"(mapa_u32(bar, (r + k) % 3)) : "memory");
    };
    if (warp < 8) {
        asm volatile("setmaxnreg.inc.sync.aligned.u32 %0;" :: "n"(REG_P));
        uint32_t wf[36][4];
        const uint32_t wl = sb + (warp >> 1) * 3072 + pw0;
        float ta0[16], ta1[16];
        auto tp_part = [&](auto lo, auto hi) {
            wg_fence();
            #pragma unroll
            for (int i = lo.value; i < hi.value; i++) {
                if (i == 0) wgmma_n32<0>(ta0, wf[0], desc_from(DESC_LO(SM_X))); else wgmma_n32<1>(ta0, wf[i], desc_from(DESC_LO(SM_X) + (i >> 2) * 256 + (i & 3) * 2));
            }
            #pragma unroll
            for (int i = lo.value; i < hi.value; i++) {
                if (i == 0) wgmma_n32<0>(ta1, wf[0], desc_from(DESC_LO(SM_X + XBUF))); else wgmma_n32<1>(ta1, wf[i], desc_from(DESC_LO(SM_X + XBUF) + (i >> 2) * 256 + (i & 3) * 2));
            }
            wg_commit();
        };
        if (tid == 32) load_w(2 * PRE_W, 40);
        if (tid == 0) GT(41 + blockIdx.x % 3, 7);
        code_pad<PAD_P>(nv);
        mbar_wait(bW, 0);
        #pragma unroll
        for (int i = 0; i < 9; i++) ldsm_x4_t(wf[i], wl + (i / 3) * 12288 + (i % 3) * 1024);
        fence_async_smem(); bar_arrive(BAR_X0, 288);
        mbar_wait(bW + 8, 0);
        #pragma unroll
        for (int i = 9; i < 18; i++) ldsm_x4_t(wf[i], wl + (i / 3) * 12288 + (i % 3) * 1024);
        fence_async_smem(); bar_arrive(BAR_X0 + 1, 288);
        mbar_wait(bX, 0); mbar_wait(bX + 8, 0);
        tp_part(ic<0>(), ic<18>());
        wg_wait0();
        sts128(sb + SM_OST + tid * 16, make_uint4(wf[0][0], wf[0][1], wf[0][2], wf[0][3]));
        mbar_wait(bW + 16, 0);
        #pragma unroll
        for (int i = 18; i < 30; i++) ldsm_x4_t(wf[i], wl + (i / 3) * 12288 + (i % 3) * 1024);
        tp_part(ic<18>(), ic<30>());
        mbar_wait(bW + 24, 0);
        if (tid == 0) GT(41 + blockIdx.x % 3, 0);
        wg_wait0();
        #pragma unroll
        for (int i = 30; i < 36; i++) ldsm_x4_t(wf[i], wl + (i / 3) * 12288 + (i % 3) * 1024);
        fence_async_smem();
        cluster_arrive_rx();
        tp_part(ic<30>(), ic<36>());
        if (tid == 0) GT(41 + blockIdx.x % 3, 2);
        const uint32_t pw = pin(pw0);
        auto tp_store = [&](const float (&acc)[16], uint32_t off) {
            const uint32_t ta = pw + launder(sb + off + (warp >> 1) * 2048);
            stsm_x4_t(ta, pack_bf16(acc[0], acc[1]), pack_bf16(acc[2], acc[3]), pack_bf16(acc[4], acc[5]), pack_bf16(acc[6], acc[7]));
            stsm_x4_t(ta + 1024, pack_bf16(acc[8], acc[9]), pack_bf16(acc[10], acc[11]), pack_bf16(acc[12], acc[13]), pack_bf16(acc[14], acc[15]));
        };
        cluster_wait();
        wg_wait0();
        tp_store(ta0, SM_TOK + r * 8192);
        if (warp == 0) { bar_sync(BAR_PRJ, 256); fence_async_smem(); tok_publish(0, 1); tok_publish(0, 2); } else bar_arrive(BAR_PRJ, 256);
        if (!TAIL) { tp_store(ta1, SM_TOK + TOKBUF + r * 8192); }
        { const uint4 v = lds128(sb + SM_OST + tid * 16); wf[0][0] = v.x; wf[0][1] = v.y; wf[0][2] = v.z; wf[0][3] = v.w; }
        if (tid == 0) GT(41 + blockIdx.x % 3, 4);
        const uint32_t l16 = pin(lane * 16), sbl = sb + l16, l4w = pin(sb + warp * 256 + lane * 4);
        uint32_t wo[8][4];
        const int exo = r < 2 ? (warp < 6 ? r * 2048 : 4096 + (2 * r - 6) * 256) : (warp < 2 ? 6 * 256 : (warp < 4 ? 2048 + 4 * 256 : 4096));
        const bool isqk = warp < nqk;
        const uint32_t exbar = isqk ? bEX : bEV;
        uint32_t vf[2][4];
        auto prep = [&](int s) {
            const uint32_t va = pw + launder(sb + SM_TOK + (s & 1) * TOKBUF + BLK_V(warp >> 1));
            mbar_wait(bTOK + 8 * (s & 1), (s >> 1) & 1);
            if (VF_EARLY) { ldsm_x4_t(vf[0], va); ldsm_x4_t(vf[1], va + 1024); }
        };
        prep(0);
        for (int s = 0; ; s++) {
            const int par = s & 1;
            const uint32_t va = pw + launder(sb + SM_TOK + par * TOKBUF + BLK_V(warp >> 1)), wa = pw + launder(sb + SM_WO + (warp >> 1) * 8192);
            const uint32_t exu = launder(SM_EX + par * EXBUF);
            {
                float acc[4][4];
                #pragma unroll
                for (int i = 0; i < 4; i++) { acc[i][0] = acc[i][1] = acc[i][2] = acc[i][3] = 0.f; }
                uint32_t b[18][4];
                if (!isqk) { bar_arrive(BAR_MEM, MEM_N); bar_sync(BAR_VGO, VGO_N); } else bar_sync(BAR_MEM, MEM_N);
                #pragma unroll
                for (int i2 = 0; i2 < 18; i2++) {
                    if (!TAIL || i2 >= MP_PRE) ldsm_x4_t(b[i2], sbl + SM_MEM + i2 * 512);
                    if (i2 == VGO_AT) bar_arrive_p(BAR_VGO, VGO_N, !isqk);
                    if (PRO_V && i2 == PRO_V) bar_arrive_p(BAR_PRO, PRO_N, isqk || s == NSEG - 1);
                    mma16816(acc[(2 * i2) & 3], wf[2 * i2], b[i2][0], b[i2][1]);
                    mma16816(acc[(2 * i2 + 1) & 3], wf[2 * i2 + 1], b[i2][2], b[i2][3]);
                }
                float q[4];
                #pragma unroll
                for (int i = 0; i < 4; i++) q[i] = (acc[0][i] + acc[1][i]) + (acc[2][i] + acc[3][i]);
                const uint32_t lo = pack_bf16(q[0], q[1]), hi = pack_bf16(q[2], q[3]);
                const uint32_t exl = l4w + launder(exu + exo), bar = exbar + par * 8;
                #pragma unroll
                for (int k = 1; k < 3; k++) {
                    const uint32_t exd = mapa_u32(exl, (r + k) % 3), exb = mapa_u32(bar, (r + k) % 3);
                    st_async32(exd, lo, exb); st_async32(exd + 128, hi, exb);
                }
                sts32(exl, lo); sts32(exl + 128, hi);
                __syncwarp();
                asm volatile("{\n.reg .pred p;\nelect.sync _|p, 0xffffffff;\n@p mbarrier.arrive.shared.b64 _, [%0];\n}\n" :: "r"(bar) : "memory");
                if (s < NSEG - 1) bar_sync_p(BAR_PRO, PRO_N, !isqk);
            }
            if (s == 0) mbar_wait(bW + 32, 0);
            if (s == NSEG - 1) break;
            {
                if (!VF_EARLY) { ldsm_x4_t(vf[0], va); ldsm_x4_t(vf[1], va + 1024); }
                #pragma unroll
                for (int i = 0; i < WO_PRE; i++) ldsm_x4_t(wo[i], wa + i * 1024);
                if (WO_PRE < 8) {
                    #pragma unroll
                    for (int k = 0; k < WO_REP; k++) mbar_wait(bEX + 8 * par, (s >> 1) & 1);
                    #pragma unroll
                    for (int i = WO_PRE; i < 8; i++) ldsm_x4_t(wo[i], wa + i * 1024);
                }
                mbar_wait(bEV + 8 * par, (s >> 1) & 1);
                const uint32_t vm0 = lds32(l4w + exu + 4096), vm1 = lds32(l4w + exu + 4096 + 128);
                const uint32_t big = bar_red_or(BAR_P, 352, 0u);
                uint32_t pb[4]; ldsm_x4_t(pb, sbl + SM_P);
                uint32_t pm = ldsm_x1_t(sbl + SM_P + 512);
                float o0[4] = {0.f, 0.f, 0.f, 0.f}, o1[4] = {0.f, 0.f, 0.f, 0.f}, o2[4] = {0.f, 0.f, 0.f, 0.f};
                if (__builtin_expect(big, 0)) {
                    bar_sync(BAR_P2, 352);
                    ldsm_x4_t(pb, sbl + SM_P); pm = ldsm_x1_t(sbl + SM_P + 512);
                }
                mma16816(o0, vf[0], pb[0], pb[1]);
                mma16816(o1, vf[1], pb[2], pb[3]);
                mma1688(o2, vm0, vm1, pm);
                uint32_t oa = pm;
                #pragma unroll
                for (int i = 0; i < 8; i++) oa ^= wo[i][0];
                oa = l4w | (oa & nv);
                sts32(oa + SM_O, pack_bf16((o0[0] + o1[0]) + o2[0], (o0[1] + o1[1]) + o2[1]));
                sts32(oa + SM_O + 128, pack_bf16((o0[2] + o1[2]) + o2[2], (o0[3] + o1[3]) + o2[3]));
                const uint32_t xd = uni(DESC_LO(SM_X) + par * (XBUF >> 4));
                auto tp = [&](auto lo, auto hi) {
                    #pragma unroll
                    for (int i = lo.value; i < hi.value; i++) {
                        if (i == 0) wgmma_n32<0>(ta1, wf[0], desc_from(xd));
                        else wgmma_n32<1>(ta1, wf[i], desc_from(xd + (i >> 2) * 256 + (i & 3) * 2));
                    }
                };
                bar_sync(BAR_O, 352);
                stage_w<false>(wo, sbl + SM_O, 12 * r + warp, SLOT_OFF(s + 1), l16, nv, sbl + SM_IL, [&] {
                    if (TP_E) { bar_sync(BAR_V, 384); wg_fence(); tp(ic<0>(), ic<TP_E>()); } });
                STAMP(warp);
                if (!TP_E) { bar_sync(BAR_V, 384); wg_fence(); }
                STAMP(12);
                tp(ic<TP_E>(), ic<TP_N>());
                wg_commit();
                prep(s + 1);
                if (!TAIL) { wg_wait0(); tp_store(ta1, SM_TOK + par * TOKBUF + r * 8192); STAMP(13 + (warp >> 2)); }
            }
        }
        cluster_arrive(); cluster_wait();
    } else {
        asm volatile("setmaxnreg.dec.sync.aligned.u32 %0;" :: "n"(504 - 2 * REG_P));
        const int a = warp - 8;
        const uint32_t sbl = sb + lane * 16;
        if (a < 3) {
            const uint32_t zs = 3 * blockIdx.x + (r8 >> 1);
            const uint32_t zoff = (r8 < 6 ? (zs >> 3) * 1024 + ((zs >> 2) & 1) * 256 + (zs & 3) * 32 : ACC_X + (blockIdx.x >> 1) * 1024 + (blockIdx.x & 1) * 256) + (lane & 1) * 16;
            const uint32_t zskip = r8 >= 6 && blockIdx.x >= 36;
            if (a == 1) {
                st_relaxed128_p((uint4*)(g_acc + zoff + SLOT_OFF(mi)), make_uint4(0, 0, 0, 0), zskip);
                __threadfence();
                __syncwarp();
                if (lane == 0) st_relaxed32(&g_init[blockIdx.x], epoch);
            }
            {
                #pragma unroll
                for (int i = 0; i < 6; i++) {
                    const int c = tid - 256 + 96 * i;
                    const unsigned short* m = (const unsigned short*)mem0 + c;
                    uint4 v;
                    v.x = m[0] | ((uint32_t)m[DM] << 16); v.y = m[2 * DM] | ((uint32_t)m[3 * DM] << 16);
                    v.z = m[4 * DM] | ((uint32_t)m[5 * DM] << 16); v.w = m[6 * DM] | ((uint32_t)m[7 * DM] << 16);
                    sts128(sb + SM_MEM + c * 16, v);
                }
                sts32(sb + SM_SG + 36, 0u);
            }
            asm volatile("barrier.cluster.arrive.release.aligned;" ::: "memory");
            { int it = 0; while (__any_sync(0xffffffffu, ld_relaxed32(&g_init[a * 32 + lane]) != epoch) && ++it < SPIN_LIMIT) {} }
            __threadfence();
            const uint32_t kl0 = (a < 2 ? SM_TOK + (16 * a + (mi & 1) * 8 + r8) * 64 + (((mi >> 1) ^ (r8 >> 1)) << 4) : SM_EX + 2048 + ((((mi & 1) << 1) | (mi >> 1)) * 8 + r8) * 16);
            const uint32_t l16 = pin(lane * 16);
            uint32_t kf[8][4], wo[8][4];
            auto load_k = [&](int tb, uint32_t kl, auto lo, auto hi) {
                const uint32_t ka = kl + launder(sb + tb * TOKBUF);
                #pragma unroll
                for (int kk = lo.value; kk < hi.value; kk++) ldsm_x4(kf[kk], (ka ^ ((kk & 1) << 5)) + BLK_K(kk >> 1));
            };
            code_pad<PAD_S>(nv);
            cluster_wait();
            if (a == 0 && lane == 0) { mbar_expect_tx(bEX, 4096 - 256 * nqk); mbar_expect_tx(bEV, 256 * nqk); }
            if (a < 2) bar_arrive(BAR_MEM, MEM_N); else bar_sync(BAR_MEM, MEM_N);
            mbar_wait(bW + 32, 0);
            #pragma unroll
            for (int i = 0; i < 8; i++) ldsm_x4_t(wo[i], pw0 + sb + SM_WO + (warp >> 1) * 8192 + i * 1024);
            sts128(sbl + SM_STASH + a * 1024 + 512, make_uint4(kl0, (pw0 ^ 32) + sb + SM_WO + 5 * 8192, zoff | ((zskip || lane >= 8) << 31), 0u));
            sts128(sbl + SM_STASH + a * 1024, make_uint4(a * 12288 + (lane >> 4) * 1024 + (mi & 1) * 256 + r8 * 16, ACC_X + a * 6144 + (lane >> 4) * 1024 + (mi & 1) * 256 + r8 * 4,
                                                         ((lane ^ mi) & 1) ? 0u : ~0u, sb + SM_MEM + a * 3072 + mi * 256 + r8 * 16 + (r8 & 1 ? 2 : 130)));
            const uint32_t stash = l16 + uni(sb + SM_STASH + a * 1024);
            #pragma unroll
            for (int i = 0; i < 8; i++) ldsm_x4_t(kf[i], (pw0 ^ 32) + sb + SM_WO + 5 * 8192 + i * 1024);
            if (a < 2) { mbar_wait(bTOK, 0); load_k(0, kl0, ic<0>(), ic<K_PRE>()); }
            __syncwarp();
            int sn = 0;
            #pragma unroll 1
            while (sn < NSEG - 1) {
              uint32_t bad, c, cx;
              #pragma unroll 1
              do {
                const int s = sn, par = s & 1;
                const uint32_t exu = launder(sb + par * EXBUF);
                const uint32_t exl = l16 + exu + SM_EX;
                const uint32_t t0 = gtime_lo();
                STAMP(15); STAMPV(31, t0);
                if (!TAIL && a == 2) st_relaxed32_p(&g_ts[blockIdx.x], (t0 & ~31u) | (s & 31), l16);
                if (a == 1) {
                    const uint32_t z = lds32(stash + 520);
                    st_relaxed128_p((uint4*)(g_acc + (z + SLOT_OFF(s + 3))), make_uint4(0, 0, 0, 0), z >> 31);
                }
                if (a == 0 && l16 == 0) { mbar_expect_tx(bEX + 8 * (par ^ 1), 4096 - 256 * nqk); mbar_expect_tx(bEV + 8 * (par ^ 1), 256 * nqk); }
                uint32_t tg;
                auto first_half = [&](auto role) {
                constexpr bool M = role.value;
                auto publish = [&] {
                    asm volatile("{\n.reg .pred p;\nelect.sync _|p, 0xffffffff;\n"
                                 "@p cp.async.bulk.shared::cluster.global.mbarrier::complete_tx::bytes.multicast::cluster [%0], [%1], 8192, [%2], %3;\n}\n"
                        :: "r"(sb + SM_TOK + (par ^ 1) * TOKBUF + r * 8192), "l"(g_tokx[blockIdx.x]), "r"(bTOK + 8 * (par ^ 1)), "h"((unsigned short)(7 ^ (1 << r))) : "memory");
                };
                uint32_t sl, sh, kl = 0, w2 = 0;
                if (M) {
                    if (TAIL) { bar_sync(BAR_TP, 288); __syncwarp(); st_relaxed32_p(&g_ts[blockIdx.x], (gtime_after(lds32(stash + 524)) & ~31u) | (s & 31), l16); }
                    fence_async_smem();
                    if (l16 == 0) {
                        asm volatile("cp.async.bulk.global.shared::cta.bulk_group [%0], [%1], 8192;\ncp.async.bulk.commit_group;"
                            :: "l"(g_tokx[blockIdx.x]), "r"(sb + SM_TOK + (par ^ 1) * TOKBUF + r * 8192) : "memory");
                        mbar_expect_tx(bTOK + 8 * (par ^ 1), 16384);
                        if (s == 0) mbar_expect_tx(bX, XBUF);
                        if (s + 3 < NSEG) mbar_expect_tx(bX + 8 * (par ^ 1), XBUF);
                    }
                    __syncwarp();
                    if (s > 0 && s + 2 < NSEG) mbar_wait(bX + 8 * par, ((s >> 1) & 1) ^ 1);
                    if (PUB_W == 0) asm volatile("cp.async.bulk.wait_group 0;" ::: "memory");
                    kl = lds32(stash + 512);
                }
                if (!M && K_PRE < 8) {
                    const uint32_t kl = lds32(stash + 512);
                    if (K_OWN == 3) mbar_wait(bTOK + 8 * par, (s >> 1) & 1);
                    if (K_TOP) load_k(par, kl, ic<K_PRE>(), ic<K_PRE + K_TOP>());
                    bar_sync(BAR_PRO, PRO_N);
                    load_k(par, kl, ic<K_PRE + K_TOP>(), ic<8>());
                }
                uint32_t pst = (launder(l16) >> 2) + launder(sb + SM_P + a * 256);
                if (!M) {
                    uint32_t x = kf[0][0];
                    #pragma unroll
                    for (int i = 1; i < 8; i++) x ^= kf[i][0];
                    sts32_p(pst, x, nv);
                }
                mbar_wait(bEX + 8 * par, (s >> 1) & 1);
                if (!M) {
                    uint32_t b[4][4];
                    ldsm16_t(b, exl);
                    float c[4][4];
                    #pragma unroll
                    for (int j = 0; j < 4; j++) { c[j][0] = c[j][1] = c[j][2] = c[j][3] = 0.f; }
                    #pragma unroll
                    for (int j = 0; j < 4; j++) { mma16816(c[(2 * j) & 3], kf[2 * j], b[j][0], b[j][1]); mma16816(c[(2 * j + 1) & 3], kf[2 * j + 1], b[j][2], b[j][3]); }
                    sl = scale_bf2(pack_bf16((c[0][0] + c[1][0]) + (c[2][0] + c[3][0]), (c[0][1] + c[1][1]) + (c[2][1] + c[3][1])));
                    sh = scale_bf2(pack_bf16((c[0][2] + c[1][2]) + (c[2][2] + c[3][2]), (c[0][3] + c[1][3]) + (c[2][3] + c[3][3])));
                } else {
                    float c[4][4];
                    #pragma unroll
                    for (int j = 0; j < 4; j++) { c[j][0] = c[j][1] = c[j][2] = c[j][3] = 0.f; }
                    uint32_t k[4][4], b[4][4];
                    #pragma unroll
                    for (int j = 0; j < 4; j++) { ldsm_x4_t(k[j], kl + exu + 512 * j); ldsm_x4_t(b[j], exl + 512 * j); }
                    if (M_SF) sched_fence<9>(nv);
                    #pragma unroll
                    for (int j = 0; j < 4; j++) { mma16816(c[2 * (j & 1)], k[j], b[j][0], b[j][1]); mma16816(c[2 * (j & 1) + 1], k[j], b[j][2], b[j][3]); }
                    if (PUB_W == 0) publish();
                    sh = sl = scale_bf2(pack_bf16((c[0][0] + c[1][2]) + (c[2][0] + c[3][2]), (c[0][1] + c[1][3]) + (c[2][1] + c[3][3])));
                }
                sts32(pst, pack_bf16(ex2(bf_lo(sl) * LOG2E), ex2(bf_hi(sl) * LOG2E)));
                if (!M) sts32(pst + 128, pack_bf16(ex2(bf_lo(sh) * LOG2E), ex2(bf_hi(sh) * LOG2E)));
                if (S_DUTY && !M) {
                    if (a == 0)
                        asm volatile("{\n.reg .pred p;\nelect.sync _|p, 0xffffffff;\n"
                                     "@p cp.async.bulk.shared::cluster.global.mbarrier::complete_tx::bytes [%0], [%1], 384, [%2];\n"
                                     "@p mbarrier.arrive.expect_tx.shared.b64 _, [%2], 384;\n}\n"
                            :: "r"(sb + SM_TS), "l"(g_ts), "r"(bFREE) : "memory");
                    else if (s > 0 && s + 3 < NSEG)
                        asm volatile("{\n.reg .pred p;\nelect.sync _|p, 0xffffffff;\n"
                                     "@p cp.async.bulk.tensor.3d.shared::cluster.global.mbarrier::complete_tx::bytes.multicast::cluster [%0], [%1, {%3, %4, %5}], [%2], %6;\n}\n"
                            :: "r"(sb + SM_X + (par ^ 1) * XBUF + r * 12288), "l"(&tmx), "r"(bX + 8 * (par ^ 1)), "r"(0), "r"((s + 3) * SEG), "r"(3 * r), "h"((unsigned short)7) : "memory");
                }
                const uint32_t big = bar_red_or(BAR_P, 352, ((maxabs_bf2(sl, sh) & 0x7fff7fffu) + 0x3ddf3ddfu) & 0x80008000u);
                auto denom = [&] {
                    uint32_t pb[4]; ldsm_x4_t(pb, l16 + sb + SM_P);
                    const uint32_t pm = ldsm_x1_t(l16 + sb + SM_P + 512), ONE = 0x3F803F80u;
                    float l0[4] = {0.f, 0.f, 0.f, 0.f}, l1[4] = {0.f, 0.f, 0.f, 0.f}, l2[4] = {0.f, 0.f, 0.f, 0.f};
                    mma16816r(l0, ONE, ONE, ONE, ONE, pb[0], pb[1]);
                    mma16816r(l1, ONE, ONE, ONE, ONE, pb[2], pb[3]);
                    mma1688(l2, ONE, ONE, pm);
                    const float dl = (l0[0] + l1[0]) + l2[0], dh = (l0[1] + l1[1]) + l2[1];
                    sts32(pst + (SM_IL - SM_P) - a * 128, __float_as_uint(rcp_approx(a ? dh : dl)));
                };
                if (!M) { denom(); bar_sync_p(BAR_O, 352, big); }
                if (__builtin_expect(big, 0)) {
                    uint32_t m2 = max_bf2(sl, sh);
                    m2 = max_bf2(m2, __shfl_xor_sync(0xffffffffu, m2, 4));
                    m2 = max_bf2(m2, __shfl_xor_sync(0xffffffffu, m2, 8));
                    m2 = max_bf2(m2, __shfl_xor_sync(0xffffffffu, m2, 16));
                    const uint32_t lq = l16 | (m2 & nv);
                    if (lq < 64) sts32(lq + sb + SM_P + 768 + a * 4, m2);
                    bar_sync(BAR_S, 96);
                    const uint4 m = lds128(sb + SM_P + 768 + (lq & 0x30));
                    m2 = max_bf2(max_bf2(m.x, m.y), m.z);
                    const float ml = bf_lo(m2), mh = bf_hi(m2);
                    sts32(pst, pack_bf16(exd(bf_lo(sl), ml), exd(bf_hi(sl), mh)));
                    if (!M) sts32(pst + 128, pack_bf16(exd(bf_lo(sh), ml), exd(bf_hi(sh), mh)));
                    bar_sync(BAR_P2, 352);
                    if (!M) { denom(); bar_sync(BAR_O, 352); }
                }
                const uint32_t ll = launder(l16), so = SLOT_OFF(launder(s) + 1);
                if (!M) {
                    stage_w<true>(wo, l16 + sb + SM_O, 12 * r + warp, so, ll, nv, l16 + sb + SM_IL, [&] { if (TP_E || V_EARLY) bar_arrive(BAR_V, 384); });
                } else {
                    w2 = lds32(stash + 516);
                    #pragma unroll
                    for (int i = M_RES; i < 8; i++) ldsm_x4_t(kf[i], w2 + i * 1024);
                    if (PUB_W == 1) { asm volatile("cp.async.bulk.wait_group 0;" ::: "memory"); publish(); }
                    const uint32_t sa = launder(SEND_LANE(ll) + (send_ua(12 * r + 10) + so)), sb_ = launder(X_LANE(ll) + (send_ub(12 * r + 10) + so));
                    bar_sync_p(BAR_O, 352, (kf[5][0] ^ kf[6][0] ^ kf[7][0] ^ sa ^ sb_) & nv);
                    float c[4][4], il, ih;
                    #pragma unroll
                    for (int i = 0; i < 4; i++) c[i][0] = c[i][1] = c[i][2] = c[i][3] = 0.f;
                    uint32_t b[4][4];
                    #pragma unroll
                    for (int j = 0; j < 4; j++) ldsm_x4_t(b[j], l16 + sb + SM_O + 512 * (3 - j));
                    lds_il(il, ih, l16 + sb + SM_IL);
                    sched_fence<11>(nv);
                                    #pragma unroll
                    for (int j = 0; j < 4; j++) {
                        if (j == 2) { if (M_F2) sched_fence<10>(nv); }
                        mma16816(c[0], wo[6 - 2 * j], b[j][0], b[j][1]); mma16816(c[2], kf[6 - 2 * j], b[j][0], b[j][1]);
                        mma16816(c[1], wo[7 - 2 * j], b[j][2], b[j][3]); mma16816(c[3], kf[7 - 2 * j], b[j][2], b[j][3]);
                    }
                    asm volatile("" : "+f"(c[0][0]), "+f"(c[1][0]), "+f"(c[2][0]), "+f"(c[3][0]));
                    if (TP_E || V_EARLY) { if (M_FENCE == 1) sched_fence<8>(nv); else asm volatile("" : "+f"(il) : "f"(c[0][0] + c[1][0]), "f"(c[2][0] + c[3][0])); if (M_FENCE < 2) bar_arrive(BAR_V, 384); }
                    send_tile<0, 0>((c[0][0] + c[1][0]) * il, (c[0][1] + c[1][1]) * ih, (c[0][2] + c[1][2]) * il, (c[0][3] + c[1][3]) * ih, sa, sb_, ll);
                    if (M_FENCE == 2) bar_arrive(BAR_V, 384);
                    send_tile<1024, 256>((c[2][0] + c[3][0]) * il, (c[2][1] + c[3][1]) * ih, (c[2][2] + c[3][2]) * il, (c[2][3] + c[3][3]) * ih, sa, sb_, ll);
                    if (M_FENCE == 3) bar_arrive(BAR_V, 384);
                }
                };
                if (a < 2) first_half(ic<0>()); else first_half(ic<1>());
                STAMP(warp);
                if (!TP_E && !V_EARLY) bar_arrive(BAR_V, 384);
                {
                    const uint4 ad = lds128(stash);
                    const uint32_t kl = lds32(stash + 512), so = SLOT_OFF(launder(s) + 1);
                    if (K_OWN == 1 && a < 2) { mbar_wait(bTOK + 8 * (par ^ 1), ((s + 1) >> 1) & 1); load_k(par ^ 1, kl, ic<0>(), ic<K_PRE>()); }
                    if (!K_OWN && K_POS == 0 && a < 2) load_k(par ^ 1, kl, ic<0>(), ic<K_PRE>());
                    const uint32_t alo = (uint32_t)(uint64_t)g_acc + so;
                    const unsigned char* pm = (const unsigned char*)(((uint64_t)g_acc & ~0xffffffffull) | (ad.x + alo));
                    const unsigned char* px = (const unsigned char*)(((uint64_t)g_acc & ~0xffffffffull) | (ad.y + alo));
                    uint4 v[6]; uint32_t x[3];
                    const uint32_t md = l16 + launder(sb + SM_MEM + a * 3072);
                    STAMP(16 + a);
                    asm volatile("{\n.reg .pred p, q;\n.reg .b32 t, d, n;\nmov.b32 n, 100000;\n"
                                 "WT_%=:\nld.volatile.shared.u32 %0, [%1];\nmov.u32 t, %%globaltimer_lo;\nsub.s32 n, n, 1;\nsetp.gt.s32 q, n, 0;\nor.b32 t, t, 1;\nxor.b32 t, t, %2;\n"
                                 "sub.s32 d, t, %0;\nand.b32 d, d, 0x80000001;\nsetp.ne.and.u32 p, d, 0, q;\n@p bra.uni WT_%=;\n}\n" : "=r"(tg) : "r"(sb + SM_SG + 36 + (l16 >> 16)), "r"(par) : "memory");
                    STAMPV(30, tg);
                    #pragma unroll
                    for (int j = 0; j < 6; j++) v[j] = ld_relaxed128((const uint4*)(pm + 2048 * j));
                    #pragma unroll
                    for (int j = 0; j < 3; j++) x[j] = ld_relaxed32((const uint32_t*)(px + 2048 * j));
                    if (K_OWN == 2) { mbar_wait(bTOK + 8 * (par ^ 1), ((s + 1) >> 1) & 1); if (a < 2) load_k(par ^ 1, kl, ic<0>(), ic<K_PRE>()); sched_fence<16>(nv); }
                    if (LD_FENCE) bar_sync(BAR_S, 96);
                    STAMP(19 + a);
                    c = ~0u;
                    #pragma unroll
                    for (int j = 0; j < 6; j++) { sts128(md + 512 * j, v[j]); c &= v[j].x; }
                    c |= ad.z;
                    #pragma unroll
                    for (int j = 0; j < 3; j++) sts16(ad.w + 1024 * j, (uint16_t)x[j]);
                    cx = x[0] & x[1] & x[2];
                    bad = __any_sync(0xffffffffu, !(c & cx & (ACC_FULL << 16)));
                    STAMP(22 + a); STAMPV(27 + a, bad);
                    bar_sync_p(BAR_MEM, MEM_N, bad);
                }
              } while (++sn < NSEG - 1 && !bad);
                {
                    if (bad) {
                        const uint32_t lq = l16 | (c & nv), so = SLOT_OFF(sn);
                        const uint4 ad = lds128(stash);
                        const unsigned char* pm = launder_p(g_acc + (ad.x + so));
                        const unsigned char* px = launder_p(g_acc + (ad.y + so));
                        int it = 0;
                        do {
                            const uint32_t again = ~(c & __shfl_xor_sync(0xffffffffu, c, 1)) & (ACC_FULL << 16);
                            uint4 u[6]; uint32_t x[3];
                            #pragma unroll
                            for (int j = 0; j < 6; j++) { u[j] = make_uint4(~0u, ~0u, ~0u, ~0u); ld_relaxed128_p(u[j], (const uint4*)(pm + 2048 * j), again); }
                            #pragma unroll
                            for (int j = 0; j < 3; j++) x[j] = ld_relaxed32((const uint32_t*)(px + 2048 * j));
                            c = ~0u;
                            #pragma unroll
                            for (int j = 0; j < 6; j++) {
                                if (again) sts128(lq + sb + SM_MEM + a * 3072 + 512 * j, u[j]);
                                c &= u[j].x;
                            }
                            __syncwarp();
                            #pragma unroll
                            for (int j = 0; j < 3; j++) sts16(ad.w + 1024 * j, (uint16_t)x[j]);
                            c |= ad.z;
                            cx = x[0] & x[1] & x[2];
                        } while (__any_sync(0xffffffffu, !(c & cx & (ACC_FULL << 16))) && ++it < SPIN_LIMIT);
                        bar_sync(BAR_MEM, MEM_N);
                    }
                }
            }
            if (TAIL && a == 2) bar_arrive(BAR_TP, 288);
        } else {
            cluster_arrive_rx();
            const uint32_t l16 = pin(lane * 16);
            bf16* dst = g_otok + h * 4096 + (r ? 1024 : 0) + (r == 2 ? 2048 : 0);
            {
                #pragma unroll
                for (int sg = 0; sg < 2; sg++) {
                    bar_sync(BAR_X0 + sg, 288);
                    if (lane == 0) {
                        mbar_expect_tx(bX + 8 * sg, XBUF);
                        #pragma unroll
                        for (int c = 0; c < 3; c++)
                            asm volatile("cp.async.bulk.tensor.3d.shared::cluster.global.mbarrier::complete_tx::bytes [%0], [%1, {%3, %4, %5}], [%2];"
                                :: "r"(sb + SM_X + sg * XBUF + c * 12288), "l"(&tmx), "r"(bX + 8 * sg), "r"(0), "r"(sg * SEG), "r"(3 * c) : "memory");
                    }
                    __syncwarp();
                }
                if (lane == 0) load_w(40, 54);
                __syncwarp();
                cluster_wait();
            }
            __syncwarp();
            auto t_loop = [&](auto mtile) {
            constexpr int MT = mtile.value;
            uint32_t q[8][4], sp[5][2], pa[5][2], bv[8][4], rng;
            code_pad<MT ? PAD_T1 : PAD_T0>(nv);
            auto issue_x = [&](int sg) {
                asm volatile("{\n.reg .pred p, q;\nelect.sync _|p, 0xffffffff;\nsetp.eq.and.u32 q, %5, 3, p;\n"
                             "@p cp.async.bulk.tensor.3d.shared::cluster.global.mbarrier::complete_tx::bytes.multicast::cluster [%0], [%1, {%3, %4, %5}], [%2], %6;\n"
                             "@q cp.async.bulk.tensor.3d.shared::cluster.global.mbarrier::complete_tx::bytes.multicast::cluster [%7], [%1, {%3, %4, %3}], [%2], %6;\n}\n"
                    :: "r"(sb + SM_X + (sg & 1) * XBUF + r * 12288), "l"(&tmx), "r"(bX + 8 * (sg & 1)), "r"(0), "r"(sg * SEG), "r"(3 * r), "h"((unsigned short)7), "r"(sb + SM_X + (sg & 1) * XBUF) : "memory");
            };
            mbar_wait(bTOK, 0);
            if (MT) { issue_x(2); issue_x(3); }
            #pragma unroll 1
            for (int s = 0; s < NSEG; s++) {
                const int par = s & 1;
                if (K_OWN) mbar_wait(bTOK + 8 * par, (s >> 1) & 1);
                const uint32_t tok = launder(sb + SM_TOK + par * TOKBUF), exl = l16 + launder(sb + SM_EX + par * EXBUF);
                const int ln = launder(l16) >> 4;
                auto announce = [&] {
                    if (s > 0) {
                        if (lane == 0) {
                            asm volatile("cp.async.bulk.wait_group 0;" ::: "memory");
                            st_relaxed32(&g_prog[blockIdx.x], epoch << 8 | s);
                        }
                        __syncwarp();
                        if (lane == 0 && blockIdx.x == 0) GT(40, s);
                    }
                };
                if (ANN_POS == 0) announce();
                tok_part1<MT>(tok, MT ? r - 1 : 0, ln, q, sp, pa, bv, rng, [&] {
                    if (ANN_POS == 3) announce();
                    if (T_HOLD == 4) sched_fence<6 + MT>(nv);
                    else if (T_HOLD) { if (s < NSEG - 1) bar_sync((T_HOLD & 1) ? BAR_PRO : BAR_VGO, (T_HOLD & 1) ? PRO_N : VGO_N); else if (T_HOLD == 2) bar_arrive(BAR_VGO, VGO_N); sched_fence<6 + MT>(nv); } });
                if (ANN_POS == 1) announce();
                STAMP(25);
                mbar_wait(bEX + 8 * par, (s >> 1) & 1);
                STAMP(26);
                auto duty = [&] { if (!S_DUTY && s + 1 < NSEG) {
                    asm volatile("{\n.reg .pred p;\nelect.sync _|p, 0xffffffff;\n"
                                 "@p cp.async.bulk.shared::cluster.global.mbarrier::complete_tx::bytes [%0], [%1], 384, [%2];\n"
                                 "@p mbarrier.arrive.expect_tx.shared.b64 _, [%2], 384;\n}\n"
                        :: "r"(sb + SM_TS), "l"(g_ts), "r"(bFREE) : "memory");
                    if (X_POS == 0 && MT && s > 0 && s + 3 < NSEG) issue_x(s + 3);
                } };
                auto pace = [&] { if (s + 1 < NSEG) {
                    if (X_POS == 2 && MT && s > 0 && s + 3 < NSEG) issue_x(s + 3);
                    const uint32_t lo = min(launder(l16), 368u), b = (gtime_lo() & ~31u) - 0x01000000u + s + (lo >> 16);
                    const uint32_t c = (b & ~31u) + (G1_NS + (s == 0 ? G1_0 : 0)) + (par ^ 1);
                    if (K_OWN) mbar_wait(bFREE, par); else mbar_wait2(bFREE, par, bTOK + 8 * (par ^ 1), ((s + 1) >> 1) & 1);
                    uint4 ts = lds128(sb + SM_TS + lo);
                    int it = 0; uint32_t m;
                    while (true) {
                        m = __reduce_max_sync(0xffffffffu, max(max(__funnelshift_r(ts.x - b, ts.x - b, 5), __funnelshift_r(ts.y - b, ts.y - b, 5)), max(__funnelshift_r(ts.z - b, ts.z - b, 5), __funnelshift_r(ts.w - b, ts.w - b, 5))));
                        if (__builtin_expect(m < 0x00100000u, 1) || ++it >= 64) break;
                        ts = ld_relaxed128((const uint4*)((const char*)g_ts + lo));
                    }
                    asm volatile("st.volatile.shared.u32 [%0], %1;" :: "r"(sb + SM_SG + 36), "r"(c + (min(m, 0x00080000u) << 5)) : "memory");
                } };
                auto wait_v = [&] {
                    if (X_POS == 1 && MT && s > 0 && s + 3 < NSEG) issue_x(s + 3);
                    mbar_wait(bEV + 8 * par, (s >> 1) & 1); };
                auto wait_x = [&] { if (__builtin_expect(s == 0, 0)) mbar_wait(bX, 1); };
                tok_part2<MT>(tok, exl, sb + SM_OST, MT ? r - 1 : 0, launder(l16) >> 4, q, sp, pa, bv, rng, s < NSEG - 1, wait_v, duty, pace, wait_x);
                STAMP(11);
                fence_async_smem();
                __syncwarp();
                if (lane == 0) {
                    asm volatile("cp.async.bulk.global.shared::cta.bulk_group [%0], [%1], 2048;" :: "l"(dst), "r"(sb + SM_OST) : "memory");
                    if (!MT) asm volatile("cp.async.bulk.global.shared::cta.bulk_group [%0], [%1], 2048;" :: "l"(dst + 2048), "r"(sb + SM_OST + 2048) : "memory");
                    asm volatile("cp.async.bulk.commit_group;" ::: "memory");
                    if (__builtin_expect(s >= NSEG - 2, 0)) {
                        asm volatile("cp.async.bulk.wait_group 0;" ::: "memory");
                        st_relaxed32(&g_prog[blockIdx.x], epoch << 8 | (s + 1));
                        if (blockIdx.x == 0 && s == NSEG - 1) GT(40, NSEG);
                    }
                }
                __syncwarp();
                dst += SEG * NH * DH;
            }
            };
            if (r == 0) t_loop(ic<0>()); else t_loop(ic<1>());
        }
        cluster_arrive(); cluster_wait();
    }
}
#define SD_THREADS 384
#define SD_CTAS  36
#define BT_RS    4624
#define SD_BT    0
#define SD_STG   74752
#define SD_EF    (SD_STG + 57344)
#define SD_BC    (SD_STG)
#define KSLOTS   5
#define BC_BYTES 10240
#define BC_LBO   1280
#define SD_KP    (SD_STG + 90112)
#define SD_Q0    205824
#define SD_Q1    (SD_STG + 111616)
#define SD_OST   222720
#define SD_XCH   (SD_Q0 + 8192)
#define SD_BAR   224256
#define SD_TOTAL 224768
#define SD_SPIN  (1 << 22)
#define PART_SLOTS 8
#define SD_GO 0
#define SD_REG 200
#define SD_WAIT 6000
#define SD_P2 150
#define SD_P3 200
#define SD_GAP 0
#define SD_RUSH 44
#define SD_P1 300

__device__ uint4 g_part[SD_CTAS][PART_SLOTS][4][8][32];
__device__ __align__(16) unsigned int g_gate[S_LEN];

struct cplx { float r, i; };
__device__ __forceinline__ cplx cmul(cplx a, cplx b) { cplx c; c.r = fmaf(a.r, b.r, -a.i * b.i); c.i = fmaf(a.r, b.i, a.i * b.r); return c; }
__device__ __forceinline__ cplx cexp_(float xr, float xi) {
    const float m = ex2(xr * 1.4426950408889634f);
    const float k = rintf(xi * 0.15915494309189535f);
    const float r = fmaf(k, 1.7484555314695172e-7f, fmaf(k, -6.2831854820251465f, xi));
    cplx o; o.r = m * __cosf(r); o.i = m * __sinf(r); return o;
}
__device__ __forceinline__ void mma_f16(float (&c)[4], const uint32_t (&a)[4], uint32_t b0, uint32_t b1) {
    asm("mma.sync.aligned.m16n8k16.row.col.f32.f16.f16.f32 {%0,%1,%2,%3}, {%4,%5,%6,%7}, {%8,%9}, {%0,%1,%2,%3};"
        : "+f"(c[0]), "+f"(c[1]), "+f"(c[2]), "+f"(c[3]) : "r"(a[0]), "r"(a[1]), "r"(a[2]), "r"(a[3]), "r"(b0), "r"(b1));
}
__device__ __forceinline__ uint32_t mul_bf2(uint32_t a, uint32_t b) { uint32_t r; asm("mul.rn.bf16x2 %0, %1, %2;" : "=r"(r) : "r"(a), "r"(b)); return r; }
__device__ __forceinline__ void mbar_wait_long(uint32_t a, uint32_t parity) { int it = 0; while (!mbar_try(a, parity) && ++it < SD_SPIN) {} }
__device__ __forceinline__ uint16_t lds16(uint32_t a) { uint16_t v; asm volatile("ld.shared.u16 %0, [%1];" : "=h"(v) : "r"(a) : "memory"); return v; }
__device__ __forceinline__ void wg_wait1() { asm volatile("wgmma.wait_group.sync.aligned 1;" ::: "memory"); }
__device__ __forceinline__ void tma2d(uint32_t dst, const CUtensorMap* tm, uint32_t bar, int c0, int c1) {
    asm volatile("cp.async.bulk.tensor.2d.shared::cluster.global.mbarrier::complete_tx::bytes [%0], [%1, {%3, %4}], [%2];"
        :: "r"(dst), "l"(tm), "r"(bar), "r"(c0), "r"(c1) : "memory");
}
__device__ __forceinline__ uint32_t add_bf2(uint32_t a, uint32_t b) { uint32_t r; asm("add.rn.bf16x2 %0, %1, %2;" : "=r"(r) : "r"(a), "r"(b)); return r; }
__device__ __forceinline__ void wgmma_conv(float (&d)[32], uint32_t a0, uint32_t a1, uint32_t a2, uint32_t a3, uint64_t desc) {
    asm volatile("{\n.reg .pred p;\nsetp.ne.b32 p, 1, 0;\n"
        "wgmma.mma_async.sync.aligned.m64n64k16.f32.bf16.bf16 {%0,%1,%2,%3,%4,%5,%6,%7,%8,%9,%10,%11,%12,%13,%14,%15,%16,%17,%18,%19,%20,%21,%22,%23,%24,%25,%26,%27,%28,%29,%30,%31}, {%32,%33,%34,%35}, %36, p, 1, 1, 0;\n}\n"
        : "+f"(d[0]), "+f"(d[1]), "+f"(d[2]), "+f"(d[3]), "+f"(d[4]), "+f"(d[5]), "+f"(d[6]), "+f"(d[7]), "+f"(d[8]), "+f"(d[9]), "+f"(d[10]), "+f"(d[11]), "+f"(d[12]), "+f"(d[13]), "+f"(d[14]), "+f"(d[15]), "+f"(d[16]), "+f"(d[17]), "+f"(d[18]), "+f"(d[19]), "+f"(d[20]), "+f"(d[21]), "+f"(d[22]), "+f"(d[23]), "+f"(d[24]), "+f"(d[25]), "+f"(d[26]), "+f"(d[27]), "+f"(d[28]), "+f"(d[29]), "+f"(d[30]), "+f"(d[31])
        : "r"(a0), "r"(a1), "r"(a2), "r"(a3), "l"(desc));
}
__device__ __forceinline__ void wgmma_conv(float (&d)[24], uint32_t a0, uint32_t a1, uint32_t a2, uint32_t a3, uint64_t desc) {
    asm volatile("{\n.reg .pred p;\nsetp.ne.b32 p, 1, 0;\n"
        "wgmma.mma_async.sync.aligned.m64n48k16.f32.bf16.bf16 {%0,%1,%2,%3,%4,%5,%6,%7,%8,%9,%10,%11,%12,%13,%14,%15,%16,%17,%18,%19,%20,%21,%22,%23}, {%24,%25,%26,%27}, %28, p, 1, 1, 0;\n}\n"
        : "+f"(d[0]), "+f"(d[1]), "+f"(d[2]), "+f"(d[3]), "+f"(d[4]), "+f"(d[5]), "+f"(d[6]), "+f"(d[7]), "+f"(d[8]), "+f"(d[9]), "+f"(d[10]), "+f"(d[11]), "+f"(d[12]), "+f"(d[13]), "+f"(d[14]), "+f"(d[15]), "+f"(d[16]), "+f"(d[17]), "+f"(d[18]), "+f"(d[19]), "+f"(d[20]), "+f"(d[21]), "+f"(d[22]), "+f"(d[23])
        : "r"(a0), "r"(a1), "r"(a2), "r"(a3), "l"(desc));
}
__device__ __forceinline__ void wgmma_conv(float (&d)[16], uint32_t a0, uint32_t a1, uint32_t a2, uint32_t a3, uint64_t desc) {
    asm volatile("{\n.reg .pred p;\nsetp.ne.b32 p, 1, 0;\n"
        "wgmma.mma_async.sync.aligned.m64n32k16.f32.bf16.bf16 {%0,%1,%2,%3,%4,%5,%6,%7,%8,%9,%10,%11,%12,%13,%14,%15}, {%16,%17,%18,%19}, %20, p, 1, 1, 0;\n}\n"
        : "+f"(d[0]), "+f"(d[1]), "+f"(d[2]), "+f"(d[3]), "+f"(d[4]), "+f"(d[5]), "+f"(d[6]), "+f"(d[7]), "+f"(d[8]), "+f"(d[9]), "+f"(d[10]), "+f"(d[11]), "+f"(d[12]), "+f"(d[13]), "+f"(d[14]), "+f"(d[15])
        : "r"(a0), "r"(a1), "r"(a2), "r"(a3), "l"(desc));
}
__device__ __forceinline__ void wgmma_conv(float (&d)[8], uint32_t a0, uint32_t a1, uint32_t a2, uint32_t a3, uint64_t desc) {
    asm volatile("{\n.reg .pred p;\nsetp.ne.b32 p, 1, 0;\n"
        "wgmma.mma_async.sync.aligned.m64n16k16.f32.bf16.bf16 {%0,%1,%2,%3,%4,%5,%6,%7}, {%8,%9,%10,%11}, %12, p, 1, 1, 0;\n}\n"
        : "+f"(d[0]), "+f"(d[1]), "+f"(d[2]), "+f"(d[3]), "+f"(d[4]), "+f"(d[5]), "+f"(d[6]), "+f"(d[7])
        : "r"(a0), "r"(a1), "r"(a2), "r"(a3), "l"(desc));
}
template<int NR> __device__ __forceinline__ void conv_mma(float (&acc)[NR], const uint32_t (&R)[16], uint32_t dlo) {
    #pragma unroll
    for (int q = 0; q < 4; q++)
        wgmma_conv(acc, R[4 * q], R[4 * q + 1], R[4 * q + 2], R[4 * q + 3], (uint64_t)(dlo + (2 * (3 - q)) * (BC_LBO >> 4)) | ((uint64_t)8 << 32));
}
__device__ __forceinline__ void conv_ld(uint32_t (&R)[16], uint32_t a) {
    #pragma unroll
    for (int q = 0; q < 4; q++) { const uint2 u = lds64(a + 64 * (2 * q + 1)); R[4 * q] = u.x; R[4 * q + 1] = u.y; }
}
__device__ __forceinline__ void conv_fix(uint32_t (&R)[16], uint32_t& carry) {
    #pragma unroll
    for (int q = 0; q < 4; q++) {
        asm volatile("mov.b32 %0, %1;" : "=r"(R[4 * q + 2]) : "r"(q ? R[4 * q - 3] : carry));
        asm volatile("mov.b32 %0, %1;" : "=r"(R[4 * q + 3]) : "r"(R[4 * q]));
    }
    asm volatile("mov.b32 %0, %1;" : "=r"(carry) : "r"(R[13]));
}
template<int A> __device__ __forceinline__ void conv_group(float (&acc)[32 - 8 * A], uint32_t (&R)[4][16], uint32_t& carry, uint32_t pb, uint32_t dlo) {
    #pragma unroll
    for (int e = 0; e < 8; e += 2) {
        const int dl = 8 * A + e;
        conv_fix(R[dl & 3], carry); conv_fix(R[(dl + 1) & 3], carry);
        wg_fence(); conv_mma(acc, R[dl & 3], dlo + 16 - 2 * e); conv_mma(acc, R[(dl + 1) & 3], dlo + 14 - 2 * e); wg_commit();
        wg_wait1();
        if (dl + 2 < 32) { conv_ld(R[(dl + 2) & 3], pb + (dl + 2) * 512); conv_ld(R[(dl + 3) & 3], pb + (dl + 3) * 512); }
    }
}

__global__ void __launch_bounds__(SD_THREADS, 1)
side_kernel(const __grid_constant__ CUtensorMap tmw, const bf16* __restrict__ x,
            const bf16* __restrict__ log_A_real, const bf16* __restrict__ A_imag, const bf16* __restrict__ C_real, const bf16* __restrict__ C_imag,
            const bf16* __restrict__ log_dt, const bf16* __restrict__ D_skip, const bf16* __restrict__ gate_w, bf16* __restrict__ out) {
    extern __shared__ __align__(1024) unsigned char smem[];
    const uint32_t sb = smem_u32(smem);
    const int tid = threadIdx.x, lane = tid & 31;
    const int warp = __shfl_sync(0xffffffffu, tid >> 5, 0);
    const int g = lane >> 2, t = lane & 3, mi = lane >> 3, r8 = lane & 7;
    const bool sh = blockIdx.x < 32;
    const int d0 = blockIdx.x * 16;
    const uint32_t b0_ = sb + SD_BAR, bKF = b0_ + 384, bKE = bKF + 8 * KSLOTS, bWO = b0_ + 48, bFULL = b0_ + 56, bEMPTY = b0_ + 88, bEPI = b0_ + 120, bPRT = b0_ + 152, bGO = b0_ + 184, bCH = b0_ + 256;
    const unsigned epoch = ld_relaxed32(&g_epoch);
    if (tid == 0) GT(blockIdx.x, 0);
    if (tid == 0) {
        for (int i = 0; i < 2 * KSLOTS; i++) mbar_init(bKF + 8 * i, 128);
        mbar_init(bWO, 1);
        for (int i = 0; i < 16; i++) mbar_init(bCH + 8 * i, 1);
        for (int i = 0; i < 4; i++) { mbar_init(bFULL + 8 * i, 1); mbar_init(bEMPTY + 8 * i, sh ? 8 : 4); mbar_init(bEPI + 8 * i, 4); mbar_init(bPRT + 8 * i, 8); mbar_init(bGO + 8 * i, 1); }
        asm volatile("fence.mbarrier_init.release.cluster;" ::: "memory");
    }
    for (int i = tid; i < KSLOTS * 8 * 16; i += SD_THREADS) sts128(sb + SD_BC + (i >> 4) * BC_LBO + (i & 15) * 16, make_uint4(0, 0, 0, 0));
    if (tid < 128) sts64(sb + ((tid & 64) ? SD_Q1 : SD_Q0) + (tid & 63) * 8, 0u, 0u);
    fence_async_smem();
    __syncthreads();

    if (warp < 8) {
        asm volatile("setmaxnreg.inc.sync.aligned.u32 %0;" :: "n"(SD_REG));
        const int wg = warp >> 2, w = warp & 3, t128 = tid & 127;
        if (SD_WAIT) __nanosleep(SD_WAIT);
        {
            #pragma unroll 1
            for (int i = 0; i < 4; i++) {
                const int tp = tid + 256 * i;
                const bf16* xp = x + (size_t)(2 * tp) * DM + d0;
                const uint4 v0 = __ldg((const uint4*)xp), v1 = __ldg((const uint4*)(xp + 8)), v2 = __ldg((const uint4*)(xp + DM)), v3 = __ldg((const uint4*)(xp + DM + 8));
                const uint32_t a = sb + SD_BT + (tp >> 5) * 144 + (tp & 31) * 4;
                const uint32_t lo[8] = {v0.x, v0.y, v0.z, v0.w, v1.x, v1.y, v1.z, v1.w};
                const uint32_t hi[8] = {v2.x, v2.y, v2.z, v2.w, v3.x, v3.y, v3.z, v3.w};
                #pragma unroll
                for (int j = 0; j < 8; j++) { sts32(a + (2 * j) * BT_RS, __byte_perm(lo[j], hi[j], 0x5410)); sts32(a + (2 * j + 1) * BT_RS, __byte_perm(lo[j], hi[j], 0x7632)); }
                if (SD_GAP) __nanosleep(SD_GAP);
            }
        }
        bar_sync(1, 256);
        if (tid == 0) GT(blockIdx.x, 65);
        const uint32_t pa = sb + (wg ? SD_Q1 : SD_Q0);
        const uint32_t pb = pa + (72 + 16 * w - 56 + g - 2 * t) * 8;
        for (int c = wg; c < 16; c += 2) {
            const uint32_t bt = sb + SD_BT + c * BT_RS;
            bar_sync(2 + wg, 128);
            #pragma unroll
            for (int it = 0; it < 9; it++) {
                const int k = it < 8 ? t128 + 128 * it : t128 - 4;
                if (it < 8 || t128 < 4) {
                    auto word = [&](int j) { return j >= 0 ? lds32(bt + (j >> 5) * 144 + (j & 31) * 4) : 0u; };
                    const uint32_t c0 = word(k), p0 = word(k - 1), c1 = word(k + 4), p1 = word(k + 3);
                    sts128(pa + (72 + 2 * k) * 8, make_uint4(__byte_perm(c0, p0, 0x7610), __byte_perm(c1, p1, 0x7610), __byte_perm(c0, c0, 0x1032), __byte_perm(c1, c1, 0x1032)));
                }
            }
            bar_sync(2 + wg, 128);
            const int slot = c % KSLOTS;
            float acc[32];
            #pragma unroll
            for (int i = 0; i < 32; i++) acc[i] = 0.f;
            uint32_t R[4][16];
            uint32_t carry = lds32(pb);
            conv_ld(R[0], pb); conv_ld(R[1], pb + 512);
            const uint32_t dlo = (((sb + SD_BC + slot * BC_BYTES) & 0x3FFFF) >> 4) | ((BC_LBO >> 4) << 16);
            mbar_wait_long(bKF + 8 * slot, (c / KSLOTS) & 1);
            const float ds = bf(D_skip[d0 + c]);
            auto fin = [&](const float* a8, int q0) {
                #pragma unroll
                for (int q = 0; q < 2; q++)
                    #pragma unroll
                    for (int hh = 0; hh < 2; hh++) {
                        const uint32_t a = bt + (4 * (q0 + q) + t) * 144 + (16 * w + g + 8 * hh) * 2;
                        const float u = __uint_as_float((uint32_t)lds16(a) << 16);
                        const float y = rbf(a8[4 * q + 2 * hh] + a8[4 * q + 2 * hh + 1]);
                        sts16(a, (uint16_t)(pack_bf16(y + rbf(u * ds), 0.f) & 0xffff));
                    }
            };
            float a1[24], a2[16], a3[8];
            conv_group<0>(acc, R, carry, pb, dlo);
            wg_wait0();
            #pragma unroll
            for (int i = 0; i < 24; i++) asm volatile("mov.b32 %0, %1;" : "=f"(a1[i]) : "f"(acc[8 + i]));
            fin(acc, 0);
            conv_group<1>(a1, R, carry, pb, dlo);
            wg_wait0();
            #pragma unroll
            for (int i = 0; i < 16; i++) asm volatile("mov.b32 %0, %1;" : "=f"(a2[i]) : "f"(a1[8 + i]));
            fin(a1, 2);
            conv_group<2>(a2, R, carry, pb, dlo);
            wg_wait0();
            #pragma unroll
            for (int i = 0; i < 8; i++) asm volatile("mov.b32 %0, %1;" : "=f"(a3[i]) : "f"(a2[8 + i]));
            fin(a2, 4);
            conv_group<3>(a3, R, carry, pb, dlo);
            wg_wait0();
            mbar_arrive(bKE + 8 * slot);
            fin(a3, 6);
        }
        fence_async_smem();
        __syncthreads();
        const uint32_t stg = sb + SD_STG + wg * 65536;
        uint32_t wf[32][4];
        if (tid == 0) GT(blockIdx.x, 66);
        mbar_wait_long(bWO, 0);
        #pragma unroll
        for (int i = 0; i < 32; i++)
            ldsm_x4_t(wf[i], stg + (i * 16 + (mi >> 1) * 8 + r8) * 128 + (((2 * w + (mi & 1)) ^ r8) << 4));
        { uint32_t x = 0;
          #pragma unroll
          for (int i = 0; i < 32; i++) x |= wf[i][0];
          asm volatile("" :: "r"(x) : "memory"); }
        __syncwarp();
        if (lane == 0) {
            mbar_arrive(bEMPTY + 16 * wg); mbar_arrive(bEMPTY + 16 * wg + 8);
            if (sh) { mbar_arrive(bEMPTY + 16 * (wg ^ 1)); mbar_arrive(bEMPTY + 16 * (wg ^ 1) + 8); }
        }
        uint4* dst = sh ? &g_part[(blockIdx.x & ~7) + 4 * wg + w][0][0][blockIdx.x & 7][lane] : &g_part[32 + w][0][0][2 * (blockIdx.x - 32) + wg][lane];
        const uint32_t dl0 = (((sb + SD_STG) & 0x3FFFF) >> 4) | 0x10000u;
        auto seg = [&](int s, auto last) {
            const int bi = sh ? s & 3 : 2 * wg + (s & 1), bp = (sh ? s >> 2 : s >> 1) & 1;
            const uint32_t xd = uni(dl0 + bi * 2048);
            float acc[16];
            #pragma unroll
            for (int i = 0; i < 32; i++) {
                if (i == 0 || (last.value && (i & 7) == 0)) { mbar_wait_long(bCH + 32 * bi + i, i ? 0 : bp); wg_fence(); }
                if (i == 0) wgmma_n32<0>(acc, wf[i], desc_from(xd));
                else wgmma_n32<1>(acc, wf[i], desc_from(xd + (i >> 2) * 256 + (i & 3) * 2));
            }
            wg_commit();
            if (s >= PART_SLOTS / 2) mbar_wait_long(bEPI + 8 * (s & 3), ((s - 4) >> 2) & 1);
            const uint32_t ph = ((s / PART_SLOTS) & 1) ^ 1;
            uint4* p = dst + (s % PART_SLOTS) * (4 * 8 * 32);
            wg_wait0();
            #pragma unroll
            for (int j = 0; j < 4; j++)
                st_relaxed128(p + 256 * j, make_uint4((__float_as_uint(acc[4 * j]) & ~1u) | ph, __float_as_uint(acc[4 * j + 1]), __float_as_uint(acc[4 * j + 2]), __float_as_uint(acc[4 * j + 3])));
            if (tid == 0 && s == NSEG - 1) GT(blockIdx.x, 71);
            __syncwarp();
            if (lane == 0) { mbar_arrive(bEMPTY + 8 * bi); mbar_arrive(bPRT + 8 * (s & 3)); }
        };
        #pragma unroll 1
        for (int s = 0; s < NSEG - 1; s++) seg(s, ic<0>());
        seg(NSEG - 1, ic<1>());
    } else {
        asm volatile("setmaxnreg.dec.sync.aligned.u32 %0;" :: "n"(504 - 2 * SD_REG));
        const int w = warp - 8, n = tid - 256;
        bf16 p_la = log_A_real[d0 * NS + n], p_ai = A_imag[d0 * NS + n], p_cr = C_real[d0 * NS + n], p_ci = C_imag[d0 * NS + n], p_dt = log_dt[d0];
        const uint32_t ef = sb + SD_EF + w * 8192;
        const uint32_t efl = ef + lane * 4;
        uint32_t goff[8];
        #pragma unroll
        for (int i = 0; i < 16; i++) {
            const int l = 64 * lane + 8 * (w + 4 * (i >> 3)) + (i & 7);
            const int p = (int)rbf((float)l);
            const int a = p >> 7, b = (p >> 3) & 15, c = p & 7;
            const int row = p < 256 ? 8 * a + c : (p < 512 ? 16 + 4 * (a - 2) + (c >> 1) : (p < 1024 ? 24 + 2 * (a - 4) + (c >> 2) : 24 + a));
            const uint32_t off = row * 72 + b * 4;
            if (i & 1) goff[i >> 1] |= off << 16; else goff[i >> 1] = off;
        }
        for (int c = 0; c < 16; c++) {
            const float dt = rbf(expf(bf(p_dt)));
            const float xr = -rbf(expf(bf(p_la))) * dt, xi = bf(p_ai) * dt;
            cplx C; C.r = 2.f * bf(p_cr) * dt; C.i = 2.f * bf(p_ci) * dt;
            if (c + 1 < 16) {
                const int o = (d0 + c + 1) * NS + n;
                p_la = log_A_real[o]; p_ai = A_imag[o]; p_cr = C_real[o]; p_ci = C_imag[o]; p_dt = log_dt[d0 + c + 1];
            }
            const uint32_t mexp = min(max(__reduce_max_sync(0xffffffffu, __float_as_uint(fmaxf(fabsf(C.r), fabsf(C.i)))) & 0x7f800000u, 0x01000000u), 0x7e000000u);
            const float unsc = __uint_as_float(mexp), sc = __uint_as_float(0x7f000000u - mexp);
            C.r *= sc; C.i *= sc;
            #define EADDR(r) ((efl ^ (((r) & 7) << 4)) + (r) * 128)
            {
                cplx f[16];
                f[1] = cexp_(8.f * xr, -8.f * xi);
                f[2] = cmul(f[1], f[1]); f[3] = cmul(f[2], f[1]); f[4] = cmul(f[2], f[2]); f[5] = cmul(f[4], f[1]); f[6] = cmul(f[4], f[2]); f[7] = cmul(f[4], f[3]);
                f[8] = cmul(f[4], f[4]);
                #pragma unroll
                for (int b = 9; b < 16; b++) f[b] = cmul(f[8], f[b - 8]);
                sts32(EADDR(0) + 6144, 0x00003c00u);
                #pragma unroll
                for (int b = 1; b < 16; b++) sts32(EADDR(b) + 6144, pack_f16(f[b].r, f[b].i));
            }
            {
                cplx G[17], wc[8];
                G[1] = cexp_(128.f * xr, 128.f * xi);
                wc[1] = cexp_(xr, xi);
                G[2] = cmul(G[1], G[1]); G[4] = cmul(G[2], G[2]); G[8] = cmul(G[4], G[4]);
                wc[2] = cmul(wc[1], wc[1]); wc[3] = cmul(wc[2], wc[1]); wc[4] = cmul(wc[2], wc[2]); wc[5] = cmul(wc[4], wc[1]); wc[6] = cmul(wc[4], wc[2]); wc[7] = cmul(wc[4], wc[3]);
                cplx CG[17];
                CG[0] = C; CG[1] = cmul(C, G[1]); CG[2] = cmul(C, G[2]); CG[3] = cmul(CG[1], G[2]);
                #pragma unroll
                for (int a = 0; a < 4; a++) CG[4 + a] = cmul(CG[a], G[4]);
                #pragma unroll
                for (int a = 0; a < 9; a++) CG[8 + a] = cmul(CG[a], G[8]);
                #pragma unroll
                for (int r = 0; r < 41; r++) {
                    const int a = r < 16 ? (r >> 3) : (r < 24 ? 2 + ((r >> 2) & 1) : (r < 32 ? 4 + ((r >> 1) & 3) : r - 24));
                    const int cc = r < 16 ? (r & 7) : (r < 24 ? 2 * (r & 3) : (r < 32 ? 4 * (r & 1) : 0));
                    const cplx e = cc ? cmul(CG[a], wc[cc]) : CG[a];
                    sts32(EADDR(r), pack_f16(e.r, e.i));
                }
            }
            __syncwarp();
            float acc[3][2][4];
            #pragma unroll
            for (int i = 0; i < 3; i++)
                #pragma unroll
                for (int j = 0; j < 2; j++) { acc[i][j][0] = acc[i][j][1] = acc[i][j][2] = acc[i][j][3] = 0.f; }
            #pragma unroll
            for (int ks = 0; ks < 4; ks++) {
                uint32_t bq[4];
                ldsm_x4(bq, ef + 6144 + ((mi >> 1) * 8 + r8) * 128 + (((2 * ks + (mi & 1)) ^ r8) << 4));
                #pragma unroll
                for (int mt = 0; mt < 3; mt++) {
                    uint32_t aq[4];
                    ldsm_x4(aq, ef + (16 * mt + (mi & 1) * 8 + r8) * 128 + (((2 * ks + (mi >> 1)) ^ r8) << 4));
                    mma_f16(acc[mt][0], aq, bq[0], bq[1]);
                    mma_f16(acc[mt][1], aq, bq[2], bq[3]);
                }
            }
            const uint32_t kp = sb + SD_KP;
            #pragma unroll
            for (int mt = 0; mt < 3; mt++)
                #pragma unroll
                for (int nt = 0; nt < 2; nt++) {
                    const uint32_t a = kp + w * 3072 + (16 * mt + g) * 64 + nt * 32 + t * 8;
                    sts64(a, __float_as_uint(acc[mt][nt][0] * unsc), __float_as_uint(acc[mt][nt][1] * unsc));
                    sts64(a + 512, __float_as_uint(acc[mt][nt][2] * unsc), __float_as_uint(acc[mt][nt][3] * unsc));
                }
            bar_sync(4, 128);
            #pragma unroll
            for (int i = 0; i < 3; i++) {
                const uint32_t a = kp + (n + 128 * i) * 8;
                const uint2 v0 = lds64(a), v1 = lds64(a + 3072), v2 = lds64(a + 6144), v3 = lds64(a + 9216);
                sts64(a + 12288 + ((n >> 3) + 16 * i) * 8, __float_as_uint((__uint_as_float(v0.x) + __uint_as_float(v1.x)) + (__uint_as_float(v2.x) + __uint_as_float(v3.x))),
                                 __float_as_uint((__uint_as_float(v0.y) + __uint_as_float(v1.y)) + (__uint_as_float(v2.y) + __uint_as_float(v3.y))));
            }
            bar_sync(4, 128);
            const int slot = c % KSLOTS;
            float kv[16];
            #pragma unroll
            for (int e = 0; e < 8; e++) { kv[2 * e] = __uint_as_float(lds32(kp + 12288 + (goff[e] & 0xffff))); kv[2 * e + 1] = __uint_as_float(lds32(kp + 12288 + (goff[e] >> 16))); }
            if (c >= KSLOTS) mbar_wait_long(bKE + 8 * slot, (c / KSLOTS - 1) & 1);
            #pragma unroll
            for (int it = 0; it < 2; it++) {
                uint32_t hi[4], lo[4];
                #pragma unroll
                for (int e = 0; e < 4; e++) {
                    const float k0 = kv[8 * it + 2 * e], k1 = kv[8 * it + 2 * e + 1];
                    hi[e] = pack_bf16(k0, k1);
                    lo[e] = pack_bf16(k0 - bf_lo(hi[e]), k1 - bf_hi(hi[e]));
                }
                const uint32_t a = sb + SD_BC + slot * BC_BYTES + (w + 4 * it) * BC_LBO + (16 + 2 * lane) * 16;
                sts128(a, make_uint4(hi[0], hi[1], hi[2], hi[3]));
                sts128(a + 16, make_uint4(lo[0], lo[1], lo[2], lo[3]));
            }
            fence_async_smem();
            mbar_arrive(bKF + 8 * slot);
        }
        {
            uint32_t gw[9];
            #pragma unroll
            for (int j = 0; j < 9; j++) gw[j] = __ldg((const uint32_t*)gate_w + lane + 32 * j);
            float z = 0.f;
            #pragma unroll 1
            for (int i0 = 0; i0 < 15; i0 += 5) {
                uint32_t xv[5][9];
                #pragma unroll
                for (int i = 0; i < 5; i++) {
                    const int tk = min(blockIdx.x * 57 + w + 4 * (i0 + i), S_LEN - 1);
                    #pragma unroll
                    for (int j = 0; j < 9; j++) xv[i][j] = __ldg((const uint32_t*)(x + (size_t)tk * DM) + lane + 32 * j);
                }
                #pragma unroll
                for (int i = 0; i < 5; i++) {
                    float acc = 0.f;
                    #pragma unroll
                    for (int j = 0; j < 9; j++) { const uint32_t m = mul_bf2(xv[i][j], gw[j]); acc += bf_lo(m) + bf_hi(m); }
                    #pragma unroll
                    for (int o = 16; o; o >>= 1) acc += __shfl_xor_sync(0xffffffffu, acc, o);
                    if (lane == i0 + i) z = rbf(acc);
                }
            }
            const int li = w + 4 * lane, tk = blockIdx.x * 57 + li;
            if (li < 57 && tk < S_LEN) st_relaxed32(&g_gate[tk], pack_bf16(1.f / (1.f + expf(-z)), 0.f) | (epoch << 16));
        }
        if (tid == 256) GT(blockIdx.x, 67);
        fence_async_smem();
        __syncthreads();
            const uint32_t ost = sb + SD_OST + w * 256;
            const uint4* const pl = &g_part[blockIdx.x][0][0][0][lane];
            uint4 v[8];
            auto fetch = [&](int u, bool block) {
                const int s = u >> 2;
                uint32_t early;
                asm volatile("{\n.reg .pred p;\nmbarrier.test_wait.parity.shared::cta.b64 p, [%1], %2;\nselp.u32 %0, 1, 0, p;\n}\n" : "=r"(early) : "r"(bPRT + 8 * (s & 3)), "r"((s >> 2) & 1) : "memory");
                if (!early) {
                    if (!block) return false;
                    mbar_wait_long(bPRT + 8 * (s & 3), (s >> 2) & 1);
                    delay_clk(s < NSEG - 2 ? SD_P1 : SD_P2);
                } else if (SD_P3 && s < SD_RUSH) delay_clk(SD_P3);
                const uint4* p = pl + (u & (4 * PART_SLOTS - 1)) * 256;
                #pragma unroll
                for (int i = 0; i < 8; i++) v[i] = ld_relaxed128(p + 32 * i);
                return true;
            };
            auto units = [&](int u, int end) {
              fetch(u, true);
              #pragma unroll 1
              while (true) {
                const int s = u >> 2;
                const int t0 = 8 * u + 2 * t;
                const uint2 gt = lds64(sb + SD_Q0 + t0 * 4);
                const uint32_t ba = sb + SD_BT + g * BT_RS + (t0 >> 6) * 144 + (t0 & 63) * 2;
                const uint32_t b0 = lds32(ba), b1 = lds32(ba + 8 * BT_RS);
                const uint32_t phm = ((s / PART_SLOTS) & 1) - 1;
                int it = 0;
                while (true) {
                    uint32_t any = 0;
                    #pragma unroll
                    for (int i = 0; i < 8; i++) any |= v[i].x ^ phm;
                    if (!__any_sync(0xffffffffu, any & 1u) || ++it >= SD_SPIN) break;
                    if (it > 1 && s < NSEG - 2) __nanosleep(200);
                    const uint4* p = pl + (u & (4 * PART_SLOTS - 1)) * 256;
                    #pragma unroll
                    for (int i = 0; i < 8; i++) ld_relaxed128_p(v[i], p + 32 * i, (v[i].x ^ phm) & 1u);
                }
                if (lane == 0) mbar_arrive(bEPI + 8 * (s & 3));
                float a0 = __uint_as_float(v[0].x), a1 = __uint_as_float(v[0].y), a2 = __uint_as_float(v[0].z), a3 = __uint_as_float(v[0].w);
                #pragma unroll
                for (int i = 1; i < 8; i++) { a0 += __uint_as_float(v[i].x); a1 += __uint_as_float(v[i].y); a2 += __uint_as_float(v[i].z); a3 += __uint_as_float(v[i].w); }
                const uint32_t s01 = pack_bf16(a0, a1), s23 = pack_bf16(a2, a3);
                const int nu = u + 3;
                const bool pre = nu < end && fetch(nu, false);
                const uint32_t gg = __byte_perm(gt.x, gt.y, 0x5410), mm = pack_bf16(1.f - bf_lo(gg), 1.f - bf_hi(gg));
                const uint32_t r0 = add_bf2(mul_bf2(gg, s01), mul_bf2(mm, b0)), r1 = add_bf2(mul_bf2(gg, s23), mul_bf2(mm, b1));
                asm volatile("stmatrix.sync.aligned.m8n8.x2.trans.shared.b16 [%0], {%1,%2};" :: "r"(ost + r8 * 32 + (mi & 1) * 16), "r"(r0), "r"(r1) : "memory");
                __syncwarp();
                if (lane < 16) *(uint4*)(out + (size_t)(8 * u + (lane >> 1)) * DM + d0 + 8 * (lane & 1)) = lds128(ost + lane * 16);
                __syncwarp();
                if (lane == 0 && (u & 3) == 3) GT(blockIdx.x, 1 + s);
                if (nu >= end) break;
                if (!pre) fetch(nu, true);
                u = nu;
              }
            };
        if (w == 0) {
            if (lane == 0) {
                mbar_expect_tx(bWO, 131072);
                #pragma unroll
                for (int q = 0; q < 4; q++) tma2d(sb + SD_STG + q * 32768, &tmw, bWO, sh ? 128 * (blockIdx.x >> 3) + 64 * (q >> 1) : 512, sh ? 512 * (blockIdx.x & 7) + 256 * (q & 1) : 1024 * (blockIdx.x - 32) + 256 * q);
            }
            bar_sync(5, 128);
            const int ke0 = sh ? blockIdx.x & 7 : 2 * (blockIdx.x - 32);
            const unsigned int* f = &g_prog[12 * ke0 + (lane < (sh ? 12 : 24) ? lane : 0)];
            int avail = 0;
            #pragma unroll 1
            for (int s = 0; s < NSEG; s++) {
                if (s >= avail) {
                    int it = 0;
                    while (true) {
                        uint32_t v;
                        asm volatile("ld.acquire.gpu.global.u32 %0, [%1];" : "=r"(v) : "l"(f) : "memory");
                        avail = __reduce_min_sync(0xffffffffu, (v >> 8) == (epoch & 0xffffffu) ? v & 255u : 0u);
                        if (avail > s || ++it >= SD_SPIN) break;
                        if (s < NSEG - 1) __nanosleep(64);
                    }
                    asm volatile("fence.proxy.async.global;" ::: "memory");
                    if (lane == 0 && s == NSEG - 1) GT(blockIdx.x, 70);
                }
                if (lane == 0 && s == 2 && blockIdx.x == 0) st_relaxed32(&g_epoch, epoch + 1);
                const int b0 = sh ? s & 3 : s & 1, bp = (sh ? s >> 2 : s >> 1) & 1;
                const bf16* src = g_otok + (size_t)s * (SEG * NH * DH) + ke0 * 16384;
                mbar_wait_long(bEMPTY + 8 * b0, bp);
                if (!sh) mbar_wait_long(bEMPTY + 16 + 8 * b0, bp);
                if (s < NSEG - 1) {
                    asm volatile("{\n.reg .pred p, q;\nelect.sync _|p, 0xffffffff;\nsetp.eq.and.u32 q, %6, 0, p;\n"
                                 "@p mbarrier.arrive.expect_tx.shared.b64 _, [%2], 32768;\n"
                                 "@p cp.async.bulk.shared::cluster.global.mbarrier::complete_tx::bytes [%0], [%1], 32768, [%2];\n"
                                 "@q mbarrier.arrive.expect_tx.shared.b64 _, [%5], 32768;\n"
                                 "@q cp.async.bulk.shared::cluster.global.mbarrier::complete_tx::bytes [%3], [%4], 32768, [%5];\n}\n"
                        :: "r"(sb + SD_STG + b0 * 32768), "l"(src), "r"(bCH + 32 * b0), "r"(sb + SD_STG + (b0 + 2) * 32768), "l"(src + 16384), "r"(bCH + 32 * (b0 + 2)), "r"((uint32_t)sh) : "memory");
                } else {
                    #pragma unroll
                    for (int hc = 0; hc < 4; hc++)
                        asm volatile("{\n.reg .pred p, q;\nelect.sync _|p, 0xffffffff;\nsetp.eq.and.u32 q, %6, 0, p;\n"
                                     "@p mbarrier.arrive.expect_tx.shared.b64 _, [%2], 8192;\n"
                                     "@p cp.async.bulk.shared::cluster.global.mbarrier::complete_tx::bytes [%0], [%1], 8192, [%2];\n"
                                     "@q mbarrier.arrive.expect_tx.shared.b64 _, [%5], 8192;\n"
                                     "@q cp.async.bulk.shared::cluster.global.mbarrier::complete_tx::bytes [%3], [%4], 8192, [%5];\n}\n"
                            :: "r"(sb + SD_STG + b0 * 32768 + hc * 8192), "l"(src + hc * 4096), "r"(bCH + 32 * b0 + 8 * hc),
                               "r"(sb + SD_STG + (b0 + 2) * 32768 + hc * 8192), "l"(src + 16384 + hc * 4096), "r"(bCH + 32 * (b0 + 2) + 8 * hc), "r"((uint32_t)sh) : "memory");
                }
            }
        } else {
            if (w == 3) {
                for (int i = 0; i < 16; i += 8) {
                    uint4 v[8]; uint32_t miss = 0xffu; int it = 0;
                    const uint32_t tag = epoch & 0xffffu;
                    #pragma unroll
                    for (int j = 0; j < 8; j++) v[j] = make_uint4(0, 0, 0, 0);
                    do {
                        #pragma unroll
                        for (int j = 0; j < 8; j++) ld_relaxed128_p(v[j], (const uint4*)g_gate + (i + j) * 32 + lane, miss & (1u << j));
                        miss = 0;
                        #pragma unroll
                        for (int j = 0; j < 8; j++) miss |= (uint32_t)((v[j].x >> 16) != tag || (v[j].y >> 16) != tag || (v[j].z >> 16) != tag || (v[j].w >> 16) != tag) << j;
                    } while (__any_sync(0xffffffffu, miss) && ++it < SD_SPIN);
                    #pragma unroll
                    for (int j = 0; j < 8; j++) sts128(sb + SD_Q0 + ((i + j) * 32 + lane) * 16, v[j]);
                }
            }
            bar_sync(5, 128);
        }
        #pragma unroll 1
        for (int k = w == 0; k < 2; k++) units(k ? 4 * (NSEG - 1) + w : w - 1, k ? 0 : 4 * (NSEG - 1));
    }
    if (tid == 256) GT(blockIdx.x, 72);
}

extern "C" void kernel_launch(void* const* d_in, const int* in_sizes, int n_in, void* d_out, int out_size) {
    const bf16* x = (const bf16*)d_in[0];
    const bf16* mem0 = (const bf16*)d_in[1];
    const bf16* Wq = (const bf16*)d_in[2];
    const bf16* Wk = (const bf16*)d_in[3];
    const bf16* Wv = (const bf16*)d_in[4];
    const bf16* Wo = (const bf16*)d_in[5];
    const bf16* log_A_real = (const bf16*)d_in[8];
    const bf16* A_imag = (const bf16*)d_in[9];
    const bf16* C_real = (const bf16*)d_in[10];
    const bf16* C_imag = (const bf16*)d_in[11];
    const bf16* log_dt = (const bf16*)d_in[12];
    const bf16* D_skip = (const bf16*)d_in[13];
    const bf16* gate_w = (const bf16*)d_in[14];
    bf16* out = (bf16*)d_out;
    typedef CUresult (*EncFn)(CUtensorMap*, CUtensorMapDataType, cuuint32_t, void*, const cuuint64_t*, const cuuint64_t*, const cuuint32_t*, const cuuint32_t*,
                              CUtensorMapInterleave, CUtensorMapSwizzle, CUtensorMapL2promotion, CUtensorMapFloatOOBfill);
    static EncFn enc = nullptr;
    if (!enc) { void* fn = nullptr; cudaDriverEntryPointQueryResult qr; cudaGetDriverEntryPoint("cuTensorMapEncodeTiled", &fn, cudaEnableDefault, &qr); enc = (EncFn)fn; }
    auto mk = [&](CUtensorMap* tm, const void* ptr, uint64_t cols, uint64_t rows, uint32_t bc, uint32_t br) {
        cuuint64_t gdim[2] = {cols, rows}; cuuint64_t gstr[1] = {cols * 2}; cuuint32_t box[2] = {bc, br}; cuuint32_t estr[2] = {1, 1};
        enc(tm, CU_TENSOR_MAP_DATA_TYPE_BFLOAT16, 2, (void*)ptr, gdim, gstr, box, estr, CU_TENSOR_MAP_INTERLEAVE_NONE, bc == 64 ? CU_TENSOR_MAP_SWIZZLE_128B : CU_TENSOR_MAP_SWIZZLE_64B,
            CU_TENSOR_MAP_L2_PROMOTION_L2_256B, CU_TENSOR_MAP_FLOAT_OOB_FILL_NONE);
    };
    static bool attr_done = false;
    if (!attr_done) {
        cudaFuncSetAttribute(chain_kernel, cudaFuncAttributeMaxDynamicSharedMemorySize, SM_TOTAL);
        cudaFuncSetAttribute(side_kernel, cudaFuncAttributeMaxDynamicSharedMemorySize, SD_TOTAL);
        attr_done = true;
    }
    CUtensorMap tmx, tmw, tmq, tmk, tmv, tmo;
    {
        cuuint64_t gdim[3] = {64, S_LEN, DM / 64}; cuuint64_t gstr[2] = {DM * 2, 128}; cuuint32_t box[3] = {64, SEG, 3}; cuuint32_t estr[3] = {1, 1, 1};
        enc(&tmx, CU_TENSOR_MAP_DATA_TYPE_BFLOAT16, 3, (void*)x, gdim, gstr, box, estr, CU_TENSOR_MAP_INTERLEAVE_NONE, CU_TENSOR_MAP_SWIZZLE_128B,
            CU_TENSOR_MAP_L2_PROMOTION_L2_256B, CU_TENSOR_MAP_FLOAT_OOB_FILL_NONE);
    }
    mk(&tmw, Wo, DM, NH * DH, 64, 256);
    mk(&tmo, Wo, DM, NH * DH, 32, 128);
    mk(&tmq, Wq, NH * DH, DM, 32, 48); mk(&tmk, Wk, NH * DH, DM, 32, 48); mk(&tmv, Wv, NH * DH, DM, 32, 48);
    chain_kernel<<<96, CH_THREADS, SM_TOTAL>>>(tmx, tmq, tmk, tmv, tmo, mem0, 0u);
    cudaLaunchConfig_t cfg = {};
    cfg.gridDim = dim3(SD_CTAS); cfg.blockDim = dim3(SD_THREADS); cfg.dynamicSmemBytes = SD_TOTAL; cfg.stream = cudaStreamPerThread;
    cudaLaunchAttribute at[1];
    at[0].id = cudaLaunchAttributeProgrammaticStreamSerialization; at[0].val.programmaticStreamSerializationAllowed = 1;
    cfg.attrs = at; cfg.numAttrs = 1;
    cudaLaunchKernelEx(&cfg, side_kernel, tmw, x, log_A_real, A_imag, C_real, C_imag, log_dt, D_skip, gate_w, out);
}
```

```cpp
#include <cuda_runtime.h>
#include <cuda.h>
#include <cuda_bf16.h>
#include <stdint.h>

#define S_LEN 2048
#define DM 576
#define NH 32
#define DH 128
#define NMEM 8
#define SEG 32
#define NSEG 64
#define LQ 40
#define NS 128

typedef __nv_bfloat16 bf16;

__device__ __forceinline__ float bf(bf16 v) { return __bfloat162float(v); }
__device__ __forceinline__ bf16 tobf(float v) { return __float2bfloat16_rn(v); }
__device__ __forceinline__ float rbf(float v) { return __bfloat162float(__float2bfloat16_rn(v)); }

#define CH_THREADS 384
#define SPIN_LIMIT (1 << 17)
#define SM_X     0
#define XBUF     36864
#define SM_TOK   73728
#define TOKBUF   24576
#define SM_STASH 139264
#define SM_TS    (SM_STASH + 3072)
#define SM_WO    147456
#define SM_MEM   196608
#define SM_EX    205824
#define EXBUF    6144
#define SM_P     218112
#define SM_OST   219136
#define SM_O     223232
#define SM_XT    225280
#define SM_BAR   228352
#define MEM_MC 1
#define SM_IL    (SM_BAR + 128)
#define SM_SG    (SM_IL + 256)
#define SM_TOTAL (SM_SG + 64)

#define ACC_X    36864
#define ACC_FULL 0x0020u
#define SLOT_OFF(sl) ((((sl) & 1) << 7) | (((sl) & 2) << 8))
__device__ __align__(65536) unsigned char g_acc[65536];
__device__ unsigned int g_init[96];
__device__ unsigned int g_epoch = 1;
__device__ __align__(128) unsigned int g_ts[128];
__device__ __align__(1024) bf16 g_otok[S_LEN * NH * DH];
__device__ __align__(1024) unsigned char g_tokx[96][8192];
__device__ __align__(128) unsigned int g_prog[96];
#define STAMP(i)
#define STAMPV(i, v)
#define GT(b, i)
#define STAMPB(i)

__device__ __forceinline__ uint32_t smem_u32(const void* p) { return (uint32_t)__cvta_generic_to_shared(p); }
__device__ __forceinline__ void ldsm_x4(uint32_t (&r)[4], uint32_t addr) {
    asm volatile("ldmatrix.sync.aligned.m8n8.x4.shared.b16 {%0,%1,%2,%3}, [%4];" : "=r"(r[0]), "=r"(r[1]), "=r"(r[2]), "=r"(r[3]) : "r"(addr) : "memory");
}
__device__ __forceinline__ void ldsm_x4_p(uint32_t (&r)[4], uint32_t addr, uint32_t skip) {
    asm volatile("{\n.reg .pred p;\nsetp.eq.u32 p, %5, 0;\n@p ldmatrix.sync.aligned.m8n8.x4.shared.b16 {%0,%1,%2,%3}, [%4];\n}\n" : "+r"(r[0]), "+r"(r[1]), "+r"(r[2]), "+r"(r[3]) : "r"(addr), "r"(skip) : "memory");
}
__device__ __forceinline__ void ldsm_x4_t(uint32_t (&r)[4], uint32_t addr) {
    asm volatile("ldmatrix.sync.aligned.m8n8.x4.trans.shared.b16 {%0,%1,%2,%3}, [%4];" : "=r"(r[0]), "=r"(r[1]), "=r"(r[2]), "=r"(r[3]) : "r"(addr) : "memory");
}
__device__ __forceinline__ uint32_t ldsm_x1_t(uint32_t addr) {
    uint32_t r; asm volatile("ldmatrix.sync.aligned.m8n8.x1.trans.shared.b16 {%0}, [%1];" : "=r"(r) : "r"(addr) : "memory"); return r;
}
__device__ __forceinline__ void ldsm_x2_t(uint32_t& r0, uint32_t& r1, uint32_t addr) {
    asm volatile("ldmatrix.sync.aligned.m8n8.x2.trans.shared.b16 {%0,%1}, [%2];" : "=r"(r0), "=r"(r1) : "r"(addr) : "memory");
}
__device__ __forceinline__ void stsm_x4(uint32_t addr, uint32_t r0, uint32_t r1, uint32_t r2, uint32_t r3) {
    asm volatile("stmatrix.sync.aligned.m8n8.x4.shared.b16 [%0], {%1,%2,%3,%4};" :: "r"(addr), "r"(r0), "r"(r1), "r"(r2), "r"(r3) : "memory");
}
__device__ __forceinline__ void stsm_x4_t(uint32_t addr, uint32_t r0, uint32_t r1, uint32_t r2, uint32_t r3) {
    asm volatile("stmatrix.sync.aligned.m8n8.x4.trans.shared.b16 [%0], {%1,%2,%3,%4};" :: "r"(addr), "r"(r0), "r"(r1), "r"(r2), "r"(r3) : "memory");
}
__device__ __forceinline__ void mma16816(float (&c)[4], const uint32_t (&a)[4], uint32_t b0, uint32_t b1) {
    asm("mma.sync.aligned.m16n8k16.row.col.f32.bf16.bf16.f32 {%0,%1,%2,%3}, {%4,%5,%6,%7}, {%8,%9}, {%0,%1,%2,%3};"
        : "+f"(c[0]), "+f"(c[1]), "+f"(c[2]), "+f"(c[3]) : "r"(a[0]), "r"(a[1]), "r"(a[2]), "r"(a[3]), "r"(b0), "r"(b1));
}
__device__ __forceinline__ void mma16816r(float (&c)[4], uint32_t a0, uint32_t a1, uint32_t a2, uint32_t a3, uint32_t b0, uint32_t b1) {
    asm("mma.sync.aligned.m16n8k16.row.col.f32.bf16.bf16.f32 {%0,%1,%2,%3}, {%4,%5,%6,%7}, {%8,%9}, {%0,%1,%2,%3};"
        : "+f"(c[0]), "+f"(c[1]), "+f"(c[2]), "+f"(c[3]) : "r"(a0), "r"(a1), "r"(a2), "r"(a3), "r"(b0), "r"(b1));
}
__device__ __forceinline__ void mma1688(float (&c)[4], uint32_t a0, uint32_t a1, uint32_t b0) {
    asm("mma.sync.aligned.m16n8k8.row.col.f32.bf16.bf16.f32 {%0,%1,%2,%3}, {%4,%5}, {%6}, {%0,%1,%2,%3};"
        : "+f"(c[0]), "+f"(c[1]), "+f"(c[2]), "+f"(c[3]) : "r"(a0), "r"(a1), "r"(b0));
}
__device__ __forceinline__ uint32_t pack_bf16(float lo, float hi) {
    uint32_t r; asm("cvt.rn.bf16x2.f32 %0, %1, %2;" : "=r"(r) : "f"(hi), "f"(lo)); return r;
}
__device__ __forceinline__ float bf_lo(uint32_t v) { return __uint_as_float(v << 16); }
__device__ __forceinline__ float bf_hi(uint32_t v) { return __uint_as_float(v & 0xffff0000u); }
__device__ __forceinline__ uint32_t max_bf2(uint32_t a, uint32_t b) { uint32_t r; asm("max.bf16x2 %0, %1, %2;" : "=r"(r) : "r"(a), "r"(b)); return r; }
__device__ __forceinline__ uint32_t maxabs_bf2(uint32_t a, uint32_t b) { uint32_t r; asm("max.NaN.xorsign.abs.bf16x2 %0, %1, %2;" : "=r"(r) : "r"(a), "r"(b)); return r; }
__device__ __forceinline__ float ex2(float x) { float r; asm("ex2.approx.ftz.f32 %0, %1;" : "=f"(r) : "f"(x)); return r; }
__device__ __forceinline__ void ld_relaxed128_p(uint4& v, const uint4* p, uint32_t pred) {
    asm volatile("{\n.reg .pred p;\nsetp.ne.u32 p, %5, 0;\n@p ld.relaxed.gpu.global.v4.u32 {%0,%1,%2,%3}, [%4];\n}\n" : "+r"(v.x), "+r"(v.y), "+r"(v.z), "+r"(v.w) : "l"(p), "r"(pred) : "memory");
}
__device__ __forceinline__ uint4 ld_relaxed128(const uint4* p) { uint4 v; asm volatile("ld.relaxed.gpu.global.v4.u32 {%0,%1,%2,%3}, [%4];" : "=r"(v.x), "=r"(v.y), "=r"(v.z), "=r"(v.w) : "l"(p) : "memory"); return v; }
__device__ __forceinline__ uint32_t ld_relaxed32(const uint32_t* p) { uint32_t v; asm volatile("ld.relaxed.gpu.global.u32 %0, [%1];" : "=r"(v) : "l"(p) : "memory"); return v; }
__device__ __forceinline__ void st_relaxed128(uint4* p, uint4 v) { asm volatile("st.relaxed.gpu.global.v4.u32 [%0], {%1,%2,%3,%4};" :: "l"(p), "r"(v.x), "r"(v.y), "r"(v.z), "r"(v.w) : "memory"); }
__device__ __forceinline__ void st_relaxed32(uint32_t* p, uint32_t v) { asm volatile("st.relaxed.gpu.global.u32 [%0], %1;" :: "l"(p), "r"(v) : "memory"); }
__device__ __forceinline__ void st_relaxed128_p(uint4* p, uint4 v, uint32_t skip) {
    asm volatile("{\n.reg .pred p;\nsetp.eq.u32 p, %5, 0;\n@p st.relaxed.gpu.global.v4.u32 [%0], {%1,%2,%3,%4};\n}\n" :: "l"(p), "r"(v.x), "r"(v.y), "r"(v.z), "r"(v.w), "r"(skip) : "memory");
}
__device__ __forceinline__ void st_relaxed64_p(void* p, uint32_t x, uint32_t y, uint32_t skip) {
    asm volatile("{\n.reg .pred p;\n.reg .b64 v;\nsetp.eq.u32 p, %3, 0;\nmov.b64 v, {%1,%2};\n@p st.relaxed.gpu.global.b64 [%0], v;\n}\n" :: "l"(p), "r"(x), "r"(y), "r"(skip) : "memory");
}
__device__ __forceinline__ void ld_relaxed64_p(uint2& v, const void* p, uint32_t pred) {
    asm volatile("{\n.reg .pred p;\n.reg .b64 v;\nsetp.ne.u32 p, %3, 0;\nmov.b64 v, {%0,%1};\n@p ld.relaxed.gpu.global.b64 v, [%2];\nmov.b64 {%0,%1}, v;\n}\n" : "+r"(v.x), "+r"(v.y) : "l"(p), "r"(pred) : "memory");
}
__device__ __forceinline__ uint2 ld_relaxed64(const void* p) {
    uint2 v; asm volatile("{\n.reg .b64 v;\nld.relaxed.gpu.global.b64 v, [%2];\nmov.b64 {%0,%1}, v;\n}\n" : "=r"(v.x), "=r"(v.y) : "l"(p) : "memory"); return v;
}
__device__ __forceinline__ void st_relaxed32_p(void* p, uint32_t v, uint32_t skip) {
    asm volatile("{\n.reg .pred p;\nsetp.eq.u32 p, %2, 0;\n@p st.relaxed.gpu.global.u32 [%0], %1;\n}\n" :: "l"(p), "r"(v), "r"(skip) : "memory");
}
__device__ __forceinline__ void bar_arrive_p(int id, int n, uint32_t skip) {
    asm volatile("{\n.reg .pred p;\nsetp.eq.u32 p, %2, 0;\n@p bar.arrive %0, %1;\n}\n" :: "r"(id), "r"(n), "r"(skip) : "memory");
}
__device__ __forceinline__ void bar_sync_p(int id, int n, uint32_t skip) {
    asm volatile("{\n.reg .pred p;\nsetp.eq.u32 p, %2, 0;\n@p bar.sync %0, %1;\n}\n" :: "r"(id), "r"(n), "r"(skip) : "memory");
}
__device__ __forceinline__ uint32_t movm(uint32_t x) { uint32_t r; asm volatile("movmatrix.sync.aligned.m8n8.trans.b16 %0, %1;" : "=r"(r) : "r"(x)); return r; }
__device__ __forceinline__ void sts32_p(uint32_t a, uint32_t v, uint32_t doit) {
    asm volatile("{\n.reg .pred p;\nsetp.ne.u32 p, %2, 0;\n@p st.shared.u32 [%0], %1;\n}\n" :: "r"(a), "r"(v), "r"(doit) : "memory");
}
__device__ __forceinline__ uint32_t pin(uint32_t x) { return __shfl_sync(0xffffffffu, x, threadIdx.x & 31); }
__device__ __forceinline__ void ldsm16_t(uint32_t (&b)[4][4], uint32_t a) {
    asm volatile("ldmatrix.sync.aligned.m8n8.x4.trans.shared.b16 {%0,%1,%2,%3}, [%16];\n"
                 "ldmatrix.sync.aligned.m8n8.x4.trans.shared.b16 {%4,%5,%6,%7}, [%16+512];\n"
                 "ldmatrix.sync.aligned.m8n8.x4.trans.shared.b16 {%8,%9,%10,%11}, [%16+1024];\n"
                 "ldmatrix.sync.aligned.m8n8.x4.trans.shared.b16 {%12,%13,%14,%15}, [%16+1536];\n"
        : "=r"(b[0][0]), "=r"(b[0][1]), "=r"(b[0][2]), "=r"(b[0][3]), "=r"(b[1][0]), "=r"(b[1][1]), "=r"(b[1][2]), "=r"(b[1][3]),
          "=r"(b[2][0]), "=r"(b[2][1]), "=r"(b[2][2]), "=r"(b[2][3]), "=r"(b[3][0]), "=r"(b[3][1]), "=r"(b[3][2]), "=r"(b[3][3]) : "r"(a) : "memory");
}
template<int ID> __device__ __forceinline__ void sched_fence(uint32_t never) { while (never == 0x7fffff00u + ID) { asm volatile("nanosleep.u32 64;" ::: "memory"); } }
__device__ __forceinline__ uint32_t opaque_u() { uint32_t v; asm volatile("mov.u32 %0, %%nsmid;" : "=r"(v)); return v; }
__device__ __forceinline__ uint32_t bar_red_or(int id, int n, uint32_t v) {
    uint32_t r; asm volatile("{\n.reg .pred p, q;\nsetp.ne.u32 p, %3, 0;\nbar.red.or.pred q, %1, %2, p;\nselp.u32 %0, 1, 0, q;\n}\n" : "=r"(r) : "r"(id), "r"(n), "r"(v) : "memory"); return r;
}
template<class T> __device__ __forceinline__ T* launder_p(T* p) { asm volatile("" : "+l"(p)); return p; }
__device__ __forceinline__ uint32_t mapa_u32(uint32_t addr, uint32_t rank) { uint32_t d; asm("mapa.shared::cluster.u32 %0, %1, %2;" : "=r"(d) : "r"(addr), "r"(rank)); return d; }
__device__ __forceinline__ uint32_t mapa_v(uint32_t addr, uint32_t rank) { uint32_t d; asm volatile("mapa.shared::cluster.u32 %0, %1, %2;" : "=r"(d) : "r"(addr), "r"(rank)); return d; }
__device__ __forceinline__ void st_async32(uint32_t addr, uint32_t v, uint32_t mbar) { asm volatile("st.async.shared::cluster.mbarrier::complete_tx::bytes.u32 [%0], %1, [%2];" :: "r"(addr), "r"(v), "r"(mbar) : "memory"); }
__device__ __forceinline__ void cluster_arrive() { asm volatile("barrier.cluster.arrive.release.aligned;" ::: "memory"); }
__device__ __forceinline__ void cluster_wait() { asm volatile("barrier.cluster.wait.acquire.aligned;" ::: "memory"); }
__device__ __forceinline__ void cp_async16(uint32_t dst, const void* src) { asm volatile("cp.async.cg.shared.global [%0], [%1], 16;" :: "r"(dst), "l"(src) : "memory"); }
__device__ __forceinline__ void cp_async_commit() { asm volatile("cp.async.commit_group;" ::: "memory"); }
template<int N> __device__ __forceinline__ void cp_async_wait() { asm volatile("cp.async.wait_group %0;" :: "n"(N) : "memory"); }
__device__ __forceinline__ void cp_async_wait0() { asm volatile("cp.async.wait_group 0;" ::: "memory"); }
__device__ __forceinline__ void mbar_init(uint32_t a, uint32_t cnt) { asm volatile("mbarrier.init.shared.b64 [%0], %1;" :: "r"(a), "r"(cnt) : "memory"); }
__device__ __forceinline__ void mbar_expect_tx(uint32_t a, uint32_t bytes) { asm volatile("mbarrier.arrive.expect_tx.shared.b64 _, [%0], %1;" :: "r"(a), "r"(bytes) : "memory"); }
__device__ __forceinline__ bool mbar_try(uint32_t a, uint32_t parity) {
    uint32_t ok; asm volatile("{\n.reg .pred p;\nmbarrier.try_wait.parity.shared::cta.b64 p, [%1], %2;\nselp.u32 %0, 1, 0, p;\n}\n" : "=r"(ok) : "r"(a), "r"(parity) : "memory"); return ok;
}
__device__ __forceinline__ void mbar_wait(uint32_t a, uint32_t parity) { int it = 0; bool more; do { more = ++it < SPIN_LIMIT; } while (!mbar_try(a, parity) && more); }
__device__ __forceinline__ void bar_sync(int id, int n) { asm volatile("bar.sync %0, %1;" :: "r"(id), "r"(n) : "memory"); }
__device__ __forceinline__ void bar_arrive(int id, int n) { asm volatile("bar.arrive %0, %1;" :: "r"(id), "r"(n) : "memory"); }
__device__ __forceinline__ void fence_async_smem() { asm volatile("fence.proxy.async.shared::cta;" ::: "memory"); }
__device__ __forceinline__ void sts32(uint32_t a, uint32_t v) { asm volatile("st.shared.u32 [%0], %1;" :: "r"(a), "r"(v) : "memory"); }
__device__ __forceinline__ void sts128(uint32_t a, uint4 v) { asm volatile("st.shared.v4.u32 [%0], {%1,%2,%3,%4};" :: "r"(a), "r"(v.x), "r"(v.y), "r"(v.z), "r"(v.w) : "memory"); }
__device__ __forceinline__ uint4 lds128(uint32_t a) { uint4 v; asm volatile("ld.shared.v4.u32 {%0,%1,%2,%3}, [%4];" : "=r"(v.x), "=r"(v.y), "=r"(v.z), "=r"(v.w) : "r"(a) : "memory"); return v; }
__device__ __forceinline__ uint32_t lds32(uint32_t a) { uint32_t v; asm volatile("ld.shared.u32 %0, [%1];" : "=r"(v) : "r"(a) : "memory"); return v; }
__device__ __forceinline__ uint32_t gtime_lo() { uint32_t t; asm volatile("mov.u32 %0, %globaltimer_lo;" : "=r"(t)); return t; }
__device__ __forceinline__ void wait_gtime(uint32_t tg) {
    asm volatile("{\n.reg .pred p, q;\n.reg .b64 t;\n.reg .b32 lo, hi, d, n;\nmov.b32 n, 300;\n"
                 "WG_%=:\nmov.u64 t, %%globaltimer;\nmov.b64 {lo, hi}, t;\nsub.s32 d, lo, %0;\nsub.s32 n, n, 1;\n"
                 "setp.gt.s32 q, n, 0;\nsetp.lt.and.s32 p, d, 0, q;\n@p bra.uni WG_%=;\n}\n" :: "r"(tg) : "memory");
}
__device__ __forceinline__ void delay_clk(int d) { uint32_t t0 = clock(); while ((int)(clock() - t0) < d) {} }

__device__ __forceinline__ uint64_t desc128(uint32_t addr) {
    return (uint64_t)((addr & 0x3FFFF) >> 4) | ((uint64_t)1 << 16) | ((uint64_t)64 << 32) | ((uint64_t)1 << 62);
}
template<int accum> __device__ __forceinline__ void wgmma_n32(float (&d)[16], const uint32_t (&a)[4], uint64_t desc) {
    if (accum) {
        asm volatile("{\n.reg .pred p;\nsetp.ne.b32 p, 1, 0;\n"
            "wgmma.mma_async.sync.aligned.m64n32k16.f32.bf16.bf16 {%0,%1,%2,%3,%4,%5,%6,%7,%8,%9,%10,%11,%12,%13,%14,%15}, {%16,%17,%18,%19}, %20, p, 1, 1, 0;\n}\n"
            : "+f"(d[0]), "+f"(d[1]), "+f"(d[2]), "+f"(d[3]), "+f"(d[4]), "+f"(d[5]), "+f"(d[6]), "+f"(d[7]),
              "+f"(d[8]), "+f"(d[9]), "+f"(d[10]), "+f"(d[11]), "+f"(d[12]), "+f"(d[13]), "+f"(d[14]), "+f"(d[15])
            : "r"(a[0]), "r"(a[1]), "r"(a[2]), "r"(a[3]), "l"(desc));
    } else {
        asm volatile("{\n.reg .pred p;\nsetp.ne.b32 p, 0, 0;\n"
            "wgmma.mma_async.sync.aligned.m64n32k16.f32.bf16.bf16 {%0,%1,%2,%3,%4,%5,%6,%7,%8,%9,%10,%11,%12,%13,%14,%15}, {%16,%17,%18,%19}, %20, p, 1, 1, 0;\n}\n"
            : "=f"(d[0]), "=f"(d[1]), "=f"(d[2]), "=f"(d[3]), "=f"(d[4]), "=f"(d[5]), "=f"(d[6]), "=f"(d[7]),
              "=f"(d[8]), "=f"(d[9]), "=f"(d[10]), "=f"(d[11]), "=f"(d[12]), "=f"(d[13]), "=f"(d[14]), "=f"(d[15])
            : "r"(a[0]), "r"(a[1]), "r"(a[2]), "r"(a[3]), "l"(desc));
    }
}
__device__ __forceinline__ float rcp_approx(float x) { float r; asm("rcp.approx.ftz.f32 %0, %1;" : "=f"(r) : "f"(x)); return r; }
__device__ __forceinline__ void wg_fence() { asm volatile("wgmma.fence.sync.aligned;" ::: "memory"); }
__device__ __forceinline__ void wg_commit() { asm volatile("wgmma.commit_group.sync.aligned;" ::: "memory"); }
__device__ __forceinline__ void wg_wait0() { asm volatile("wgmma.wait_group.sync.aligned 0;" ::: "memory"); }

#define SCALE_HI 0x3db53db5u
#define SCALE_LO 0x371e371eu
#define LOG2E 1.4426950408889634f
#define NEG_BIG2 0xce6ece6eu
__device__ __forceinline__ uint32_t scale_bf2(uint32_t x) {
    uint32_t t, r;
    asm("mul.rn.bf16x2 %0, %1, %2;" : "=r"(t) : "r"(x), "r"(SCALE_LO));
    asm("fma.rn.bf16x2 %0, %1, %2, %3;" : "=r"(r) : "r"(x), "r"(SCALE_HI), "r"(t));
    return r;
}
__device__ __forceinline__ void cluster_arrive_rx() { asm volatile("barrier.cluster.arrive.relaxed.aligned;" ::: "memory"); }
__device__ __forceinline__ uint32_t launder(uint32_t x) { asm volatile("" : "+r"(x)); return x; }
__device__ __forceinline__ void mbar_arrive(uint32_t a) { asm volatile("mbarrier.arrive.shared.b64 _, [%0];" :: "r"(a) : "memory"); }
__device__ __forceinline__ void mbar_wait_cl(uint32_t a, uint32_t parity) {
    int it = 0; uint32_t ok;
    do { asm volatile("{\n.reg .pred p;\nmbarrier.try_wait.parity.acquire.cluster.shared::cta.b64 p, [%1], %2;\nselp.u32 %0, 1, 0, p;\n}\n" : "=r"(ok) : "r"(a), "r"(parity) : "memory"); } while (!ok && ++it < SPIN_LIMIT);
}
__device__ __forceinline__ uint64_t desc_from(uint32_t lo) { return (uint64_t)lo | ((uint64_t)0x40000040u << 32); }
#define SB_OFF 1024u
#define DESC_LO(off) ((((SB_OFF + (uint32_t)(off)) & 0x3FFFFu) >> 4) | 0x10000u)
template<int N> struct ic { static constexpr int value = N; };
__device__ __forceinline__ uint32_t uni(uint32_t x) { return __shfl_sync(0xffffffffu, x, 0); }

__device__ __forceinline__ uint32_t pack_f16(float lo, float hi) { uint32_t r; asm("cvt.rn.f16x2.f32 %0, %1, %2;" : "=r"(r) : "f"(hi), "f"(lo)); return r; }
__device__ __forceinline__ void sts16(uint32_t a, uint16_t v) { asm volatile("st.shared.u16 [%0], %1;" :: "r"(a), "h"(v) : "memory"); }
__device__ __forceinline__ void sts64(uint32_t a, uint32_t x, uint32_t y) { asm volatile("st.shared.v2.u32 [%0], {%1,%2};" :: "r"(a), "r"(x), "r"(y) : "memory"); }
__device__ __forceinline__ void ld_relaxed32_p(uint32_t& v, const void* p, uint32_t pred) {
    asm volatile("{\n.reg .pred p;\nsetp.ne.u32 p, %2, 0;\n@p ld.relaxed.gpu.global.u32 %0, [%1];\n}\n" : "+r"(v) : "l"(p), "r"(pred) : "memory");
}
__device__ __forceinline__ uint2 lds64(uint32_t a) { uint2 v; asm volatile("ld.shared.v2.u32 {%0,%1}, [%2];" : "=r"(v.x), "=r"(v.y) : "r"(a) : "memory"); return v; }
__device__ __forceinline__ void mbar_wait2(uint32_t a, uint32_t pa, uint32_t b, uint32_t pb) {
    int it = 0; uint32_t ok;
    do { asm volatile("{\n.reg .pred p, q;\nmbarrier.try_wait.parity.shared::cta.b64 p, [%1], %2;\nmbarrier.try_wait.parity.shared::cta.b64 q, [%3], %4;\nand.pred p, p, q;\nselp.u32 %0, 1, 0, p;\n}\n"
                      : "=r"(ok) : "r"(a), "r"(pa), "r"(b), "r"(pb) : "memory"); } while (!ok && ++it < SPIN_LIMIT);
}
__device__ __forceinline__ float exd(float s, float m) { return ex2(__fmul_rn(__fsub_rn(s, m), LOG2E)); }
__device__ __forceinline__ uint32_t gtime_after(uint32_t z) {
    uint32_t t = 0; asm volatile("{\n.reg .pred p;\nsetp.eq.u32 p, %1, 0;\n@p mov.u32 %0, %%globaltimer_lo;\n}\n" : "+r"(t) : "r"(z)); return t;
}
#define T_HOLD 4
#define T_KPRE 3
#define BLK_Q(p) (((p) < 3 ? (p) : 8) * 2048)
#define BLK_K(p) (((p) < 3 ? 4 + (p) : 9) * 2048)
#define BLK_V(p) (((p) < 2 ? 3 + 4 * (p) : 8 + (p)) * 2048)
__device__ __forceinline__ uint32_t exp_bf2(uint32_t s) { return pack_bf16(ex2(bf_lo(s) * LOG2E), ex2(bf_hi(s) * LOG2E)); }
template<int MT, int LO, int HI>
__device__ __forceinline__ void tok_loadv(uint32_t tok, int eh, int lane, uint32_t (&bv)[8][4]) {
    const int r8 = lane & 7;
    const uint32_t va = MT ? tok + lane * 64 + ((r8 >> 1) << 4) : tok + (lane & 15) * 64 + (((lane >> 4) ^ (r8 >> 1)) << 4);
    const uint32_t o0 = eh ? BLK_V(2) : BLK_V(0), o1 = eh ? BLK_V(3) : BLK_V(1);
    #pragma unroll
    for (int n = LO; n < HI; n++) { if (MT) ldsm_x4_t(bv[n], (va ^ ((n & 3) << 4)) + (n < 4 ? o0 : o1)); else ldsm_x4_t(bv[n], (va ^ ((n & 1) << 5)) + BLK_V(n >> 1)); }
}
#define T_VPRE 4
template<int MT, class F>
__device__ __forceinline__ void tok_part1(uint32_t tok, int eh, int lane, uint32_t (&q)[8][4], uint32_t (&sp)[5][2], uint32_t (&pa)[5][2], uint32_t (&bv)[8][4], uint32_t& rng, F&& hold) {
    float e[5][4];
    constexpr int NK = MT ? 5 : 3;
    const int g = lane >> 2, t = lane & 3, mi = lane >> 3, r8 = lane & 7;
    #pragma unroll
    for (int nt = 1; nt < NK; nt++) { e[nt][0] = e[nt][1] = e[nt][2] = e[nt][3] = 0.f; }
    const uint32_t qa = tok + (16 * MT + (mi & 1) * 8 + r8) * 64 + (((mi >> 1) ^ (r8 >> 1)) << 4);
    const uint32_t ka = tok + r8 * 64 + ((mi ^ (r8 >> 1)) << 4);
    uint32_t b[4][NK][4];
    constexpr int PRE = T_HOLD >= 3 ? (MT ? T_KPRE : 4) : 0;
    #pragma unroll
    for (int k2 = 0; k2 < 4; k2++) {
        if (T_HOLD >= 3) { ldsm_x4(q[2 * k2], qa + BLK_Q(k2)); ldsm_x4(q[2 * k2 + 1], (qa ^ 32) + BLK_Q(k2)); }
        if (k2 < PRE) {
            #pragma unroll
            for (int nt = 1; nt < NK; nt++) ldsm_x4(b[k2][nt], ka + BLK_K(k2) + (nt - 1) * 512);
        }
    }
    if (T_HOLD >= 3) hold();
    #pragma unroll
    for (int k2 = 0; k2 < 4; k2++) {
        if (T_HOLD < 3) { ldsm_x4(q[2 * k2], qa + BLK_Q(k2)); ldsm_x4(q[2 * k2 + 1], (qa ^ 32) + BLK_Q(k2)); }
        if (k2 >= PRE) {
            #pragma unroll
            for (int nt = 1; nt < NK; nt++) ldsm_x4(b[k2][nt], ka + BLK_K(k2) + (nt - 1) * 512);
        }
        #pragma unroll
        for (int nt = 1; nt < NK; nt++) mma16816(e[nt], q[2 * k2], b[k2][nt][0], b[k2][nt][1]);
        #pragma unroll
        for (int nt = 1; nt < NK; nt++) mma16816(e[nt], q[2 * k2 + 1], b[k2][nt][2], b[k2][nt][3]);
    }
    #pragma unroll
    for (int nt = 1; nt < NK; nt++) asm volatile("" : "+f"(e[nt][0]), "+f"(e[nt][1]), "+f"(e[nt][2]), "+f"(e[nt][3]));
    if (T_HOLD < 3) hold();
    #pragma unroll
    for (int nt = 1; nt < NK; nt++) {
        sp[nt][0] = nt < NK - 1 ? scale_bf2(pack_bf16(e[nt][0], e[nt][1])) : NEG_BIG2; sp[nt][1] = scale_bf2(pack_bf16(e[nt][2], e[nt][3]));
        rng = maxabs_bf2(nt == 1 ? sp[1][0] : (nt < NK - 1 ? maxabs_bf2(rng, sp[nt][0]) : rng), sp[nt][1]);
    }
    const uint32_t keep = (2 * t <= g ? 0x0000ffffu : 0u) | (2 * t + 1 <= g ? 0xffff0000u : 0u);
    sp[NK - 2][0] = (sp[NK - 2][0] & keep) | (NEG_BIG2 & ~keep);
    sp[NK - 1][1] = (sp[NK - 1][1] & keep) | (NEG_BIG2 & ~keep);
    #pragma unroll
    for (int nt = 1; nt < NK; nt++) { pa[nt][0] = nt < NK - 1 ? exp_bf2(sp[nt][0]) : 0u; pa[nt][1] = exp_bf2(sp[nt][1]); }
    tok_loadv<MT, 0, MT ? T_VPRE : 8>(tok, eh, lane, bv);
}
template<int MT, class F, class G, class H, class I>
__device__ __forceinline__ void tok_part2(uint32_t tok, uint32_t exl, uint32_t ost, int eh, int lane, const uint32_t (&q)[8][4], uint32_t (&sp)[5][2], uint32_t (&pa)[5][2], uint32_t (&bv)[8][4], uint32_t rng, bool vb,
                                          F&& wait_v, G&& duty, H&& pace, I&& wait_x) {
    constexpr int NK = MT ? 5 : 3;
    const int mi = lane >> 3, r8 = lane & 7;
    {
        float c[4][4];
        uint32_t b[4][4];
        ldsm16_t(b, exl + 2048);
        duty();
        #pragma unroll
        for (int j = 0; j < 4; j++) { c[j][0] = c[j][1] = c[j][2] = c[j][3] = 0.f; }
        #pragma unroll
        for (int k2 = 0; k2 < 4; k2++) { mma16816(c[(2 * k2) & 3], q[2 * k2], b[k2][0], b[k2][1]); mma16816(c[(2 * k2 + 1) & 3], q[2 * k2 + 1], b[k2][2], b[k2][3]); }
        sp[0][0] = scale_bf2(pack_bf16((c[0][0] + c[1][0]) + (c[2][0] + c[3][0]), (c[0][1] + c[1][1]) + (c[2][1] + c[3][1])));
        sp[0][1] = scale_bf2(pack_bf16((c[0][2] + c[1][2]) + (c[2][2] + c[3][2]), (c[0][3] + c[1][3]) + (c[2][3] + c[3][3])));
    }
    pa[0][0] = exp_bf2(sp[0][0]); pa[0][1] = exp_bf2(sp[0][1]);
    rng = maxabs_bf2(maxabs_bf2(rng, sp[0][0]), sp[0][1]);
    if (__builtin_expect(__any_sync(0xffffffffu, ((rng & 0x7fff7fffu) + 0x3ddf3ddfu) & 0x80008000u), 0)) {
        uint32_t m0 = sp[0][0], m1 = sp[0][1];
        #pragma unroll
        for (int nt = 1; nt < NK; nt++) { if (nt < NK - 1) m0 = max_bf2(m0, sp[nt][0]); m1 = max_bf2(m1, sp[nt][1]); }
        uint32_t mm = max_bf2(__byte_perm(m0, m1, 0x5410), __byte_perm(m0, m1, 0x7632));
        mm = max_bf2(mm, __shfl_xor_sync(0xffffffffu, mm, 1));
        mm = max_bf2(mm, __shfl_xor_sync(0xffffffffu, mm, 2));
        #pragma unroll
        for (int nt = 0; nt < NK; nt++) {
            if (nt < NK - 1) pa[nt][0] = pack_bf16(exd(bf_lo(sp[nt][0]), bf_lo(mm)), exd(bf_hi(sp[nt][0]), bf_lo(mm)));
            pa[nt][1] = pack_bf16(exd(bf_lo(sp[nt][1]), bf_hi(mm)), exd(bf_hi(sp[nt][1]), bf_hi(mm)));
        }
    }
    tok_loadv<MT, MT ? T_VPRE : 8, 8>(tok, eh, lane, bv);
    wait_v();
    constexpr int NQ = MT ? 2 : 4;
    float o[NQ][4][4], l[4] = {0.f, 0.f, 0.f, 0.f};
    const uint32_t ONE = 0x3F803F80u;
    mma16816r(l, pa[1][0], pa[1][1], pa[2][0], pa[2][1], ONE, ONE);
    if (MT) mma16816r(l, pa[3 % NK][0], pa[3 % NK][1], pa[4 % NK][0], pa[4 % NK][1], ONE, ONE);
    mma1688(l, pa[0][0], pa[0][1], ONE);
    #pragma unroll
    for (int j = 0; j < NQ; j++) {
        uint32_t bm[4];
        ldsm_x4(bm, exl + 4096 + (MT ? eh * 1024 : 0) + 512 * j);
        #pragma unroll
        for (int n = 0; n < 4; n++) {
            o[j][n][0] = o[j][n][1] = o[j][n][2] = o[j][n][3] = 0.f;
            if (MT) mma16816r(o[j][n], pa[1][0], pa[1][1], pa[2][0], pa[2][1], bv[4 * j + n][0], bv[4 * j + n][1]);
            else mma16816r(o[j][n], pa[1][0], pa[1][1], pa[2][0], pa[2][1], bv[2 * j + (n >> 1)][2 * (n & 1)], bv[2 * j + (n >> 1)][2 * (n & 1) + 1]);
        }
        if (MT) {
            #pragma unroll
            for (int n = 0; n < 4; n++) mma16816r(o[j][n], pa[3 % NK][0], pa[3 % NK][1], pa[4 % NK][0], pa[4 % NK][1], bv[4 * j + n][2], bv[4 * j + n][3]);
        }
        #pragma unroll
        for (int n = 0; n < 4; n++) mma1688(o[j][n], pa[0][0], pa[0][1], bm[n]);
    }
    #pragma unroll
    for (int j = 0; j < NQ; j++) asm volatile("" : "+f"(o[j][0][0]), "+f"(o[j][1][0]), "+f"(o[j][2][0]), "+f"(o[j][3][0]));
    asm volatile("" : "+f"(l[0]), "+f"(l[2]));
    wait_x();
    bar_arrive_p(12, 384, !vb);
    pace();
    const float i0 = rcp_approx(l[0]), i1 = rcp_approx(l[2]);
    const uint32_t oa = ost + ((mi & 1) * 8 + r8) * 128 + (((mi >> 1) ^ r8) << 4);
    #pragma unroll
    for (int j = 0; j < NQ; j++) {
        stsm_x4((oa ^ ((j & 1) << 6)) + (j >> 1) * 2048, pack_bf16(o[j][0][0] * i0, o[j][0][1] * i0), pack_bf16(o[j][0][2] * i1, o[j][0][3] * i1), pack_bf16(o[j][1][0] * i0, o[j][1][1] * i0), pack_bf16(o[j][1][2] * i1, o[j][1][3] * i1));
        stsm_x4((oa ^ (((j & 1) << 6) | 32)) + (j >> 1) * 2048, pack_bf16(o[j][2][0] * i0, o[j][2][1] * i0), pack_bf16(o[j][2][2] * i1, o[j][2][3] * i1), pack_bf16(o[j][3][0] * i0, o[j][3][1] * i0), pack_bf16(o[j][3][2] * i1, o[j][3][3] * i1));
    }
}

#define X_PRED "@q "
#define X_LANE(ll) ((ll) >> 4)
#define SEND_LANE(ll) ((ll) >> 2)
#define TP_E 0
#define V_EARLY 1
#ifndef M_SF
#define M_SF 0
#endif
#ifndef M_F2
#define M_F2 0
#endif
#ifndef M_FENCE
#define M_FENCE 1
#endif
#define SW_FENCE 0
#define PV_FENCE 1
#define IL_AT 3
#define TAIL 0
#define MP_PRE 4
#define VF_EARLY 1
__device__ __forceinline__ void stsm2_p(uint32_t a, const uint32_t (&v)[8], uint32_t skip) {
    asm volatile("{\n.reg .pred p;\nsetp.eq.u32 p, %9, 0;\n@p stmatrix.sync.aligned.m8n8.x4.trans.shared.b16 [%0], {%1,%2,%3,%4};\n"
                 "@p stmatrix.sync.aligned.m8n8.x4.trans.shared.b16 [%0+1024], {%5,%6,%7,%8};\n}\n"
        :: "r"(a), "r"(v[0]), "r"(v[1]), "r"(v[2]), "r"(v[3]), "r"(v[4]), "r"(v[5]), "r"(v[6]), "r"(v[7]), "r"(skip) : "memory");
}
template<int OA, int OB>
__device__ __forceinline__ void send_tile(float c0, float c1, float c2, float c3, uint32_t a, uint32_t b, uint32_t l16) {
    const uint32_t hi = (uint32_t)((uint64_t)g_acc >> 32);
    asm volatile("{\n.reg .pred q, pl, ph;\n.reg .b64 pa, pb;\n.reg .b32 t, w0, w1, w2;\n.reg .f32 x, y, z;\n"
                 "and.b32 t, %7, 0x30;\nsetp.eq.u32 q, t, 0;\nand.b32 t, %7, 0x70;\nsetp.eq.u32 ph, t, 0;\nxor.pred pl, q, ph;\n"
                 "selp.f32 x, 0f00010000, %4, pl;\nselp.f32 y, 0f00010000, %6, ph;\nselp.f32 z, %6, %4, ph;\n"
                 "cvt.rn.bf16x2.f32 w0, x, %3;\ncvt.rn.bf16x2.f32 w1, y, %5;\ncvt.rn.bf16x2.f32 w2, 0f00010000, z;\n"
                 "mov.b64 pa, {%0, %2};\nmov.b64 pb, {%1, %2};\n"
                 "red.relaxed.gpu.global.add.noftz.bf16x2 [pa+%8], w0;\nred.relaxed.gpu.global.add.noftz.bf16x2 [pa+%10], w1;\n" X_PRED "red.relaxed.gpu.global.add.noftz.bf16x2 [pb+%9], w2;\n}\n"
        :: "r"(a), "r"(b), "r"(hi), "f"(c0), "f"(c1), "f"(c2), "f"(c3), "r"(l16), "n"(OA), "n"(OB), "n"(OA + 256) : "memory");
}
__device__ __forceinline__ uint32_t send_ua(uint32_t tile) { return (uint32_t)(uint64_t)g_acc + tile * 1024; }
__device__ __forceinline__ uint32_t send_ub(uint32_t tile) { return (uint32_t)(uint64_t)g_acc + ACC_X + (tile >> 1) * 1024 + (tile & 1) * 256; }
__device__ __forceinline__ void lds_il(float& il, float& ih, uint32_t a) {
    uint32_t x, y; asm volatile("ldmatrix.sync.aligned.m8n8.x2.shared.b16 {%0,%1}, [%2];" : "=r"(x), "=r"(y) : "r"(a) : "memory");
    il = __uint_as_float(x); ih = __uint_as_float(y);
}
template<bool OWN, class F>
__device__ __forceinline__ void stage_w(const uint32_t (&wo)[8][4], uint32_t ol, uint32_t tile, uint32_t so, uint32_t l16, uint32_t nv, uint32_t ila, F&& issued) {
    float il, ih;
    uint32_t b[4][4], sa, sb_, ll;
    float c[2][4];
    auto addr = [&] {
        ll = OWN ? l16 : l16 | (__float_as_uint(c[0][0]) & nv);
        sa = SEND_LANE(ll) + (send_ua(tile) + so); sb_ = X_LANE(ll) + (send_ub(tile) + so);
    };
    ldsm16_t(b, ol);
    lds_il(il, ih, ila);
    if (OWN) addr();
    if (!OWN || SW_FENCE) sched_fence<0>(nv);
    #pragma unroll
    for (int i = 0; i < 2; i++) c[i][0] = c[i][1] = c[i][2] = c[i][3] = 0.f;
    #pragma unroll
    for (int j = 0; j < 4; j++) {
        if (!OWN && j == 3) addr();
        mma16816(c[0], wo[2 * j], b[j][0], b[j][1]); mma16816(c[1], wo[2 * j + 1], b[j][2], b[j][3]);
    }
    if (TP_E || (OWN && V_EARLY)) { asm volatile("" : "+f"(c[0][0]), "+f"(c[1][0])); sched_fence<OWN ? 4 : 5>(nv); }
    issued();
    send_tile<0, 0>((c[0][0] + c[1][0]) * il, (c[0][1] + c[1][1]) * ih, (c[0][2] + c[1][2]) * il, (c[0][3] + c[1][3]) * ih, sa, sb_, l16);
}

template<int N> __device__ __forceinline__ void code_pad(uint32_t nv) {
    if (N && nv == 0x7fffffe0u + N % 16) {
        float v = __uint_as_float(nv);
        #pragma unroll
        for (int i = 0; i < N; i++) asm volatile("fma.rn.f32 %0, %0, %0, %0;" : "+f"(v));
        sts32_p(0u, __float_as_uint(v), nv);
    }
}
#define PAD_T0 4
#define PAD_T1 0
#define PAD_S 346
#define PAD_P 99
#define BAR_PRO 1
#define BAR_MEM 2
#define BAR_P   3
#define BAR_PRJ 4
#define BAR_VGO 7
#define BAR_X0  7
#define BAR_S   9
#define BAR_P2  10
#define BAR_O   11
#define BAR_O2  14
#define BAR_TP  15
#define BAR_V   12
#define BAR_FB  13
#define VGO_AT 9
#define TP_N 36
#define TP_N1 24
#define REG_P 200
#define W_FENCE 1
#define WO_PRE 3
#define WO_MID 8
#define WO_EX 8
#define WO_REP 2
#define TP_DELAY 0
#define PRE_W 4
#ifndef M_RES
#define M_RES 5
#endif
#define K_PRE 8
#define K_POS 0
#define LD_FENCE 0
#define CV_FENCE 4
#define ANN_POS 1
#define PRO_V 0
#define PUB_W 0
#define ST_AT 2
#define MEM_N 352
#define VGO_N (256 + (T_HOLD == 2 ? 32 : 0))
#define PRO_N ((PRO_V ? 256 : 32 * nqk) + (K_PRE < 8 ? 64 : 0) + ((T_HOLD & 1) ? 32 : 0))
#define S_DUTY 0
#define X_POS 0
#define K_OWN 1
#define TG_MERGE 1
#define K_TOP 0
#define MEM_ROT 1
#define TM_PF 1
#define TS_CAP 64
#define G1_MIN 128
#define G1_0 256
#define G1_NS 1120

__global__ void __cluster_dims__(3, 1, 1) __launch_bounds__(CH_THREADS, 1)
chain_kernel(const __grid_constant__ CUtensorMap tmx, const __grid_constant__ CUtensorMap tmq, const __grid_constant__ CUtensorMap tmk,
             const __grid_constant__ CUtensorMap tmv, const __grid_constant__ CUtensorMap tmo,
             const __grid_constant__ CUtensorMap tma, const __grid_constant__ CUtensorMap tmb, const bf16* __restrict__ mem0, const uint32_t nv_) {
    extern __shared__ __align__(1024) unsigned char smem[];
    const uint32_t sb = smem_u32(smem);
    const int tid = threadIdx.x, lane = tid & 31;
    const int warp = __shfl_sync(0xffffffffu, tid >> 5, 0);
    const uint32_t nv = __shfl_sync(0xffffffffu, nv_ * tid, 0);
    const int h = blockIdx.x / 3, r = blockIdx.x % 3;
    const int mi = lane >> 3, r8 = lane & 7;
    const uint32_t bX = sb + SM_BAR, bTOK = bX + 16, bEX = bX + 40, bW = bX + 64, bEV = bX + 104, bFREE = bX + 32, bMEM = bX + 56;
    const int nqk = r < 2 ? 6 : 4;
    if ((sb & 0xFFFFFFu) != SB_OFF) __trap();
    asm volatile("griddepcontrol.launch_dependents;");
    if (tid == 0 && blockIdx.x == 0) GT(40, 0);

    auto load_w = [&](int lo, int hi) {
        #pragma unroll 1
        for (int i = lo; i < hi; i++) {
            const int blk = i >> 2, j = i & 3;
            if (i < 48) {
                const int m = r < 2 ? (j < 3 ? r : 2) : (j < 2 ? j : 2), p = r < 2 ? (j < 3 ? j : r) : (j < 2 ? 3 : j);
                asm volatile("cp.async.bulk.tensor.2d.shared::cluster.global.mbarrier::complete_tx::bytes [%0], [%1, {%3, %4}], [%2];"
                    :: "r"(sb + i * 3072), "l"(m == 0 ? &tmq : (m == 1 ? &tmk : &tmv)), "r"(bW + (blk < 3 ? 0 : (blk < 6 ? 8 : (blk < 10 ? 16 : 24)))), "r"(h * DH + p * 32), "r"(blk * 48) : "memory");
            } else asm volatile("cp.async.bulk.tensor.2d.shared::cluster.global.mbarrier::complete_tx::bytes [%0], [%1, {%3, %4}], [%2];"
                :: "r"(sb + SM_WO + (i - 48) * 8192), "l"(&tmo), "r"(bW + 32), "r"(192 * r + 32 * (i - 48)), "r"(h * DH) : "memory");
        }
    };
    if (tid == 352) {
        #pragma unroll
        for (int i = 0; i < 15; i++) mbar_init(bX + 8 * i, (i == 5 || i == 6) ? 1 + nqk : (i >= 13 ? 9 - nqk : 1));
        asm volatile("fence.mbarrier_init.release.cluster;" ::: "memory");
        mbar_expect_tx(bW, 36864); mbar_expect_tx(bW + 8, 36864); mbar_expect_tx(bW + 16, 49152); mbar_expect_tx(bW + 24, 24576); mbar_expect_tx(bW + 32, 49152);
        load_w(0, 2 * PRE_W);
    }
    if (TM_PF && tid < 4) asm volatile("prefetch.param.tensormap [%0];" :: "l"(__cvta_generic_to_grid_constant(tid == 0 ? &tmo : (tid == 1 ? &tmx : (tid == 2 ? &tma : &tmb)))) : "memory");
    const unsigned epoch = ld_relaxed32(&g_epoch);
    __syncthreads();
    const uint32_t pw0 = ((mi >> 1) * 8 + r8) * 64 + (((2 * (warp & 1) + (mi & 1)) ^ (r8 >> 1)) << 4);
    auto tok_publish = [&](int tb, int k) {
        const uint32_t src = sb + SM_TOK + tb * TOKBUF + r * 8192, bar = bTOK + 8 * tb;
        if (k == 1) asm volatile("{\n.reg .pred p;\nelect.sync _|p, 0xffffffff;\n@p mbarrier.arrive.expect_tx.shared.b64 _, [%0], 16384;\n}\n" :: "r"(bar) : "memory");
        asm volatile("{\n.reg .pred p;\nelect.sync _|p, 0xffffffff;\n"
                     "@p cp.async.bulk.shared::cluster.shared::cta.mbarrier::complete_tx::bytes [%0], [%1], 8192, [%2];\n}\n"
            :: "r"(mapa_u32(src, (r + k) % 3)), "r"(src), "r"(mapa_u32(bar, (r + k) % 3)) : "memory");
    };
    if (warp < 8) {
        asm volatile("setmaxnreg.inc.sync.aligned.u32 %0;" :: "n"(REG_P));
        uint32_t wf[36][4];
        const uint32_t wl = sb + (warp >> 1) * 3072 + pw0;
        float ta0[16], ta1[16];
        auto tp_part = [&](auto lo, auto hi) {
            wg_fence();
            #pragma unroll
            for (int i = lo.value; i < hi.value; i++) {
                if (i == 0) wgmma_n32<0>(ta0, wf[0], desc_from(DESC_LO(SM_X))); else wgmma_n32<1>(ta0, wf[i], desc_from(DESC_LO(SM_X) + (i >> 2) * 256 + (i & 3) * 2));
            }
            #pragma unroll
            for (int i = lo.value; i < hi.value; i++) {
                if (i == 0) wgmma_n32<0>(ta1, wf[0], desc_from(DESC_LO(SM_X + XBUF))); else wgmma_n32<1>(ta1, wf[i], desc_from(DESC_LO(SM_X + XBUF) + (i >> 2) * 256 + (i & 3) * 2));
            }
            wg_commit();
        };
        if (tid == 32) load_w(2 * PRE_W, 40);
        if (tid == 0) GT(41 + blockIdx.x % 3, 7);
        code_pad<PAD_P>(nv);
        mbar_wait(bW, 0);
        #pragma unroll
        for (int i = 0; i < 9; i++) ldsm_x4_t(wf[i], wl + (i / 3) * 12288 + (i % 3) * 1024);
        fence_async_smem(); bar_arrive(BAR_X0, 288);
        mbar_wait(bW + 8, 0);
        #pragma unroll
        for (int i = 9; i < 18; i++) ldsm_x4_t(wf[i], wl + (i / 3) * 12288 + (i % 3) * 1024);
        fence_async_smem(); bar_arrive(BAR_X0 + 1, 288);
        mbar_wait(bX, 0); mbar_wait(bX + 8, 0);
        tp_part(ic<0>(), ic<18>());
        wg_wait0();
        sts128(sb + SM_OST + tid * 16, make_uint4(wf[0][0], wf[0][1], wf[0][2], wf[0][3]));
        mbar_wait(bW + 16, 0);
        #pragma unroll
        for (int i = 18; i < 30; i++) ldsm_x4_t(wf[i], wl + (i / 3) * 12288 + (i % 3) * 1024);
        tp_part(ic<18>(), ic<30>());
        mbar_wait(bW + 24, 0);
        if (tid == 0) GT(41 + blockIdx.x % 3, 0);
        wg_wait0();
        #pragma unroll
        for (int i = 30; i < 36; i++) ldsm_x4_t(wf[i], wl + (i / 3) * 12288 + (i % 3) * 1024);
        fence_async_smem();
        cluster_arrive_rx();
        tp_part(ic<30>(), ic<36>());
        if (tid == 0) GT(41 + blockIdx.x % 3, 2);
        const uint32_t pw = pin(pw0);
        auto tp_store = [&](const float (&acc)[16], uint32_t off) {
            const uint32_t ta = pw + launder(sb + off + (warp >> 1) * 2048);
            stsm_x4_t(ta, pack_bf16(acc[0], acc[1]), pack_bf16(acc[2], acc[3]), pack_bf16(acc[4], acc[5]), pack_bf16(acc[6], acc[7]));
            stsm_x4_t(ta + 1024, pack_bf16(acc[8], acc[9]), pack_bf16(acc[10], acc[11]), pack_bf16(acc[12], acc[13]), pack_bf16(acc[14], acc[15]));
        };
        cluster_wait();
        wg_wait0();
        tp_store(ta0, SM_TOK + r * 8192);
        if (warp == 0) { bar_sync(BAR_PRJ, 256); fence_async_smem(); tok_publish(0, 1); tok_publish(0, 2); } else bar_arrive(BAR_PRJ, 256);
        if (!TAIL) { tp_store(ta1, SM_TOK + TOKBUF + r * 8192); }
        { const uint4 v = lds128(sb + SM_OST + tid * 16); wf[0][0] = v.x; wf[0][1] = v.y; wf[0][2] = v.z; wf[0][3] = v.w; sts32_p(v.x, v.y, nv); }
        if (tid == 0) GT(41 + blockIdx.x % 3, 4);
        const uint32_t l16 = pin(lane * 16), sbl = sb + l16, l4w = pin(sb + warp * 256 + lane * 4);
        uint32_t wo[8][4];
        const int exo = r < 2 ? (warp < 6 ? r * 2048 : 4096 + (2 * r - 6) * 256) : (warp < 2 ? 6 * 256 : (warp < 4 ? 2048 + 4 * 256 : 4096));
        const bool isqk = warp < nqk;
        const uint32_t exbar = isqk ? bEX : bEV;
        uint32_t vf[2][4];
        auto prep = [&](int s) {
            const uint32_t va = pw + launder(sb + SM_TOK + (s & 1) * TOKBUF + BLK_V(warp >> 1));
            mbar_wait(bTOK + 8 * (s & 1), (s >> 1) & 1);
            if (VF_EARLY) { ldsm_x4_t(vf[0], va); ldsm_x4_t(vf[1], va + 1024); sts32_p(vf[0][0], vf[1][0], nv); }
        };
        prep(0);
        if (!TAIL && MEM_ROT) bar_sync(BAR_MEM, MEM_N);
        for (int s = 0; ; s++) {
            const int par = s & 1;
            const uint32_t va = pw + launder(sb + SM_TOK + par * TOKBUF + BLK_V(warp >> 1)), wa = pw + launder(sb + SM_WO + (warp >> 1) * 8192);
            const uint32_t exu = launder(SM_EX + par * EXBUF);
            {
                float acc[4][4];
                #pragma unroll
                for (int i = 0; i < 4; i++) { acc[i][0] = acc[i][1] = acc[i][2] = acc[i][3] = 0.f; }
                uint32_t b[18][4];
                if (MEM_ROT) bar_sync_p(BAR_VGO, VGO_N, isqk);
                else if (!isqk) { bar_arrive(BAR_MEM, MEM_N); bar_sync(BAR_VGO, VGO_N); } else bar_sync(BAR_MEM, MEM_N);
                #pragma unroll
                for (int i2 = 0; i2 < 18; i2++) {
                    if (!TAIL) ldsm_x4_t(b[i2], sbl + SM_MEM + i2 * 512);
                    else if (i2 >= 1 && i2 - 1 + MP_PRE < 18) ldsm_x4_t(b[i2 - 1 + MP_PRE], sbl + SM_MEM + (i2 - 1 + MP_PRE) * 512);
                    if (i2 == (TAIL ? VGO_AT - MP_PRE + 1 : VGO_AT)) bar_arrive_p(BAR_VGO, VGO_N, !isqk);
                    if (PRO_V && i2 == PRO_V) bar_arrive_p(BAR_PRO, PRO_N, isqk || s == NSEG - 1);
                    mma16816(acc[(2 * i2) & 3], wf[2 * i2], b[i2][0], b[i2][1]);
                    mma16816(acc[(2 * i2 + 1) & 3], wf[2 * i2 + 1], b[i2][2], b[i2][3]);
                }
                float q[4];
                #pragma unroll
                for (int i = 0; i < 4; i++) q[i] = (acc[0][i] + acc[1][i]) + (acc[2][i] + acc[3][i]);
                const uint32_t lo = pack_bf16(q[0], q[1]), hi = pack_bf16(q[2], q[3]);
                const uint32_t exl = l4w + launder(exu + exo), bar = exbar + par * 8;
                #pragma unroll
                for (int k = 1; k < 3; k++) {
                    const uint32_t exd = mapa_u32(exl, (r + k) % 3), exb = mapa_u32(bar, (r + k) % 3);
                    st_async32(exd, lo, exb); st_async32(exd + 128, hi, exb);
                }
                sts32(exl, lo); sts32(exl + 128, hi);
                __syncwarp();
                asm volatile("{\n.reg .pred p;\nelect.sync _|p, 0xffffffff;\n@p mbarrier.arrive.shared.b64 _, [%0];\n}\n" :: "r"(bar) : "memory");
                if (s < NSEG - 1) bar_sync_p(BAR_PRO, PRO_N, !isqk);
            }
            if (s == 0) mbar_wait(bW + 32, 0);
            if (s == NSEG - 1) break;
            {
                if (!VF_EARLY) { ldsm_x4_t(vf[0], va); ldsm_x4_t(vf[1], va + 1024); }
                #pragma unroll
                for (int i = 0; i < WO_PRE; i++) ldsm_x4_t(wo[i], wa + i * 1024);
                if (WO_PRE < 8) {
                    #pragma unroll
                    for (int k = 0; k < WO_REP; k++) mbar_wait(bEX + 8 * par, (s >> 1) & 1);
                    #pragma unroll
                    for (int i = WO_PRE; i < 8; i++) ldsm_x4_t(wo[i], wa + i * 1024);
                }
                mbar_wait(bEV + 8 * par, (s >> 1) & 1);
                const uint32_t vm0 = lds32(l4w + exu + 4096), vm1 = lds32(l4w + exu + 4096 + 128);
                const uint32_t big = bar_red_or(BAR_P, 352, 0u);
                uint32_t pb[4]; ldsm_x4_t(pb, sbl + SM_P);
                uint32_t pm = ldsm_x1_t(sbl + SM_P + 512);
                float o0[4] = {0.f, 0.f, 0.f, 0.f}, o1[4] = {0.f, 0.f, 0.f, 0.f}, o2[4] = {0.f, 0.f, 0.f, 0.f};
                if (__builtin_expect(big, 0)) {
                    bar_sync(BAR_P2, 352);
                    ldsm_x4_t(pb, sbl + SM_P); pm = ldsm_x1_t(sbl + SM_P + 512);
                }
                mma16816(o0, vf[0], pb[0], pb[1]);
                mma16816(o1, vf[1], pb[2], pb[3]);
                mma1688(o2, vm0, vm1, pm);
                uint32_t oa = pm;
                #pragma unroll
                for (int i = 0; i < 8; i++) oa ^= wo[i][0];
                oa = l4w | (oa & nv);
                sts32(oa + SM_O, pack_bf16((o0[0] + o1[0]) + o2[0], (o0[1] + o1[1]) + o2[1]));
                sts32(oa + SM_O + 128, pack_bf16((o0[2] + o1[2]) + o2[2], (o0[3] + o1[3]) + o2[3]));
                const uint32_t xd = uni(DESC_LO(SM_X) + par * (XBUF >> 4));
                auto tp = [&](auto lo, auto hi) {
                    #pragma unroll
                    for (int i = lo.value; i < hi.value; i++) {
                        if (i == 0) wgmma_n32<0>(ta1, wf[0], desc_from(xd));
                        else wgmma_n32<1>(ta1, wf[i], desc_from(xd + (i >> 2) * 256 + (i & 3) * 2));
                    }
                };
                bar_sync(BAR_O, 352);
                stage_w<false>(wo, sbl + SM_O, 12 * r + warp, SLOT_OFF(s + 1), l16, nv, sbl + SM_IL, [&] {
                    if (TP_E) { bar_sync(BAR_V, 384); wg_fence(); tp(ic<0>(), ic<TP_E>()); } });
                STAMP(warp);
                if (!TP_E) { bar_sync(BAR_V, 384); wg_fence(); }
                STAMP(12);
                tp(ic<TP_E>(), ic<TP_N>());
                wg_commit();
                prep(s + 1);
                if (!TAIL) { wg_wait0(); tp_store(ta1, SM_TOK + par * TOKBUF + r * 8192); STAMP(13 + (warp >> 2)); if (MEM_ROT) bar_sync(BAR_MEM, MEM_N); }
            }
        }
        cluster_arrive(); cluster_wait();
    } else {
        asm volatile("setmaxnreg.dec.sync.aligned.u32 %0;" :: "n"(504 - 2 * REG_P));
        const int a = warp - 8;
        const uint32_t sbl = sb + lane * 16;
        if (a < 3) {
            const uint32_t zs = 3 * blockIdx.x + (r8 >> 1);
            const uint32_t zoff = (r8 < 6 ? (zs >> 3) * 1024 + ((zs >> 2) & 1) * 256 + (zs & 3) * 32 : ACC_X + (blockIdx.x >> 1) * 1024 + (blockIdx.x & 1) * 256) + (lane & 1) * 16;
            const uint32_t zskip = r8 >= 6 && blockIdx.x >= 36;
            if (a == 1) {
                st_relaxed128_p((uint4*)(g_acc + zoff + SLOT_OFF(mi)), make_uint4(0, 0, 0, 0), zskip);
                __threadfence();
                __syncwarp();
                if (lane == 0) st_relaxed32(&g_init[blockIdx.x], epoch);
            }
            {
                #pragma unroll
                for (int i = 0; i < 6; i++) {
                    const int c = tid - 256 + 96 * i;
                    const unsigned short* m = (const unsigned short*)mem0 + c;
                    uint4 v;
                    v.x = m[0] | ((uint32_t)m[DM] << 16); v.y = m[2 * DM] | ((uint32_t)m[3 * DM] << 16);
                    v.z = m[4 * DM] | ((uint32_t)m[5 * DM] << 16); v.w = m[6 * DM] | ((uint32_t)m[7 * DM] << 16);
                    sts128(sb + SM_MEM + c * 16, v);
                }
                sts32(sb + SM_SG + 36, 0u);
            }
            asm volatile("barrier.cluster.arrive.release.aligned;" ::: "memory");
            { int it = 0; while (__any_sync(0xffffffffu, ld_relaxed32(&g_init[a * 32 + lane]) != epoch) && ++it < SPIN_LIMIT) {} }
            __threadfence();
            const uint32_t kl0 = (a < 2 ? SM_TOK + (16 * a + (mi & 1) * 8 + r8) * 64 + (((mi >> 1) ^ (r8 >> 1)) << 4) : SM_EX + 2048 + ((((mi & 1) << 1) | (mi >> 1)) * 8 + r8) * 16);
            const uint32_t l16 = pin(lane * 16);
            uint32_t kf[8][4], wo[8][4];
            auto load_k = [&](int tb, uint32_t kl, auto lo, auto hi) {
                const uint32_t ka = kl + launder(sb + tb * TOKBUF);
                #pragma unroll
                for (int kk = lo.value; kk < hi.value; kk++) ldsm_x4(kf[kk], (ka ^ ((kk & 1) << 5)) + BLK_K(kk >> 1));
            };
            code_pad<PAD_S>(nv);
            cluster_wait();
            if (a == 0 && lane == 0) { mbar_expect_tx(bEX, 4096 - 256 * nqk); mbar_expect_tx(bEV, 256 * nqk); }
            if (a < 2) bar_arrive(BAR_MEM, MEM_N); else bar_sync(BAR_MEM, MEM_N);
            mbar_wait(bW + 32, 0);
            #pragma unroll
            for (int i = 0; i < 8; i++) ldsm_x4_t(wo[i], pw0 + sb + SM_WO + (warp >> 1) * 8192 + i * 1024);
            sts128(sbl + SM_STASH + a * 1024 + 512, make_uint4(kl0, (pw0 ^ 32) + sb + SM_WO + 5 * 8192, zoff | ((zskip || lane >= 8) << 31), 0u));
            sts128(sbl + SM_STASH + a * 1024, make_uint4(a * 12288 + (lane >> 4) * 1024 + (mi & 1) * 256 + r8 * 16, ACC_X + a * 6144 + (lane >> 4) * 1024 + (mi & 1) * 256 + r8 * 4,
                                                         ((lane ^ mi) & 1) ? 0u : ~0u, sb + SM_MEM + a * 3072 + mi * 256 + r8 * 16 + (r8 & 1 ? 2 : 130)));
            const uint32_t stash = l16 + uni(sb + SM_STASH + a * 1024);
            #pragma unroll
            for (int i = 0; i < 8; i++) ldsm_x4_t(kf[i], (pw0 ^ 32) + sb + SM_WO + 5 * 8192 + i * 1024);
            if (a < 2) { mbar_wait(bTOK, 0); load_k(0, kl0, ic<0>(), ic<K_PRE>()); }
            __syncwarp();
            int sn = 0;
            #pragma unroll 1
            while (sn < NSEG - 1) {
              uint32_t bad;
              #pragma unroll 1
              do {
                const int s = sn, par = s & 1;
                const uint32_t exu = launder(sb + par * EXBUF);
                const uint32_t exl = l16 + exu + SM_EX;
                const uint32_t t0 = gtime_lo();
                STAMP(15); STAMPV(31, t0);
                if (!TAIL && a == 2) st_relaxed32_p(&g_ts[blockIdx.x], (t0 & ~31u) | (s & 31), l16);
                if (a == 1) {
                    const uint32_t z = lds32(stash + 520);
                    st_relaxed128_p((uint4*)(g_acc + (z + SLOT_OFF(s + 3))), make_uint4(0, 0, 0, 0), z >> 31);
                }
                if (a == 0 && l16 == 0) { mbar_expect_tx(bEX + 8 * (par ^ 1), 4096 - 256 * nqk); mbar_expect_tx(bEV + 8 * (par ^ 1), 256 * nqk); }
                uint32_t tg;
                auto first_half = [&](auto role) {
                constexpr bool M = role.value;
                auto publish = [&] {
                    asm volatile("{\n.reg .pred p;\nelect.sync _|p, 0xffffffff;\n"
                                 "@p cp.async.bulk.shared::cluster.global.mbarrier::complete_tx::bytes.multicast::cluster [%0], [%1], 8192, [%2], %3;\n}\n"
                        :: "r"(sb + SM_TOK + (par ^ 1) * TOKBUF + r * 8192), "l"(g_tokx[blockIdx.x]), "r"(bTOK + 8 * (par ^ 1)), "h"((unsigned short)(7 ^ (1 << r))) : "memory");
                };
                uint32_t sl, sh, kl = 0, w2 = 0;
                if (M) {
                    if (TAIL) { bar_sync(BAR_TP, 288); __syncwarp(); st_relaxed32_p(&g_ts[blockIdx.x], (gtime_after(lds32(stash + 524)) & ~31u) | (s & 31), l16); }
                    fence_async_smem();
                    if (l16 == 0) {
                        asm volatile("cp.async.bulk.global.shared::cta.bulk_group [%0], [%1], 8192;\ncp.async.bulk.commit_group;"
                            :: "l"(g_tokx[blockIdx.x]), "r"(sb + SM_TOK + (par ^ 1) * TOKBUF + r * 8192) : "memory");
                        mbar_expect_tx(bTOK + 8 * (par ^ 1), 16384); mbar_expect_tx(bMEM, 10368);
                        if (s == 0) mbar_expect_tx(bX, XBUF);
                        if (s + 3 < NSEG) mbar_expect_tx(bX + 8 * (par ^ 1), XBUF);
                    }
                    __syncwarp();
                    if (s > 0 && s + 2 < NSEG) mbar_wait(bX + 8 * par, ((s >> 1) & 1) ^ 1);
                    if (PUB_W == 0) asm volatile("cp.async.bulk.wait_group 0;" ::: "memory");
                    kl = lds32(stash + 512);
                }
                if (!M && K_PRE < 8) {
                    const uint32_t kl = lds32(stash + 512);
                    if (K_OWN == 3) mbar_wait(bTOK + 8 * par, (s >> 1) & 1);
                    if (K_TOP) load_k(par, kl, ic<K_PRE>(), ic<K_PRE + K_TOP>());
                    bar_sync(BAR_PRO, PRO_N);
                    load_k(par, kl, ic<K_PRE + K_TOP>(), ic<8>());
                }
                uint32_t pst = (launder(l16) >> 2) + launder(sb + SM_P + a * 256);
                if (!M) {
                    uint32_t x = kf[0][0];
                    #pragma unroll
                    for (int i = 1; i < 8; i++) x ^= kf[i][0];
                    sts32_p(pst, x, nv);
                }
                mbar_wait(bEX + 8 * par, (s >> 1) & 1);
                if (!M) {
                    uint32_t b[4][4];
                    ldsm16_t(b, exl);
                    float c[4][4];
                    #pragma unroll
                    for (int j = 0; j < 4; j++) { c[j][0] = c[j][1] = c[j][2] = c[j][3] = 0.f; }
                    #pragma unroll
                    for (int j = 0; j < 4; j++) { mma16816(c[(2 * j) & 3], kf[2 * j], b[j][0], b[j][1]); mma16816(c[(2 * j + 1) & 3], kf[2 * j + 1], b[j][2], b[j][3]); }
                    sl = scale_bf2(pack_bf16((c[0][0] + c[1][0]) + (c[2][0] + c[3][0]), (c[0][1] + c[1][1]) + (c[2][1] + c[3][1])));
                    sh = scale_bf2(pack_bf16((c[0][2] + c[1][2]) + (c[2][2] + c[3][2]), (c[0][3] + c[1][3]) + (c[2][3] + c[3][3])));
                } else {
                    float c[4][4];
                    #pragma unroll
                    for (int j = 0; j < 4; j++) { c[j][0] = c[j][1] = c[j][2] = c[j][3] = 0.f; }
                    uint32_t k[4][4], b[4][4];
                    #pragma unroll
                    for (int j = 0; j < 4; j++) { ldsm_x4_t(k[j], kl + exu + 512 * j); ldsm_x4_t(b[j], exl + 512 * j); }
                    if (M_SF) sched_fence<9>(nv);
                    #pragma unroll
                    for (int j = 0; j < 4; j++) { mma16816(c[2 * (j & 1)], k[j], b[j][0], b[j][1]); mma16816(c[2 * (j & 1) + 1], k[j], b[j][2], b[j][3]); }
                    if (PUB_W == 0) publish();
                    sh = sl = scale_bf2(pack_bf16((c[0][0] + c[1][2]) + (c[2][0] + c[3][2]), (c[0][1] + c[1][3]) + (c[2][1] + c[3][3])));
                }
                sts32(pst, pack_bf16(ex2(bf_lo(sl) * LOG2E), ex2(bf_hi(sl) * LOG2E)));
                if (!M) sts32(pst + 128, pack_bf16(ex2(bf_lo(sh) * LOG2E), ex2(bf_hi(sh) * LOG2E)));
                if (S_DUTY && !M) {
                    if (a == 0)
                        asm volatile("{\n.reg .pred p;\nelect.sync _|p, 0xffffffff;\n"
                                     "@p cp.async.bulk.shared::cluster.global.mbarrier::complete_tx::bytes [%0], [%1], 384, [%2];\n"
                                     "@p mbarrier.arrive.expect_tx.shared.b64 _, [%2], 384;\n}\n"
                            :: "r"(sb + SM_TS), "l"(g_ts), "r"(bFREE) : "memory");
                    else if (s > 0 && s + 3 < NSEG)
                        asm volatile("{\n.reg .pred p;\nelect.sync _|p, 0xffffffff;\n"
                                     "@p cp.async.bulk.tensor.3d.shared::cluster.global.mbarrier::complete_tx::bytes.multicast::cluster [%0], [%1, {%3, %4, %5}], [%2], %6;\n}\n"
                            :: "r"(sb + SM_X + (par ^ 1) * XBUF + r * 12288), "l"(&tmx), "r"(bX + 8 * (par ^ 1)), "r"(0), "r"((s + 3) * SEG), "r"(3 * r), "h"((unsigned short)7) : "memory");
                }
                const uint32_t big = bar_red_or(BAR_P, 352, ((maxabs_bf2(sl, sh) & 0x7fff7fffu) + 0x3ddf3ddfu) & 0x80008000u);
                auto denom = [&] {
                    uint32_t pb[4]; ldsm_x4_t(pb, l16 + sb + SM_P);
                    const uint32_t pm = ldsm_x1_t(l16 + sb + SM_P + 512), ONE = 0x3F803F80u;
                    float l0[4] = {0.f, 0.f, 0.f, 0.f}, l1[4] = {0.f, 0.f, 0.f, 0.f}, l2[4] = {0.f, 0.f, 0.f, 0.f};
                    mma16816r(l0, ONE, ONE, ONE, ONE, pb[0], pb[1]);
                    mma16816r(l1, ONE, ONE, ONE, ONE, pb[2], pb[3]);
                    mma1688(l2, ONE, ONE, pm);
                    const float dl = (l0[0] + l1[0]) + l2[0], dh = (l0[1] + l1[1]) + l2[1];
                    sts32(pst + (SM_IL - SM_P) - a * 128, __float_as_uint(rcp_approx(a ? dh : dl)));
                };
                if (!M) { denom(); bar_sync_p(BAR_O, 352, big); }
                if (__builtin_expect(big, 0)) {
                    uint32_t m2 = max_bf2(sl, sh);
                    m2 = max_bf2(m2, __shfl_xor_sync(0xffffffffu, m2, 4));
                    m2 = max_bf2(m2, __shfl_xor_sync(0xffffffffu, m2, 8));
                    m2 = max_bf2(m2, __shfl_xor_sync(0xffffffffu, m2, 16));
                    const uint32_t lq = l16 | (m2 & nv);
                    if (lq < 64) sts32(lq + sb + SM_P + 768 + a * 4, m2);
                    bar_sync(BAR_S, 96);
                    const uint4 m = lds128(sb + SM_P + 768 + (lq & 0x30));
                    m2 = max_bf2(max_bf2(m.x, m.y), m.z);
                    const float ml = bf_lo(m2), mh = bf_hi(m2);
                    sts32(pst, pack_bf16(exd(bf_lo(sl), ml), exd(bf_hi(sl), mh)));
                    if (!M) sts32(pst + 128, pack_bf16(exd(bf_lo(sh), ml), exd(bf_hi(sh), mh)));
                    bar_sync(BAR_P2, 352);
                    if (!M) { denom(); bar_sync(BAR_O, 352); }
                }
                const uint32_t ll = launder(l16), so = SLOT_OFF(launder(s) + 1);
                if (!M) {
                    stage_w<true>(wo, l16 + sb + SM_O, 12 * r + warp, so, ll, nv, l16 + sb + SM_IL, [&] { if (TP_E || V_EARLY) bar_arrive(BAR_V, 384); });
                } else {
                    w2 = lds32(stash + 516);
                    #pragma unroll
                    for (int i = M_RES; i < 8; i++) ldsm_x4_t(kf[i], w2 + i * 1024);
                    if (PUB_W == 1) { asm volatile("cp.async.bulk.wait_group 0;" ::: "memory"); publish(); }
                    const uint32_t sa = launder(SEND_LANE(ll) + (send_ua(12 * r + 10) + so)), sb_ = launder(X_LANE(ll) + (send_ub(12 * r + 10) + so));
                    bar_sync_p(BAR_O, 352, (kf[5][0] ^ kf[6][0] ^ kf[7][0] ^ sa ^ sb_) & nv);
                    float c[4][4], il, ih;
                    #pragma unroll
                    for (int i = 0; i < 4; i++) c[i][0] = c[i][1] = c[i][2] = c[i][3] = 0.f;
                    uint32_t b[4][4];
                    #pragma unroll
                    for (int j = 0; j < 4; j++) ldsm_x4_t(b[j], l16 + sb + SM_O + 512 * (3 - j));
                    lds_il(il, ih, l16 + sb + SM_IL);
                    sched_fence<11>(nv);
                                    #pragma unroll
                    for (int j = 0; j < 4; j++) {
                        if (j == 2) { if (M_F2) sched_fence<10>(nv); }
                        mma16816(c[0], wo[6 - 2 * j], b[j][0], b[j][1]); mma16816(c[2], kf[6 - 2 * j], b[j][0], b[j][1]);
                        mma16816(c[1], wo[7 - 2 * j], b[j][2], b[j][3]); mma16816(c[3], kf[7 - 2 * j], b[j][2], b[j][3]);
                    }
                    asm volatile("" : "+f"(c[0][0]), "+f"(c[1][0]), "+f"(c[2][0]), "+f"(c[3][0]));
                    if (TP_E || V_EARLY) { if (M_FENCE == 1) sched_fence<8>(nv); else asm volatile("" : "+f"(il) : "f"(c[0][0] + c[1][0]), "f"(c[2][0] + c[3][0])); if (M_FENCE < 2) bar_arrive(BAR_V, 384); }
                    send_tile<0, 0>((c[0][0] + c[1][0]) * il, (c[0][1] + c[1][1]) * ih, (c[0][2] + c[1][2]) * il, (c[0][3] + c[1][3]) * ih, sa, sb_, ll);
                    if (M_FENCE == 2) bar_arrive(BAR_V, 384);
                    send_tile<1024, 256>((c[2][0] + c[3][0]) * il, (c[2][1] + c[3][1]) * ih, (c[2][2] + c[3][2]) * il, (c[2][3] + c[3][3]) * ih, sa, sb_, ll);
                    if (M_FENCE == 3) bar_arrive(BAR_V, 384);
                }
                };
                if (a < 2) first_half(ic<0>()); else first_half(ic<1>());
                STAMP(warp);
                if (!TP_E && !V_EARLY) bar_arrive(BAR_V, 384);
                {
                    const uint32_t cd = lds32(stash + 12), xa = (launder(l16) >> 2) + launder(sb + SM_XT + a * 384);
                    if (a < 2) { const uint32_t kl = lds32(stash + 512); mbar_wait(bTOK + 8 * (par ^ 1), ((s + 1) >> 1) & 1); load_k(par ^ 1, kl, ic<0>(), ic<K_PRE>()); }
                    else {
                        STAMP(16 + a);
                        asm volatile("{\n.reg .pred p, q;\n.reg .b64 w;\n.reg .b32 t, u, d, n;\nmov.b32 n, 100000;\n"
                                     "WT_%=:\nld.volatile.shared.u32 %0, [%1];\nmov.u64 w, %%globaltimer;\nmov.b64 {t, u}, w;\nsub.s32 n, n, 1;\nsetp.gt.s32 q, n, 0;\nor.b32 t, t, 1;\nxor.b32 t, t, %2;\n"
                                     "sub.s32 d, t, %0;\nand.b32 d, d, 0x80000001;\nsetp.ne.and.u32 p, d, 0, q;\n@p bra.uni WT_%=;\n}\n" : "=r"(tg) : "r"(sb + SM_SG + 36 + (l16 >> 16)), "r"(par + (l16 >> 16)) : "memory");
                        asm volatile("{\n.reg .pred p;\nelect.sync _|p, 0xffffffff;\n"
                                     "@p cp.async.bulk.tensor.3d.shared::cluster.global.mbarrier::complete_tx::bytes.multicast::cluster [%0], [%1, {%3, %4, %5}], [%2], %9;\n"
                                     "@p cp.async.bulk.tensor.3d.shared::cluster.global.mbarrier::complete_tx::bytes.multicast::cluster [%6], [%7, {%3, %4, %8}], [%2], %9;\n}\n"
                            :: "r"(sb + SM_MEM + r * 3072), "l"(&tma), "r"(bMEM), "r"((par ^ 1) * 32), "r"((s + 1) & 2), "r"(12 * r), "r"(sb + SM_XT + r * 384), "l"(&tmb), "r"(ACC_X / 1024 + 6 * r), "h"((unsigned short)7) : "memory");
                        STAMPV(30, tg);
                    }
                    STAMP(19 + a);
                    mbar_wait(bMEM, par);
                    uint32_t x[3], k[3];
                    #pragma unroll
                    for (int j = 0; j < 3; j++) { x[j] = lds32(xa + 128 * j); k[j] = lds32(cd - 2 + 1024 * j); }
                    #pragma unroll
                    for (int j = 0; j < 3; j++) sts16(cd + 1024 * j, (uint16_t)x[j]);
                    bad = __any_sync(0xffffffffu, !((x[0] & x[1] & x[2]) & (k[0] & k[1] & k[2]) & (ACC_FULL << 16)));
                    STAMP(22 + a); STAMPV(27 + a, bad);
                    bar_sync_p(BAR_MEM, MEM_N, bad);
                }
              } while (++sn < NSEG - 1 && !bad);
                {
                    if (bad) {
                        uint32_t c = nv, cx;
                        const uint32_t lq = l16 | (lds32(stash + 524) & nv), so = SLOT_OFF(sn);
                        const uint4 ad = lds128(stash);
                        const unsigned char* pm = launder_p(g_acc + (ad.x + so));
                        const unsigned char* px = launder_p(g_acc + (ad.y + so));
                        int it = 0;
                        do {
                            const uint32_t again = ~(c & __shfl_xor_sync(0xffffffffu, c, 1)) & (ACC_FULL << 16);
                            uint4 u[6]; uint32_t x[3];
                            #pragma unroll
                            for (int j = 0; j < 6; j++) { u[j] = make_uint4(~0u, ~0u, ~0u, ~0u); ld_relaxed128_p(u[j], (const uint4*)(pm + 2048 * j), again); }
                            #pragma unroll
                            for (int j = 0; j < 3; j++) x[j] = ld_relaxed32((const uint32_t*)(px + 2048 * j));
                            c = ~0u;
                            #pragma unroll
                            for (int j = 0; j < 6; j++) {
                                if (again) sts128(lq + sb + SM_MEM + a * 3072 + 512 * j, u[j]);
                                c &= u[j].x;
                            }
                            __syncwarp();
                            #pragma unroll
                            for (int j = 0; j < 3; j++) sts16(ad.w + 1024 * j, (uint16_t)x[j]);
                            c |= ad.z;
                            cx = x[0] & x[1] & x[2];
                        } while (__any_sync(0xffffffffu, !(c & cx & (ACC_FULL << 16))) && ++it < SPIN_LIMIT);
                        bar_sync(BAR_MEM, MEM_N);
                    }
                }
            }
            if (TAIL && a == 2) bar_arrive(BAR_TP, 288);
        } else {
            cluster_arrive_rx();
            const uint32_t l16 = pin(lane * 16);
            bf16* dst = g_otok + h * 4096 + (r ? 1024 : 0) + (r == 2 ? 2048 : 0);
            {
                #pragma unroll
                for (int sg = 0; sg < 2; sg++) {
                    bar_sync(BAR_X0 + sg, 288);
                    if (lane == 0) {
                        mbar_expect_tx(bX + 8 * sg, XBUF);
                        #pragma unroll
                        for (int c = 0; c < 3; c++)
                            asm volatile("cp.async.bulk.tensor.3d.shared::cluster.global.mbarrier::complete_tx::bytes [%0], [%1, {%3, %4, %5}], [%2];"
                                :: "r"(sb + SM_X + sg * XBUF + c * 12288), "l"(&tmx), "r"(bX + 8 * sg), "r"(0), "r"(sg * SEG), "r"(3 * c) : "memory");
                    }
                    __syncwarp();
                }
                if (lane == 0) load_w(40, 54);
                __syncwarp();
                cluster_wait();
            }
            __syncwarp();
            auto t_loop = [&](auto mtile) {
            constexpr int MT = mtile.value;
            uint32_t q[8][4], sp[5][2], pa[5][2], bv[8][4], rng;
            code_pad<MT ? PAD_T1 : PAD_T0>(nv);
            auto issue_x = [&](int sg) {
                asm volatile("{\n.reg .pred p, q;\nelect.sync _|p, 0xffffffff;\nsetp.eq.and.u32 q, %5, 3, p;\n"
                             "@p cp.async.bulk.tensor.3d.shared::cluster.global.mbarrier::complete_tx::bytes.multicast::cluster [%0], [%1, {%3, %4, %5}], [%2], %6;\n"
                             "@q cp.async.bulk.tensor.3d.shared::cluster.global.mbarrier::complete_tx::bytes.multicast::cluster [%7], [%1, {%3, %4, %3}], [%2], %6;\n}\n"
                    :: "r"(sb + SM_X + (sg & 1) * XBUF + r * 12288), "l"(&tmx), "r"(bX + 8 * (sg & 1)), "r"(0), "r"(sg * SEG), "r"(3 * r), "h"((unsigned short)7), "r"(sb + SM_X + (sg & 1) * XBUF) : "memory");
            };
            mbar_wait(bTOK, 0);
            if (MT) { issue_x(2); issue_x(3); }
            #pragma unroll 1
            for (int s = 0; s < NSEG; s++) {
                const int par = s & 1;
                if (K_OWN) mbar_wait(bTOK + 8 * par, (s >> 1) & 1);
                const uint32_t tok = launder(sb + SM_TOK + par * TOKBUF), exl = l16 + launder(sb + SM_EX + par * EXBUF);
                const int ln = launder(l16) >> 4;
                auto announce = [&] {
                    if (s > 0) {
                        if (lane == 0) {
                            asm volatile("cp.async.bulk.wait_group 0;" ::: "memory");
                            st_relaxed32(&g_prog[blockIdx.x], epoch << 8 | s);
                        }
                        __syncwarp();
                        if (lane == 0 && blockIdx.x == 0) GT(40, s);
                    }
                };
                if (ANN_POS == 0) announce();
                tok_part1<MT>(tok, MT ? r - 1 : 0, ln, q, sp, pa, bv, rng, [&] {
                    if (ANN_POS == 3) announce();
                    if (T_HOLD == 4) sched_fence<6 + MT>(nv);
                    else if (T_HOLD) { if (s < NSEG - 1) bar_sync((T_HOLD & 1) ? BAR_PRO : BAR_VGO, (T_HOLD & 1) ? PRO_N : VGO_N); else if (T_HOLD == 2) bar_arrive(BAR_VGO, VGO_N); sched_fence<6 + MT>(nv); } });
                if (ANN_POS == 1) announce();
                STAMP(25);
                mbar_wait(bEX + 8 * par, (s >> 1) & 1);
                STAMP(26);
                auto duty = [&] { if (!S_DUTY && s + 1 < NSEG) {
                    asm volatile("{\n.reg .pred p;\nelect.sync _|p, 0xffffffff;\n"
                                 "@p cp.async.bulk.shared::cluster.global.mbarrier::complete_tx::bytes [%0], [%1], 384, [%2];\n"
                                 "@p mbarrier.arrive.expect_tx.shared.b64 _, [%2], 384;\n}\n"
                        :: "r"(sb + SM_TS), "l"(g_ts), "r"(bFREE) : "memory");
                    if (X_POS == 0 && MT && s > 0 && s + 3 < NSEG) issue_x(s + 3);
                } };
                auto pace = [&] { if (s + 1 < NSEG) {
                    if (X_POS == 2 && MT && s > 0 && s + 3 < NSEG) issue_x(s + 3);
                    const uint32_t lo = min(launder(l16), 368u), b = (gtime_lo() & ~31u) - 0x01000000u + s + (lo >> 16);
                    const uint32_t c = (b & ~31u) + (G1_NS + (s == 0 ? G1_0 : 0)) + (par ^ 1);
                    if (K_OWN) mbar_wait(bFREE, par); else mbar_wait2(bFREE, par, bTOK + 8 * (par ^ 1), ((s + 1) >> 1) & 1);
                    uint4 ts = lds128(sb + SM_TS + lo);
                    int it = 0; uint32_t m;
                    while (true) {
                        m = __reduce_max_sync(0xffffffffu, max(max(__funnelshift_r(ts.x - b, ts.x - b, 5), __funnelshift_r(ts.y - b, ts.y - b, 5)), max(__funnelshift_r(ts.z - b, ts.z - b, 5), __funnelshift_r(ts.w - b, ts.w - b, 5))));
                        if (__builtin_expect(m < 0x00100000u, 1) || ++it >= 64) break;
                        ts = ld_relaxed128((const uint4*)((const char*)g_ts + lo));
                    }
                    asm volatile("st.volatile.shared.u32 [%0], %1;" :: "r"(sb + SM_SG + 36), "r"(c + (min(m, 0x00080000u) << 5)) : "memory");
                } };
                auto wait_v = [&] {
                    if (X_POS == 1 && MT && s > 0 && s + 3 < NSEG) issue_x(s + 3);
                    mbar_wait(bEV + 8 * par, (s >> 1) & 1); };
                auto wait_x = [&] { if (__builtin_expect(s == 0, 0)) mbar_wait(bX, 1); };
                tok_part2<MT>(tok, exl, sb + SM_OST, MT ? r - 1 : 0, launder(l16) >> 4, q, sp, pa, bv, rng, s < NSEG - 1, wait_v, duty, pace, wait_x);
                STAMP(11);
                fence_async_smem();
                __syncwarp();
                if (lane == 0) {
                    asm volatile("cp.async.bulk.global.shared::cta.bulk_group [%0], [%1], 2048;" :: "l"(dst), "r"(sb + SM_OST) : "memory");
                    if (!MT) asm volatile("cp.async.bulk.global.shared::cta.bulk_group [%0], [%1], 2048;" :: "l"(dst + 2048), "r"(sb + SM_OST + 2048) : "memory");
                    asm volatile("cp.async.bulk.commit_group;" ::: "memory");
                    if (__builtin_expect(s >= NSEG - 2, 0)) {
                        asm volatile("cp.async.bulk.wait_group 0;" ::: "memory");
                        st_relaxed32(&g_prog[blockIdx.x], epoch << 8 | (s + 1));
                        if (blockIdx.x == 0 && s == NSEG - 1) GT(40, NSEG);
                    }
                }
                __syncwarp();
                dst += SEG * NH * DH;
            }
            };
            if (r == 0) t_loop(ic<0>()); else t_loop(ic<1>());
        }
        cluster_arrive(); cluster_wait();
    }
}
#define SD_THREADS 384
#define SD_CTAS  36
#define BT_RS    4624
#define SD_BT    0
#define SD_STG   74752
#define SD_EF    (SD_STG + 57344)
#define SD_BC    (SD_STG)
#define KSLOTS   5
#define BC_BYTES 10240
#define BC_LBO   1280
#define SD_KP    (SD_STG + 90112)
#define SD_Q0    205824
#define SD_Q1    (SD_STG + 111616)
#define SD_OST   222720
#define SD_XCH   (SD_Q0 + 8192)
#define SD_BAR   224256
#define SD_TOTAL 224768
#define SD_SPIN  (1 << 22)
#define PART_SLOTS 8
#define SD_GO 0
#define SD_REG 200
#define SD_WAIT 6000
#define SD_P2 150
#define SD_P3 200
#define SD_GAP 0
#define SD_RUSH 44
#define SD_P1 300

__device__ uint4 g_part[SD_CTAS][PART_SLOTS][4][8][32];
__device__ __align__(16) unsigned int g_gate[S_LEN];

struct cplx { float r, i; };
__device__ __forceinline__ cplx cmul(cplx a, cplx b) { cplx c; c.r = fmaf(a.r, b.r, -a.i * b.i); c.i = fmaf(a.r, b.i, a.i * b.r); return c; }
__device__ __forceinline__ cplx cexp_(float xr, float xi) {
    const float m = ex2(xr * 1.4426950408889634f);
    const float k = rintf(xi * 0.15915494309189535f);
    const float r = fmaf(k, 1.7484555314695172e-7f, fmaf(k, -6.2831854820251465f, xi));
    cplx o; o.r = m * __cosf(r); o.i = m * __sinf(r); return o;
}
__device__ __forceinline__ void mma_f16(float (&c)[4], const uint32_t (&a)[4], uint32_t b0, uint32_t b1) {
    asm("mma.sync.aligned.m16n8k16.row.col.f32.f16.f16.f32 {%0,%1,%2,%3}, {%4,%5,%6,%7}, {%8,%9}, {%0,%1,%2,%3};"
        : "+f"(c[0]), "+f"(c[1]), "+f"(c[2]), "+f"(c[3]) : "r"(a[0]), "r"(a[1]), "r"(a[2]), "r"(a[3]), "r"(b0), "r"(b1));
}
__device__ __forceinline__ uint32_t mul_bf2(uint32_t a, uint32_t b) { uint32_t r; asm("mul.rn.bf16x2 %0, %1, %2;" : "=r"(r) : "r"(a), "r"(b)); return r; }
__device__ __forceinline__ void mbar_wait_long(uint32_t a, uint32_t parity) { int it = 0; while (!mbar_try(a, parity) && ++it < SD_SPIN) {} }
__device__ __forceinline__ uint16_t lds16(uint32_t a) { uint16_t v; asm volatile("ld.shared.u16 %0, [%1];" : "=h"(v) : "r"(a) : "memory"); return v; }
__device__ __forceinline__ void wg_wait1() { asm volatile("wgmma.wait_group.sync.aligned 1;" ::: "memory"); }
__device__ __forceinline__ void tma2d(uint32_t dst, const CUtensorMap* tm, uint32_t bar, int c0, int c1) {
    asm volatile("cp.async.bulk.tensor.2d.shared::cluster.global.mbarrier::complete_tx::bytes [%0], [%1, {%3, %4}], [%2];"
        :: "r"(dst), "l"(tm), "r"(bar), "r"(c0), "r"(c1) : "memory");
}
__device__ __forceinline__ uint32_t add_bf2(uint32_t a, uint32_t b) { uint32_t r; asm("add.rn.bf16x2 %0, %1, %2;" : "=r"(r) : "r"(a), "r"(b)); return r; }
__device__ __forceinline__ void wgmma_conv(float (&d)[32], uint32_t a0, uint32_t a1, uint32_t a2, uint32_t a3, uint64_t desc) {
    asm volatile("{\n.reg .pred p;\nsetp.ne.b32 p, 1, 0;\n"
        "wgmma.mma_async.sync.aligned.m64n64k16.f32.bf16.bf16 {%0,%1,%2,%3,%4,%5,%6,%7,%8,%9,%10,%11,%12,%13,%14,%15,%16,%17,%18,%19,%20,%21,%22,%23,%24,%25,%26,%27,%28,%29,%30,%31}, {%32,%33,%34,%35}, %36, p, 1, 1, 0;\n}\n"
        : "+f"(d[0]), "+f"(d[1]), "+f"(d[2]), "+f"(d[3]), "+f"(d[4]), "+f"(d[5]), "+f"(d[6]), "+f"(d[7]), "+f"(d[8]), "+f"(d[9]), "+f"(d[10]), "+f"(d[11]), "+f"(d[12]), "+f"(d[13]), "+f"(d[14]), "+f"(d[15]), "+f"(d[16]), "+f"(d[17]), "+f"(d[18]), "+f"(d[19]), "+f"(d[20]), "+f"(d[21]), "+f"(d[22]), "+f"(d[23]), "+f"(d[24]), "+f"(d[25]), "+f"(d[26]), "+f"(d[27]), "+f"(d[28]), "+f"(d[29]), "+f"(d[30]), "+f"(d[31])
        : "r"(a0), "r"(a1), "r"(a2), "r"(a3), "l"(desc));
}
__device__ __forceinline__ void wgmma_conv(float (&d)[24], uint32_t a0, uint32_t a1, uint32_t a2, uint32_t a3, uint64_t desc) {
    asm volatile("{\n.reg .pred p;\nsetp.ne.b32 p, 1, 0;\n"
        "wgmma.mma_async.sync.aligned.m64n48k16.f32.bf16.bf16 {%0,%1,%2,%3,%4,%5,%6,%7,%8,%9,%10,%11,%12,%13,%14,%15,%16,%17,%18,%19,%20,%21,%22,%23}, {%24,%25,%26,%27}, %28, p, 1, 1, 0;\n}\n"
        : "+f"(d[0]), "+f"(d[1]), "+f"(d[2]), "+f"(d[3]), "+f"(d[4]), "+f"(d[5]), "+f"(d[6]), "+f"(d[7]), "+f"(d[8]), "+f"(d[9]), "+f"(d[10]), "+f"(d[11]), "+f"(d[12]), "+f"(d[13]), "+f"(d[14]), "+f"(d[15]), "+f"(d[16]), "+f"(d[17]), "+f"(d[18]), "+f"(d[19]), "+f"(d[20]), "+f"(d[21]), "+f"(d[22]), "+f"(d[23])
        : "r"(a0), "r"(a1), "r"(a2), "r"(a3), "l"(desc));
}
__device__ __forceinline__ void wgmma_conv(float (&d)[16], uint32_t a0, uint32_t a1, uint32_t a2, uint32_t a3, uint64_t desc) {
    asm volatile("{\n.reg .pred p;\nsetp.ne.b32 p, 1, 0;\n"
        "wgmma.mma_async.sync.aligned.m64n32k16.f32.bf16.bf16 {%0,%1,%2,%3,%4,%5,%6,%7,%8,%9,%10,%11,%12,%13,%14,%15}, {%16,%17,%18,%19}, %20, p, 1, 1, 0;\n}\n"
        : "+f"(d[0]), "+f"(d[1]), "+f"(d[2]), "+f"(d[3]), "+f"(d[4]), "+f"(d[5]), "+f"(d[6]), "+f"(d[7]), "+f"(d[8]), "+f"(d[9]), "+f"(d[10]), "+f"(d[11]), "+f"(d[12]), "+f"(d[13]), "+f"(d[14]), "+f"(d[15])
        : "r"(a0), "r"(a1), "r"(a2), "r"(a3), "l"(desc));
}
__device__ __forceinline__ void wgmma_conv(float (&d)[8], uint32_t a0, uint32_t a1, uint32_t a2, uint32_t a3, uint64_t desc) {
    asm volatile("{\n.reg .pred p;\nsetp.ne.b32 p, 1, 0;\n"
        "wgmma.mma_async.sync.aligned.m64n16k16.f32.bf16.bf16 {%0,%1,%2,%3,%4,%5,%6,%7}, {%8,%9,%10,%11}, %12, p, 1, 1, 0;\n}\n"
        : "+f"(d[0]), "+f"(d[1]), "+f"(d[2]), "+f"(d[3]), "+f"(d[4]), "+f"(d[5]), "+f"(d[6]), "+f"(d[7])
        : "r"(a0), "r"(a1), "r"(a2), "r"(a3), "l"(desc));
}
template<int NR> __device__ __forceinline__ void conv_mma(float (&acc)[NR], const uint32_t (&R)[16], uint32_t dlo) {
    #pragma unroll
    for (int q = 0; q < 4; q++)
        wgmma_conv(acc, R[4 * q], R[4 * q + 1], R[4 * q + 2], R[4 * q + 3], (uint64_t)(dlo + (2 * (3 - q)) * (BC_LBO >> 4)) | ((uint64_t)8 << 32));
}
__device__ __forceinline__ void conv_ld(uint32_t (&R)[16], uint32_t a) {
    #pragma unroll
    for (int q = 0; q < 4; q++) { const uint2 u = lds64(a + 64 * (2 * q + 1)); R[4 * q] = u.x; R[4 * q + 1] = u.y; }
}
__device__ __forceinline__ void conv_fix(uint32_t (&R)[16], uint32_t& carry) {
    #pragma unroll
    for (int q = 0; q < 4; q++) {
        asm volatile("mov.b32 %0, %1;" : "=r"(R[4 * q + 2]) : "r"(q ? R[4 * q - 3] : carry));
        asm volatile("mov.b32 %0, %1;" : "=r"(R[4 * q + 3]) : "r"(R[4 * q]));
    }
    asm volatile("mov.b32 %0, %1;" : "=r"(carry) : "r"(R[13]));
}
template<int A> __device__ __forceinline__ void conv_group(float (&acc)[32 - 8 * A], uint32_t (&R)[4][16], uint32_t& carry, uint32_t pb, uint32_t dlo) {
    #pragma unroll
    for (int e = 0; e < 8; e += 2) {
        const int dl = 8 * A + e;
        conv_fix(R[dl & 3], carry); conv_fix(R[(dl + 1) & 3], carry);
        wg_fence(); conv_mma(acc, R[dl & 3], dlo + 16 - 2 * e); conv_mma(acc, R[(dl + 1) & 3], dlo + 14 - 2 * e); wg_commit();
        wg_wait1();
        if (dl + 2 < 32) { conv_ld(R[(dl + 2) & 3], pb + (dl + 2) * 512); conv_ld(R[(dl + 3) & 3], pb + (dl + 3) * 512); }
    }
}

__global__ void __launch_bounds__(SD_THREADS, 1)
side_kernel(const __grid_constant__ CUtensorMap tmw, const bf16* __restrict__ x,
            const bf16* __restrict__ log_A_real, const bf16* __restrict__ A_imag, const bf16* __restrict__ C_real, const bf16* __restrict__ C_imag,
            const bf16* __restrict__ log_dt, const bf16* __restrict__ D_skip, const bf16* __restrict__ gate_w, bf16* __restrict__ out) {
    extern __shared__ __align__(1024) unsigned char smem[];
    const uint32_t sb = smem_u32(smem);
    const int tid = threadIdx.x, lane = tid & 31;
    const int warp = __shfl_sync(0xffffffffu, tid >> 5, 0);
    const int g = lane >> 2, t = lane & 3, mi = lane >> 3, r8 = lane & 7;
    const bool sh = blockIdx.x < 32;
    const int d0 = blockIdx.x * 16;
    const uint32_t b0_ = sb + SD_BAR, bKF = b0_ + 384, bKE = bKF + 8 * KSLOTS, bWO = b0_ + 48, bFULL = b0_ + 56, bEMPTY = b0_ + 88, bEPI = b0_ + 120, bPRT = b0_ + 152, bGO = b0_ + 184, bCH = b0_ + 256;
    const unsigned epoch = ld_relaxed32(&g_epoch);
    if (tid == 0) GT(blockIdx.x, 0);
    if (tid == 0) {
        for (int i = 0; i < 2 * KSLOTS; i++) mbar_init(bKF + 8 * i, 128);
        mbar_init(bWO, 1);
        for (int i = 0; i < 16; i++) mbar_init(bCH + 8 * i, 1);
        for (int i = 0; i < 4; i++) { mbar_init(bFULL + 8 * i, 1); mbar_init(bEMPTY + 8 * i, sh ? 8 : 4); mbar_init(bEPI + 8 * i, 4); mbar_init(bPRT + 8 * i, 8); mbar_init(bGO + 8 * i, 1); }
        asm volatile("fence.mbarrier_init.release.cluster;" ::: "memory");
    }
    for (int i = tid; i < KSLOTS * 8 * 16; i += SD_THREADS) sts128(sb + SD_BC + (i >> 4) * BC_LBO + (i & 15) * 16, make_uint4(0, 0, 0, 0));
    if (tid < 128) sts64(sb + ((tid & 64) ? SD_Q1 : SD_Q0) + (tid & 63) * 8, 0u, 0u);
    fence_async_smem();
    __syncthreads();

    if (warp < 8) {
        asm volatile("setmaxnreg.inc.sync.aligned.u32 %0;" :: "n"(SD_REG));
        const int wg = warp >> 2, w = warp & 3, t128 = tid & 127;
        if (SD_WAIT) __nanosleep(SD_WAIT);
        {
            #pragma unroll 1
            for (int i = 0; i < 4; i++) {
                const int tp = tid + 256 * i;
                const bf16* xp = x + (size_t)(2 * tp) * DM + d0;
                const uint4 v0 = __ldg((const uint4*)xp), v1 = __ldg((const uint4*)(xp + 8)), v2 = __ldg((const uint4*)(xp + DM)), v3 = __ldg((const uint4*)(xp + DM + 8));
                const uint32_t a = sb + SD_BT + (tp >> 5) * 144 + (tp & 31) * 4;
                const uint32_t lo[8] = {v0.x, v0.y, v0.z, v0.w, v1.x, v1.y, v1.z, v1.w};
                const uint32_t hi[8] = {v2.x, v2.y, v2.z, v2.w, v3.x, v3.y, v3.z, v3.w};
                #pragma unroll
                for (int j = 0; j < 8; j++) { sts32(a + (2 * j) * BT_RS, __byte_perm(lo[j], hi[j], 0x5410)); sts32(a + (2 * j + 1) * BT_RS, __byte_perm(lo[j], hi[j], 0x7632)); }
                if (SD_GAP) __nanosleep(SD_GAP);
            }
        }
        bar_sync(1, 256);
        if (tid == 0) GT(blockIdx.x, 65);
        const uint32_t pa = sb + (wg ? SD_Q1 : SD_Q0);
        const uint32_t pb = pa + (72 + 16 * w - 56 + g - 2 * t) * 8;
        for (int c = wg; c < 16; c += 2) {
            const uint32_t bt = sb + SD_BT + c * BT_RS;
            bar_sync(2 + wg, 128);
            #pragma unroll
            for (int it = 0; it < 9; it++) {
                const int k = it < 8 ? t128 + 128 * it : t128 - 4;
                if (it < 8 || t128 < 4) {
                    auto word = [&](int j) { return j >= 0 ? lds32(bt + (j >> 5) * 144 + (j & 31) * 4) : 0u; };
                    const uint32_t c0 = word(k), p0 = word(k - 1), c1 = word(k + 4), p1 = word(k + 3);
                    sts128(pa + (72 + 2 * k) * 8, make_uint4(__byte_perm(c0, p0, 0x7610), __byte_perm(c1, p1, 0x7610), __byte_perm(c0, c0, 0x1032), __byte_perm(c1, c1, 0x1032)));
                }
            }
            bar_sync(2 + wg, 128);
            const int slot = c % KSLOTS;
            float acc[32];
            #pragma unroll
            for (int i = 0; i < 32; i++) acc[i] = 0.f;
            uint32_t R[4][16];
            uint32_t carry = lds32(pb);
            conv_ld(R[0], pb); conv_ld(R[1], pb + 512);
            const uint32_t dlo = (((sb + SD_BC + slot * BC_BYTES) & 0x3FFFF) >> 4) | ((BC_LBO >> 4) << 16);
            mbar_wait_long(bKF + 8 * slot, (c / KSLOTS) & 1);
            const float ds = bf(D_skip[d0 + c]);
            auto fin = [&](const float* a8, int q0) {
                #pragma unroll
                for (int q = 0; q < 2; q++)
                    #pragma unroll
                    for (int hh = 0; hh < 2; hh++) {
                        const uint32_t a = bt + (4 * (q0 + q) + t) * 144 + (16 * w + g + 8 * hh) * 2;
                        const float u = __uint_as_float((uint32_t)lds16(a) << 16);
                        const float y = rbf(a8[4 * q + 2 * hh] + a8[4 * q + 2 * hh + 1]);
                        sts16(a, (uint16_t)(pack_bf16(y + rbf(u * ds), 0.f) & 0xffff));
                    }
            };
            float a1[24], a2[16], a3[8];
            conv_group<0>(acc, R, carry, pb, dlo);
            wg_wait0();
            #pragma unroll
            for (int i = 0; i < 24; i++) asm volatile("mov.b32 %0, %1;" : "=f"(a1[i]) : "f"(acc[8 + i]));
            fin(acc, 0);
            conv_group<1>(a1, R, carry, pb, dlo);
            wg_wait0();
            #pragma unroll
            for (int i = 0; i < 16; i++) asm volatile("mov.b32 %0, %1;" : "=f"(a2[i]) : "f"(a1[8 + i]));
            fin(a1, 2);
            conv_group<2>(a2, R, carry, pb, dlo);
            wg_wait0();
            #pragma unroll
            for (int i = 0; i < 8; i++) asm volatile("mov.b32 %0, %1;" : "=f"(a3[i]) : "f"(a2[8 + i]));
            fin(a2, 4);
            conv_group<3>(a3, R, carry, pb, dlo);
            wg_wait0();
            mbar_arrive(bKE + 8 * slot);
            fin(a3, 6);
        }
        fence_async_smem();
        __syncthreads();
        const uint32_t stg = sb + SD_STG + wg * 65536;
        uint32_t wf[32][4];
        if (tid == 0) GT(blockIdx.x, 66);
        mbar_wait_long(bWO, 0);
        #pragma unroll
        for (int i = 0; i < 32; i++)
            ldsm_x4_t(wf[i], stg + (i * 16 + (mi >> 1) * 8 + r8) * 128 + (((2 * w + (mi & 1)) ^ r8) << 4));
        { uint32_t x = 0;
          #pragma unroll
          for (int i = 0; i < 32; i++) x |= wf[i][0];
          asm volatile("" :: "r"(x) : "memory"); }
        __syncwarp();
        if (lane == 0) {
            mbar_arrive(bEMPTY + 16 * wg); mbar_arrive(bEMPTY + 16 * wg + 8);
            if (sh) { mbar_arrive(bEMPTY + 16 * (wg ^ 1)); mbar_arrive(bEMPTY + 16 * (wg ^ 1) + 8); }
        }
        uint4* dst = sh ? &g_part[(blockIdx.x & ~7) + 4 * wg + w][0][0][blockIdx.x & 7][lane] : &g_part[32 + w][0][0][2 * (blockIdx.x - 32) + wg][lane];
        const uint32_t dl0 = (((sb + SD_STG) & 0x3FFFF) >> 4) | 0x10000u;
        auto seg = [&](int s, auto last) {
            const int bi = sh ? s & 3 : 2 * wg + (s & 1), bp = (sh ? s >> 2 : s >> 1) & 1;
            const uint32_t xd = uni(dl0 + bi * 2048);
            float acc[16];
            #pragma unroll
            for (int i = 0; i < 32; i++) {
                if (i == 0 || (last.value && (i & 7) == 0)) { mbar_wait_long(bCH + 32 * bi + i, i ? 0 : bp); wg_fence(); }
                if (i == 0) wgmma_n32<0>(acc, wf[i], desc_from(xd));
                else wgmma_n32<1>(acc, wf[i], desc_from(xd + (i >> 2) * 256 + (i & 3) * 2));
            }
            wg_commit();
            if (s >= PART_SLOTS / 2) mbar_wait_long(bEPI + 8 * (s & 3), ((s - 4) >> 2) & 1);
            const uint32_t ph = ((s / PART_SLOTS) & 1) ^ 1;
            uint4* p = dst + (s % PART_SLOTS) * (4 * 8 * 32);
            wg_wait0();
            #pragma unroll
            for (int j = 0; j < 4; j++)
                st_relaxed128(p + 256 * j, make_uint4((__float_as_uint(acc[4 * j]) & ~1u) | ph, __float_as_uint(acc[4 * j + 1]), __float_as_uint(acc[4 * j + 2]), __float_as_uint(acc[4 * j + 3])));
            if (tid == 0 && s == NSEG - 1) GT(blockIdx.x, 71);
            __syncwarp();
            if (lane == 0) { mbar_arrive(bEMPTY + 8 * bi); mbar_arrive(bPRT + 8 * (s & 3)); }
        };
        #pragma unroll 1
        for (int s = 0; s < NSEG - 1; s++) seg(s, ic<0>());
        seg(NSEG - 1, ic<1>());
    } else {
        asm volatile("setmaxnreg.dec.sync.aligned.u32 %0;" :: "n"(504 - 2 * SD_REG));
        const int w = warp - 8, n = tid - 256;
        bf16 p_la = log_A_real[d0 * NS + n], p_ai = A_imag[d0 * NS + n], p_cr = C_real[d0 * NS + n], p_ci = C_imag[d0 * NS + n], p_dt = log_dt[d0];
        const uint32_t ef = sb + SD_EF + w * 8192;
        const uint32_t efl = ef + lane * 4;
        uint32_t goff[8];
        #pragma unroll
        for (int i = 0; i < 16; i++) {
            const int l = 64 * lane + 8 * (w + 4 * (i >> 3)) + (i & 7);
            const int p = (int)rbf((float)l);
            const int a = p >> 7, b = (p >> 3) & 15, c = p & 7;
            const int row = p < 256 ? 8 * a + c : (p < 512 ? 16 + 4 * (a - 2) + (c >> 1) : (p < 1024 ? 24 + 2 * (a - 4) + (c >> 2) : 24 + a));
            const uint32_t off = row * 72 + b * 4;
            if (i & 1) goff[i >> 1] |= off << 16; else goff[i >> 1] = off;
        }
        for (int c = 0; c < 16; c++) {
            const float dt = rbf(expf(bf(p_dt)));
            const float xr = -rbf(expf(bf(p_la))) * dt, xi = bf(p_ai) * dt;
            cplx C; C.r = 2.f * bf(p_cr) * dt; C.i = 2.f * bf(p_ci) * dt;
            if (c + 1 < 16) {
                const int o = (d0 + c + 1) * NS + n;
                p_la = log_A_real[o]; p_ai = A_imag[o]; p_cr = C_real[o]; p_ci = C_imag[o]; p_dt = log_dt[d0 + c + 1];
            }
            const uint32_t mexp = min(max(__reduce_max_sync(0xffffffffu, __float_as_uint(fmaxf(fabsf(C.r), fabsf(C.i)))) & 0x7f800000u, 0x01000000u), 0x7e000000u);
            const float unsc = __uint_as_float(mexp), sc = __uint_as_float(0x7f000000u - mexp);
            C.r *= sc; C.i *= sc;
            #define EADDR(r) ((efl ^ (((r) & 7) << 4)) + (r) * 128)
            {
                cplx f[16];
                f[1] = cexp_(8.f * xr, -8.f * xi);
                f[2] = cmul(f[1], f[1]); f[3] = cmul(f[2], f[1]); f[4] = cmul(f[2], f[2]); f[5] = cmul(f[4], f[1]); f[6] = cmul(f[4], f[2]); f[7] = cmul(f[4], f[3]);
                f[8] = cmul(f[4], f[4]);
                #pragma unroll
                for (int b = 9; b < 16; b++) f[b] = cmul(f[8], f[b - 8]);
                sts32(EADDR(0) + 6144, 0x00003c00u);
                #pragma unroll
                for (int b = 1; b < 16; b++) sts32(EADDR(b) + 6144, pack_f16(f[b].r, f[b].i));
            }
            {
                cplx G[17], wc[8];
                G[1] = cexp_(128.f * xr, 128.f * xi);
                wc[1] = cexp_(xr, xi);
                G[2] = cmul(G[1], G[1]); G[4] = cmul(G[2], G[2]); G[8] = cmul(G[4], G[4]);
                wc[2] = cmul(wc[1], wc[1]); wc[3] = cmul(wc[2], wc[1]); wc[4] = cmul(wc[2], wc[2]); wc[5] = cmul(wc[4], wc[1]); wc[6] = cmul(wc[4], wc[2]); wc[7] = cmul(wc[4], wc[3]);
                cplx CG[17];
                CG[0] = C; CG[1] = cmul(C, G[1]); CG[2] = cmul(C, G[2]); CG[3] = cmul(CG[1], G[2]);
                #pragma unroll
                for (int a = 0; a < 4; a++) CG[4 + a] = cmul(CG[a], G[4]);
                #pragma unroll
                for (int a = 0; a < 9; a++) CG[8 + a] = cmul(CG[a], G[8]);
                #pragma unroll
                for (int r = 0; r < 41; r++) {
                    const int a = r < 16 ? (r >> 3) : (r < 24 ? 2 + ((r >> 2) & 1) : (r < 32 ? 4 + ((r >> 1) & 3) : r - 24));
                    const int cc = r < 16 ? (r & 7) : (r < 24 ? 2 * (r & 3) : (r < 32 ? 4 * (r & 1) : 0));
                    const cplx e = cc ? cmul(CG[a], wc[cc]) : CG[a];
                    sts32(EADDR(r), pack_f16(e.r, e.i));
                }
            }
            __syncwarp();
            float acc[3][2][4];
            #pragma unroll
            for (int i = 0; i < 3; i++)
                #pragma unroll
                for (int j = 0; j < 2; j++) { acc[i][j][0] = acc[i][j][1] = acc[i][j][2] = acc[i][j][3] = 0.f; }
            #pragma unroll
            for (int ks = 0; ks < 4; ks++) {
                uint32_t bq[4];
                ldsm_x4(bq, ef + 6144 + ((mi >> 1) * 8 + r8) * 128 + (((2 * ks + (mi & 1)) ^ r8) << 4));
                #pragma unroll
                for (int mt = 0; mt < 3; mt++) {
                    uint32_t aq[4];
                    ldsm_x4(aq, ef + (16 * mt + (mi & 1) * 8 + r8) * 128 + (((2 * ks + (mi >> 1)) ^ r8) << 4));
                    mma_f16(acc[mt][0], aq, bq[0], bq[1]);
                    mma_f16(acc[mt][1], aq, bq[2], bq[3]);
                }
            }
            const uint32_t kp = sb + SD_KP;
            #pragma unroll
            for (int mt = 0; mt < 3; mt++)
                #pragma unroll
                for (int nt = 0; nt < 2; nt++) {
                    const uint32_t a = kp + w * 3072 + (16 * mt + g) * 64 + nt * 32 + t * 8;
                    sts64(a, __float_as_uint(acc[mt][nt][0] * unsc), __float_as_uint(acc[mt][nt][1] * unsc));
                    sts64(a + 512, __float_as_uint(acc[mt][nt][2] * unsc), __float_as_uint(acc[mt][nt][3] * unsc));
                }
            bar_sync(4, 128);
            #pragma unroll
            for (int i = 0; i < 3; i++) {
                const uint32_t a = kp + (n + 128 * i) * 8;
                const uint2 v0 = lds64(a), v1 = lds64(a + 3072), v2 = lds64(a + 6144), v3 = lds64(a + 9216);
                sts64(a + 12288 + ((n >> 3) + 16 * i) * 8, __float_as_uint((__uint_as_float(v0.x) + __uint_as_float(v1.x)) + (__uint_as_float(v2.x) + __uint_as_float(v3.x))),
                                 __float_as_uint((__uint_as_float(v0.y) + __uint_as_float(v1.y)) + (__uint_as_float(v2.y) + __uint_as_float(v3.y))));
            }
            bar_sync(4, 128);
            const int slot = c % KSLOTS;
            float kv[16];
            #pragma unroll
            for (int e = 0; e < 8; e++) { kv[2 * e] = __uint_as_float(lds32(kp + 12288 + (goff[e] & 0xffff))); kv[2 * e + 1] = __uint_as_float(lds32(kp + 12288 + (goff[e] >> 16))); }
            if (c >= KSLOTS) mbar_wait_long(bKE + 8 * slot, (c / KSLOTS - 1) & 1);
            #pragma unroll
            for (int it = 0; it < 2; it++) {
                uint32_t hi[4], lo[4];
                #pragma unroll
                for (int e = 0; e < 4; e++) {
                    const float k0 = kv[8 * it + 2 * e], k1 = kv[8 * it + 2 * e + 1];
                    hi[e] = pack_bf16(k0, k1);
                    lo[e] = pack_bf16(k0 - bf_lo(hi[e]), k1 - bf_hi(hi[e]));
                }
                const uint32_t a = sb + SD_BC + slot * BC_BYTES + (w + 4 * it) * BC_LBO + (16 + 2 * lane) * 16;
                sts128(a, make_uint4(hi[0], hi[1], hi[2], hi[3]));
                sts128(a + 16, make_uint4(lo[0], lo[1], lo[2], lo[3]));
            }
            fence_async_smem();
            mbar_arrive(bKF + 8 * slot);
        }
        {
            uint32_t gw[9];
            #pragma unroll
            for (int j = 0; j < 9; j++) gw[j] = __ldg((const uint32_t*)gate_w + lane + 32 * j);
            float z = 0.f;
            #pragma unroll 1
            for (int i0 = 0; i0 < 15; i0 += 5) {
                uint32_t xv[5][9];
                #pragma unroll
                for (int i = 0; i < 5; i++) {
                    const int tk = min(blockIdx.x * 57 + w + 4 * (i0 + i), S_LEN - 1);
                    #pragma unroll
                    for (int j = 0; j < 9; j++) xv[i][j] = __ldg((const uint32_t*)(x + (size_t)tk * DM) + lane + 32 * j);
                }
                #pragma unroll
                for (int i = 0; i < 5; i++) {
                    float acc = 0.f;
                    #pragma unroll
                    for (int j = 0; j < 9; j++) { const uint32_t m = mul_bf2(xv[i][j], gw[j]); acc += bf_lo(m) + bf_hi(m); }
                    #pragma unroll
                    for (int o = 16; o; o >>= 1) acc += __shfl_xor_sync(0xffffffffu, acc, o);
                    if (lane == i0 + i) z = rbf(acc);
                }
            }
            const int li = w + 4 * lane, tk = blockIdx.x * 57 + li;
            if (li < 57 && tk < S_LEN) st_relaxed32(&g_gate[tk], pack_bf16(1.f / (1.f + expf(-z)), 0.f) | (epoch << 16));
        }
        if (tid == 256) GT(blockIdx.x, 67);
        fence_async_smem();
        __syncthreads();
            const uint32_t ost = sb + SD_OST + w * 256;
            const uint4* const pl = &g_part[blockIdx.x][0][0][0][lane];
            uint4 v[8];
            auto fetch = [&](int u, bool block) {
                const int s = u >> 2;
                uint32_t early;
                asm volatile("{\n.reg .pred p;\nmbarrier.test_wait.parity.shared::cta.b64 p, [%1], %2;\nselp.u32 %0, 1, 0, p;\n}\n" : "=r"(early) : "r"(bPRT + 8 * (s & 3)), "r"((s >> 2) & 1) : "memory");
                if (!early) {
                    if (!block) return false;
                    mbar_wait_long(bPRT + 8 * (s & 3), (s >> 2) & 1);
                    delay_clk(s < NSEG - 2 ? SD_P1 : SD_P2);
                } else if (SD_P3 && s < SD_RUSH) delay_clk(SD_P3);
                const uint4* p = pl + (u & (4 * PART_SLOTS - 1)) * 256;
                #pragma unroll
                for (int i = 0; i < 8; i++) v[i] = ld_relaxed128(p + 32 * i);
                return true;
            };
            auto units = [&](int u, int end) {
              fetch(u, true);
              #pragma unroll 1
              while (true) {
                const int s = u >> 2;
                const int t0 = 8 * u + 2 * t;
                const uint2 gt = lds64(sb + SD_Q0 + t0 * 4);
                const uint32_t ba = sb + SD_BT + g * BT_RS + (t0 >> 6) * 144 + (t0 & 63) * 2;
                const uint32_t b0 = lds32(ba), b1 = lds32(ba + 8 * BT_RS);
                const uint32_t phm = ((s / PART_SLOTS) & 1) - 1;
                int it = 0;
                while (true) {
                    uint32_t any = 0;
                    #pragma unroll
                    for (int i = 0; i < 8; i++) any |= v[i].x ^ phm;
                    if (!__any_sync(0xffffffffu, any & 1u) || ++it >= SD_SPIN) break;
                    if (it > 1 && s < NSEG - 2) __nanosleep(200);
                    const uint4* p = pl + (u & (4 * PART_SLOTS - 1)) * 256;
                    #pragma unroll
                    for (int i = 0; i < 8; i++) ld_relaxed128_p(v[i], p + 32 * i, (v[i].x ^ phm) & 1u);
                }
                if (lane == 0) mbar_arrive(bEPI + 8 * (s & 3));
                float a0 = __uint_as_float(v[0].x), a1 = __uint_as_float(v[0].y), a2 = __uint_as_float(v[0].z), a3 = __uint_as_float(v[0].w);
                #pragma unroll
                for (int i = 1; i < 8; i++) { a0 += __uint_as_float(v[i].x); a1 += __uint_as_float(v[i].y); a2 += __uint_as_float(v[i].z); a3 += __uint_as_float(v[i].w); }
                const uint32_t s01 = pack_bf16(a0, a1), s23 = pack_bf16(a2, a3);
                const int nu = u + 3;
                const bool pre = nu < end && fetch(nu, false);
                const uint32_t gg = __byte_perm(gt.x, gt.y, 0x5410), mm = pack_bf16(1.f - bf_lo(gg), 1.f - bf_hi(gg));
                const uint32_t r0 = add_bf2(mul_bf2(gg, s01), mul_bf2(mm, b0)), r1 = add_bf2(mul_bf2(gg, s23), mul_bf2(mm, b1));
                asm volatile("stmatrix.sync.aligned.m8n8.x2.trans.shared.b16 [%0], {%1,%2};" :: "r"(ost + r8 * 32 + (mi & 1) * 16), "r"(r0), "r"(r1) : "memory");
                __syncwarp();
                if (lane < 16) *(uint4*)(out + (size_t)(8 * u + (lane >> 1)) * DM + d0 + 8 * (lane & 1)) = lds128(ost + lane * 16);
                __syncwarp();
                if (lane == 0 && (u & 3) == 3) GT(blockIdx.x, 1 + s);
                if (nu >= end) break;
                if (!pre) fetch(nu, true);
                u = nu;
              }
            };
        if (w == 0) {
            if (lane == 0) {
                mbar_expect_tx(bWO, 131072);
                #pragma unroll
                for (int q = 0; q < 4; q++) tma2d(sb + SD_STG + q * 32768, &tmw, bWO, sh ? 128 * (blockIdx.x >> 3) + 64 * (q >> 1) : 512, sh ? 512 * (blockIdx.x & 7) + 256 * (q & 1) : 1024 * (blockIdx.x - 32) + 256 * q);
            }
            bar_sync(5, 128);
            const int ke0 = sh ? blockIdx.x & 7 : 2 * (blockIdx.x - 32);
            const unsigned int* f = &g_prog[12 * ke0 + (lane < (sh ? 12 : 24) ? lane : 0)];
            int avail = 0;
            #pragma unroll 1
            for (int s = 0; s < NSEG; s++) {
                if (s >= avail) {
                    int it = 0;
                    while (true) {
                        uint32_t v;
                        asm volatile("ld.acquire.gpu.global.u32 %0, [%1];" : "=r"(v) : "l"(f) : "memory");
                        avail = __reduce_min_sync(0xffffffffu, (v >> 8) == (epoch & 0xffffffu) ? v & 255u : 0u);
                        if (avail > s || ++it >= SD_SPIN) break;
                        if (s < NSEG - 1) __nanosleep(64);
                    }
                    asm volatile("fence.proxy.async.global;" ::: "memory");
                    if (lane == 0 && s == NSEG - 1) GT(blockIdx.x, 70);
                }
                if (lane == 0 && s == 2 && blockIdx.x == 0) st_relaxed32(&g_epoch, epoch + 1);
                const int b0 = sh ? s & 3 : s & 1, bp = (sh ? s >> 2 : s >> 1) & 1;
                const bf16* src = g_otok + (size_t)s * (SEG * NH * DH) + ke0 * 16384;
                mbar_wait_long(bEMPTY + 8 * b0, bp);
                if (!sh) mbar_wait_long(bEMPTY + 16 + 8 * b0, bp);
                if (s < NSEG - 1) {
                    asm volatile("{\n.reg .pred p, q;\nelect.sync _|p, 0xffffffff;\nsetp.eq.and.u32 q, %6, 0, p;\n"
                                 "@p mbarrier.arrive.expect_tx.shared.b64 _, [%2], 32768;\n"
                                 "@p cp.async.bulk.shared::cluster.global.mbarrier::complete_tx::bytes [%0], [%1], 32768, [%2];\n"
                                 "@q mbarrier.arrive.expect_tx.shared.b64 _, [%5], 32768;\n"
                                 "@q cp.async.bulk.shared::cluster.global.mbarrier::complete_tx::bytes [%3], [%4], 32768, [%5];\n}\n"
                        :: "r"(sb + SD_STG + b0 * 32768), "l"(src), "r"(bCH + 32 * b0), "r"(sb + SD_STG + (b0 + 2) * 32768), "l"(src + 16384), "r"(bCH + 32 * (b0 + 2)), "r"((uint32_t)sh) : "memory");
                } else {
                    #pragma unroll
                    for (int hc = 0; hc < 4; hc++)
                        asm volatile("{\n.reg .pred p, q;\nelect.sync _|p, 0xffffffff;\nsetp.eq.and.u32 q, %6, 0, p;\n"
                                     "@p mbarrier.arrive.expect_tx.shared.b64 _, [%2], 8192;\n"
                                     "@p cp.async.bulk.shared::cluster.global.mbarrier::complete_tx::bytes [%0], [%1], 8192, [%2];\n"
                                     "@q mbarrier.arrive.expect_tx.shared.b64 _, [%5], 8192;\n"
                                     "@q cp.async.bulk.shared::cluster.global.mbarrier::complete_tx::bytes [%3], [%4], 8192, [%5];\n}\n"
                            :: "r"(sb + SD_STG + b0 * 32768 + hc * 8192), "l"(src + hc * 4096), "r"(bCH + 32 * b0 + 8 * hc),
                               "r"(sb + SD_STG + (b0 + 2) * 32768 + hc * 8192), "l"(src + 16384 + hc * 4096), "r"(bCH + 32 * (b0 + 2) + 8 * hc), "r"((uint32_t)sh) : "memory");
                }
            }
        } else {
            if (w == 3) {
                for (int i = 0; i < 16; i += 8) {
                    uint4 v[8]; uint32_t miss = 0xffu; int it = 0;
                    const uint32_t tag = epoch & 0xffffu;
                    #pragma unroll
                    for (int j = 0; j < 8; j++) v[j] = make_uint4(0, 0, 0, 0);
                    do {
                        #pragma unroll
                        for (int j = 0; j < 8; j++) ld_relaxed128_p(v[j], (const uint4*)g_gate + (i + j) * 32 + lane, miss & (1u << j));
                        miss = 0;
                        #pragma unroll
                        for (int j = 0; j < 8; j++) miss |= (uint32_t)((v[j].x >> 16) != tag || (v[j].y >> 16) != tag || (v[j].z >> 16) != tag || (v[j].w >> 16) != tag) << j;
                    } while (__any_sync(0xffffffffu, miss) && ++it < SD_SPIN);
                    #pragma unroll
                    for (int j = 0; j < 8; j++) sts128(sb + SD_Q0 + ((i + j) * 32 + lane) * 16, v[j]);
                }
            }
            bar_sync(5, 128);
        }
        #pragma unroll 1
        for (int k = w == 0; k < 2; k++) units(k ? 4 * (NSEG - 1) + w : w - 1, k ? 0 : 4 * (NSEG - 1));
    }
    if (tid == 256) GT(blockIdx.x, 72);
}

extern "C" void kernel_launch(void* const* d_in, const int* in_sizes, int n_in, void* d_out, int out_size) {
    const bf16* x = (const bf16*)d_in[0];
    const bf16* mem0 = (const bf16*)d_in[1];
    const bf16* Wq = (const bf16*)d_in[2];
    const bf16* Wk = (const bf16*)d_in[3];
    const bf16* Wv = (const bf16*)d_in[4];
    const bf16* Wo = (const bf16*)d_in[5];
    const bf16* log_A_real = (const bf16*)d_in[8];
    const bf16* A_imag = (const bf16*)d_in[9];
    const bf16* C_real = (const bf16*)d_in[10];
    const bf16* C_imag = (const bf16*)d_in[11];
    const bf16* log_dt = (const bf16*)d_in[12];
    const bf16* D_skip = (const bf16*)d_in[13];
    const bf16* gate_w = (const bf16*)d_in[14];
    bf16* out = (bf16*)d_out;
    typedef CUresult (*EncFn)(CUtensorMap*, CUtensorMapDataType, cuuint32_t, void*, const cuuint64_t*, const cuuint64_t*, const cuuint32_t*, const cuuint32_t*,
                              CUtensorMapInterleave, CUtensorMapSwizzle, CUtensorMapL2promotion, CUtensorMapFloatOOBfill);
    static EncFn enc = nullptr;
    if (!enc) { void* fn = nullptr; cudaDriverEntryPointQueryResult qr; cudaGetDriverEntryPoint("cuTensorMapEncodeTiled", &fn, cudaEnableDefault, &qr); enc = (EncFn)fn; }
    auto mk = [&](CUtensorMap* tm, const void* ptr, uint64_t cols, uint64_t rows, uint32_t bc, uint32_t br) {
        cuuint64_t gdim[2] = {cols, rows}; cuuint64_t gstr[1] = {cols * 2}; cuuint32_t box[2] = {bc, br}; cuuint32_t estr[2] = {1, 1};
        enc(tm, CU_TENSOR_MAP_DATA_TYPE_BFLOAT16, 2, (void*)ptr, gdim, gstr, box, estr, CU_TENSOR_MAP_INTERLEAVE_NONE, bc == 64 ? CU_TENSOR_MAP_SWIZZLE_128B : CU_TENSOR_MAP_SWIZZLE_64B,
            CU_TENSOR_MAP_L2_PROMOTION_L2_256B, CU_TENSOR_MAP_FLOAT_OOB_FILL_NONE);
    };
    static bool attr_done = false;
    if (!attr_done) {
        cudaFuncSetAttribute(chain_kernel, cudaFuncAttributeMaxDynamicSharedMemorySize, SM_TOTAL);
        cudaFuncSetAttribute(side_kernel, cudaFuncAttributeMaxDynamicSharedMemorySize, SD_TOTAL);
        attr_done = true;
    }
    CUtensorMap tmx, tma, tmb, tmw, tmq, tmk, tmv, tmo;
    {
        cuuint64_t gdim[3] = {64, S_LEN, DM / 64}; cuuint64_t gstr[2] = {DM * 2, 128}; cuuint32_t box[3] = {64, SEG, 3}; cuuint32_t estr[3] = {1, 1, 1};
        enc(&tmx, CU_TENSOR_MAP_DATA_TYPE_BFLOAT16, 3, (void*)x, gdim, gstr, box, estr, CU_TENSOR_MAP_INTERLEAVE_NONE, CU_TENSOR_MAP_SWIZZLE_128B,
            CU_TENSOR_MAP_L2_PROMOTION_L2_256B, CU_TENSOR_MAP_FLOAT_OOB_FILL_NONE);
    }
    static void* acc = nullptr;
    if (!acc) cudaGetSymbolAddress(&acc, g_acc);
    for (int w = 0; w < 2; w++) {
        cuuint64_t gdim[3] = {64, 4, 64}; cuuint64_t gstr[2] = {256, 1024}; cuuint32_t box[3] = {w ? 8u : 32u, 2, (w ? 18u : 36u) / (MEM_MC ? 3u : 1u)}; cuuint32_t estr[3] = {1, 1, 1};
        enc(w ? &tmb : &tma, CU_TENSOR_MAP_DATA_TYPE_UINT32, 3, acc, gdim, gstr, box, estr, CU_TENSOR_MAP_INTERLEAVE_NONE, CU_TENSOR_MAP_SWIZZLE_NONE,
            CU_TENSOR_MAP_L2_PROMOTION_NONE, CU_TENSOR_MAP_FLOAT_OOB_FILL_NONE);
    }
    mk(&tmw, Wo, DM, NH * DH, 64, 256);
    mk(&tmo, Wo, DM, NH * DH, 32, 128);
    mk(&tmq, Wq, NH * DH, DM, 32, 48); mk(&tmk, Wk, NH * DH, DM, 32, 48); mk(&tmv, Wv, NH * DH, DM, 32, 48);
    chain_kernel<<<96, CH_THREADS, SM_TOTAL>>>(tmx, tmq, tmk, tmv, tmo, tma, tmb, mem0, 0u);
    cudaLaunchConfig_t cfg = {};
    cfg.gridDim = dim3(SD_CTAS); cfg.blockDim = dim3(SD_THREADS); cfg.dynamicSmemBytes = SD_TOTAL; cfg.stream = cudaStreamPerThread;
    cudaLaunchAttribute at[1];
    at[0].id = cudaLaunchAttributeProgrammaticStreamSerialization; at[0].val.programmaticStreamSerializationAllowed = 1;
    cfg.attrs = at; cfg.numAttrs = 1;
    cudaLaunchKernelEx(&cfg, side_kernel, tmw, x, log_A_real, A_imag, C_real, C_imag, log_dt, D_skip, gate_w, out);
}
```

```cpp
#include <cuda_runtime.h>
#include <cuda.h>
#include <cuda_bf16.h>
#include <stdint.h>

#define S_LEN 2048
#define DM 576
#define NH 32
#define DH 128
#define NMEM 8
#define SEG 32
#define NSEG 64
#define LQ 40
#define NS 128

typedef __nv_bfloat16 bf16;

__device__ __forceinline__ float bf(bf16 v) { return __bfloat162float(v); }
__device__ __forceinline__ bf16 tobf(float v) { return __float2bfloat16_rn(v); }
__device__ __forceinline__ float rbf(float v) { return __bfloat162float(__float2bfloat16_rn(v)); }

#define CH_THREADS 384
#define SPIN_LIMIT (1 << 17)
#define SM_X     0
#define XBUF     36864
#define SM_TOK   73728
#define TOKBUF   24576
#define SM_STASH 139264
#define SM_TS    (SM_STASH + 3072)
#define SM_WO    147456
#define SM_MEM   196608
#define SM_EX    205824
#define EXBUF    6144
#define SM_P     218112
#define SM_OST   219136
#define SM_O     223232
#define SM_XT    225280
#define SM_BAR   228352
#define MEM_MC 1
#define SM_IL    (SM_BAR + 128)
#define SM_SG    (SM_IL + 256)
#define SM_TOTAL (SM_SG + 64)

#define ACC_X    36864
#define ACC_FULL 0x0020u
#define SLOT_OFF(sl) ((((sl) & 1) << 7) | (((sl) & 2) << 8))
__device__ __align__(65536) unsigned char g_acc[65536];
__device__ unsigned int g_init[96];
__device__ unsigned int g_epoch = 1;
__device__ __align__(128) unsigned int g_ts[128];
__device__ __align__(1024) bf16 g_otok[S_LEN * NH * DH];
__device__ __align__(1024) unsigned char g_tokx[96][8192];
__device__ __align__(128) unsigned int g_prog[96];
#define STAMP(i)
#define STAMPV(i, v)
#define GT(b, i)
#define STAMPB(i)

__device__ __forceinline__ uint32_t smem_u32(const void* p) { return (uint32_t)__cvta_generic_to_shared(p); }
__device__ __forceinline__ void ldsm_x4(uint32_t (&r)[4], uint32_t addr) {
    asm volatile("ldmatrix.sync.aligned.m8n8.x4.shared.b16 {%0,%1,%2,%3}, [%4];" : "=r"(r[0]), "=r"(r[1]), "=r"(r[2]), "=r"(r[3]) : "r"(addr) : "memory");
}
__device__ __forceinline__ void ldsm_x4_p(uint32_t (&r)[4], uint32_t addr, uint32_t skip) {
    asm volatile("{\n.reg .pred p;\nsetp.eq.u32 p, %5, 0;\n@p ldmatrix.sync.aligned.m8n8.x4.shared.b16 {%0,%1,%2,%3}, [%4];\n}\n" : "+r"(r[0]), "+r"(r[1]), "+r"(r[2]), "+r"(r[3]) : "r"(addr), "r"(skip) : "memory");
}
__device__ __forceinline__ void ldsm_x4_t(uint32_t (&r)[4], uint32_t addr) {
    asm volatile("ldmatrix.sync.aligned.m8n8.x4.trans.shared.b16 {%0,%1,%2,%3}, [%4];" : "=r"(r[0]), "=r"(r[1]), "=r"(r[2]), "=r"(r[3]) : "r"(addr) : "memory");
}
__device__ __forceinline__ uint32_t ldsm_x1_t(uint32_t addr) {
    uint32_t r; asm volatile("ldmatrix.sync.aligned.m8n8.x1.trans.shared.b16 {%0}, [%1];" : "=r"(r) : "r"(addr) : "memory"); return r;
}
__device__ __forceinline__ void ldsm_x2_t(uint32_t& r0, uint32_t& r1, uint32_t addr) {
    asm volatile("ldmatrix.sync.aligned.m8n8.x2.trans.shared.b16 {%0,%1}, [%2];" : "=r"(r0), "=r"(r1) : "r"(addr) : "memory");
}
__device__ __forceinline__ void stsm_x4(uint32_t addr, uint32_t r0, uint32_t r1, uint32_t r2, uint32_t r3) {
    asm volatile("stmatrix.sync.aligned.m8n8.x4.shared.b16 [%0], {%1,%2,%3,%4};" :: "r"(addr), "r"(r0), "r"(r1), "r"(r2), "r"(r3) : "memory");
}
__device__ __forceinline__ void stsm_x4_t(uint32_t addr, uint32_t r0, uint32_t r1, uint32_t r2, uint32_t r3) {
    asm volatile("stmatrix.sync.aligned.m8n8.x4.trans.shared.b16 [%0], {%1,%2,%3,%4};" :: "r"(addr), "r"(r0), "r"(r1), "r"(r2), "r"(r3) : "memory");
}
__device__ __forceinline__ void mma16816(float (&c)[4], const uint32_t (&a)[4], uint32_t b0, uint32_t b1) {
    asm("mma.sync.aligned.m16n8k16.row.col.f32.bf16.bf16.f32 {%0,%1,%2,%3}, {%4,%5,%6,%7}, {%8,%9}, {%0,%1,%2,%3};"
        : "+f"(c[0]), "+f"(c[1]), "+f"(c[2]), "+f"(c[3]) : "r"(a[0]), "r"(a[1]), "r"(a[2]), "r"(a[3]), "r"(b0), "r"(b1));
}
__device__ __forceinline__ void mma16816r(float (&c)[4], uint32_t a0, uint32_t a1, uint32_t a2, uint32_t a3, uint32_t b0, uint32_t b1) {
    asm("mma.sync.aligned.m16n8k16.row.col.f32.bf16.bf16.f32 {%0,%1,%2,%3}, {%4,%5,%6,%7}, {%8,%9}, {%0,%1,%2,%3};"
        : "+f"(c[0]), "+f"(c[1]), "+f"(c[2]), "+f"(c[3]) : "r"(a0), "r"(a1), "r"(a2), "r"(a3), "r"(b0), "r"(b1));
}
__device__ __forceinline__ void mma1688(float (&c)[4], uint32_t a0, uint32_t a1, uint32_t b0) {
    asm("mma.sync.aligned.m16n8k8.row.col.f32.bf16.bf16.f32 {%0,%1,%2,%3}, {%4,%5}, {%6}, {%0,%1,%2,%3};"
        : "+f"(c[0]), "+f"(c[1]), "+f"(c[2]), "+f"(c[3]) : "r"(a0), "r"(a1), "r"(b0));
}
__device__ __forceinline__ uint32_t pack_bf16(float lo, float hi) {
    uint32_t r; asm("cvt.rn.bf16x2.f32 %0, %1, %2;" : "=r"(r) : "f"(hi), "f"(lo)); return r;
}
__device__ __forceinline__ float bf_lo(uint32_t v) { return __uint_as_float(v << 16); }
__device__ __forceinline__ float bf_hi(uint32_t v) { return __uint_as_float(v & 0xffff0000u); }
__device__ __forceinline__ uint32_t max_bf2(uint32_t a, uint32_t b) { uint32_t r; asm("max.bf16x2 %0, %1, %2;" : "=r"(r) : "r"(a), "r"(b)); return r; }
__device__ __forceinline__ uint32_t maxabs_bf2(uint32_t a, uint32_t b) { uint32_t r; asm("max.NaN.xorsign.abs.bf16x2 %0, %1, %2;" : "=r"(r) : "r"(a), "r"(b)); return r; }
__device__ __forceinline__ float ex2(float x) { float r; asm("ex2.approx.ftz.f32 %0, %1;" : "=f"(r) : "f"(x)); return r; }
__device__ __forceinline__ void ld_relaxed128_p(uint4& v, const uint4* p, uint32_t pred) {
    asm volatile("{\n.reg .pred p;\nsetp.ne.u32 p, %5, 0;\n@p ld.relaxed.gpu.global.v4.u32 {%0,%1,%2,%3}, [%4];\n}\n" : "+r"(v.x), "+r"(v.y), "+r"(v.z), "+r"(v.w) : "l"(p), "r"(pred) : "memory");
}
__device__ __forceinline__ uint4 ld_relaxed128(const uint4* p) { uint4 v; asm volatile("ld.relaxed.gpu.global.v4.u32 {%0,%1,%2,%3}, [%4];" : "=r"(v.x), "=r"(v.y), "=r"(v.z), "=r"(v.w) : "l"(p) : "memory"); return v; }
__device__ __forceinline__ uint32_t ld_relaxed32(const uint32_t* p) { uint32_t v; asm volatile("ld.relaxed.gpu.global.u32 %0, [%1];" : "=r"(v) : "l"(p) : "memory"); return v; }
__device__ __forceinline__ void st_relaxed128(uint4* p, uint4 v) { asm volatile("st.relaxed.gpu.global.v4.u32 [%0], {%1,%2,%3,%4};" :: "l"(p), "r"(v.x), "r"(v.y), "r"(v.z), "r"(v.w) : "memory"); }
__device__ __forceinline__ void st_relaxed32(uint32_t* p, uint32_t v) { asm volatile("st.relaxed.gpu.global.u32 [%0], %1;" :: "l"(p), "r"(v) : "memory"); }
__device__ __forceinline__ void st_relaxed128_p(uint4* p, uint4 v, uint32_t skip) {
    asm volatile("{\n.reg .pred p;\nsetp.eq.u32 p, %5, 0;\n@p st.relaxed.gpu.global.v4.u32 [%0], {%1,%2,%3,%4};\n}\n" :: "l"(p), "r"(v.x), "r"(v.y), "r"(v.z), "r"(v.w), "r"(skip) : "memory");
}
__device__ __forceinline__ void st_relaxed64_p(void* p, uint32_t x, uint32_t y, uint32_t skip) {
    asm volatile("{\n.reg .pred p;\n.reg .b64 v;\nsetp.eq.u32 p, %3, 0;\nmov.b64 v, {%1,%2};\n@p st.relaxed.gpu.global.b64 [%0], v;\n}\n" :: "l"(p), "r"(x), "r"(y), "r"(skip) : "memory");
}
__device__ __forceinline__ void ld_relaxed64_p(uint2& v, const void* p, uint32_t pred) {
    asm volatile("{\n.reg .pred p;\n.reg .b64 v;\nsetp.ne.u32 p, %3, 0;\nmov.b64 v, {%0,%1};\n@p ld.relaxed.gpu.global.b64 v, [%2];\nmov.b64 {%0,%1}, v;\n}\n" : "+r"(v.x), "+r"(v.y) : "l"(p), "r"(pred) : "memory");
}
__device__ __forceinline__ uint2 ld_relaxed64(const void* p) {
    uint2 v; asm volatile("{\n.reg .b64 v;\nld.relaxed.gpu.global.b64 v, [%2];\nmov.b64 {%0,%1}, v;\n}\n" : "=r"(v.x), "=r"(v.y) : "l"(p) : "memory"); return v;
}
__device__ __forceinline__ void st_relaxed32_p(void* p, uint32_t v, uint32_t skip) {
    asm volatile("{\n.reg .pred p;\nsetp.eq.u32 p, %2, 0;\n@p st.relaxed.gpu.global.u32 [%0], %1;\n}\n" :: "l"(p), "r"(v), "r"(skip) : "memory");
}
__device__ __forceinline__ void bar_arrive_p(int id, int n, uint32_t skip) {
    asm volatile("{\n.reg .pred p;\nsetp.eq.u32 p, %2, 0;\n@p bar.arrive %0, %1;\n}\n" :: "r"(id), "r"(n), "r"(skip) : "memory");
}
__device__ __forceinline__ void bar_sync_p(int id, int n, uint32_t skip) {
    asm volatile("{\n.reg .pred p;\nsetp.eq.u32 p, %2, 0;\n@p bar.sync %0, %1;\n}\n" :: "r"(id), "r"(n), "r"(skip) : "memory");
}
__device__ __forceinline__ uint32_t movm(uint32_t x) { uint32_t r; asm volatile("movmatrix.sync.aligned.m8n8.trans.b16 %0, %1;" : "=r"(r) : "r"(x)); return r; }
__device__ __forceinline__ void sts32_p(uint32_t a, uint32_t v, uint32_t doit) {
    asm volatile("{\n.reg .pred p;\nsetp.ne.u32 p, %2, 0;\n@p st.shared.u32 [%0], %1;\n}\n" :: "r"(a), "r"(v), "r"(doit) : "memory");
}
__device__ __forceinline__ uint32_t pin(uint32_t x) { return __shfl_sync(0xffffffffu, x, threadIdx.x & 31); }
__device__ __forceinline__ void ldsm16_t(uint32_t (&b)[4][4], uint32_t a) {
    asm volatile("ldmatrix.sync.aligned.m8n8.x4.trans.shared.b16 {%0,%1,%2,%3}, [%16];\n"
                 "ldmatrix.sync.aligned.m8n8.x4.trans.shared.b16 {%4,%5,%6,%7}, [%16+512];\n"
                 "ldmatrix.sync.aligned.m8n8.x4.trans.shared.b16 {%8,%9,%10,%11}, [%16+1024];\n"
                 "ldmatrix.sync.aligned.m8n8.x4.trans.shared.b16 {%12,%13,%14,%15}, [%16+1536];\n"
        : "=r"(b[0][0]), "=r"(b[0][1]), "=r"(b[0][2]), "=r"(b[0][3]), "=r"(b[1][0]), "=r"(b[1][1]), "=r"(b[1][2]), "=r"(b[1][3]),
          "=r"(b[2][0]), "=r"(b[2][1]), "=r"(b[2][2]), "=r"(b[2][3]), "=r"(b[3][0]), "=r"(b[3][1]), "=r"(b[3][2]), "=r"(b[3][3]) : "r"(a) : "memory");
}
template<int ID> __device__ __forceinline__ void sched_fence(uint32_t never) { while (never == 0x7fffff00u + ID) { asm volatile("nanosleep.u32 64;" ::: "memory"); } }
__device__ __forceinline__ uint32_t opaque_u() { uint32_t v; asm volatile("mov.u32 %0, %%nsmid;" : "=r"(v)); return v; }
__device__ __forceinline__ uint32_t bar_red_or(int id, int n, uint32_t v) {
    uint32_t r; asm volatile("{\n.reg .pred p, q;\nsetp.ne.u32 p, %3, 0;\nbar.red.or.pred q, %1, %2, p;\nselp.u32 %0, 1, 0, q;\n}\n" : "=r"(r) : "r"(id), "r"(n), "r"(v) : "memory"); return r;
}
template<class T> __device__ __forceinline__ T* launder_p(T* p) { asm volatile("" : "+l"(p)); return p; }
__device__ __forceinline__ uint32_t mapa_u32(uint32_t addr, uint32_t rank) { uint32_t d; asm("mapa.shared::cluster.u32 %0, %1, %2;" : "=r"(d) : "r"(addr), "r"(rank)); return d; }
__device__ __forceinline__ uint32_t mapa_v(uint32_t addr, uint32_t rank) { uint32_t d; asm volatile("mapa.shared::cluster.u32 %0, %1, %2;" : "=r"(d) : "r"(addr), "r"(rank)); return d; }
__device__ __forceinline__ void st_async32(uint32_t addr, uint32_t v, uint32_t mbar) { asm volatile("st.async.shared::cluster.mbarrier::complete_tx::bytes.u32 [%0], %1, [%2];" :: "r"(addr), "r"(v), "r"(mbar) : "memory"); }
__device__ __forceinline__ void cluster_arrive() { asm volatile("barrier.cluster.arrive.release.aligned;" ::: "memory"); }
__device__ __forceinline__ void cluster_wait() { asm volatile("barrier.cluster.wait.acquire.aligned;" ::: "memory"); }
__device__ __forceinline__ void cp_async16(uint32_t dst, const void* src) { asm volatile("cp.async.cg.shared.global [%0], [%1], 16;" :: "r"(dst), "l"(src) : "memory"); }
__device__ __forceinline__ void cp_async_commit() { asm volatile("cp.async.commit_group;" ::: "memory"); }
template<int N> __device__ __forceinline__ void cp_async_wait() { asm volatile("cp.async.wait_group %0;" :: "n"(N) : "memory"); }
__device__ __forceinline__ void cp_async_wait0() { asm volatile("cp.async.wait_group 0;" ::: "memory"); }
__device__ __forceinline__ void mbar_init(uint32_t a, uint32_t cnt) { asm volatile("mbarrier.init.shared.b64 [%0], %1;" :: "r"(a), "r"(cnt) : "memory"); }
__device__ __forceinline__ void mbar_expect_tx(uint32_t a, uint32_t bytes) { asm volatile("mbarrier.arrive.expect_tx.shared.b64 _, [%0], %1;" :: "r"(a), "r"(bytes) : "memory"); }
__device__ __forceinline__ bool mbar_try(uint32_t a, uint32_t parity) {
    uint32_t ok; asm volatile("{\n.reg .pred p;\nmbarrier.try_wait.parity.shared::cta.b64 p, [%1], %2;\nselp.u32 %0, 1, 0, p;\n}\n" : "=r"(ok) : "r"(a), "r"(parity) : "memory"); return ok;
}
__device__ __forceinline__ void mbar_wait(uint32_t a, uint32_t parity) { int it = 0; bool more; do { more = ++it < SPIN_LIMIT; } while (!mbar_try(a, parity) && more); }
__device__ __forceinline__ void bar_sync(int id, int n) { asm volatile("bar.sync %0, %1;" :: "r"(id), "r"(n) : "memory"); }
__device__ __forceinline__ void bar_arrive(int id, int n) { asm volatile("bar.arrive %0, %1;" :: "r"(id), "r"(n) : "memory"); }
__device__ __forceinline__ void fence_async_smem() { asm volatile("fence.proxy.async.shared::cta;" ::: "memory"); }
__device__ __forceinline__ void sts32(uint32_t a, uint32_t v) { asm volatile("st.shared.u32 [%0], %1;" :: "r"(a), "r"(v) : "memory"); }
__device__ __forceinline__ void sts128(uint32_t a, uint4 v) { asm volatile("st.shared.v4.u32 [%0], {%1,%2,%3,%4};" :: "r"(a), "r"(v.x), "r"(v.y), "r"(v.z), "r"(v.w) : "memory"); }
__device__ __forceinline__ uint4 lds128(uint32_t a) { uint4 v; asm volatile("ld.shared.v4.u32 {%0,%1,%2,%3}, [%4];" : "=r"(v.x), "=r"(v.y), "=r"(v.z), "=r"(v.w) : "r"(a) : "memory"); return v; }
__device__ __forceinline__ uint32_t lds32(uint32_t a) { uint32_t v; asm volatile("ld.shared.u32 %0, [%1];" : "=r"(v) : "r"(a) : "memory"); return v; }
__device__ __forceinline__ uint32_t gtime_lo() { uint32_t t; asm volatile("mov.u32 %0, %globaltimer_lo;" : "=r"(t)); return t; }
__device__ __forceinline__ void wait_gtime(uint32_t tg) {
    asm volatile("{\n.reg .pred p, q;\n.reg .b64 t;\n.reg .b32 lo, hi, d, n;\nmov.b32 n, 300;\n"
                 "WG_%=:\nmov.u64 t, %%globaltimer;\nmov.b64 {lo, hi}, t;\nsub.s32 d, lo, %0;\nsub.s32 n, n, 1;\n"
                 "setp.gt.s32 q, n, 0;\nsetp.lt.and.s32 p, d, 0, q;\n@p bra.uni WG_%=;\n}\n" :: "r"(tg) : "memory");
}
__device__ __forceinline__ void delay_clk(int d) { uint32_t t0 = clock(); while ((int)(clock() - t0) < d) {} }

__device__ __forceinline__ uint64_t desc128(uint32_t addr) {
    return (uint64_t)((addr & 0x3FFFF) >> 4) | ((uint64_t)1 << 16) | ((uint64_t)64 << 32) | ((uint64_t)1 << 62);
}
template<int accum> __device__ __forceinline__ void wgmma_n32(float (&d)[16], const uint32_t (&a)[4], uint64_t desc) {
    if (accum) {
        asm volatile("{\n.reg .pred p;\nsetp.ne.b32 p, 1, 0;\n"
            "wgmma.mma_async.sync.aligned.m64n32k16.f32.bf16.bf16 {%0,%1,%2,%3,%4,%5,%6,%7,%8,%9,%10,%11,%12,%13,%14,%15}, {%16,%17,%18,%19}, %20, p, 1, 1, 0;\n}\n"
            : "+f"(d[0]), "+f"(d[1]), "+f"(d[2]), "+f"(d[3]), "+f"(d[4]), "+f"(d[5]), "+f"(d[6]), "+f"(d[7]),
              "+f"(d[8]), "+f"(d[9]), "+f"(d[10]), "+f"(d[11]), "+f"(d[12]), "+f"(d[13]), "+f"(d[14]), "+f"(d[15])
            : "r"(a[0]), "r"(a[1]), "r"(a[2]), "r"(a[3]), "l"(desc));
    } else {
        asm volatile("{\n.reg .pred p;\nsetp.ne.b32 p, 0, 0;\n"
            "wgmma.mma_async.sync.aligned.m64n32k16.f32.bf16.bf16 {%0,%1,%2,%3,%4,%5,%6,%7,%8,%9,%10,%11,%12,%13,%14,%15}, {%16,%17,%18,%19}, %20, p, 1, 1, 0;\n}\n"
            : "=f"(d[0]), "=f"(d[1]), "=f"(d[2]), "=f"(d[3]), "=f"(d[4]), "=f"(d[5]), "=f"(d[6]), "=f"(d[7]),
              "=f"(d[8]), "=f"(d[9]), "=f"(d[10]), "=f"(d[11]), "=f"(d[12]), "=f"(d[13]), "=f"(d[14]), "=f"(d[15])
            : "r"(a[0]), "r"(a[1]), "r"(a[2]), "r"(a[3]), "l"(desc));
    }
}
__device__ __forceinline__ float rcp_approx(float x) { float r; asm("rcp.approx.ftz.f32 %0, %1;" : "=f"(r) : "f"(x)); return r; }
__device__ __forceinline__ void wg_fence() { asm volatile("wgmma.fence.sync.aligned;" ::: "memory"); }
__device__ __forceinline__ void wg_commit() { asm volatile("wgmma.commit_group.sync.aligned;" ::: "memory"); }
__device__ __forceinline__ void wg_wait0() { asm volatile("wgmma.wait_group.sync.aligned 0;" ::: "memory"); }

#define SCALE_HI 0x3db53db5u
#define SCALE_LO 0x371e371eu
#define LOG2E 1.4426950408889634f
#define NEG_BIG2 0xce6ece6eu
__device__ __forceinline__ uint32_t scale_bf2(uint32_t x) {
    uint32_t t, r;
    asm("mul.rn.bf16x2 %0, %1, %2;" : "=r"(t) : "r"(x), "r"(SCALE_LO));
    asm("fma.rn.bf16x2 %0, %1, %2, %3;" : "=r"(r) : "r"(x), "r"(SCALE_HI), "r"(t));
    return r;
}
__device__ __forceinline__ void cluster_arrive_rx() { asm volatile("barrier.cluster.arrive.relaxed.aligned;" ::: "memory"); }
__device__ __forceinline__ uint32_t launder(uint32_t x) { asm volatile("" : "+r"(x)); return x; }
__device__ __forceinline__ void mbar_arrive(uint32_t a) { asm volatile("mbarrier.arrive.shared.b64 _, [%0];" :: "r"(a) : "memory"); }
__device__ __forceinline__ void mbar_wait_cl(uint32_t a, uint32_t parity) {
    int it = 0; uint32_t ok;
    do { asm volatile("{\n.reg .pred p;\nmbarrier.try_wait.parity.acquire.cluster.shared::cta.b64 p, [%1], %2;\nselp.u32 %0, 1, 0, p;\n}\n" : "=r"(ok) : "r"(a), "r"(parity) : "memory"); } while (!ok && ++it < SPIN_LIMIT);
}
__device__ __forceinline__ uint64_t desc_from(uint32_t lo) { return (uint64_t)lo | ((uint64_t)0x40000040u << 32); }
#define SB_OFF 1024u
#define DESC_LO(off) ((((SB_OFF + (uint32_t)(off)) & 0x3FFFFu) >> 4) | 0x10000u)
template<int N> struct ic { static constexpr int value = N; };
__device__ __forceinline__ uint32_t uni(uint32_t x) { return __shfl_sync(0xffffffffu, x, 0); }

__device__ __forceinline__ uint32_t pack_f16(float lo, float hi) { uint32_t r; asm("cvt.rn.f16x2.f32 %0, %1, %2;" : "=r"(r) : "f"(hi), "f"(lo)); return r; }
__device__ __forceinline__ void sts16(uint32_t a, uint16_t v) { asm volatile("st.shared.u16 [%0], %1;" :: "r"(a), "h"(v) : "memory"); }
__device__ __forceinline__ void sts64(uint32_t a, uint32_t x, uint32_t y) { asm volatile("st.shared.v2.u32 [%0], {%1,%2};" :: "r"(a), "r"(x), "r"(y) : "memory"); }
__device__ __forceinline__ void ld_relaxed32_p(uint32_t& v, const void* p, uint32_t pred) {
    asm volatile("{\n.reg .pred p;\nsetp.ne.u32 p, %2, 0;\n@p ld.relaxed.gpu.global.u32 %0, [%1];\n}\n" : "+r"(v) : "l"(p), "r"(pred) : "memory");
}
__device__ __forceinline__ uint2 lds64(uint32_t a) { uint2 v; asm volatile("ld.shared.v2.u32 {%0,%1}, [%2];" : "=r"(v.x), "=r"(v.y) : "r"(a) : "memory"); return v; }
__device__ __forceinline__ void mbar_wait2(uint32_t a, uint32_t pa, uint32_t b, uint32_t pb) {
    int it = 0; uint32_t ok;
    do { asm volatile("{\n.reg .pred p, q;\nmbarrier.try_wait.parity.shared::cta.b64 p, [%1], %2;\nmbarrier.try_wait.parity.shared::cta.b64 q, [%3], %4;\nand.pred p, p, q;\nselp.u32 %0, 1, 0, p;\n}\n"
                      : "=r"(ok) : "r"(a), "r"(pa), "r"(b), "r"(pb) : "memory"); } while (!ok && ++it < SPIN_LIMIT);
}
__device__ __forceinline__ float exd(float s, float m) { return ex2(__fmul_rn(__fsub_rn(s, m), LOG2E)); }
__device__ __forceinline__ uint32_t gtime_after(uint32_t z) {
    uint32_t t = 0; asm volatile("{\n.reg .pred p;\nsetp.eq.u32 p, %1, 0;\n@p mov.u32 %0, %%globaltimer_lo;\n}\n" : "+r"(t) : "r"(z)); return t;
}
#define T_MMAK 4
#define T_HOLD 4
#define T_KPRE 3
#define BLK_Q(p) (((p) < 3 ? (p) : 8) * 2048)
#define BLK_K(p) (((p) < 3 ? 4 + (p) : 9) * 2048)
#define BLK_V(p) (((p) < 2 ? 3 + 4 * (p) : 8 + (p)) * 2048)
__device__ __forceinline__ uint32_t exp_bf2(uint32_t s) { return pack_bf16(ex2(bf_lo(s) * LOG2E), ex2(bf_hi(s) * LOG2E)); }
template<int MT, int LO, int HI>
__device__ __forceinline__ void tok_loadv(uint32_t tok, int eh, int lane, uint32_t (&bv)[8][4]) {
    const int r8 = lane & 7;
    const uint32_t va = MT ? tok + lane * 64 + ((r8 >> 1) << 4) : tok + (lane & 15) * 64 + (((lane >> 4) ^ (r8 >> 1)) << 4);
    const uint32_t o0 = eh ? BLK_V(2) : BLK_V(0), o1 = eh ? BLK_V(3) : BLK_V(1);
    #pragma unroll
    for (int n = LO; n < HI; n++) { if (MT) ldsm_x4_t(bv[n], (va ^ ((n & 3) << 4)) + (n < 4 ? o0 : o1)); else ldsm_x4_t(bv[n], (va ^ ((n & 1) << 5)) + BLK_V(n >> 1)); }
}
#define T_VPRE 4
template<int MT, class F>
__device__ __forceinline__ void tok_part1(uint32_t tok, int eh, int lane, uint32_t (&q)[8][4], uint32_t (&sp)[5][2], uint32_t (&pa)[5][2], uint32_t (&bv)[8][4], uint32_t& rng, F&& hold) {
    float e[5][4];
    constexpr int NK = MT ? 5 : 3;
    const int g = lane >> 2, t = lane & 3, mi = lane >> 3, r8 = lane & 7;
    #pragma unroll
    for (int nt = 1; nt < NK; nt++) { e[nt][0] = e[nt][1] = e[nt][2] = e[nt][3] = 0.f; }
    const uint32_t qa = tok + (16 * MT + (mi & 1) * 8 + r8) * 64 + (((mi >> 1) ^ (r8 >> 1)) << 4);
    const uint32_t ka = tok + r8 * 64 + ((mi ^ (r8 >> 1)) << 4);
    uint32_t b[4][NK][4];
    constexpr int PRE = T_HOLD >= 3 ? (MT ? T_KPRE : 4) : 0;
    #pragma unroll
    for (int k2 = 0; k2 < 4; k2++) {
        if (T_HOLD >= 3) { ldsm_x4(q[2 * k2], qa + BLK_Q(k2)); ldsm_x4(q[2 * k2 + 1], (qa ^ 32) + BLK_Q(k2)); }
        if (k2 < PRE) {
            #pragma unroll
            for (int nt = 1; nt < NK; nt++) ldsm_x4(b[k2][nt], ka + BLK_K(k2) + (nt - 1) * 512);
        }
    }
    if (T_HOLD >= 3) hold(ic<0>());
    #pragma unroll
    for (int k2 = 0; k2 < 4; k2++) {
        if (T_HOLD < 3) { ldsm_x4(q[2 * k2], qa + BLK_Q(k2)); ldsm_x4(q[2 * k2 + 1], (qa ^ 32) + BLK_Q(k2)); }
        if (k2 >= PRE) {
            #pragma unroll
            for (int nt = 1; nt < NK; nt++) ldsm_x4(b[k2][nt], ka + BLK_K(k2) + (nt - 1) * 512);
        }
        #pragma unroll
        for (int nt = 1; nt < NK; nt++) if (k2 < T_MMAK) mma16816(e[nt], q[2 * k2], b[k2][nt][0], b[k2][nt][1]);
        #pragma unroll
        for (int nt = 1; nt < NK; nt++) if (k2 < T_MMAK) mma16816(e[nt], q[2 * k2 + 1], b[k2][nt][2], b[k2][nt][3]);
    }
    #pragma unroll
    for (int nt = 1; nt < NK; nt++) asm volatile("" : "+f"(e[nt][0]), "+f"(e[nt][1]), "+f"(e[nt][2]), "+f"(e[nt][3]));
    if (T_HOLD < 3 || T_HOLD >= 5) hold(ic<1>());
    #pragma unroll
    for (int nt = 1; nt < NK; nt++) {
        sp[nt][0] = nt < NK - 1 ? scale_bf2(pack_bf16(e[nt][0], e[nt][1])) : NEG_BIG2; sp[nt][1] = scale_bf2(pack_bf16(e[nt][2], e[nt][3]));
        rng = maxabs_bf2(nt == 1 ? sp[1][0] : (nt < NK - 1 ? maxabs_bf2(rng, sp[nt][0]) : rng), sp[nt][1]);
    }
    const uint32_t keep = (2 * t <= g ? 0x0000ffffu : 0u) | (2 * t + 1 <= g ? 0xffff0000u : 0u);
    sp[NK - 2][0] = (sp[NK - 2][0] & keep) | (NEG_BIG2 & ~keep);
    sp[NK - 1][1] = (sp[NK - 1][1] & keep) | (NEG_BIG2 & ~keep);
    #pragma unroll
    for (int nt = 1; nt < NK; nt++) { pa[nt][0] = nt < NK - 1 ? exp_bf2(sp[nt][0]) : 0u; pa[nt][1] = exp_bf2(sp[nt][1]); }
    tok_loadv<MT, 0, MT ? T_VPRE : 8>(tok, eh, lane, bv);
}
template<int MT, class F, class G, class H, class I>
__device__ __forceinline__ void tok_part2(uint32_t tok, uint32_t exl, uint32_t ost, int eh, int lane, const uint32_t (&q)[8][4], uint32_t (&sp)[5][2], uint32_t (&pa)[5][2], uint32_t (&bv)[8][4], uint32_t rng, bool vb,
                                          F&& wait_v, G&& duty, H&& pace, I&& wait_x) {
    constexpr int NK = MT ? 5 : 3;
    const int mi = lane >> 3, r8 = lane & 7;
    {
        float c[4][4];
        uint32_t b[4][4];
        ldsm16_t(b, exl + 2048);
        duty();
        #pragma unroll
        for (int j = 0; j < 4; j++) { c[j][0] = c[j][1] = c[j][2] = c[j][3] = 0.f; }
        #pragma unroll
        for (int k2 = 0; k2 < 4; k2++) { mma16816(c[(2 * k2) & 3], q[2 * k2], b[k2][0], b[k2][1]); mma16816(c[(2 * k2 + 1) & 3], q[2 * k2 + 1], b[k2][2], b[k2][3]); }
        sp[0][0] = scale_bf2(pack_bf16((c[0][0] + c[1][0]) + (c[2][0] + c[3][0]), (c[0][1] + c[1][1]) + (c[2][1] + c[3][1])));
        sp[0][1] = scale_bf2(pack_bf16((c[0][2] + c[1][2]) + (c[2][2] + c[3][2]), (c[0][3] + c[1][3]) + (c[2][3] + c[3][3])));
    }
    pa[0][0] = exp_bf2(sp[0][0]); pa[0][1] = exp_bf2(sp[0][1]);
    rng = maxabs_bf2(maxabs_bf2(rng, sp[0][0]), sp[0][1]);
    if (__builtin_expect(__any_sync(0xffffffffu, ((rng & 0x7fff7fffu) + 0x3ddf3ddfu) & 0x80008000u), 0)) {
        uint32_t m0 = sp[0][0], m1 = sp[0][1];
        #pragma unroll
        for (int nt = 1; nt < NK; nt++) { if (nt < NK - 1) m0 = max_bf2(m0, sp[nt][0]); m1 = max_bf2(m1, sp[nt][1]); }
        uint32_t mm = max_bf2(__byte_perm(m0, m1, 0x5410), __byte_perm(m0, m1, 0x7632));
        mm = max_bf2(mm, __shfl_xor_sync(0xffffffffu, mm, 1));
        mm = max_bf2(mm, __shfl_xor_sync(0xffffffffu, mm, 2));
        #pragma unroll
        for (int nt = 0; nt < NK; nt++) {
            if (nt < NK - 1) pa[nt][0] = pack_bf16(exd(bf_lo(sp[nt][0]), bf_lo(mm)), exd(bf_hi(sp[nt][0]), bf_lo(mm)));
            pa[nt][1] = pack_bf16(exd(bf_lo(sp[nt][1]), bf_hi(mm)), exd(bf_hi(sp[nt][1]), bf_hi(mm)));
        }
    }
    tok_loadv<MT, MT ? T_VPRE : 8, 8>(tok, eh, lane, bv);
    wait_v();
    constexpr int NQ = MT ? 2 : 4;
    float o[NQ][4][4], l[4] = {0.f, 0.f, 0.f, 0.f};
    const uint32_t ONE = 0x3F803F80u;
    mma16816r(l, pa[1][0], pa[1][1], pa[2][0], pa[2][1], ONE, ONE);
    if (MT) mma16816r(l, pa[3 % NK][0], pa[3 % NK][1], pa[4 % NK][0], pa[4 % NK][1], ONE, ONE);
    mma1688(l, pa[0][0], pa[0][1], ONE);
    #pragma unroll
    for (int j = 0; j < NQ; j++) {
        uint32_t bm[4];
        ldsm_x4(bm, exl + 4096 + (MT ? eh * 1024 : 0) + 512 * j);
        #pragma unroll
        for (int n = 0; n < 4; n++) {
            o[j][n][0] = o[j][n][1] = o[j][n][2] = o[j][n][3] = 0.f;
            if (MT) mma16816r(o[j][n], pa[1][0], pa[1][1], pa[2][0], pa[2][1], bv[4 * j + n][0], bv[4 * j + n][1]);
            else mma16816r(o[j][n], pa[1][0], pa[1][1], pa[2][0], pa[2][1], bv[2 * j + (n >> 1)][2 * (n & 1)], bv[2 * j + (n >> 1)][2 * (n & 1) + 1]);
        }
        if (MT) {
            #pragma unroll
            for (int n = 0; n < 4; n++) mma16816r(o[j][n], pa[3 % NK][0], pa[3 % NK][1], pa[4 % NK][0], pa[4 % NK][1], bv[4 * j + n][2], bv[4 * j + n][3]);
        }
        #pragma unroll
        for (int n = 0; n < 4; n++) mma1688(o[j][n], pa[0][0], pa[0][1], bm[n]);
    }
    #pragma unroll
    for (int j = 0; j < NQ; j++) asm volatile("" : "+f"(o[j][0][0]), "+f"(o[j][1][0]), "+f"(o[j][2][0]), "+f"(o[j][3][0]));
    asm volatile("" : "+f"(l[0]), "+f"(l[2]));
    wait_x();
    bar_arrive_p(12, 384, !vb);
    pace();
    const float i0 = rcp_approx(l[0]), i1 = rcp_approx(l[2]);
    const uint32_t oa = ost + ((mi & 1) * 8 + r8) * 128 + (((mi >> 1) ^ r8) << 4);
    #pragma unroll
    for (int j = 0; j < NQ; j++) {
        stsm_x4((oa ^ ((j & 1) << 6)) + (j >> 1) * 2048, pack_bf16(o[j][0][0] * i0, o[j][0][1] * i0), pack_bf16(o[j][0][2] * i1, o[j][0][3] * i1), pack_bf16(o[j][1][0] * i0, o[j][1][1] * i0), pack_bf16(o[j][1][2] * i1, o[j][1][3] * i1));
        stsm_x4((oa ^ (((j & 1) << 6) | 32)) + (j >> 1) * 2048, pack_bf16(o[j][2][0] * i0, o[j][2][1] * i0), pack_bf16(o[j][2][2] * i1, o[j][2][3] * i1), pack_bf16(o[j][3][0] * i0, o[j][3][1] * i0), pack_bf16(o[j][3][2] * i1, o[j][3][3] * i1));
    }
}

#define X_PRED "@q "
#define X_LANE(ll) ((ll) >> 4)
#define SEND_LANE(ll) ((ll) >> 2)
#define TP_E 0
#define V_EARLY 1
#define S_ARR 4
#ifndef M_LAG
#define M_LAG 2
#endif
#ifndef M_SF
#define M_SF 0
#endif
#ifndef M_F2
#define M_F2 0
#endif
#ifndef M_FENCE
#define M_FENCE 0
#endif
#define SW_FENCE 0
#define PV_FENCE 1
#define IL_AT 3
#define TAIL 0
#define MP_PRE 4
#define VF_EARLY 1
__device__ __forceinline__ void stsm2_p(uint32_t a, const uint32_t (&v)[8], uint32_t skip) {
    asm volatile("{\n.reg .pred p;\nsetp.eq.u32 p, %9, 0;\n@p stmatrix.sync.aligned.m8n8.x4.trans.shared.b16 [%0], {%1,%2,%3,%4};\n"
                 "@p stmatrix.sync.aligned.m8n8.x4.trans.shared.b16 [%0+1024], {%5,%6,%7,%8};\n}\n"
        :: "r"(a), "r"(v[0]), "r"(v[1]), "r"(v[2]), "r"(v[3]), "r"(v[4]), "r"(v[5]), "r"(v[6]), "r"(v[7]), "r"(skip) : "memory");
}
template<int OA, int OB>
__device__ __forceinline__ void send_tile(float c0, float c1, float c2, float c3, uint32_t a, uint32_t b, uint32_t l16) {
    const uint32_t hi = (uint32_t)((uint64_t)g_acc >> 32);
    asm volatile("{\n.reg .pred q, pl, ph;\n.reg .b64 pa, pb;\n.reg .b32 t, w0, w1, w2;\n.reg .f32 x, y, z;\n"
                 "and.b32 t, %7, 0x30;\nsetp.eq.u32 q, t, 0;\nand.b32 t, %7, 0x70;\nsetp.eq.u32 ph, t, 0;\nxor.pred pl, q, ph;\n"
                 "selp.f32 x, 0f00010000, %4, pl;\nselp.f32 y, 0f00010000, %6, ph;\nselp.f32 z, %6, %4, ph;\n"
                 "cvt.rn.bf16x2.f32 w0, x, %3;\ncvt.rn.bf16x2.f32 w1, y, %5;\ncvt.rn.bf16x2.f32 w2, 0f00010000, z;\n"
                 "mov.b64 pa, {%0, %2};\nmov.b64 pb, {%1, %2};\n"
                 "red.relaxed.gpu.global.add.noftz.bf16x2 [pa+%8], w0;\nred.relaxed.gpu.global.add.noftz.bf16x2 [pa+%10], w1;\n" X_PRED "red.relaxed.gpu.global.add.noftz.bf16x2 [pb+%9], w2;\n}\n"
        :: "r"(a), "r"(b), "r"(hi), "f"(c0), "f"(c1), "f"(c2), "f"(c3), "r"(l16), "n"(OA), "n"(OB), "n"(OA + 256) : "memory");
}
__device__ __forceinline__ uint32_t send_ua(uint32_t tile) { return (uint32_t)(uint64_t)g_acc + tile * 1024; }
__device__ __forceinline__ uint32_t send_ub(uint32_t tile) { return (uint32_t)(uint64_t)g_acc + ACC_X + (tile >> 1) * 1024 + (tile & 1) * 256; }
__device__ __forceinline__ void lds_il(float& il, float& ih, uint32_t a) {
    uint32_t x, y; asm volatile("ldmatrix.sync.aligned.m8n8.x2.shared.b16 {%0,%1}, [%2];" : "=r"(x), "=r"(y) : "r"(a) : "memory");
    il = __uint_as_float(x); ih = __uint_as_float(y);
}
template<bool OWN, class F>
__device__ __forceinline__ void stage_w(const uint32_t (&wo)[8][4], uint32_t ol, uint32_t tile, uint32_t so, uint32_t l16, uint32_t nv, uint32_t ila, F&& issued) {
    float il, ih;
    uint32_t b[4][4], sa, sb_, ll;
    float c[2][4];
    auto addr = [&] {
        ll = OWN ? l16 : l16 | (__float_as_uint(c[0][0]) & nv);
        sa = SEND_LANE(ll) + (send_ua(tile) + so); sb_ = X_LANE(ll) + (send_ub(tile) + so);
    };
    ldsm16_t(b, ol);
    lds_il(il, ih, ila);
    if (OWN) addr();
    if (!OWN || SW_FENCE) sched_fence<0>(nv);
    #pragma unroll
    for (int i = 0; i < 2; i++) c[i][0] = c[i][1] = c[i][2] = c[i][3] = 0.f;
    #pragma unroll
    for (int j = 0; j < 4; j++) {
        if (!OWN && j == 3) addr();
        if (OWN && j == S_ARR) { asm volatile("" : "+f"(c[0][0]), "+f"(c[1][0])); sched_fence<4>(nv); issued(); }
        mma16816(c[0], wo[2 * j], b[j][0], b[j][1]); mma16816(c[1], wo[2 * j + 1], b[j][2], b[j][3]);
    }
    if (TP_E || (OWN && V_EARLY && S_ARR == 4)) { asm volatile("" : "+f"(c[0][0]), "+f"(c[1][0])); sched_fence<OWN ? 4 : 5>(nv); }
    if (!OWN || S_ARR >= 4) issued();
    send_tile<0, 0>((c[0][0] + c[1][0]) * il, (c[0][1] + c[1][1]) * ih, (c[0][2] + c[1][2]) * il, (c[0][3] + c[1][3]) * ih, sa, sb_, l16);
}

template<int N> __device__ __forceinline__ void code_pad(uint32_t nv) {
    if (N && nv == 0x7fffffe0u + N % 16) {
        float v = __uint_as_float(nv);
        #pragma unroll
        for (int i = 0; i < N; i++) asm volatile("fma.rn.f32 %0, %0, %0, %0;" : "+f"(v));
        sts32_p(0u, __float_as_uint(v), nv);
    }
}
#define PAD_T0 4
#define PAD_T1 0
#define PAD_S 344
#define PAD_P 97
#define BAR_PRO 1
#define BAR_MEM 2
#define BAR_P   3
#define BAR_PRJ 4
#define BAR_VGO 7
#define BAR_X0  7
#define BAR_S   9
#define BAR_P2  10
#define BAR_O   11
#define BAR_O2  14
#define BAR_TP  15
#define BAR_V   12
#define BAR_FB  13
#define VGO_AT 9
#define TP_N 36
#define TP_N1 24
#define REG_P 200
#define W_FENCE 1
#define WO_PRE 3
#define WO_MID 8
#define WO_EX 8
#define WO_REP 2
#define TP_DELAY 0
#define PRE_W 4
#ifndef M_RES
#define M_RES 5
#endif
#define K_PRE 8
#define K_POS 0
#define LD_FENCE 0
#define CV_FENCE 4
#define ANN_POS 3
#define PRO_V 0
#define PUB_W 0
#define ST_AT 2
#define T_GATE 0
#define MEM_N (T_GATE == 2 ? 384 : 352)
#define VGO_N (256 + (T_HOLD == 2 || T_HOLD == 6 ? 32 : 0))
#define PRO_N ((PRO_V ? 256 : 32 * nqk) + (K_PRE < 8 ? 64 : 0) + ((T_HOLD & 1) ? 32 : 0))
#define S_DUTY 0
#define X_POS 0
#define K_OWN 1
#define TG_MERGE 1
#define K_TOP 0
#define MEM_ROT 1
#define W_PERM 0
#define WO_EARLY 0
#define MP_ACC 4
#define MP_D 0
#define MP_L 2
#define MP_F 0
#define G2_AT 0
#define BAR_G2 5
#define TM_PF 1
#define TS_CAP 64
#define G1_MIN 128
#define G1_0 256
#define G1_NS 1152

__global__ void __cluster_dims__(3, 1, 1) __launch_bounds__(CH_THREADS, 1)
chain_kernel(const __grid_constant__ CUtensorMap tmx, const __grid_constant__ CUtensorMap tmq, const __grid_constant__ CUtensorMap tmk,
             const __grid_constant__ CUtensorMap tmv, const __grid_constant__ CUtensorMap tmo,
             const __grid_constant__ CUtensorMap tma, const __grid_constant__ CUtensorMap tmb, const bf16* __restrict__ mem0, const uint32_t nv_) {
    extern __shared__ __align__(1024) unsigned char smem[];
    const uint32_t sb = smem_u32(smem);
    const int tid = threadIdx.x, lane = tid & 31;
    const int warp = __shfl_sync(0xffffffffu, W_PERM && tid < 256 ? (0x75436210u >> (tid >> 5 << 2)) & 7 : tid >> 5, 0);
    const uint32_t nv = __shfl_sync(0xffffffffu, nv_ * tid, 0);
    const int h = blockIdx.x / 3, r = blockIdx.x % 3;
    const int mi = lane >> 3, r8 = lane & 7;
    const uint32_t bX = sb + SM_BAR, bTOK = bX + 16, bEX = bX + 40, bW = bX + 64, bEV = bX + 104, bFREE = bX + 32, bMEM = bX + 56;
    const int nqk = r < 2 ? 6 : 4;
    if ((sb & 0xFFFFFFu) != SB_OFF) __trap();
    asm volatile("griddepcontrol.launch_dependents;");
    if (tid == 0 && blockIdx.x == 0) GT(40, 0);

    auto load_w = [&](int lo, int hi) {
        #pragma unroll 1
        for (int i = lo; i < hi; i++) {
            const int blk = i >> 2, j = i & 3;
            if (i < 48) {
                const int m = r < 2 ? (j < 3 ? r : 2) : (j < 2 ? j : 2), p = r < 2 ? (j < 3 ? j : r) : (j < 2 ? 3 : j);
                asm volatile("cp.async.bulk.tensor.2d.shared::cluster.global.mbarrier::complete_tx::bytes [%0], [%1, {%3, %4}], [%2];"
                    :: "r"(sb + i * 3072), "l"(m == 0 ? &tmq : (m == 1 ? &tmk : &tmv)), "r"(bW + (blk < 3 ? 0 : (blk < 6 ? 8 : (blk < 10 ? 16 : 24)))), "r"(h * DH + p * 32), "r"(blk * 48) : "memory");
            } else asm volatile("cp.async.bulk.tensor.2d.shared::cluster.global.mbarrier::complete_tx::bytes [%0], [%1, {%3, %4}], [%2];"
                :: "r"(sb + SM_WO + (i - 48) * 8192), "l"(&tmo), "r"(bW + 32), "r"(192 * r + 32 * (i - 48)), "r"(h * DH) : "memory");
        }
    };
    if (tid == 352) {
        #pragma unroll
        for (int i = 0; i < 15; i++) mbar_init(bX + 8 * i, (i == 5 || i == 6) ? 1 + nqk : (i >= 13 ? 9 - nqk : 1));
        asm volatile("fence.mbarrier_init.release.cluster;" ::: "memory");
        mbar_expect_tx(bW, 36864); mbar_expect_tx(bW + 8, 36864); mbar_expect_tx(bW + 16, 49152); mbar_expect_tx(bW + 24, 24576); mbar_expect_tx(bW + 32, 49152);
        load_w(0, 2 * PRE_W);
    }
    if (TM_PF && tid < 4) asm volatile("prefetch.param.tensormap [%0];" :: "l"(__cvta_generic_to_grid_constant(tid == 0 ? &tmo : (tid == 1 ? &tmx : (tid == 2 ? &tma : &tmb)))) : "memory");
    const unsigned epoch = ld_relaxed32(&g_epoch);
    __syncthreads();
    const uint32_t pw0 = ((mi >> 1) * 8 + r8) * 64 + (((2 * (warp & 1) + (mi & 1)) ^ (r8 >> 1)) << 4);
    auto tok_publish = [&](int tb, int k) {
        const uint32_t src = sb + SM_TOK + tb * TOKBUF + r * 8192, bar = bTOK + 8 * tb;
        if (k == 1) asm volatile("{\n.reg .pred p;\nelect.sync _|p, 0xffffffff;\n@p mbarrier.arrive.expect_tx.shared.b64 _, [%0], 16384;\n}\n" :: "r"(bar) : "memory");
        asm volatile("{\n.reg .pred p;\nelect.sync _|p, 0xffffffff;\n"
                     "@p cp.async.bulk.shared::cluster.shared::cta.mbarrier::complete_tx::bytes [%0], [%1], 8192, [%2];\n}\n"
            :: "r"(mapa_u32(src, (r + k) % 3)), "r"(src), "r"(mapa_u32(bar, (r + k) % 3)) : "memory");
    };
    if (warp < 8) {
        asm volatile("setmaxnreg.inc.sync.aligned.u32 %0;" :: "n"(REG_P));
        uint32_t wf[36][4];
        const uint32_t wl = sb + (warp >> 1) * 3072 + pw0;
        float ta0[16], ta1[16];
        auto tp_part = [&](auto lo, auto hi) {
            wg_fence();
            #pragma unroll
            for (int i = lo.value; i < hi.value; i++) {
                if (i == 0) wgmma_n32<0>(ta0, wf[0], desc_from(DESC_LO(SM_X))); else wgmma_n32<1>(ta0, wf[i], desc_from(DESC_LO(SM_X) + (i >> 2) * 256 + (i & 3) * 2));
            }
            #pragma unroll
            for (int i = lo.value; i < hi.value; i++) {
                if (i == 0) wgmma_n32<0>(ta1, wf[0], desc_from(DESC_LO(SM_X + XBUF))); else wgmma_n32<1>(ta1, wf[i], desc_from(DESC_LO(SM_X + XBUF) + (i >> 2) * 256 + (i & 3) * 2));
            }
            wg_commit();
        };
        if (tid == 32) load_w(2 * PRE_W, 40);
        if (tid == 0) GT(41 + blockIdx.x % 3, 7);
        code_pad<PAD_P>(nv);
        mbar_wait(bW, 0);
        #pragma unroll
        for (int i = 0; i < 9; i++) ldsm_x4_t(wf[i], wl + (i / 3) * 12288 + (i % 3) * 1024);
        fence_async_smem(); bar_arrive(BAR_X0, 288);
        mbar_wait(bW + 8, 0);
        #pragma unroll
        for (int i = 9; i < 18; i++) ldsm_x4_t(wf[i], wl + (i / 3) * 12288 + (i % 3) * 1024);
        fence_async_smem(); bar_arrive(BAR_X0 + 1, 288);
        mbar_wait(bX, 0); mbar_wait(bX + 8, 0);
        tp_part(ic<0>(), ic<18>());
        wg_wait0();
        sts128(sb + SM_OST + tid * 16, make_uint4(wf[0][0], wf[0][1], wf[0][2], wf[0][3]));
        mbar_wait(bW + 16, 0);
        #pragma unroll
        for (int i = 18; i < 30; i++) ldsm_x4_t(wf[i], wl + (i / 3) * 12288 + (i % 3) * 1024);
        tp_part(ic<18>(), ic<30>());
        mbar_wait(bW + 24, 0);
        if (tid == 0) GT(41 + blockIdx.x % 3, 0);
        wg_wait0();
        #pragma unroll
        for (int i = 30; i < 36; i++) ldsm_x4_t(wf[i], wl + (i / 3) * 12288 + (i % 3) * 1024);
        fence_async_smem();
        cluster_arrive_rx();
        tp_part(ic<30>(), ic<36>());
        if (tid == 0) GT(41 + blockIdx.x % 3, 2);
        const uint32_t pw = pin(pw0);
        auto tp_store = [&](const float (&acc)[16], uint32_t off) {
            const uint32_t ta = pw + launder(sb + off + (warp >> 1) * 2048);
            stsm_x4_t(ta, pack_bf16(acc[0], acc[1]), pack_bf16(acc[2], acc[3]), pack_bf16(acc[4], acc[5]), pack_bf16(acc[6], acc[7]));
            stsm_x4_t(ta + 1024, pack_bf16(acc[8], acc[9]), pack_bf16(acc[10], acc[11]), pack_bf16(acc[12], acc[13]), pack_bf16(acc[14], acc[15]));
        };
        cluster_wait();
        wg_wait0();
        tp_store(ta0, SM_TOK + r * 8192);
        if (warp == 0) { bar_sync(BAR_PRJ, 256); fence_async_smem(); tok_publish(0, 1); tok_publish(0, 2); } else bar_arrive(BAR_PRJ, 256);
        if (!TAIL) { tp_store(ta1, SM_TOK + TOKBUF + r * 8192); if (T_GATE == 1) bar_arrive(BAR_TP, 288); }
        { const uint4 v = lds128(sb + SM_OST + tid * 16); wf[0][0] = v.x; wf[0][1] = v.y; wf[0][2] = v.z; wf[0][3] = v.w; sts32_p(v.x, v.y, nv); }
        if (tid == 0) GT(41 + blockIdx.x % 3, 4);
        const uint32_t l16 = pin(lane * 16), sbl = sb + l16, l4w = pin(sb + warp * 256 + lane * 4);
        uint32_t wo[8][4];
        const int exo = r < 2 ? (warp < 6 ? r * 2048 : 4096 + (2 * r - 6) * 256) : (warp < 2 ? 6 * 256 : (warp < 4 ? 2048 + 4 * 256 : 4096));
        const bool isqk = warp < nqk, single = G2_AT && r < 2 && (warp & 6) == 2;
        const uint32_t exbar = isqk ? bEX : bEV;
        uint32_t vf[2][4];
        auto prep = [&](int s) {
            const uint32_t va = pw + launder(sb + SM_TOK + (s & 1) * TOKBUF + BLK_V(warp >> 1));
            mbar_wait(bTOK + 8 * (s & 1), (s >> 1) & 1);
            if (WO_EARLY) {
                if (s == 0) mbar_wait(bW + 32, 0);
                #pragma unroll
                for (int i = 0; i < WO_EARLY; i++) ldsm_x4_t(wo[i], pw + launder(sb + SM_WO + (warp >> 1) * 8192) + i * 1024);
                sts32_p(wo[0][0], wo[WO_EARLY ? WO_EARLY - 1 : 0][0], nv);
            }
            if (VF_EARLY) { ldsm_x4_t(vf[0], va); ldsm_x4_t(vf[1], va + 1024); sts32_p(vf[0][0], vf[1][0], nv); }
        };
        prep(0);
        if (!TAIL && MEM_ROT) bar_sync(BAR_MEM, MEM_N);
        for (int s = 0; ; s++) {
            const int par = s & 1;
            const uint32_t va = pw + launder(sb + SM_TOK + par * TOKBUF + BLK_V(warp >> 1)), wa = pw + launder(sb + SM_WO + (warp >> 1) * 8192);
            const uint32_t exu = launder(SM_EX + par * EXBUF);
            {
                float acc[4][4];
                #pragma unroll
                for (int i = 0; i < 4; i++) { acc[i][0] = acc[i][1] = acc[i][2] = acc[i][3] = 0.f; }
                uint32_t b[18][4];
                if (G2_AT) { bar_arrive_p(BAR_VGO, VGO_N, !single); bar_sync_p(isqk ? BAR_G2 : BAR_VGO, isqk ? 192 : VGO_N, isqk && !single); }
                else if (MEM_ROT) bar_sync_p(BAR_VGO, VGO_N, isqk);
                else if (!isqk) { bar_arrive(BAR_MEM, MEM_N); bar_sync(BAR_VGO, VGO_N); } else bar_sync(BAR_MEM, MEM_N);
                if (!TAIL && MP_D) {
                    #pragma unroll
                    for (int i2 = 0; i2 < MP_D; i2++) ldsm_x4_t(b[i2], sbl + SM_MEM + i2 * 512);
                    if (MP_F & 1) bar_arrive_p(BAR_S, 64, !nv);
                }
                #pragma unroll
                for (int i2 = 0; i2 < 18; i2++) {
                    if (!TAIL && MP_D) { if (i2 >= MP_L && i2 - MP_L + MP_D < 18) ldsm_x4_t(b[i2 - MP_L + MP_D], sbl + SM_MEM + (i2 - MP_L + MP_D) * 512); if (MP_F & (2 << i2)) bar_arrive_p(BAR_S, 64, !nv); }
                    else if (!TAIL) ldsm_x4_t(b[i2], sbl + SM_MEM + i2 * 512);
                    else if (i2 >= 1 && i2 - 1 + MP_PRE < 18) ldsm_x4_t(b[i2 - 1 + MP_PRE], sbl + SM_MEM + (i2 - 1 + MP_PRE) * 512);
                    if (i2 == (TAIL ? VGO_AT - MP_PRE + 1 : (MP_D ? VGO_AT - MP_D + MP_L : VGO_AT))) bar_arrive_p(BAR_VGO, VGO_N, !isqk || single);
                    if (G2_AT && i2 == G2_AT) bar_arrive_p(BAR_G2, 192, !isqk || single || r == 2);
                    if (PRO_V && i2 == PRO_V) bar_arrive_p(BAR_PRO, PRO_N, isqk || s == NSEG - 1);
                    mma16816(acc[(2 * i2) % MP_ACC], wf[2 * i2], b[i2][0], b[i2][1]);
                    mma16816(acc[(2 * i2 + 1) % MP_ACC], wf[2 * i2 + 1], b[i2][2], b[i2][3]);
                }
                float q[4];
                #pragma unroll
                for (int i = 0; i < 4; i++) q[i] = MP_ACC == 4 ? (acc[0][i] + acc[1][i]) + (acc[2][i] + acc[3][i]) : (MP_ACC == 3 ? (acc[0][i] + acc[1][i]) + acc[2][i] : acc[0][i] + acc[1][i]);
                const uint32_t lo = pack_bf16(q[0], q[1]), hi = pack_bf16(q[2], q[3]);
                const uint32_t exl = l4w + launder(exu + exo), bar = exbar + par * 8;
                #pragma unroll
                for (int k = 1; k < 3; k++) {
                    const uint32_t exd = mapa_u32(exl, (r + k) % 3), exb = mapa_u32(bar, (r + k) % 3);
                    st_async32(exd, lo, exb); st_async32(exd + 128, hi, exb);
                }
                sts32(exl, lo); sts32(exl + 128, hi);
                __syncwarp();
                asm volatile("{\n.reg .pred p;\nelect.sync _|p, 0xffffffff;\n@p mbarrier.arrive.shared.b64 _, [%0];\n}\n" :: "r"(bar) : "memory");
                if (s < NSEG - 1) bar_sync_p(BAR_PRO, PRO_N, !isqk);
            }
            if (s == 0) mbar_wait(bW + 32, 0);
            if (s == NSEG - 1) break;
            {
                if (!VF_EARLY) { ldsm_x4_t(vf[0], va); ldsm_x4_t(vf[1], va + 1024); }
                #pragma unroll
                for (int i = WO_EARLY; i < WO_PRE; i++) ldsm_x4_t(wo[i], wa + i * 1024);
                if (WO_PRE < 8) {
                    #pragma unroll
                    for (int k = 0; k < WO_REP; k++) mbar_wait(bEX + 8 * par, (s >> 1) & 1);
                    #pragma unroll
                    for (int i = WO_PRE; i < 8; i++) ldsm_x4_t(wo[i], wa + i * 1024);
                }
                mbar_wait(bEV + 8 * par, (s >> 1) & 1);
                const uint32_t vm0 = lds32(l4w + exu + 4096), vm1 = lds32(l4w + exu + 4096 + 128);
                const uint32_t big = bar_red_or(BAR_P, 352, 0u);
                uint32_t pb[4]; ldsm_x4_t(pb, sbl + SM_P);
                uint32_t pm = ldsm_x1_t(sbl + SM_P + 512);
                float o0[4] = {0.f, 0.f, 0.f, 0.f}, o1[4] = {0.f, 0.f, 0.f, 0.f}, o2[4] = {0.f, 0.f, 0.f, 0.f};
                if (__builtin_expect(big, 0)) {
                    bar_sync(BAR_P2, 352);
                    ldsm_x4_t(pb, sbl + SM_P); pm = ldsm_x1_t(sbl + SM_P + 512);
                }
                mma16816(o0, vf[0], pb[0], pb[1]);
                mma16816(o1, vf[1], pb[2], pb[3]);
                mma1688(o2, vm0, vm1, pm);
                uint32_t oa = pm;
                #pragma unroll
                for (int i = 0; i < 8; i++) oa ^= wo[i][0];
                oa = l4w | (oa & nv);
                sts32(oa + SM_O, pack_bf16((o0[0] + o1[0]) + o2[0], (o0[1] + o1[1]) + o2[1]));
                sts32(oa + SM_O + 128, pack_bf16((o0[2] + o1[2]) + o2[2], (o0[3] + o1[3]) + o2[3]));
                const uint32_t xd = uni(DESC_LO(SM_X) + par * (XBUF >> 4));
                auto tp = [&](auto lo, auto hi) {
                    #pragma unroll
                    for (int i = lo.value; i < hi.value; i++) {
                        if (i == 0) wgmma_n32<0>(ta1, wf[0], desc_from(xd));
                        else wgmma_n32<1>(ta1, wf[i], desc_from(xd + (i >> 2) * 256 + (i & 3) * 2));
                    }
                };
                bar_sync(BAR_O, 352);
                stage_w<false>(wo, sbl + SM_O, 12 * r + warp, SLOT_OFF(s + 1), l16, nv, sbl + SM_IL, [&] {
                    if (TP_E) { bar_sync(BAR_V, 384); wg_fence(); tp(ic<0>(), ic<TP_E>()); } });
                STAMP(warp);
                if (!TP_E) { bar_sync(BAR_V, 384); wg_fence(); }
                STAMP(12);
                tp(ic<TP_E>(), ic<TP_N>());
                wg_commit();
                prep(s + 1);
                if (!TAIL) { wg_wait0(); if (T_GATE == 1) bar_arrive(BAR_TP, 288); tp_store(ta1, SM_TOK + par * TOKBUF + r * 8192); STAMP(13 + (warp >> 2)); if (MEM_ROT) bar_sync(BAR_MEM, MEM_N); }
            }
        }
        cluster_arrive(); cluster_wait();
    } else {
        asm volatile("setmaxnreg.dec.sync.aligned.u32 %0;" :: "n"(504 - 2 * REG_P));
        const int a = warp - 8;
        const uint32_t sbl = sb + lane * 16;
        if (a < 3) {
            const uint32_t zs = 3 * blockIdx.x + (r8 >> 1);
            const uint32_t zoff = (r8 < 6 ? (zs >> 3) * 1024 + ((zs >> 2) & 1) * 256 + (zs & 3) * 32 : ACC_X + (blockIdx.x >> 1) * 1024 + (blockIdx.x & 1) * 256) + (lane & 1) * 16;
            const uint32_t zskip = r8 >= 6 && blockIdx.x >= 36;
            if (a == 1) {
                st_relaxed128_p((uint4*)(g_acc + zoff + SLOT_OFF(mi)), make_uint4(0, 0, 0, 0), zskip);
                __threadfence();
                __syncwarp();
                if (lane == 0) st_relaxed32(&g_init[blockIdx.x], epoch);
            }
            {
                #pragma unroll
                for (int i = 0; i < 6; i++) {
                    const int c = tid - 256 + 96 * i;
                    const unsigned short* m = (const unsigned short*)mem0 + c;
                    uint4 v;
                    v.x = m[0] | ((uint32_t)m[DM] << 16); v.y = m[2 * DM] | ((uint32_t)m[3 * DM] << 16);
                    v.z = m[4 * DM] | ((uint32_t)m[5 * DM] << 16); v.w = m[6 * DM] | ((uint32_t)m[7 * DM] << 16);
                    sts128(sb + SM_MEM + c * 16, v);
                }
                sts32(sb + SM_SG + 36, 0u);
            }
            asm volatile("barrier.cluster.arrive.release.aligned;" ::: "memory");
            { int it = 0; while (__any_sync(0xffffffffu, ld_relaxed32(&g_init[a * 32 + lane]) != epoch) && ++it < SPIN_LIMIT) {} }
            __threadfence();
            const uint32_t kl0 = (a < 2 ? SM_TOK + (16 * a + (mi & 1) * 8 + r8) * 64 + (((mi >> 1) ^ (r8 >> 1)) << 4) : SM_EX + 2048 + ((((mi & 1) << 1) | (mi >> 1)) * 8 + r8) * 16);
            const uint32_t l16 = pin(lane * 16);
            uint32_t kf[8][4], wo[8][4];
            auto load_k = [&](int tb, uint32_t kl, auto lo, auto hi) {
                const uint32_t ka = kl + launder(sb + tb * TOKBUF);
                #pragma unroll
                for (int kk = lo.value; kk < hi.value; kk++) ldsm_x4(kf[kk], (ka ^ ((kk & 1) << 5)) + BLK_K(kk >> 1));
            };
            code_pad<PAD_S>(nv);
            cluster_wait();
            if (a == 0 && lane == 0) { mbar_expect_tx(bEX, 4096 - 256 * nqk); mbar_expect_tx(bEV, 256 * nqk); }
            if (a < 2) bar_arrive(BAR_MEM, MEM_N); else bar_sync(BAR_MEM, MEM_N);
            mbar_wait(bW + 32, 0);
            #pragma unroll
            for (int i = 0; i < 8; i++) ldsm_x4_t(wo[i], pw0 + sb + SM_WO + (warp >> 1) * 8192 + i * 1024);
            sts128(sbl + SM_STASH + a * 1024 + 512, make_uint4(kl0, (pw0 ^ 32) + sb + SM_WO + 5 * 8192, zoff | ((zskip || lane >= 8) << 31), 0u));
            sts128(sbl + SM_STASH + a * 1024, make_uint4(a * 12288 + (lane >> 4) * 1024 + (mi & 1) * 256 + r8 * 16, ACC_X + a * 6144 + (lane >> 4) * 1024 + (mi & 1) * 256 + r8 * 4,
                                                         ((lane ^ mi) & 1) ? 0u : ~0u, sb + SM_MEM + a * 3072 + mi * 256 + r8 * 16 + (r8 & 1 ? 2 : 130)));
            const uint32_t stash = l16 + uni(sb + SM_STASH + a * 1024);
            #pragma unroll
            for (int i = 0; i < 8; i++) ldsm_x4_t(kf[i], (pw0 ^ 32) + sb + SM_WO + 5 * 8192 + i * 1024);
            if (a < 2) { mbar_wait(bTOK, 0); load_k(0, kl0, ic<0>(), ic<K_PRE>()); }
            __syncwarp();
            int sn = 0;
            #pragma unroll 1
            while (sn < NSEG - 1) {
              uint32_t bad;
              #pragma unroll 1
              do {
                const int s = sn, par = s & 1;
                const uint32_t exu = launder(sb + par * EXBUF);
                const uint32_t exl = l16 + exu + SM_EX;
                const uint32_t t0 = gtime_lo();
                STAMP(15); STAMPV(31, t0);
                if (!TAIL && a == 2) st_relaxed32_p(&g_ts[blockIdx.x], (t0 & ~31u) | (s & 31), l16);
                if (a == 1) {
                    const uint32_t z = lds32(stash + 520);
                    st_relaxed128_p((uint4*)(g_acc + (z + SLOT_OFF(s + 3))), make_uint4(0, 0, 0, 0), z >> 31);
                }
                if (a == 0 && l16 == 0) { mbar_expect_tx(bEX + 8 * (par ^ 1), 4096 - 256 * nqk); mbar_expect_tx(bEV + 8 * (par ^ 1), 256 * nqk); }
                uint32_t tg;
                auto first_half = [&](auto role) {
                constexpr bool M = role.value;
                auto publish = [&] {
                    asm volatile("{\n.reg .pred p;\nelect.sync _|p, 0xffffffff;\n"
                                 "@p cp.async.bulk.shared::cluster.global.mbarrier::complete_tx::bytes.multicast::cluster [%0], [%1], 8192, [%2], %3;\n}\n"
                        :: "r"(sb + SM_TOK + (par ^ 1) * TOKBUF + r * 8192), "l"(g_tokx[blockIdx.x]), "r"(bTOK + 8 * (par ^ 1)), "h"((unsigned short)(7 ^ (1 << r))) : "memory");
                };
                uint32_t sl, sh, kl = 0, w2 = 0;
                if (M) {
                    if (TAIL) { bar_sync(BAR_TP, 288); __syncwarp(); st_relaxed32_p(&g_ts[blockIdx.x], (gtime_after(lds32(stash + 524)) & ~31u) | (s & 31), l16); }
                    fence_async_smem();
                    if (l16 == 0) {
                        asm volatile("cp.async.bulk.global.shared::cta.bulk_group [%0], [%1], 8192;\ncp.async.bulk.commit_group;"
                            :: "l"(g_tokx[blockIdx.x]), "r"(sb + SM_TOK + (par ^ 1) * TOKBUF + r * 8192) : "memory");
                        mbar_expect_tx(bTOK + 8 * (par ^ 1), 16384); mbar_expect_tx(bMEM, 10368);
                        if (s == 0) mbar_expect_tx(bX, XBUF);
                        if (s + 3 < NSEG) mbar_expect_tx(bX + 8 * (par ^ 1), XBUF);
                    }
                    __syncwarp();
                    if (s > 0 && s + 2 < NSEG) mbar_wait(bX + 8 * par, ((s >> 1) & 1) ^ 1);
                    if (PUB_W == 0) asm volatile("cp.async.bulk.wait_group 0;" ::: "memory");
                    kl = lds32(stash + 512);
                }
                if (!M && K_PRE < 8) {
                    const uint32_t kl = lds32(stash + 512);
                    if (K_OWN == 3) mbar_wait(bTOK + 8 * par, (s >> 1) & 1);
                    if (K_TOP) load_k(par, kl, ic<K_PRE>(), ic<K_PRE + K_TOP>());
                    bar_sync(BAR_PRO, PRO_N);
                    load_k(par, kl, ic<K_PRE + K_TOP>(), ic<8>());
                }
                uint32_t pst = (launder(l16) >> 2) + launder(sb + SM_P + a * 256);
                if (!M) {
                    uint32_t x = kf[0][0];
                    #pragma unroll
                    for (int i = 1; i < 8; i++) x ^= kf[i][0];
                    sts32_p(pst, x, nv);
                }
                mbar_wait(bEX + 8 * par, (s >> 1) & 1);
                if (!M) {
                    uint32_t b[4][4];
                    ldsm16_t(b, exl);
                    float c[4][4];
                    #pragma unroll
                    for (int j = 0; j < 4; j++) { c[j][0] = c[j][1] = c[j][2] = c[j][3] = 0.f; }
                    #pragma unroll
                    for (int j = 0; j < 4; j++) { mma16816(c[(2 * j) & 3], kf[2 * j], b[j][0], b[j][1]); mma16816(c[(2 * j + 1) & 3], kf[2 * j + 1], b[j][2], b[j][3]); }
                    sl = scale_bf2(pack_bf16((c[0][0] + c[1][0]) + (c[2][0] + c[3][0]), (c[0][1] + c[1][1]) + (c[2][1] + c[3][1])));
                    sh = scale_bf2(pack_bf16((c[0][2] + c[1][2]) + (c[2][2] + c[3][2]), (c[0][3] + c[1][3]) + (c[2][3] + c[3][3])));
                } else {
                    float c[4][4];
                    #pragma unroll
                    for (int j = 0; j < 4; j++) { c[j][0] = c[j][1] = c[j][2] = c[j][3] = 0.f; }
                    uint32_t k[4][4], b[4][4];
                    #pragma unroll
                    for (int j = 0; j < 4; j++) { ldsm_x4_t(k[j], kl + exu + 512 * j); ldsm_x4_t(b[j], exl + 512 * j); }
                    if (M_SF) sched_fence<9>(nv);
                    #pragma unroll
                    for (int j = 0; j < 4; j++) { mma16816(c[2 * (j & 1)], k[j], b[j][0], b[j][1]); mma16816(c[2 * (j & 1) + 1], k[j], b[j][2], b[j][3]); }
                    if (PUB_W == 0) publish();
                    sh = sl = scale_bf2(pack_bf16((c[0][0] + c[1][2]) + (c[2][0] + c[3][2]), (c[0][1] + c[1][3]) + (c[2][1] + c[3][3])));
                }
                sts32(pst, pack_bf16(ex2(bf_lo(sl) * LOG2E), ex2(bf_hi(sl) * LOG2E)));
                if (!M) sts32(pst + 128, pack_bf16(ex2(bf_lo(sh) * LOG2E), ex2(bf_hi(sh) * LOG2E)));
                if (S_DUTY && !M) {
                    if (a == 0)
                        asm volatile("{\n.reg .pred p;\nelect.sync _|p, 0xffffffff;\n"
                                     "@p cp.async.bulk.shared::cluster.global.mbarrier::complete_tx::bytes [%0], [%1], 384, [%2];\n"
                                     "@p mbarrier.arrive.expect_tx.shared.b64 _, [%2], 384;\n}\n"
                            :: "r"(sb + SM_TS), "l"(g_ts), "r"(bFREE) : "memory");
                    else if (s > 0 && s + 3 < NSEG)
                        asm volatile("{\n.reg .pred p;\nelect.sync _|p, 0xffffffff;\n"
                                     "@p cp.async.bulk.tensor.3d.shared::cluster.global.mbarrier::complete_tx::bytes.multicast::cluster [%0], [%1, {%3, %4, %5}], [%2], %6;\n}\n"
                            :: "r"(sb + SM_X + (par ^ 1) * XBUF + r * 12288), "l"(&tmx), "r"(bX + 8 * (par ^ 1)), "r"(0), "r"((s + 3) * SEG), "r"(3 * r), "h"((unsigned short)7) : "memory");
                }
                const uint32_t big = bar_red_or(BAR_P, 352, ((maxabs_bf2(sl, sh) & 0x7fff7fffu) + 0x3ddf3ddfu) & 0x80008000u);
                auto denom = [&] {
                    uint32_t pb[4]; ldsm_x4_t(pb, l16 + sb + SM_P);
                    const uint32_t pm = ldsm_x1_t(l16 + sb + SM_P + 512), ONE = 0x3F803F80u;
                    float l0[4] = {0.f, 0.f, 0.f, 0.f}, l1[4] = {0.f, 0.f, 0.f, 0.f}, l2[4] = {0.f, 0.f, 0.f, 0.f};
                    mma16816r(l0, ONE, ONE, ONE, ONE, pb[0], pb[1]);
                    mma16816r(l1, ONE, ONE, ONE, ONE, pb[2], pb[3]);
                    mma1688(l2, ONE, ONE, pm);
                    const float dl = (l0[0] + l1[0]) + l2[0], dh = (l0[1] + l1[1]) + l2[1];
                    sts32(pst + (SM_IL - SM_P) - a * 128, __float_as_uint(rcp_approx(a ? dh : dl)));
                };
                if (!M) { denom(); bar_sync_p(BAR_O, 352, big); }
                if (__builtin_expect(big, 0)) {
                    uint32_t m2 = max_bf2(sl, sh);
                    m2 = max_bf2(m2, __shfl_xor_sync(0xffffffffu, m2, 4));
                    m2 = max_bf2(m2, __shfl_xor_sync(0xffffffffu, m2, 8));
                    m2 = max_bf2(m2, __shfl_xor_sync(0xffffffffu, m2, 16));
                    const uint32_t lq = l16 | (m2 & nv);
                    if (lq < 64) sts32(lq + sb + SM_P + 768 + a * 4, m2);
                    bar_sync(BAR_S, 96);
                    const uint4 m = lds128(sb + SM_P + 768 + (lq & 0x30));
                    m2 = max_bf2(max_bf2(m.x, m.y), m.z);
                    const float ml = bf_lo(m2), mh = bf_hi(m2);
                    sts32(pst, pack_bf16(exd(bf_lo(sl), ml), exd(bf_hi(sl), mh)));
                    if (!M) sts32(pst + 128, pack_bf16(exd(bf_lo(sh), ml), exd(bf_hi(sh), mh)));
                    bar_sync(BAR_P2, 352);
                    if (!M) { denom(); bar_sync(BAR_O, 352); }
                }
                const uint32_t ll = launder(l16), so = SLOT_OFF(launder(s) + 1);
                if (!M) {
                    stage_w<true>(wo, l16 + sb + SM_O, 12 * r + warp, so, ll, nv, l16 + sb + SM_IL, [&] { if (TP_E || V_EARLY) bar_arrive(BAR_V, 384); });
                } else {
                    w2 = lds32(stash + 516);
                    #pragma unroll
                    for (int i = M_RES; i < 8; i++) ldsm_x4_t(kf[i], w2 + i * 1024);
                    if (PUB_W == 1) { asm volatile("cp.async.bulk.wait_group 0;" ::: "memory"); publish(); }
                    const uint32_t sa = launder(SEND_LANE(ll) + (send_ua(12 * r + 10) + so)), sb_ = launder(X_LANE(ll) + (send_ub(12 * r + 10) + so));
                    bar_sync_p(BAR_O, 352, (kf[5][0] ^ kf[6][0] ^ kf[7][0] ^ sa ^ sb_) & nv);
                    #pragma unroll
                    for (int k = 0; k < M_LAG; k++) mbar_wait(bEX + 8 * par, (s >> 1) & 1);
                    float c[4][4], il, ih;
                    #pragma unroll
                    for (int i = 0; i < 4; i++) c[i][0] = c[i][1] = c[i][2] = c[i][3] = 0.f;
                    uint32_t b[4][4];
                    #pragma unroll
                    for (int j = 0; j < 4; j++) ldsm_x4_t(b[j], l16 + sb + SM_O + 512 * (3 - j));
                    lds_il(il, ih, l16 + sb + SM_IL);
                    sched_fence<11>(nv);
                                    #pragma unroll
                    for (int j = 0; j < 4; j++) {
                        if (j == 2) { if (M_F2) sched_fence<10>(nv); }
                        mma16816(c[0], wo[6 - 2 * j], b[j][0], b[j][1]); mma16816(c[2], kf[6 - 2 * j], b[j][0], b[j][1]);
                        mma16816(c[1], wo[7 - 2 * j], b[j][2], b[j][3]); mma16816(c[3], kf[7 - 2 * j], b[j][2], b[j][3]);
                    }
                    asm volatile("" : "+f"(c[0][0]), "+f"(c[1][0]), "+f"(c[2][0]), "+f"(c[3][0]));
                    if (TP_E || V_EARLY) { if (M_FENCE == 1) sched_fence<8>(nv); else asm volatile("" : "+f"(il) : "f"(c[0][0] + c[1][0]), "f"(c[2][0] + c[3][0])); if (M_FENCE < 2) bar_arrive(BAR_V, 384); }
                    send_tile<0, 0>((c[0][0] + c[1][0]) * il, (c[0][1] + c[1][1]) * ih, (c[0][2] + c[1][2]) * il, (c[0][3] + c[1][3]) * ih, sa, sb_, ll);
                    if (M_FENCE == 2) bar_arrive(BAR_V, 384);
                    send_tile<1024, 256>((c[2][0] + c[3][0]) * il, (c[2][1] + c[3][1]) * ih, (c[2][2] + c[3][2]) * il, (c[2][3] + c[3][3]) * ih, sa, sb_, ll);
                    if (M_FENCE == 3) bar_arrive(BAR_V, 384);
                }
                };
                if (a < 2) first_half(ic<0>()); else first_half(ic<1>());
                STAMP(warp);
                if (!TP_E && !V_EARLY) bar_arrive(BAR_V, 384);
                {
                    const uint32_t cd = lds32(stash + 12), xa = (launder(l16) >> 2) + launder(sb + SM_XT + a * 384);
                    if (a < 2) { const uint32_t kl = lds32(stash + 512); mbar_wait(bTOK + 8 * (par ^ 1), ((s + 1) >> 1) & 1); load_k(par ^ 1, kl, ic<0>(), ic<K_PRE>()); }
                    else {
                        STAMP(16 + a);
                        asm volatile("{\n.reg .pred p, q;\n.reg .b64 w;\n.reg .b32 t, u, d, n;\nmov.b32 n, 100000;\n"
                                     "WT_%=:\nld.volatile.shared.u32 %0, [%1];\nmov.u64 w, %%globaltimer;\nmov.b64 {t, u}, w;\nsub.s32 n, n, 1;\nsetp.gt.s32 q, n, 0;\nor.b32 t, t, 1;\nxor.b32 t, t, %2;\n"
                                     "sub.s32 d, t, %0;\nand.b32 d, d, 0x80000001;\nsetp.ne.and.u32 p, d, 0, q;\n@p bra.uni WT_%=;\n}\n" : "=r"(tg) : "r"(sb + SM_SG + 36 + (l16 >> 16)), "r"(par + (l16 >> 16)) : "memory");
                        asm volatile("{\n.reg .pred p;\nelect.sync _|p, 0xffffffff;\n"
                                     "@p cp.async.bulk.tensor.3d.shared::cluster.global.mbarrier::complete_tx::bytes.multicast::cluster [%0], [%1, {%3, %4, %5}], [%2], %9;\n"
                                     "@p cp.async.bulk.tensor.3d.shared::cluster.global.mbarrier::complete_tx::bytes.multicast::cluster [%6], [%7, {%3, %4, %8}], [%2], %9;\n}\n"
                            :: "r"(sb + SM_MEM + r * 3072), "l"(&tma), "r"(bMEM), "r"((par ^ 1) * 32), "r"((s + 1) & 2), "r"(12 * r), "r"(sb + SM_XT + r * 384), "l"(&tmb), "r"(ACC_X / 1024 + 6 * r), "h"((unsigned short)7) : "memory");
                        STAMPV(30, tg);
                    }
                    STAMP(19 + a);
                    mbar_wait(bMEM, par);
                    uint32_t x[3], k[3];
                    #pragma unroll
                    for (int j = 0; j < 3; j++) { x[j] = lds32(xa + 128 * j); k[j] = lds32(cd - 2 + 1024 * j); }
                    #pragma unroll
                    for (int j = 0; j < 3; j++) sts16(cd + 1024 * j, (uint16_t)x[j]);
                    bad = __any_sync(0xffffffffu, !((x[0] & x[1] & x[2]) & (k[0] & k[1] & k[2]) & (ACC_FULL << 16)));
                    STAMP(22 + a); STAMPV(27 + a, bad);
                    bar_sync_p(BAR_MEM, MEM_N, bad);
                }
              } while (++sn < NSEG - 1 && !bad);
                {
                    if (bad) {
                        uint32_t c = nv, cx;
                        const uint32_t lq = l16 | (lds32(stash + 524) & nv), so = SLOT_OFF(sn);
                        const uint4 ad = lds128(stash);
                        const unsigned char* pm = launder_p(g_acc + (ad.x + so));
                        const unsigned char* px = launder_p(g_acc + (ad.y + so));
                        int it = 0;
                        do {
                            const uint32_t again = ~(c & __shfl_xor_sync(0xffffffffu, c, 1)) & (ACC_FULL << 16);
                            uint4 u[6]; uint32_t x[3];
                            #pragma unroll
                            for (int j = 0; j < 6; j++) { u[j] = make_uint4(~0u, ~0u, ~0u, ~0u); ld_relaxed128_p(u[j], (const uint4*)(pm + 2048 * j), again); }
                            #pragma unroll
                            for (int j = 0; j < 3; j++) x[j] = ld_relaxed32((const uint32_t*)(px + 2048 * j));
                            c = ~0u;
                            #pragma unroll
                            for (int j = 0; j < 6; j++) {
                                if (again) sts128(lq + sb + SM_MEM + a * 3072 + 512 * j, u[j]);
                                c &= u[j].x;
                            }
                            __syncwarp();
                            #pragma unroll
                            for (int j = 0; j < 3; j++) sts16(ad.w + 1024 * j, (uint16_t)x[j]);
                            c |= ad.z;
                            cx = x[0] & x[1] & x[2];
                        } while (__any_sync(0xffffffffu, !(c & cx & (ACC_FULL << 16))) && ++it < SPIN_LIMIT);
                        bar_sync(BAR_MEM, MEM_N);
                    }
                }
            }
            if (TAIL && a == 2) bar_arrive(BAR_TP, 288);
        } else {
            cluster_arrive_rx();
            const uint32_t l16 = pin(lane * 16);
            bf16* dst = g_otok + h * 4096 + (r ? 1024 : 0) + (r == 2 ? 2048 : 0);
            {
                #pragma unroll
                for (int sg = 0; sg < 2; sg++) {
                    bar_sync(BAR_X0 + sg, 288);
                    if (lane == 0) {
                        mbar_expect_tx(bX + 8 * sg, XBUF);
                        #pragma unroll
                        for (int c = 0; c < 3; c++)
                            asm volatile("cp.async.bulk.tensor.3d.shared::cluster.global.mbarrier::complete_tx::bytes [%0], [%1, {%3, %4, %5}], [%2];"
                                :: "r"(sb + SM_X + sg * XBUF + c * 12288), "l"(&tmx), "r"(bX + 8 * sg), "r"(0), "r"(sg * SEG), "r"(3 * c) : "memory");
                    }
                    __syncwarp();
                }
                if (lane == 0) load_w(40, 54);
                __syncwarp();
                cluster_wait();
            }
            __syncwarp();
            auto t_loop = [&](auto mtile) {
            constexpr int MT = mtile.value;
            uint32_t q[8][4], sp[5][2], pa[5][2], bv[8][4], rng;
            code_pad<MT ? PAD_T1 : PAD_T0>(nv);
            auto issue_x = [&](int sg) {
                asm volatile("{\n.reg .pred p, q;\nelect.sync _|p, 0xffffffff;\nsetp.eq.and.u32 q, %5, 3, p;\n"
                             "@p cp.async.bulk.tensor.3d.shared::cluster.global.mbarrier::complete_tx::bytes.multicast::cluster [%0], [%1, {%3, %4, %5}], [%2], %6;\n"
                             "@q cp.async.bulk.tensor.3d.shared::cluster.global.mbarrier::complete_tx::bytes.multicast::cluster [%7], [%1, {%3, %4, %3}], [%2], %6;\n}\n"
                    :: "r"(sb + SM_X + (sg & 1) * XBUF + r * 12288), "l"(&tmx), "r"(bX + 8 * (sg & 1)), "r"(0), "r"(sg * SEG), "r"(3 * r), "h"((unsigned short)7), "r"(sb + SM_X + (sg & 1) * XBUF) : "memory");
            };
            mbar_wait(bTOK, 0);
            if (MT) { issue_x(2); issue_x(3); }
            #pragma unroll 1
            for (int s = 0; s < NSEG; s++) {
                const int par = s & 1;
                if (K_OWN) mbar_wait(bTOK + 8 * par, (s >> 1) & 1);
                const uint32_t tok = launder(sb + SM_TOK + par * TOKBUF), exl = l16 + launder(sb + SM_EX + par * EXBUF);
                const int ln = launder(l16) >> 4;
                auto announce = [&] {
                    if (s > 0) {
                        if (lane == 0) {
                            asm volatile("cp.async.bulk.wait_group 0;" ::: "memory");
                            st_relaxed32(&g_prog[blockIdx.x], epoch << 8 | s);
                        }
                        __syncwarp();
                        if (lane == 0 && blockIdx.x == 0) GT(40, s);
                    }
                };
                if (ANN_POS == 0) announce();
                tok_part1<MT>(tok, MT ? r - 1 : 0, ln, q, sp, pa, bv, rng, [&](auto pos) {
                    if (ANN_POS == 3 && (T_HOLD < 5 || pos.value == 0)) announce();
                    if (T_GATE == 1 && pos.value == 0) bar_sync(BAR_TP, 288);
                    if (T_GATE == 2 && pos.value == 0) bar_sync(BAR_MEM, MEM_N);
                    if (T_HOLD == 4 || (T_HOLD >= 5 && pos.value == 0)) sched_fence<6 + MT>(nv);
                    else if (T_HOLD) { if (s < NSEG - 1) bar_sync((T_HOLD & 1) ? BAR_PRO : BAR_VGO, (T_HOLD & 1) ? PRO_N : VGO_N); else if (!(T_HOLD & 1)) bar_arrive(BAR_VGO, VGO_N); sched_fence<26 + MT>(nv); } });
                if (ANN_POS == 1) announce();
                STAMP(25);
                mbar_wait(bEX + 8 * par, (s >> 1) & 1);
                STAMP(26);
                auto duty = [&] { if (!S_DUTY && s + 1 < NSEG) {
                    asm volatile("{\n.reg .pred p;\nelect.sync _|p, 0xffffffff;\n"
                                 "@p cp.async.bulk.shared::cluster.global.mbarrier::complete_tx::bytes [%0], [%1], 384, [%2];\n"
                                 "@p mbarrier.arrive.expect_tx.shared.b64 _, [%2], 384;\n}\n"
                        :: "r"(sb + SM_TS), "l"(g_ts), "r"(bFREE) : "memory");
                    if (X_POS == 0 && MT && s > 0 && s + 3 < NSEG) issue_x(s + 3);
                } };
                auto pace = [&] { if (s + 1 < NSEG) {
                    if (X_POS == 2 && MT && s > 0 && s + 3 < NSEG) issue_x(s + 3);
                    const uint32_t lo = min(launder(l16), 368u), b = (gtime_lo() & ~31u) - 0x01000000u + s + (lo >> 16);
                    const uint32_t c = (b & ~31u) + (G1_NS + (s == 0 ? G1_0 : 0)) + (par ^ 1);
                    if (K_OWN) mbar_wait(bFREE, par); else mbar_wait2(bFREE, par, bTOK + 8 * (par ^ 1), ((s + 1) >> 1) & 1);
                    uint4 ts = lds128(sb + SM_TS + lo);
                    int it = 0; uint32_t m;
                    while (true) {
                        m = __reduce_max_sync(0xffffffffu, max(max(__funnelshift_r(ts.x - b, ts.x - b, 5), __funnelshift_r(ts.y - b, ts.y - b, 5)), max(__funnelshift_r(ts.z - b, ts.z - b, 5), __funnelshift_r(ts.w - b, ts.w - b, 5))));
                        if (__builtin_expect(m < 0x00100000u, 1) || ++it >= 64) break;
                        ts = ld_relaxed128((const uint4*)((const char*)g_ts + lo));
                    }
                    asm volatile("st.volatile.shared.u32 [%0], %1;" :: "r"(sb + SM_SG + 36), "r"(c + (min(m, 0x00080000u) << 5)) : "memory");
                } };
                auto wait_v = [&] {
                    if (X_POS == 1 && MT && s > 0 && s + 3 < NSEG) issue_x(s + 3);
                    mbar_wait(bEV + 8 * par, (s >> 1) & 1); };
                auto wait_x = [&] { if (__builtin_expect(s == 0, 0)) mbar_wait(bX, 1); };
                tok_part2<MT>(tok, exl, sb + SM_OST, MT ? r - 1 : 0, launder(l16) >> 4, q, sp, pa, bv, rng, s < NSEG - 1, wait_v, duty, pace, wait_x);
                STAMP(11);
                fence_async_smem();
                __syncwarp();
                if (lane == 0) {
                    asm volatile("cp.async.bulk.global.shared::cta.bulk_group [%0], [%1], 2048;" :: "l"(dst), "r"(sb + SM_OST) : "memory");
                    if (!MT) asm volatile("cp.async.bulk.global.shared::cta.bulk_group [%0], [%1], 2048;" :: "l"(dst + 2048), "r"(sb + SM_OST + 2048) : "memory");
                    asm volatile("cp.async.bulk.commit_group;" ::: "memory");
                    if (__builtin_expect(s >= NSEG - 2, 0)) {
                        asm volatile("cp.async.bulk.wait_group 0;" ::: "memory");
                        st_relaxed32(&g_prog[blockIdx.x], epoch << 8 | (s + 1));
                        if (blockIdx.x == 0 && s == NSEG - 1) GT(40, NSEG);
                    }
                }
                __syncwarp();
                dst += SEG * NH * DH;
            }
            };
            if (r == 0) t_loop(ic<0>()); else t_loop(ic<1>());
        }
        cluster_arrive(); cluster_wait();
    }
}
#define SD_THREADS 384
#define SD_CTAS  36
#define BT_RS    4624
#define SD_BT    0
#define SD_STG   74752
#define SD_EF    (SD_STG + 57344)
#define SD_BC    (SD_STG)
#define KSLOTS   5
#define BC_BYTES 10240
#define BC_LBO   1280
#define SD_KP    (SD_STG + 90112)
#define SD_Q0    205824
#define SD_Q1    (SD_STG + 111616)
#define SD_OST   (SD_Q0 + 8192)
#define SD_XCH   (SD_Q0 + 8192)
#define SD_BAR   224256
#define SD_TOTAL 224768
#define SD_SPIN  (1 << 22)
#define PART_SLOTS 8
#define SD_WOP 300
#define SD_GO 0
#define SD_REG 200
#define SD_WAIT 6000
#define SD_P2 150
#define SD_P3 600
#define SD_GAP 0
#define SD_RUSH 44
#define SD_P1 300

__device__ uint4 g_part[SD_CTAS][PART_SLOTS][4][8][32];
__device__ __align__(16) unsigned int g_gate[S_LEN];

struct cplx { float r, i; };
__device__ __forceinline__ cplx cmul(cplx a, cplx b) { cplx c; c.r = fmaf(a.r, b.r, -a.i * b.i); c.i = fmaf(a.r, b.i, a.i * b.r); return c; }
__device__ __forceinline__ cplx cexp_(float xr, float xi) {
    const float m = ex2(xr * 1.4426950408889634f);
    const float k = rintf(xi * 0.15915494309189535f);
    const float r = fmaf(k, 1.7484555314695172e-7f, fmaf(k, -6.2831854820251465f, xi));
    cplx o; o.r = m * __cosf(r); o.i = m * __sinf(r); return o;
}
__device__ __forceinline__ void mma_f16(float (&c)[4], const uint32_t (&a)[4], uint32_t b0, uint32_t b1) {
    asm("mma.sync.aligned.m16n8k16.row.col.f32.f16.f16.f32 {%0,%1,%2,%3}, {%4,%5,%6,%7}, {%8,%9}, {%0,%1,%2,%3};"
        : "+f"(c[0]), "+f"(c[1]), "+f"(c[2]), "+f"(c[3]) : "r"(a[0]), "r"(a[1]), "r"(a[2]), "r"(a[3]), "r"(b0), "r"(b1));
}
__device__ __forceinline__ uint32_t mul_bf2(uint32_t a, uint32_t b) { uint32_t r; asm("mul.rn.bf16x2 %0, %1, %2;" : "=r"(r) : "r"(a), "r"(b)); return r; }
__device__ __forceinline__ void mbar_wait_long(uint32_t a, uint32_t parity) { int it = 0; while (!mbar_try(a, parity) && ++it < SD_SPIN) {} }
__device__ __forceinline__ uint16_t lds16(uint32_t a) { uint16_t v; asm volatile("ld.shared.u16 %0, [%1];" : "=h"(v) : "r"(a) : "memory"); return v; }
__device__ __forceinline__ void wg_wait1() { asm volatile("wgmma.wait_group.sync.aligned 1;" ::: "memory"); }
__device__ __forceinline__ void tma2d(uint32_t dst, const CUtensorMap* tm, uint32_t bar, int c0, int c1) {
    asm volatile("cp.async.bulk.tensor.2d.shared::cluster.global.mbarrier::complete_tx::bytes [%0], [%1, {%3, %4}], [%2];"
        :: "r"(dst), "l"(tm), "r"(bar), "r"(c0), "r"(c1) : "memory");
}
__device__ __forceinline__ uint32_t add_bf2(uint32_t a, uint32_t b) { uint32_t r; asm("add.rn.bf16x2 %0, %1, %2;" : "=r"(r) : "r"(a), "r"(b)); return r; }
__device__ __forceinline__ void wgmma_conv(float (&d)[32], uint32_t a0, uint32_t a1, uint32_t a2, uint32_t a3, uint64_t desc) {
    asm volatile("{\n.reg .pred p;\nsetp.ne.b32 p, 1, 0;\n"
        "wgmma.mma_async.sync.aligned.m64n64k16.f32.bf16.bf16 {%0,%1,%2,%3,%4,%5,%6,%7,%8,%9,%10,%11,%12,%13,%14,%15,%16,%17,%18,%19,%20,%21,%22,%23,%24,%25,%26,%27,%28,%29,%30,%31}, {%32,%33,%34,%35}, %36, p, 1, 1, 0;\n}\n"
        : "+f"(d[0]), "+f"(d[1]), "+f"(d[2]), "+f"(d[3]), "+f"(d[4]), "+f"(d[5]), "+f"(d[6]), "+f"(d[7]), "+f"(d[8]), "+f"(d[9]), "+f"(d[10]), "+f"(d[11]), "+f"(d[12]), "+f"(d[13]), "+f"(d[14]), "+f"(d[15]), "+f"(d[16]), "+f"(d[17]), "+f"(d[18]), "+f"(d[19]), "+f"(d[20]), "+f"(d[21]), "+f"(d[22]), "+f"(d[23]), "+f"(d[24]), "+f"(d[25]), "+f"(d[26]), "+f"(d[27]), "+f"(d[28]), "+f"(d[29]), "+f"(d[30]), "+f"(d[31])
        : "r"(a0), "r"(a1), "r"(a2), "r"(a3), "l"(desc));
}
__device__ __forceinline__ void wgmma_conv(float (&d)[24], uint32_t a0, uint32_t a1, uint32_t a2, uint32_t a3, uint64_t desc) {
    asm volatile("{\n.reg .pred p;\nsetp.ne.b32 p, 1, 0;\n"
        "wgmma.mma_async.sync.aligned.m64n48k16.f32.bf16.bf16 {%0,%1,%2,%3,%4,%5,%6,%7,%8,%9,%10,%11,%12,%13,%14,%15,%16,%17,%18,%19,%20,%21,%22,%23}, {%24,%25,%26,%27}, %28, p, 1, 1, 0;\n}\n"
        : "+f"(d[0]), "+f"(d[1]), "+f"(d[2]), "+f"(d[3]), "+f"(d[4]), "+f"(d[5]), "+f"(d[6]), "+f"(d[7]), "+f"(d[8]), "+f"(d[9]), "+f"(d[10]), "+f"(d[11]), "+f"(d[12]), "+f"(d[13]), "+f"(d[14]), "+f"(d[15]), "+f"(d[16]), "+f"(d[17]), "+f"(d[18]), "+f"(d[19]), "+f"(d[20]), "+f"(d[21]), "+f"(d[22]), "+f"(d[23])
        : "r"(a0), "r"(a1), "r"(a2), "r"(a3), "l"(desc));
}
__device__ __forceinline__ void wgmma_conv(float (&d)[16], uint32_t a0, uint32_t a1, uint32_t a2, uint32_t a3, uint64_t desc) {
    asm volatile("{\n.reg .pred p;\nsetp.ne.b32 p, 1, 0;\n"
        "wgmma.mma_async.sync.aligned.m64n32k16.f32.bf16.bf16 {%0,%1,%2,%3,%4,%5,%6,%7,%8,%9,%10,%11,%12,%13,%14,%15}, {%16,%17,%18,%19}, %20, p, 1, 1, 0;\n}\n"
        : "+f"(d[0]), "+f"(d[1]), "+f"(d[2]), "+f"(d[3]), "+f"(d[4]), "+f"(d[5]), "+f"(d[6]), "+f"(d[7]), "+f"(d[8]), "+f"(d[9]), "+f"(d[10]), "+f"(d[11]), "+f"(d[12]), "+f"(d[13]), "+f"(d[14]), "+f"(d[15])
        : "r"(a0), "r"(a1), "r"(a2), "r"(a3), "l"(desc));
}
__device__ __forceinline__ void wgmma_conv(float (&d)[8], uint32_t a0, uint32_t a1, uint32_t a2, uint32_t a3, uint64_t desc) {
    asm volatile("{\n.reg .pred p;\nsetp.ne.b32 p, 1, 0;\n"
        "wgmma.mma_async.sync.aligned.m64n16k16.f32.bf16.bf16 {%0,%1,%2,%3,%4,%5,%6,%7}, {%8,%9,%10,%11}, %12, p, 1, 1, 0;\n}\n"
        : "+f"(d[0]), "+f"(d[1]), "+f"(d[2]), "+f"(d[3]), "+f"(d[4]), "+f"(d[5]), "+f"(d[6]), "+f"(d[7])
        : "r"(a0), "r"(a1), "r"(a2), "r"(a3), "l"(desc));
}
template<int NR> __device__ __forceinline__ void conv_mma(float (&acc)[NR], const uint32_t (&R)[16], uint32_t dlo) {
    #pragma unroll
    for (int q = 0; q < 4; q++)
        wgmma_conv(acc, R[4 * q], R[4 * q + 1], R[4 * q + 2], R[4 * q + 3], (uint64_t)(dlo + (2 * (3 - q)) * (BC_LBO >> 4)) | ((uint64_t)8 << 32));
}
__device__ __forceinline__ void conv_ld(uint32_t (&R)[16], uint32_t a) {
    #pragma unroll
    for (int q = 0; q < 4; q++) { const uint2 u = lds64(a + 64 * (2 * q + 1)); R[4 * q] = u.x; R[4 * q + 1] = u.y; }
}
__device__ __forceinline__ void conv_fix(uint32_t (&R)[16], uint32_t& carry) {
    #pragma unroll
    for (int q = 0; q < 4; q++) {
        asm volatile("mov.b32 %0, %1;" : "=r"(R[4 * q + 2]) : "r"(q ? R[4 * q - 3] : carry));
        asm volatile("mov.b32 %0, %1;" : "=r"(R[4 * q + 3]) : "r"(R[4 * q]));
    }
    asm volatile("mov.b32 %0, %1;" : "=r"(carry) : "r"(R[13]));
}
template<int A> __device__ __forceinline__ void conv_group(float (&acc)[32 - 8 * A], uint32_t (&R)[4][16], uint32_t& carry, uint32_t pb, uint32_t dlo) {
    #pragma unroll
    for (int e = 0; e < 8; e += 2) {
        const int dl = 8 * A + e;
        conv_fix(R[dl & 3], carry); conv_fix(R[(dl + 1) & 3], carry);
        wg_fence(); conv_mma(acc, R[dl & 3], dlo + 16 - 2 * e); conv_mma(acc, R[(dl + 1) & 3], dlo + 14 - 2 * e); wg_commit();
        wg_wait1();
        if (dl + 2 < 32) { conv_ld(R[(dl + 2) & 3], pb + (dl + 2) * 512); conv_ld(R[(dl + 3) & 3], pb + (dl + 3) * 512); }
    }
}

__global__ void __launch_bounds__(SD_THREADS, 1)
side_kernel(const __grid_constant__ CUtensorMap tmw, const bf16* __restrict__ x,
            const bf16* __restrict__ log_A_real, const bf16* __restrict__ A_imag, const bf16* __restrict__ C_real, const bf16* __restrict__ C_imag,
            const bf16* __restrict__ log_dt, const bf16* __restrict__ D_skip, const bf16* __restrict__ gate_w, bf16* __restrict__ out) {
    extern __shared__ __align__(1024) unsigned char smem[];
    const uint32_t sb = smem_u32(smem);
    const int tid = threadIdx.x, lane = tid & 31;
    const int warp = __shfl_sync(0xffffffffu, tid >> 5, 0);
    const int g = lane >> 2, t = lane & 3, mi = lane >> 3, r8 = lane & 7;
    const bool sh = blockIdx.x < 32;
    const int d0 = blockIdx.x * 16;
    const uint32_t b0_ = sb + SD_BAR, bKF = b0_ + 384, bKE = bKF + 8 * KSLOTS, bWO = b0_ + 48, bFULL = b0_ + 56, bEMPTY = b0_ + 88, bEPI = b0_ + 120, bPRT = b0_ + 152, bGO = b0_ + 184, bCH = b0_ + 256;
    const unsigned epoch = ld_relaxed32(&g_epoch);
    if (tid == 0) GT(blockIdx.x, 0);
    if (tid == 0) {
        for (int i = 0; i < 2 * KSLOTS; i++) mbar_init(bKF + 8 * i, 128);
        mbar_init(bWO, 1);
        for (int i = 0; i < 16; i++) mbar_init(bCH + 8 * i, 1);
        for (int i = 0; i < 4; i++) { mbar_init(bFULL + 8 * i, 1); mbar_init(bEMPTY + 8 * i, sh ? 8 : 4); mbar_init(bEPI + 8 * i, 4); mbar_init(bPRT + 8 * i, 8); mbar_init(bGO + 8 * i, 1); }
        asm volatile("fence.mbarrier_init.release.cluster;" ::: "memory");
    }
    for (int i = tid; i < KSLOTS * 8 * 16; i += SD_THREADS) sts128(sb + SD_BC + (i >> 4) * BC_LBO + (i & 15) * 16, make_uint4(0, 0, 0, 0));
    if (tid < 128) sts64(sb + ((tid & 64) ? SD_Q1 : SD_Q0) + (tid & 63) * 8, 0u, 0u);
    fence_async_smem();
    __syncthreads();

    if (warp < 8) {
        asm volatile("setmaxnreg.inc.sync.aligned.u32 %0;" :: "n"(SD_REG));
        const int wg = warp >> 2, w = warp & 3, t128 = tid & 127;
        if (SD_WAIT) __nanosleep(SD_WAIT);
        {
            #pragma unroll 1
            for (int i = 0; i < 4; i++) {
                const int tp = tid + 256 * i;
                const bf16* xp = x + (size_t)(2 * tp) * DM + d0;
                const uint4 v0 = __ldg((const uint4*)xp), v1 = __ldg((const uint4*)(xp + 8)), v2 = __ldg((const uint4*)(xp + DM)), v3 = __ldg((const uint4*)(xp + DM + 8));
                const uint32_t a = sb + SD_BT + (tp >> 5) * 144 + (tp & 31) * 4;
                const uint32_t lo[8] = {v0.x, v0.y, v0.z, v0.w, v1.x, v1.y, v1.z, v1.w};
                const uint32_t hi[8] = {v2.x, v2.y, v2.z, v2.w, v3.x, v3.y, v3.z, v3.w};
                #pragma unroll
                for (int j = 0; j < 8; j++) { sts32(a + (2 * j) * BT_RS, __byte_perm(lo[j], hi[j], 0x5410)); sts32(a + (2 * j + 1) * BT_RS, __byte_perm(lo[j], hi[j], 0x7632)); }
                if (SD_GAP) __nanosleep(SD_GAP);
            }
        }
        bar_sync(1, 256);
        if (tid == 0) GT(blockIdx.x, 65);
        const uint32_t pa = sb + (wg ? SD_Q1 : SD_Q0);
        const uint32_t pb = pa + (72 + 16 * w - 56 + g - 2 * t) * 8;
        for (int c = wg; c < 16; c += 2) {
            const uint32_t bt = sb + SD_BT + c * BT_RS;
            bar_sync(2 + wg, 128);
            #pragma unroll
            for (int it = 0; it < 9; it++) {
                const int k = it < 8 ? t128 + 128 * it : t128 - 4;
                if (it < 8 || t128 < 4) {
                    auto word = [&](int j) { return j >= 0 ? lds32(bt + (j >> 5) * 144 + (j & 31) * 4) : 0u; };
                    const uint32_t c0 = word(k), p0 = word(k - 1), c1 = word(k + 4), p1 = word(k + 3);
                    sts128(pa + (72 + 2 * k) * 8, make_uint4(__byte_perm(c0, p0, 0x7610), __byte_perm(c1, p1, 0x7610), __byte_perm(c0, c0, 0x1032), __byte_perm(c1, c1, 0x1032)));
                }
            }
            bar_sync(2 + wg, 128);
            const int slot = c % KSLOTS;
            float acc[32];
            #pragma unroll
            for (int i = 0; i < 32; i++) acc[i] = 0.f;
            uint32_t R[4][16];
            uint32_t carry = lds32(pb);
            conv_ld(R[0], pb); conv_ld(R[1], pb + 512);
            const uint32_t dlo = (((sb + SD_BC + slot * BC_BYTES) & 0x3FFFF) >> 4) | ((BC_LBO >> 4) << 16);
            mbar_wait_long(bKF + 8 * slot, (c / KSLOTS) & 1);
            const float ds = bf(D_skip[d0 + c]);
            auto fin = [&](const float* a8, int q0) {
                #pragma unroll
                for (int q = 0; q < 2; q++)
                    #pragma unroll
                    for (int hh = 0; hh < 2; hh++) {
                        const uint32_t a = bt + (4 * (q0 + q) + t) * 144 + (16 * w + g + 8 * hh) * 2;
                        const float u = __uint_as_float((uint32_t)lds16(a) << 16);
                        const float y = rbf(a8[4 * q + 2 * hh] + a8[4 * q + 2 * hh + 1]);
                        sts16(a, (uint16_t)(pack_bf16(y + rbf(u * ds), 0.f) & 0xffff));
                    }
            };
            float a1[24], a2[16], a3[8];
            conv_group<0>(acc, R, carry, pb, dlo);
            wg_wait0();
            #pragma unroll
            for (int i = 0; i < 24; i++) asm volatile("mov.b32 %0, %1;" : "=f"(a1[i]) : "f"(acc[8 + i]));
            fin(acc, 0);
            conv_group<1>(a1, R, carry, pb, dlo);
            wg_wait0();
            #pragma unroll
            for (int i = 0; i < 16; i++) asm volatile("mov.b32 %0, %1;" : "=f"(a2[i]) : "f"(a1[8 + i]));
            fin(a1, 2);
            conv_group<2>(a2, R, carry, pb, dlo);
            wg_wait0();
            #pragma unroll
            for (int i = 0; i < 8; i++) asm volatile("mov.b32 %0, %1;" : "=f"(a3[i]) : "f"(a2[8 + i]));
            fin(a2, 4);
            conv_group<3>(a3, R, carry, pb, dlo);
            wg_wait0();
            mbar_arrive(bKE + 8 * slot);
            fin(a3, 6);
        }
        fence_async_smem();
        __syncthreads();
        const uint32_t stg = sb + SD_STG + wg * 65536;
        uint32_t wf[32][4];
        if (tid == 0) GT(blockIdx.x, 66);
        mbar_wait_long(bWO, 0);
        #pragma unroll
        for (int i = 0; i < 32; i++)
            ldsm_x4_t(wf[i], stg + (i * 16 + (mi >> 1) * 8 + r8) * 128 + (((2 * w + (mi & 1)) ^ r8) << 4));
        { uint32_t x = 0;
          #pragma unroll
          for (int i = 0; i < 32; i++) x |= wf[i][0];
          asm volatile("" :: "r"(x) : "memory"); }
        __syncwarp();
        if (lane == 0) {
            mbar_arrive(bEMPTY + 16 * wg); mbar_arrive(bEMPTY + 16 * wg + 8);
            if (sh) { mbar_arrive(bEMPTY + 16 * (wg ^ 1)); mbar_arrive(bEMPTY + 16 * (wg ^ 1) + 8); }
        }
        uint4* dst = sh ? &g_part[(blockIdx.x & ~7) + 4 * wg + w][0][0][blockIdx.x & 7][lane] : &g_part[32 + w][0][0][2 * (blockIdx.x - 32) + wg][lane];
        const uint32_t dl0 = (((sb + SD_STG) & 0x3FFFF) >> 4) | 0x10000u;
        auto seg = [&](int s, auto last) {
            const int bi = sh ? s & 3 : 2 * wg + (s & 1), bp = (sh ? s >> 2 : s >> 1) & 1;
            const uint32_t xd = uni(dl0 + bi * 2048);
            float acc[16];
            #pragma unroll
            for (int i = 0; i < 32; i++) {
                if (i == 0 || (last.value && (i & 7) == 0)) { mbar_wait_long(bCH + 32 * bi + i, i ? 0 : bp); wg_fence(); }
                if (i == 0) wgmma_n32<0>(acc, wf[i], desc_from(xd));
                else wgmma_n32<1>(acc, wf[i], desc_from(xd + (i >> 2) * 256 + (i & 3) * 2));
            }
            wg_commit();
            if (s >= PART_SLOTS / 2) mbar_wait_long(bEPI + 8 * (s & 3), ((s - 4) >> 2) & 1);
            const uint32_t ph = ((s / PART_SLOTS) & 1) ^ 1;
            uint4* p = dst + (s % PART_SLOTS) * (4 * 8 * 32);
            wg_wait0();
            #pragma unroll
            for (int j = 0; j < 4; j++)
                st_relaxed128(p + 256 * j, make_uint4((__float_as_uint(acc[4 * j]) & ~1u) | ph, __float_as_uint(acc[4 * j + 1]), __float_as_uint(acc[4 * j + 2]), __float_as_uint(acc[4 * j + 3])));
            if (tid == 0 && s == NSEG - 1) GT(blockIdx.x, 71);
            __syncwarp();
            if (lane == 0) { mbar_arrive(bEMPTY + 8 * bi); mbar_arrive(bPRT + 8 * (s & 3)); }
        };
        #pragma unroll 1
        for (int s = 0; s < NSEG - 1; s++) seg(s, ic<0>());
        seg(NSEG - 1, ic<1>());
    } else {
        asm volatile("setmaxnreg.dec.sync.aligned.u32 %0;" :: "n"(504 - 2 * SD_REG));
        const int w = warp - 8, n = tid - 256;
        bf16 p_la = log_A_real[d0 * NS + n], p_ai = A_imag[d0 * NS + n], p_cr = C_real[d0 * NS + n], p_ci = C_imag[d0 * NS + n], p_dt = log_dt[d0];
        const uint32_t ef = sb + SD_EF + w * 8192;
        const uint32_t efl = ef + lane * 4;
        uint32_t goff[8];
        #pragma unroll
        for (int i = 0; i < 16; i++) {
            const int l = 64 * lane + 8 * (w + 4 * (i >> 3)) + (i & 7);
            const int p = (int)rbf((float)l);
            const int a = p >> 7, b = (p >> 3) & 15, c = p & 7;
            const int row = p < 256 ? 8 * a + c : (p < 512 ? 16 + 4 * (a - 2) + (c >> 1) : (p < 1024 ? 24 + 2 * (a - 4) + (c >> 2) : 24 + a));
            const uint32_t off = row * 72 + b * 4;
            if (i & 1) goff[i >> 1] |= off << 16; else goff[i >> 1] = off;
        }
        for (int c = 0; c < 16; c++) {
            const float dt = rbf(expf(bf(p_dt)));
            const float xr = -rbf(expf(bf(p_la))) * dt, xi = bf(p_ai) * dt;
            cplx C; C.r = 2.f * bf(p_cr) * dt; C.i = 2.f * bf(p_ci) * dt;
            if (c + 1 < 16) {
                const int o = (d0 + c + 1) * NS + n;
                p_la = log_A_real[o]; p_ai = A_imag[o]; p_cr = C_real[o]; p_ci = C_imag[o]; p_dt = log_dt[d0 + c + 1];
            }
            const uint32_t mexp = min(max(__reduce_max_sync(0xffffffffu, __float_as_uint(fmaxf(fabsf(C.r), fabsf(C.i)))) & 0x7f800000u, 0x01000000u), 0x7e000000u);
            const float unsc = __uint_as_float(mexp), sc = __uint_as_float(0x7f000000u - mexp);
            C.r *= sc; C.i *= sc;
            #define EADDR(r) ((efl ^ (((r) & 7) << 4)) + (r) * 128)
            {
                cplx f[16];
                f[1] = cexp_(8.f * xr, -8.f * xi);
                f[2] = cmul(f[1], f[1]); f[3] = cmul(f[2], f[1]); f[4] = cmul(f[2], f[2]); f[5] = cmul(f[4], f[1]); f[6] = cmul(f[4], f[2]); f[7] = cmul(f[4], f[3]);
                f[8] = cmul(f[4], f[4]);
                #pragma unroll
                for (int b = 9; b < 16; b++) f[b] = cmul(f[8], f[b - 8]);
                sts32(EADDR(0) + 6144, 0x00003c00u);
                #pragma unroll
                for (int b = 1; b < 16; b++) sts32(EADDR(b) + 6144, pack_f16(f[b].r, f[b].i));
            }
            {
                cplx G[17], wc[8];
                G[1] = cexp_(128.f * xr, 128.f * xi);
                wc[1] = cexp_(xr, xi);
                G[2] = cmul(G[1], G[1]); G[4] = cmul(G[2], G[2]); G[8] = cmul(G[4], G[4]);
                wc[2] = cmul(wc[1], wc[1]); wc[3] = cmul(wc[2], wc[1]); wc[4] = cmul(wc[2], wc[2]); wc[5] = cmul(wc[4], wc[1]); wc[6] = cmul(wc[4], wc[2]); wc[7] = cmul(wc[4], wc[3]);
                cplx CG[17];
                CG[0] = C; CG[1] = cmul(C, G[1]); CG[2] = cmul(C, G[2]); CG[3] = cmul(CG[1], G[2]);
                #pragma unroll
                for (int a = 0; a < 4; a++) CG[4 + a] = cmul(CG[a], G[4]);
                #pragma unroll
                for (int a = 0; a < 9; a++) CG[8 + a] = cmul(CG[a], G[8]);
                #pragma unroll
                for (int r = 0; r < 41; r++) {
                    const int a = r < 16 ? (r >> 3) : (r < 24 ? 2 + ((r >> 2) & 1) : (r < 32 ? 4 + ((r >> 1) & 3) : r - 24));
                    const int cc = r < 16 ? (r & 7) : (r < 24 ? 2 * (r & 3) : (r < 32 ? 4 * (r & 1) : 0));
                    const cplx e = cc ? cmul(CG[a], wc[cc]) : CG[a];
                    sts32(EADDR(r), pack_f16(e.r, e.i));
                }
            }
            __syncwarp();
            float acc[3][2][4];
            #pragma unroll
            for (int i = 0; i < 3; i++)
                #pragma unroll
                for (int j = 0; j < 2; j++) { acc[i][j][0] = acc[i][j][1] = acc[i][j][2] = acc[i][j][3] = 0.f; }
            #pragma unroll
            for (int ks = 0; ks < 4; ks++) {
                uint32_t bq[4];
                ldsm_x4(bq, ef + 6144 + ((mi >> 1) * 8 + r8) * 128 + (((2 * ks + (mi & 1)) ^ r8) << 4));
                #pragma unroll
                for (int mt = 0; mt < 3; mt++) {
                    uint32_t aq[4];
                    ldsm_x4(aq, ef + (16 * mt + (mi & 1) * 8 + r8) * 128 + (((2 * ks + (mi >> 1)) ^ r8) << 4));
                    mma_f16(acc[mt][0], aq, bq[0], bq[1]);
                    mma_f16(acc[mt][1], aq, bq[2], bq[3]);
                }
            }
            const uint32_t kp = sb + SD_KP;
            #pragma unroll
            for (int mt = 0; mt < 3; mt++)
                #pragma unroll
                for (int nt = 0; nt < 2; nt++) {
                    const uint32_t a = kp + w * 3072 + (16 * mt + g) * 64 + nt * 32 + t * 8;
                    sts64(a, __float_as_uint(acc[mt][nt][0] * unsc), __float_as_uint(acc[mt][nt][1] * unsc));
                    sts64(a + 512, __float_as_uint(acc[mt][nt][2] * unsc), __float_as_uint(acc[mt][nt][3] * unsc));
                }
            bar_sync(4, 128);
            #pragma unroll
            for (int i = 0; i < 3; i++) {
                const uint32_t a = kp + (n + 128 * i) * 8;
                const uint2 v0 = lds64(a), v1 = lds64(a + 3072), v2 = lds64(a + 6144), v3 = lds64(a + 9216);
                sts64(a + 12288 + ((n >> 3) + 16 * i) * 8, __float_as_uint((__uint_as_float(v0.x) + __uint_as_float(v1.x)) + (__uint_as_float(v2.x) + __uint_as_float(v3.x))),
                                 __float_as_uint((__uint_as_float(v0.y) + __uint_as_float(v1.y)) + (__uint_as_float(v2.y) + __uint_as_float(v3.y))));
            }
            bar_sync(4, 128);
            const int slot = c % KSLOTS;
            float kv[16];
            #pragma unroll
            for (int e = 0; e < 8; e++) { kv[2 * e] = __uint_as_float(lds32(kp + 12288 + (goff[e] & 0xffff))); kv[2 * e + 1] = __uint_as_float(lds32(kp + 12288 + (goff[e] >> 16))); }
            if (c >= KSLOTS) mbar_wait_long(bKE + 8 * slot, (c / KSLOTS - 1) & 1);
            #pragma unroll
            for (int it = 0; it < 2; it++) {
                uint32_t hi[4], lo[4];
                #pragma unroll
                for (int e = 0; e < 4; e++) {
                    const float k0 = kv[8 * it + 2 * e], k1 = kv[8 * it + 2 * e + 1];
                    hi[e] = pack_bf16(k0, k1);
                    lo[e] = pack_bf16(k0 - bf_lo(hi[e]), k1 - bf_hi(hi[e]));
                }
                const uint32_t a = sb + SD_BC + slot * BC_BYTES + (w + 4 * it) * BC_LBO + (16 + 2 * lane) * 16;
                sts128(a, make_uint4(hi[0], hi[1], hi[2], hi[3]));
                sts128(a + 16, make_uint4(lo[0], lo[1], lo[2], lo[3]));
            }
            fence_async_smem();
            mbar_arrive(bKF + 8 * slot);
        }
        {
            uint32_t gw[9];
            #pragma unroll
            for (int j = 0; j < 9; j++) gw[j] = __ldg((const uint32_t*)gate_w + lane + 32 * j);
            float z = 0.f;
            #pragma unroll 1
            for (int i0 = 0; i0 < 15; i0 += 5) {
                uint32_t xv[5][9];
                #pragma unroll
                for (int i = 0; i < 5; i++) {
                    const int tk = min(blockIdx.x * 57 + w + 4 * (i0 + i), S_LEN - 1);
                    #pragma unroll
                    for (int j = 0; j < 9; j++) xv[i][j] = __ldg((const uint32_t*)(x + (size_t)tk * DM) + lane + 32 * j);
                }
                #pragma unroll
                for (int i = 0; i < 5; i++) {
                    float acc = 0.f;
                    #pragma unroll
                    for (int j = 0; j < 9; j++) { const uint32_t m = mul_bf2(xv[i][j], gw[j]); acc += bf_lo(m) + bf_hi(m); }
                    #pragma unroll
                    for (int o = 16; o; o >>= 1) acc += __shfl_xor_sync(0xffffffffu, acc, o);
                    if (lane == i0 + i) z = rbf(acc);
                }
            }
            const int li = w + 4 * lane, tk = blockIdx.x * 57 + li;
            if (li < 57 && tk < S_LEN) st_relaxed32(&g_gate[tk], pack_bf16(1.f / (1.f + expf(-z)), 0.f) | (epoch << 16));
        }
        if (tid == 256) GT(blockIdx.x, 67);
        fence_async_smem();
        __syncthreads();
            const uint32_t ost = sb + SD_OST + w * 512;
            const uint4* const pl = &g_part[blockIdx.x][0][0][0][lane];
            bf16* const ol = out + (size_t)(lane >> 1) * DM + d0 + 8 * (lane & 1);
            auto units = [&](auto nu_, int u, int end) {
              constexpr int NU = nu_.value;
              uint4 v[8 * NU];
              auto fetch = [&](int u, bool block) {
                const int s = u >> 2;
                uint32_t early;
                asm volatile("{\n.reg .pred p;\nmbarrier.test_wait.parity.shared::cta.b64 p, [%1], %2;\nselp.u32 %0, 1, 0, p;\n}\n" : "=r"(early) : "r"(bPRT + 8 * (s & 3)), "r"((s >> 2) & 1) : "memory");
                if (!early) {
                    if (!block) return false;
                    mbar_wait_long(bPRT + 8 * (s & 3), (s >> 2) & 1);
                    delay_clk(s < NSEG - 2 ? SD_P1 : SD_P2);
                } else if (SD_P3 && s < SD_RUSH) delay_clk(SD_P3);
                const uint4* p = pl + (u & (4 * PART_SLOTS - 1)) * 256;
                #pragma unroll
                for (int i = 0; i < 8 * NU; i++) v[i] = ld_relaxed128(p + 32 * i);
                return true;
              };
              fetch(u, true);
              #pragma unroll 1
              while (true) {
                const int s = u >> 2;
                const uint32_t phm = ((s / PART_SLOTS) & 1) - 1;
                int it = 0;
                while (true) {
                    uint32_t all = ~0u, any = 0;
                    #pragma unroll
                    for (int i = 0; i < 8 * NU; i++) { all &= v[i].x; any |= v[i].x; }
                    if (!__any_sync(0xffffffffu, ((all ^ phm) | (any ^ phm)) & 1u) || ++it >= SD_SPIN) break;
                    if (it > 1 && s < NSEG - 2) __nanosleep(200);
                    const uint4* p = pl + (u & (4 * PART_SLOTS - 1)) * 256;
                    #pragma unroll
                    for (int i = 0; i < 8 * NU; i++) ld_relaxed128_p(v[i], p + 32 * i, (v[i].x ^ phm) & 1u);
                }
                if (lane < NU) mbar_arrive(bEPI + 8 * (s & 3));
                uint32_t sm[NU][2];
                #pragma unroll
                for (int k = 0; k < NU; k++) {
                    float a0 = __uint_as_float(v[8 * k].x), a1 = __uint_as_float(v[8 * k].y), a2 = __uint_as_float(v[8 * k].z), a3 = __uint_as_float(v[8 * k].w);
                    #pragma unroll
                    for (int i = 1; i < 8; i++) { a0 += __uint_as_float(v[8 * k + i].x); a1 += __uint_as_float(v[8 * k + i].y); a2 += __uint_as_float(v[8 * k + i].z); a3 += __uint_as_float(v[8 * k + i].w); }
                    sm[k][0] = pack_bf16(a0, a1); sm[k][1] = pack_bf16(a2, a3);
                }
                const int nu = u + 3 * NU;
                const bool pre = nu < end && fetch(nu, false);
                #pragma unroll
                for (int k = 0; k < NU; k++) {
                    const int t0 = 8 * (u + k) + 2 * t;
                    const uint2 gt = lds64(sb + SD_Q0 + t0 * 4);
                    const uint32_t ba = sb + SD_BT + g * BT_RS + (t0 >> 6) * 144 + (t0 & 63) * 2;
                    const uint32_t b0 = lds32(ba), b1 = lds32(ba + 8 * BT_RS);
                    const uint32_t gg = __byte_perm(gt.x, gt.y, 0x5410), mm = pack_bf16(1.f - bf_lo(gg), 1.f - bf_hi(gg));
                    const uint32_t r0 = add_bf2(mul_bf2(gg, sm[k][0]), mul_bf2(mm, b0)), r1 = add_bf2(mul_bf2(gg, sm[k][1]), mul_bf2(mm, b1));
                    asm volatile("stmatrix.sync.aligned.m8n8.x2.trans.shared.b16 [%0], {%1,%2};" :: "r"(ost + k * 256 + r8 * 32 + (mi & 1) * 16), "r"(r0), "r"(r1) : "memory");
                }
                __syncwarp();
                if (lane < 16 * NU) *(uint4*)(ol + (size_t)(8 * u) * DM) = lds128(ost + lane * 16);
                __syncwarp();
                if (lane == 0 && ((u + NU - 1) & 3) == 3) GT(blockIdx.x, 1 + s);
                if (nu >= end) break;
                if (!pre) fetch(nu, true);
                u = nu;
              }
            };
        if (w == 0) {
            if (lane == 0) {
                mbar_expect_tx(bWO, 131072);
                #pragma unroll 1
                for (int q = 0; q < 16; q++) {
                    tma2d(sb + SD_STG + q * 8192, &tmw, bWO, sh ? 128 * (blockIdx.x >> 3) + 64 * (q >> 3) : 512, sh ? 512 * (blockIdx.x & 7) + 64 * (q & 7) : 1024 * (blockIdx.x - 32) + 64 * q);
                    if (SD_WOP) delay_clk(SD_WOP);
                }
            }
            bar_sync(5, 128);
            const int ke0 = sh ? blockIdx.x & 7 : 2 * (blockIdx.x - 32);
            const unsigned int* f = &g_prog[12 * ke0 + (lane < (sh ? 12 : 24) ? lane : 0)];
            int avail = 0;
            #pragma unroll 1
            for (int s = 0; s < NSEG; s++) {
                if (s >= avail) {
                    int it = 0;
                    while (true) {
                        uint32_t v;
                        asm volatile("ld.acquire.gpu.global.u32 %0, [%1];" : "=r"(v) : "l"(f) : "memory");
                        avail = __reduce_min_sync(0xffffffffu, (v >> 8) == (epoch & 0xffffffu) ? v & 255u : 0u);
                        if (avail > s || ++it >= SD_SPIN) break;
                        if (s < NSEG - 1) __nanosleep(64);
                    }
                    asm volatile("fence.proxy.async.global;" ::: "memory");
                    if (lane == 0 && s == NSEG - 1) GT(blockIdx.x, 70);
                }
                if (lane == 0 && s == 2 && blockIdx.x == 0) st_relaxed32(&g_epoch, epoch + 1);
                const int b0 = sh ? s & 3 : s & 1, bp = (sh ? s >> 2 : s >> 1) & 1;
                const bf16* src = g_otok + (size_t)s * (SEG * NH * DH) + ke0 * 16384;
                mbar_wait_long(bEMPTY + 8 * b0, bp);
                if (!sh) mbar_wait_long(bEMPTY + 16 + 8 * b0, bp);
                if (s < NSEG - 1) {
                    asm volatile("{\n.reg .pred p, q;\nelect.sync _|p, 0xffffffff;\nsetp.eq.and.u32 q, %6, 0, p;\n"
                                 "@p mbarrier.arrive.expect_tx.shared.b64 _, [%2], 32768;\n"
                                 "@p cp.async.bulk.shared::cluster.global.mbarrier::complete_tx::bytes [%0], [%1], 32768, [%2];\n"
                                 "@q mbarrier.arrive.expect_tx.shared.b64 _, [%5], 32768;\n"
                                 "@q cp.async.bulk.shared::cluster.global.mbarrier::complete_tx::bytes [%3], [%4], 32768, [%5];\n}\n"
                        :: "r"(sb + SD_STG + b0 * 32768), "l"(src), "r"(bCH + 32 * b0), "r"(sb + SD_STG + (b0 + 2) * 32768), "l"(src + 16384), "r"(bCH + 32 * (b0 + 2)), "r"((uint32_t)sh) : "memory");
                } else {
                    #pragma unroll
                    for (int hc = 0; hc < 4; hc++)
                        asm volatile("{\n.reg .pred p, q;\nelect.sync _|p, 0xffffffff;\nsetp.eq.and.u32 q, %6, 0, p;\n"
                                     "@p mbarrier.arrive.expect_tx.shared.b64 _, [%2], 8192;\n"
                                     "@p cp.async.bulk.shared::cluster.global.mbarrier::complete_tx::bytes [%0], [%1], 8192, [%2];\n"
                                     "@q mbarrier.arrive.expect_tx.shared.b64 _, [%5], 8192;\n"
                                     "@q cp.async.bulk.shared::cluster.global.mbarrier::complete_tx::bytes [%3], [%4], 8192, [%5];\n}\n"
                            :: "r"(sb + SD_STG + b0 * 32768 + hc * 8192), "l"(src + hc * 4096), "r"(bCH + 32 * b0 + 8 * hc),
                               "r"(sb + SD_STG + (b0 + 2) * 32768 + hc * 8192), "l"(src + 16384 + hc * 4096), "r"(bCH + 32 * (b0 + 2) + 8 * hc), "r"((uint32_t)sh) : "memory");
                }
            }
        } else {
            if (w == 3) {
                for (int i = 0; i < 16; i += 8) {
                    uint4 v[8]; uint32_t miss = 0xffu; int it = 0;
                    const uint32_t tag = epoch & 0xffffu;
                    #pragma unroll
                    for (int j = 0; j < 8; j++) v[j] = make_uint4(0, 0, 0, 0);
                    do {
                        #pragma unroll
                        for (int j = 0; j < 8; j++) ld_relaxed128_p(v[j], (const uint4*)g_gate + (i + j) * 32 + lane, miss & (1u << j));
                        miss = 0;
                        #pragma unroll
                        for (int j = 0; j < 8; j++) miss |= (uint32_t)((v[j].x >> 16) != tag || (v[j].y >> 16) != tag || (v[j].z >> 16) != tag || (v[j].w >> 16) != tag) << j;
                    } while (__any_sync(0xffffffffu, miss) && ++it < SD_SPIN);
                    #pragma unroll
                    for (int j = 0; j < 8; j++) sts128(sb + SD_Q0 + ((i + j) * 32 + lane) * 16, v[j]);
                }
            }
            bar_sync(5, 128);
        }
        if (w) units(ic<2>(), 2 * (w - 1), 4 * (NSEG - 1));
        units(ic<1>(), 4 * (NSEG - 1) + w, 0);
    }
    if (tid == 256) GT(blockIdx.x, 72);
}

extern "C" void kernel_launch(void* const* d_in, const int* in_sizes, int n_in, void* d_out, int out_size) {
    const bf16* x = (const bf16*)d_in[0];
    const bf16* mem0 = (const bf16*)d_in[1];
    const bf16* Wq = (const bf16*)d_in[2];
    const bf16* Wk = (const bf16*)d_in[3];
    const bf16* Wv = (const bf16*)d_in[4];
    const bf16* Wo = (const bf16*)d_in[5];
    const bf16* log_A_real = (const bf16*)d_in[8];
    const bf16* A_imag = (const bf16*)d_in[9];
    const bf16* C_real = (const bf16*)d_in[10];
    const bf16* C_imag = (const bf16*)d_in[11];
    const bf16* log_dt = (const bf16*)d_in[12];
    const bf16* D_skip = (const bf16*)d_in[13];
    const bf16* gate_w = (const bf16*)d_in[14];
    bf16* out = (bf16*)d_out;
    typedef CUresult (*EncFn)(CUtensorMap*, CUtensorMapDataType, cuuint32_t, void*, const cuuint64_t*, const cuuint64_t*, const cuuint32_t*, const cuuint32_t*,
                              CUtensorMapInterleave, CUtensorMapSwizzle, CUtensorMapL2promotion, CUtensorMapFloatOOBfill);
    static EncFn enc = nullptr;
    if (!enc) { void* fn = nullptr; cudaDriverEntryPointQueryResult qr; cudaGetDriverEntryPoint("cuTensorMapEncodeTiled", &fn, cudaEnableDefault, &qr); enc = (EncFn)fn; }
    auto mk = [&](CUtensorMap* tm, const void* ptr, uint64_t cols, uint64_t rows, uint32_t bc, uint32_t br) {
        cuuint64_t gdim[2] = {cols, rows}; cuuint64_t gstr[1] = {cols * 2}; cuuint32_t box[2] = {bc, br}; cuuint32_t estr[2] = {1, 1};
        enc(tm, CU_TENSOR_MAP_DATA_TYPE_BFLOAT16, 2, (void*)ptr, gdim, gstr, box, estr, CU_TENSOR_MAP_INTERLEAVE_NONE, bc == 64 ? CU_TENSOR_MAP_SWIZZLE_128B : CU_TENSOR_MAP_SWIZZLE_64B,
            CU_TENSOR_MAP_L2_PROMOTION_L2_256B, CU_TENSOR_MAP_FLOAT_OOB_FILL_NONE);
    };
    static bool attr_done = false;
    if (!attr_done) {
        cudaFuncSetAttribute(chain_kernel, cudaFuncAttributeMaxDynamicSharedMemorySize, SM_TOTAL);
        cudaFuncSetAttribute(side_kernel, cudaFuncAttributeMaxDynamicSharedMemorySize, SD_TOTAL);
        attr_done = true;
    }
    CUtensorMap tmx, tma, tmb, tmw, tmq, tmk, tmv, tmo;
    {
        cuuint64_t gdim[3] = {64, S_LEN, DM / 64}; cuuint64_t gstr[2] = {DM * 2, 128}; cuuint32_t box[3] = {64, SEG, 3}; cuuint32_t estr[3] = {1, 1, 1};
        enc(&tmx, CU_TENSOR_MAP_DATA_TYPE_BFLOAT16, 3, (void*)x, gdim, gstr, box, estr, CU_TENSOR_MAP_INTERLEAVE_NONE, CU_TENSOR_MAP_SWIZZLE_128B,
            CU_TENSOR_MAP_L2_PROMOTION_L2_256B, CU_TENSOR_MAP_FLOAT_OOB_FILL_NONE);
    }
    static void* acc = nullptr;
    if (!acc) cudaGetSymbolAddress(&acc, g_acc);
    for (int w = 0; w < 2; w++) {
        cuuint64_t gdim[3] = {64, 4, 64}; cuuint64_t gstr[2] = {256, 1024}; cuuint32_t box[3] = {w ? 8u : 32u, 2, (w ? 18u : 36u) / (MEM_MC ? 3u : 1u)}; cuuint32_t estr[3] = {1, 1, 1};
        enc(w ? &tmb : &tma, CU_TENSOR_MAP_DATA_TYPE_UINT32, 3, acc, gdim, gstr, box, estr, CU_TENSOR_MAP_INTERLEAVE_NONE, CU_TENSOR_MAP_SWIZZLE_NONE,
            CU_TENSOR_MAP_L2_PROMOTION_NONE, CU_TENSOR_MAP_FLOAT_OOB_FILL_NONE);
    }
    mk(&tmw, Wo, DM, NH * DH, 64, 64);
    mk(&tmo, Wo, DM, NH * DH, 32, 128);
    mk(&tmq, Wq, NH * DH, DM, 32, 48); mk(&tmk, Wk, NH * DH, DM, 32, 48); mk(&tmv, Wv, NH * DH, DM, 32, 48);
    chain_kernel<<<96, CH_THREADS, SM_TOTAL>>>(tmx, tmq, tmk, tmv, tmo, tma, tmb, mem0, 0u);
    cudaLaunchConfig_t cfg = {};
    cfg.gridDim = dim3(SD_CTAS); cfg.blockDim = dim3(SD_THREADS); cfg.dynamicSmemBytes = SD_TOTAL; cfg.stream = cudaStreamPerThread;
    cudaLaunchAttribute at[1];
    at[0].id = cudaLaunchAttributeProgrammaticStreamSerialization; at[0].val.programmaticStreamSerializationAllowed = 1;
    cfg.attrs = at; cfg.numAttrs = 1;
    cudaLaunchKernelEx(&cfg, side_kernel, tmw, x, log_A_real, A_imag, C_real, C_imag, log_dt, D_skip, gate_w, out);
}
```

```cpp
#include <cuda_runtime.h>
#include <cuda.h>
#include <cuda_bf16.h>
#include <stdint.h>

#define S_LEN 2048
#define DM 576
#define NH 32
#define DH 128
#define NMEM 8
#define SEG 32
#define NSEG 64
#define LQ 40
#define NS 128

typedef __nv_bfloat16 bf16;

__device__ __forceinline__ float bf(bf16 v) { return __bfloat162float(v); }
__device__ __forceinline__ bf16 tobf(float v) { return __float2bfloat16_rn(v); }
__device__ __forceinline__ float rbf(float v) { return __bfloat162float(__float2bfloat16_rn(v)); }

#define CH_THREADS 384
#define SPIN_LIMIT (1 << 17)
#define SM_X     0
#define XBUF     36864
#define SM_TOK   73728
#define TOKBUF   24576
#define SM_STASH 139264
#define SM_TS    (SM_STASH + 3072)
#define SM_WO    147456
#define SM_MEM   196608
#define SM_EX    205824
#define EXBUF    6144
#define SM_P     218112
#define SM_OST   122880
#define SM_PARK  219136
#define SM_O     223232
#define SM_XT    225280
#define SM_BAR   228352
#define SM_IL    (SM_BAR + 128)
#define SM_TG    (SM_IL + 256)
#define SM_TOTAL (SM_TG + 64)

#define ACC_X    36864
#define ACC_FULL 0x0020u
#define SLOT_OFF(sl) ((((sl) & 1) << 7) | (((sl) & 2) << 8))
__device__ __align__(65536) unsigned char g_acc[65536];
__device__ unsigned int g_init[96];
__device__ __align__(1024) uint4 g_last[36][2][32][32];
__device__ unsigned int g_epoch = 1;
__device__ __align__(128) unsigned int g_ts[128];
__device__ __align__(1024) bf16 g_otok[S_LEN * NH * DH];
__device__ __align__(1024) unsigned char g_tokx[96][8192];
__device__ __align__(128) unsigned int g_prog[96];
#define STAMP(i)
#define STAMPV(i, v)
#define GT(b, i)
#define STAMPB(i)

__device__ __forceinline__ uint32_t smem_u32(const void* p) { return (uint32_t)__cvta_generic_to_shared(p); }
__device__ __forceinline__ void ldsm_x4(uint32_t (&r)[4], uint32_t addr) {
    asm volatile("ldmatrix.sync.aligned.m8n8.x4.shared.b16 {%0,%1,%2,%3}, [%4];" : "=r"(r[0]), "=r"(r[1]), "=r"(r[2]), "=r"(r[3]) : "r"(addr) : "memory");
}
__device__ __forceinline__ void ldsm_x4_p(uint32_t (&r)[4], uint32_t addr, uint32_t skip) {
    asm volatile("{\n.reg .pred p;\nsetp.eq.u32 p, %5, 0;\n@p ldmatrix.sync.aligned.m8n8.x4.shared.b16 {%0,%1,%2,%3}, [%4];\n}\n" : "+r"(r[0]), "+r"(r[1]), "+r"(r[2]), "+r"(r[3]) : "r"(addr), "r"(skip) : "memory");
}
__device__ __forceinline__ void ldsm_x4_t(uint32_t (&r)[4], uint32_t addr) {
    asm volatile("ldmatrix.sync.aligned.m8n8.x4.trans.shared.b16 {%0,%1,%2,%3}, [%4];" : "=r"(r[0]), "=r"(r[1]), "=r"(r[2]), "=r"(r[3]) : "r"(addr) : "memory");
}
__device__ __forceinline__ uint32_t ldsm_x1_t(uint32_t addr) {
    uint32_t r; asm volatile("ldmatrix.sync.aligned.m8n8.x1.trans.shared.b16 {%0}, [%1];" : "=r"(r) : "r"(addr) : "memory"); return r;
}
__device__ __forceinline__ void ldsm_x2_t(uint32_t& r0, uint32_t& r1, uint32_t addr) {
    asm volatile("ldmatrix.sync.aligned.m8n8.x2.trans.shared.b16 {%0,%1}, [%2];" : "=r"(r0), "=r"(r1) : "r"(addr) : "memory");
}
__device__ __forceinline__ void stsm_x4(uint32_t addr, uint32_t r0, uint32_t r1, uint32_t r2, uint32_t r3) {
    asm volatile("stmatrix.sync.aligned.m8n8.x4.shared.b16 [%0], {%1,%2,%3,%4};" :: "r"(addr), "r"(r0), "r"(r1), "r"(r2), "r"(r3) : "memory");
}
__device__ __forceinline__ void stsm_x4_t(uint32_t addr, uint32_t r0, uint32_t r1, uint32_t r2, uint32_t r3) {
    asm volatile("stmatrix.sync.aligned.m8n8.x4.trans.shared.b16 [%0], {%1,%2,%3,%4};" :: "r"(addr), "r"(r0), "r"(r1), "r"(r2), "r"(r3) : "memory");
}
__device__ __forceinline__ void mma16816(float (&c)[4], const uint32_t (&a)[4], uint32_t b0, uint32_t b1) {
    asm("mma.sync.aligned.m16n8k16.row.col.f32.bf16.bf16.f32 {%0,%1,%2,%3}, {%4,%5,%6,%7}, {%8,%9}, {%0,%1,%2,%3};"
        : "+f"(c[0]), "+f"(c[1]), "+f"(c[2]), "+f"(c[3]) : "r"(a[0]), "r"(a[1]), "r"(a[2]), "r"(a[3]), "r"(b0), "r"(b1));
}
__device__ __forceinline__ void mma16816r(float (&c)[4], uint32_t a0, uint32_t a1, uint32_t a2, uint32_t a3, uint32_t b0, uint32_t b1) {
    asm("mma.sync.aligned.m16n8k16.row.col.f32.bf16.bf16.f32 {%0,%1,%2,%3}, {%4,%5,%6,%7}, {%8,%9}, {%0,%1,%2,%3};"
        : "+f"(c[0]), "+f"(c[1]), "+f"(c[2]), "+f"(c[3]) : "r"(a0), "r"(a1), "r"(a2), "r"(a3), "r"(b0), "r"(b1));
}
__device__ __forceinline__ void mma1688(float (&c)[4], uint32_t a0, uint32_t a1, uint32_t b0) {
    asm("mma.sync.aligned.m16n8k8.row.col.f32.bf16.bf16.f32 {%0,%1,%2,%3}, {%4,%5}, {%6}, {%0,%1,%2,%3};"
        : "+f"(c[0]), "+f"(c[1]), "+f"(c[2]), "+f"(c[3]) : "r"(a0), "r"(a1), "r"(b0));
}
__device__ __forceinline__ uint32_t pack_bf16(float lo, float hi) {
    uint32_t r; asm("cvt.rn.bf16x2.f32 %0, %1, %2;" : "=r"(r) : "f"(hi), "f"(lo)); return r;
}
__device__ __forceinline__ float bf_lo(uint32_t v) { return __uint_as_float(v << 16); }
__device__ __forceinline__ float bf_hi(uint32_t v) { return __uint_as_float(v & 0xffff0000u); }
__device__ __forceinline__ uint32_t max_bf2(uint32_t a, uint32_t b) { uint32_t r; asm("max.bf16x2 %0, %1, %2;" : "=r"(r) : "r"(a), "r"(b)); return r; }
__device__ __forceinline__ uint32_t maxabs_bf2(uint32_t a, uint32_t b) { uint32_t r; asm("max.NaN.xorsign.abs.bf16x2 %0, %1, %2;" : "=r"(r) : "r"(a), "r"(b)); return r; }
__device__ __forceinline__ float ex2(float x) { float r; asm("ex2.approx.ftz.f32 %0, %1;" : "=f"(r) : "f"(x)); return r; }
__device__ __forceinline__ void ld_relaxed128_p(uint4& v, const uint4* p, uint32_t pred) {
    asm volatile("{\n.reg .pred p;\nsetp.ne.u32 p, %5, 0;\n@p ld.relaxed.gpu.global.v4.u32 {%0,%1,%2,%3}, [%4];\n}\n" : "+r"(v.x), "+r"(v.y), "+r"(v.z), "+r"(v.w) : "l"(p), "r"(pred) : "memory");
}
__device__ __forceinline__ uint4 ld_relaxed128(const uint4* p) { uint4 v; asm volatile("ld.relaxed.gpu.global.v4.u32 {%0,%1,%2,%3}, [%4];" : "=r"(v.x), "=r"(v.y), "=r"(v.z), "=r"(v.w) : "l"(p) : "memory"); return v; }
__device__ __forceinline__ uint32_t ld_relaxed32(const uint32_t* p) { uint32_t v; asm volatile("ld.relaxed.gpu.global.u32 %0, [%1];" : "=r"(v) : "l"(p) : "memory"); return v; }
__device__ __forceinline__ void st_relaxed128(uint4* p, uint4 v) { asm volatile("st.relaxed.gpu.global.v4.u32 [%0], {%1,%2,%3,%4};" :: "l"(p), "r"(v.x), "r"(v.y), "r"(v.z), "r"(v.w) : "memory"); }
__device__ __forceinline__ void st_relaxed32(uint32_t* p, uint32_t v) { asm volatile("st.relaxed.gpu.global.u32 [%0], %1;" :: "l"(p), "r"(v) : "memory"); }
__device__ __forceinline__ void st_relaxed128_p(uint4* p, uint4 v, uint32_t skip) {
    asm volatile("{\n.reg .pred p;\nsetp.eq.u32 p, %5, 0;\n@p st.relaxed.gpu.global.v4.u32 [%0], {%1,%2,%3,%4};\n}\n" :: "l"(p), "r"(v.x), "r"(v.y), "r"(v.z), "r"(v.w), "r"(skip) : "memory");
}
__device__ __forceinline__ void st_relaxed64_p(void* p, uint32_t x, uint32_t y, uint32_t skip) {
    asm volatile("{\n.reg .pred p;\n.reg .b64 v;\nsetp.eq.u32 p, %3, 0;\nmov.b64 v, {%1,%2};\n@p st.relaxed.gpu.global.b64 [%0], v;\n}\n" :: "l"(p), "r"(x), "r"(y), "r"(skip) : "memory");
}
__device__ __forceinline__ void ld_relaxed64_p(uint2& v, const void* p, uint32_t pred) {
    asm volatile("{\n.reg .pred p;\n.reg .b64 v;\nsetp.ne.u32 p, %3, 0;\nmov.b64 v, {%0,%1};\n@p ld.relaxed.gpu.global.b64 v, [%2];\nmov.b64 {%0,%1}, v;\n}\n" : "+r"(v.x), "+r"(v.y) : "l"(p), "r"(pred) : "memory");
}
__device__ __forceinline__ uint2 ld_relaxed64(const void* p) {
    uint2 v; asm volatile("{\n.reg .b64 v;\nld.relaxed.gpu.global.b64 v, [%2];\nmov.b64 {%0,%1}, v;\n}\n" : "=r"(v.x), "=r"(v.y) : "l"(p) : "memory"); return v;
}
__device__ __forceinline__ void st_relaxed32_p(void* p, uint32_t v, uint32_t skip) {
    asm volatile("{\n.reg .pred p;\nsetp.eq.u32 p, %2, 0;\n@p st.relaxed.gpu.global.u32 [%0], %1;\n}\n" :: "l"(p), "r"(v), "r"(skip) : "memory");
}
__device__ __forceinline__ void bar_arrive_p(int id, int n, uint32_t skip) {
    asm volatile("{\n.reg .pred p;\nsetp.eq.u32 p, %2, 0;\n@p bar.arrive %0, %1;\n}\n" :: "r"(id), "r"(n), "r"(skip) : "memory");
}
__device__ __forceinline__ void bar_sync_p(int id, int n, uint32_t skip) {
    asm volatile("{\n.reg .pred p;\nsetp.eq.u32 p, %2, 0;\n@p bar.sync %0, %1;\n}\n" :: "r"(id), "r"(n), "r"(skip) : "memory");
}
__device__ __forceinline__ uint32_t movm(uint32_t x) { uint32_t r; asm volatile("movmatrix.sync.aligned.m8n8.trans.b16 %0, %1;" : "=r"(r) : "r"(x)); return r; }
__device__ __forceinline__ void sts32_p(uint32_t a, uint32_t v, uint32_t doit) {
    asm volatile("{\n.reg .pred p;\nsetp.ne.u32 p, %2, 0;\n@p st.shared.u32 [%0], %1;\n}\n" :: "r"(a), "r"(v), "r"(doit) : "memory");
}
__device__ __forceinline__ uint32_t pin(uint32_t x) { return __shfl_sync(0xffffffffu, x, threadIdx.x & 31); }
__device__ __forceinline__ void ldsm16_t(uint32_t (&b)[4][4], uint32_t a) {
    asm volatile("ldmatrix.sync.aligned.m8n8.x4.trans.shared.b16 {%0,%1,%2,%3}, [%16];\n"
                 "ldmatrix.sync.aligned.m8n8.x4.trans.shared.b16 {%4,%5,%6,%7}, [%16+512];\n"
                 "ldmatrix.sync.aligned.m8n8.x4.trans.shared.b16 {%8,%9,%10,%11}, [%16+1024];\n"
                 "ldmatrix.sync.aligned.m8n8.x4.trans.shared.b16 {%12,%13,%14,%15}, [%16+1536];\n"
        : "=r"(b[0][0]), "=r"(b[0][1]), "=r"(b[0][2]), "=r"(b[0][3]), "=r"(b[1][0]), "=r"(b[1][1]), "=r"(b[1][2]), "=r"(b[1][3]),
          "=r"(b[2][0]), "=r"(b[2][1]), "=r"(b[2][2]), "=r"(b[2][3]), "=r"(b[3][0]), "=r"(b[3][1]), "=r"(b[3][2]), "=r"(b[3][3]) : "r"(a) : "memory");
}
template<int ID> __device__ __forceinline__ void sched_fence(uint32_t never) { while (never == 0x7fffff00u + ID) { asm volatile("nanosleep.u32 64;" ::: "memory"); } }
__device__ __forceinline__ uint32_t opaque_u() { uint32_t v; asm volatile("mov.u32 %0, %%nsmid;" : "=r"(v)); return v; }
__device__ __forceinline__ uint32_t bar_red_or(int id, int n, uint32_t v) {
    uint32_t r; asm volatile("{\n.reg .pred p, q;\nsetp.ne.u32 p, %3, 0;\nbar.red.or.pred q, %1, %2, p;\nselp.u32 %0, 1, 0, q;\n}\n" : "=r"(r) : "r"(id), "r"(n), "r"(v) : "memory"); return r;
}
template<class T> __device__ __forceinline__ T* launder_p(T* p) { asm volatile("" : "+l"(p)); return p; }
__device__ __forceinline__ uint32_t mapa_u32(uint32_t addr, uint32_t rank) { uint32_t d; asm("mapa.shared::cluster.u32 %0, %1, %2;" : "=r"(d) : "r"(addr), "r"(rank)); return d; }
__device__ __forceinline__ uint32_t mapa_v(uint32_t addr, uint32_t rank) { uint32_t d; asm volatile("mapa.shared::cluster.u32 %0, %1, %2;" : "=r"(d) : "r"(addr), "r"(rank)); return d; }
__device__ __forceinline__ void st_async32(uint32_t addr, uint32_t v, uint32_t mbar) { asm volatile("st.async.shared::cluster.mbarrier::complete_tx::bytes.u32 [%0], %1, [%2];" :: "r"(addr), "r"(v), "r"(mbar) : "memory"); }
__device__ __forceinline__ void cluster_arrive() { asm volatile("barrier.cluster.arrive.release.aligned;" ::: "memory"); }
__device__ __forceinline__ void cluster_wait() { asm volatile("barrier.cluster.wait.acquire.aligned;" ::: "memory"); }
__device__ __forceinline__ void cp_async16(uint32_t dst, const void* src) { asm volatile("cp.async.cg.shared.global [%0], [%1], 16;" :: "r"(dst), "l"(src) : "memory"); }
__device__ __forceinline__ void cp_async_commit() { asm volatile("cp.async.commit_group;" ::: "memory"); }
template<int N> __device__ __forceinline__ void cp_async_wait() { asm volatile("cp.async.wait_group %0;" :: "n"(N) : "memory"); }
__device__ __forceinline__ void cp_async_wait0() { asm volatile("cp.async.wait_group 0;" ::: "memory"); }
__device__ __forceinline__ void mbar_init(uint32_t a, uint32_t cnt) { asm volatile("mbarrier.init.shared.b64 [%0], %1;" :: "r"(a), "r"(cnt) : "memory"); }
__device__ __forceinline__ void mbar_expect_tx(uint32_t a, uint32_t bytes) { asm volatile("mbarrier.arrive.expect_tx.shared.b64 _, [%0], %1;" :: "r"(a), "r"(bytes) : "memory"); }
__device__ __forceinline__ bool mbar_try(uint32_t a, uint32_t parity) {
    uint32_t ok; asm volatile("{\n.reg .pred p;\nmbarrier.try_wait.parity.shared::cta.b64 p, [%1], %2;\nselp.u32 %0, 1, 0, p;\n}\n" : "=r"(ok) : "r"(a), "r"(parity) : "memory"); return ok;
}
__device__ __forceinline__ void mbar_wait(uint32_t a, uint32_t parity) { int it = 0; bool more; do { more = ++it < SPIN_LIMIT; } while (!mbar_try(a, parity) && more); }
__device__ __forceinline__ void bar_sync(int id, int n) { asm volatile("bar.sync %0, %1;" :: "r"(id), "r"(n) : "memory"); }
__device__ __forceinline__ void bar_arrive(int id, int n) { asm volatile("bar.arrive %0, %1;" :: "r"(id), "r"(n) : "memory"); }
__device__ __forceinline__ void fence_async_smem() { asm volatile("fence.proxy.async.shared::cta;" ::: "memory"); }
__device__ __forceinline__ void sts32(uint32_t a, uint32_t v) { asm volatile("st.shared.u32 [%0], %1;" :: "r"(a), "r"(v) : "memory"); }
__device__ __forceinline__ void sts128(uint32_t a, uint4 v) { asm volatile("st.shared.v4.u32 [%0], {%1,%2,%3,%4};" :: "r"(a), "r"(v.x), "r"(v.y), "r"(v.z), "r"(v.w) : "memory"); }
__device__ __forceinline__ uint4 lds128(uint32_t a) { uint4 v; asm volatile("ld.shared.v4.u32 {%0,%1,%2,%3}, [%4];" : "=r"(v.x), "=r"(v.y), "=r"(v.z), "=r"(v.w) : "r"(a) : "memory"); return v; }
__device__ __forceinline__ uint32_t lds32(uint32_t a) { uint32_t v; asm volatile("ld.shared.u32 %0, [%1];" : "=r"(v) : "r"(a) : "memory"); return v; }
__device__ __forceinline__ uint32_t gtime_lo() { uint32_t t; asm volatile("mov.u32 %0, %globaltimer_lo;" : "=r"(t)); return t; }
__device__ __forceinline__ void wait_gtime(uint32_t tg) {
    asm volatile("{\n.reg .pred p, q;\n.reg .b64 t;\n.reg .b32 lo, hi, d, n;\nmov.b32 n, 300;\n"
                 "WG_%=:\nmov.u64 t, %%globaltimer;\nmov.b64 {lo, hi}, t;\nsub.s32 d, lo, %0;\nsub.s32 n, n, 1;\n"
                 "setp.gt.s32 q, n, 0;\nsetp.lt.and.s32 p, d, 0, q;\n@p bra.uni WG_%=;\n}\n" :: "r"(tg) : "memory");
}
__device__ __forceinline__ void delay_clk(int d) { uint32_t t0 = clock(); while ((int)(clock() - t0) < d) {} }

__device__ __forceinline__ uint64_t desc128(uint32_t addr) {
    return (uint64_t)((addr & 0x3FFFF) >> 4) | ((uint64_t)1 << 16) | ((uint64_t)64 << 32) | ((uint64_t)1 << 62);
}
template<int accum> __device__ __forceinline__ void wgmma_n32(float (&d)[16], const uint32_t (&a)[4], uint64_t desc) {
    if (accum) {
        asm volatile("{\n.reg .pred p;\nsetp.ne.b32 p, 1, 0;\n"
            "wgmma.mma_async.sync.aligned.m64n32k16.f32.bf16.bf16 {%0,%1,%2,%3,%4,%5,%6,%7,%8,%9,%10,%11,%12,%13,%14,%15}, {%16,%17,%18,%19}, %20, p, 1, 1, 0;\n}\n"
            : "+f"(d[0]), "+f"(d[1]), "+f"(d[2]), "+f"(d[3]), "+f"(d[4]), "+f"(d[5]), "+f"(d[6]), "+f"(d[7]),
              "+f"(d[8]), "+f"(d[9]), "+f"(d[10]), "+f"(d[11]), "+f"(d[12]), "+f"(d[13]), "+f"(d[14]), "+f"(d[15])
            : "r"(a[0]), "r"(a[1]), "r"(a[2]), "r"(a[3]), "l"(desc));
    } else {
        asm volatile("{\n.reg .pred p;\nsetp.ne.b32 p, 0, 0;\n"
            "wgmma.mma_async.sync.aligned.m64n32k16.f32.bf16.bf16 {%0,%1,%2,%3,%4,%5,%6,%7,%8,%9,%10,%11,%12,%13,%14,%15}, {%16,%17,%18,%19}, %20, p, 1, 1, 0;\n}\n"
            : "=f"(d[0]), "=f"(d[1]), "=f"(d[2]), "=f"(d[3]), "=f"(d[4]), "=f"(d[5]), "=f"(d[6]), "=f"(d[7]),
              "=f"(d[8]), "=f"(d[9]), "=f"(d[10]), "=f"(d[11]), "=f"(d[12]), "=f"(d[13]), "=f"(d[14]), "=f"(d[15])
            : "r"(a[0]), "r"(a[1]), "r"(a[2]), "r"(a[3]), "l"(desc));
    }
}
__device__ __forceinline__ float rcp_approx(float x) { float r; asm("rcp.approx.ftz.f32 %0, %1;" : "=f"(r) : "f"(x)); return r; }
__device__ __forceinline__ void wg_fence() { asm volatile("wgmma.fence.sync.aligned;" ::: "memory"); }
__device__ __forceinline__ void wg_commit() { asm volatile("wgmma.commit_group.sync.aligned;" ::: "memory"); }
__device__ __forceinline__ void wg_wait0() { asm volatile("wgmma.wait_group.sync.aligned 0;" ::: "memory"); }

#define SCALE_HI 0x3db53db5u
#define SCALE_LO 0x371e371eu
#define LOG2E 1.4426950408889634f
#define NEG_BIG2 0xce6ece6eu
__device__ __forceinline__ uint32_t scale_bf2(uint32_t x) {
    uint32_t t, r;
    asm("mul.rn.bf16x2 %0, %1, %2;" : "=r"(t) : "r"(x), "r"(SCALE_LO));
    asm("fma.rn.bf16x2 %0, %1, %2, %3;" : "=r"(r) : "r"(x), "r"(SCALE_HI), "r"(t));
    return r;
}
__device__ __forceinline__ void cluster_arrive_rx() { asm volatile("barrier.cluster.arrive.relaxed.aligned;" ::: "memory"); }
__device__ __forceinline__ uint32_t launder(uint32_t x) { asm volatile("" : "+r"(x)); return x; }
__device__ __forceinline__ void mbar_arrive(uint32_t a) { asm volatile("mbarrier.arrive.shared.b64 _, [%0];" :: "r"(a) : "memory"); }
__device__ __forceinline__ void mbar_wait_cl(uint32_t a, uint32_t parity) {
    int it = 0; uint32_t ok;
    do { asm volatile("{\n.reg .pred p;\nmbarrier.try_wait.parity.acquire.cluster.shared::cta.b64 p, [%1], %2;\nselp.u32 %0, 1, 0, p;\n}\n" : "=r"(ok) : "r"(a), "r"(parity) : "memory"); } while (!ok && ++it < SPIN_LIMIT);
}
__device__ __forceinline__ uint64_t desc_from(uint32_t lo) { return (uint64_t)lo | ((uint64_t)0x40000040u << 32); }
#define SB_OFF 1024u
#define DESC_LO(off) ((((SB_OFF + (uint32_t)(off)) & 0x3FFFFu) >> 4) | 0x10000u)
template<int N> struct ic { static constexpr int value = N; };
__device__ __forceinline__ uint32_t uni(uint32_t x) { return __shfl_sync(0xffffffffu, x, 0); }

__device__ __forceinline__ uint32_t pack_f16(float lo, float hi) { uint32_t r; asm("cvt.rn.f16x2.f32 %0, %1, %2;" : "=r"(r) : "f"(hi), "f"(lo)); return r; }
__device__ __forceinline__ void sts16(uint32_t a, uint16_t v) { asm volatile("st.shared.u16 [%0], %1;" :: "r"(a), "h"(v) : "memory"); }
__device__ __forceinline__ void sts64(uint32_t a, uint32_t x, uint32_t y) { asm volatile("st.shared.v2.u32 [%0], {%1,%2};" :: "r"(a), "r"(x), "r"(y) : "memory"); }
__device__ __forceinline__ void ld_relaxed32_p(uint32_t& v, const void* p, uint32_t pred) {
    asm volatile("{\n.reg .pred p;\nsetp.ne.u32 p, %2, 0;\n@p ld.relaxed.gpu.global.u32 %0, [%1];\n}\n" : "+r"(v) : "l"(p), "r"(pred) : "memory");
}
__device__ __forceinline__ uint2 lds64(uint32_t a) { uint2 v; asm volatile("ld.shared.v2.u32 {%0,%1}, [%2];" : "=r"(v.x), "=r"(v.y) : "r"(a) : "memory"); return v; }
__device__ __forceinline__ void mbar_wait2(uint32_t a, uint32_t pa, uint32_t b, uint32_t pb) {
    int it = 0; uint32_t ok;
    do { asm volatile("{\n.reg .pred p, q;\nmbarrier.try_wait.parity.shared::cta.b64 p, [%1], %2;\nmbarrier.try_wait.parity.shared::cta.b64 q, [%3], %4;\nand.pred p, p, q;\nselp.u32 %0, 1, 0, p;\n}\n"
                      : "=r"(ok) : "r"(a), "r"(pa), "r"(b), "r"(pb) : "memory"); } while (!ok && ++it < SPIN_LIMIT);
}
__device__ __forceinline__ float exd(float s, float m) { return ex2(__fmul_rn(__fsub_rn(s, m), LOG2E)); }
__device__ __forceinline__ uint32_t gtime_after(uint32_t z) {
    uint32_t t = 0; asm volatile("{\n.reg .pred p;\nsetp.eq.u32 p, %1, 0;\n@p mov.u32 %0, %%globaltimer_lo;\n}\n" : "+r"(t) : "r"(z)); return t;
}
#define T_KPRE 3
#define BLK_Q(p) (((p) < 3 ? (p) : 8) * 2048)
#define BLK_K(p) (((p) < 3 ? 4 + (p) : 9) * 2048)
#define BLK_V(p) (((p) < 2 ? 3 + 4 * (p) : 8 + (p)) * 2048)
__device__ __forceinline__ uint32_t exp_bf2(uint32_t s) { return pack_bf16(ex2(bf_lo(s) * LOG2E), ex2(bf_hi(s) * LOG2E)); }
template<int MT, int LO, int HI>
__device__ __forceinline__ void tok_loadv(uint32_t tok, int eh, int lane, uint32_t (&bv)[8][4]) {
    const int r8 = lane & 7;
    const uint32_t va = MT ? tok + lane * 64 + ((r8 >> 1) << 4) : tok + (lane & 15) * 64 + (((lane >> 4) ^ (r8 >> 1)) << 4);
    const uint32_t o0 = eh ? BLK_V(2) : BLK_V(0), o1 = eh ? BLK_V(3) : BLK_V(1);
    #pragma unroll
    for (int n = LO; n < HI; n++) { if (MT) ldsm_x4_t(bv[n], (va ^ ((n & 3) << 4)) + (n < 4 ? o0 : o1)); else ldsm_x4_t(bv[n], (va ^ ((n & 1) << 5)) + BLK_V(n >> 1)); }
}
#define T_VPRE 4
template<int MT, class F>
__device__ __forceinline__ void tok_part1(uint32_t tok, int eh, int lane, uint32_t (&q)[8][4], uint32_t (&sp)[5][2], uint32_t (&pa)[5][2], uint32_t (&bv)[8][4], uint32_t& rng, F&& hold) {
    float e[5][4];
    constexpr int NK = MT ? 5 : 3;
    const int g = lane >> 2, t = lane & 3, mi = lane >> 3, r8 = lane & 7;
    #pragma unroll
    for (int nt = 1; nt < NK; nt++) { e[nt][0] = e[nt][1] = e[nt][2] = e[nt][3] = 0.f; }
    const uint32_t qa = tok + (16 * MT + (mi & 1) * 8 + r8) * 64 + (((mi >> 1) ^ (r8 >> 1)) << 4);
    const uint32_t ka = tok + r8 * 64 + ((mi ^ (r8 >> 1)) << 4);
    uint32_t b[4][NK][4];
    constexpr int PRE = MT ? T_KPRE : 4;
    #pragma unroll
    for (int k2 = 0; k2 < 4; k2++) {
        ldsm_x4(q[2 * k2], qa + BLK_Q(k2)); ldsm_x4(q[2 * k2 + 1], (qa ^ 32) + BLK_Q(k2));
        if (k2 < PRE) {
            #pragma unroll
            for (int nt = 1; nt < NK; nt++) ldsm_x4(b[k2][nt], ka + BLK_K(k2) + (nt - 1) * 512);
        }
    }
    hold();
    #pragma unroll
    for (int k2 = 0; k2 < 4; k2++) {
        if (k2 >= PRE) {
            #pragma unroll
            for (int nt = 1; nt < NK; nt++) ldsm_x4(b[k2][nt], ka + BLK_K(k2) + (nt - 1) * 512);
        }
        #pragma unroll
        for (int nt = 1; nt < NK; nt++) mma16816(e[nt], q[2 * k2], b[k2][nt][0], b[k2][nt][1]);
        #pragma unroll
        for (int nt = 1; nt < NK; nt++) mma16816(e[nt], q[2 * k2 + 1], b[k2][nt][2], b[k2][nt][3]);
    }
    #pragma unroll
    for (int nt = 1; nt < NK; nt++) asm volatile("" : "+f"(e[nt][0]), "+f"(e[nt][1]), "+f"(e[nt][2]), "+f"(e[nt][3]));
    #pragma unroll
    for (int nt = 1; nt < NK; nt++) {
        sp[nt][0] = nt < NK - 1 ? scale_bf2(pack_bf16(e[nt][0], e[nt][1])) : NEG_BIG2; sp[nt][1] = scale_bf2(pack_bf16(e[nt][2], e[nt][3]));
        rng = maxabs_bf2(nt == 1 ? sp[1][0] : (nt < NK - 1 ? maxabs_bf2(rng, sp[nt][0]) : rng), sp[nt][1]);
    }
    const uint32_t keep = (2 * t <= g ? 0x0000ffffu : 0u) | (2 * t + 1 <= g ? 0xffff0000u : 0u);
    sp[NK - 2][0] = (sp[NK - 2][0] & keep) | (NEG_BIG2 & ~keep);
    sp[NK - 1][1] = (sp[NK - 1][1] & keep) | (NEG_BIG2 & ~keep);
    #pragma unroll
    for (int nt = 1; nt < NK; nt++) { pa[nt][0] = nt < NK - 1 ? exp_bf2(sp[nt][0]) : 0u; pa[nt][1] = exp_bf2(sp[nt][1]); }
    tok_loadv<MT, 0, MT ? T_VPRE : 8>(tok, eh, lane, bv);
}
template<int MT, class F, class G, class H, class I>
__device__ __forceinline__ void tok_part2(uint32_t tok, uint32_t exl, uint32_t ost, int eh, int lane, const uint32_t (&q)[8][4], uint32_t (&sp)[5][2], uint32_t (&pa)[5][2], uint32_t (&bv)[8][4], uint32_t rng, bool vb,
                                          F&& wait_v, G&& duty, H&& pace, I&& wait_x) {
    constexpr int NK = MT ? 5 : 3;
    const int mi = lane >> 3, r8 = lane & 7;
    {
        float c[4][4];
        uint32_t b[4][4];
        ldsm16_t(b, exl + 2048);
        duty();
        #pragma unroll
        for (int j = 0; j < 4; j++) { c[j][0] = c[j][1] = c[j][2] = c[j][3] = 0.f; }
        #pragma unroll
        for (int k2 = 0; k2 < 4; k2++) { mma16816(c[(2 * k2) & 3], q[2 * k2], b[k2][0], b[k2][1]); mma16816(c[(2 * k2 + 1) & 3], q[2 * k2 + 1], b[k2][2], b[k2][3]); }
        sp[0][0] = scale_bf2(pack_bf16((c[0][0] + c[1][0]) + (c[2][0] + c[3][0]), (c[0][1] + c[1][1]) + (c[2][1] + c[3][1])));
        sp[0][1] = scale_bf2(pack_bf16((c[0][2] + c[1][2]) + (c[2][2] + c[3][2]), (c[0][3] + c[1][3]) + (c[2][3] + c[3][3])));
    }
    pa[0][0] = exp_bf2(sp[0][0]); pa[0][1] = exp_bf2(sp[0][1]);
    rng = maxabs_bf2(maxabs_bf2(rng, sp[0][0]), sp[0][1]);
    if (__builtin_expect(__any_sync(0xffffffffu, ((rng & 0x7fff7fffu) + 0x3ddf3ddfu) & 0x80008000u), 0)) {
        uint32_t m0 = sp[0][0], m1 = sp[0][1];
        #pragma unroll
        for (int nt = 1; nt < NK; nt++) { if (nt < NK - 1) m0 = max_bf2(m0, sp[nt][0]); m1 = max_bf2(m1, sp[nt][1]); }
        uint32_t mm = max_bf2(__byte_perm(m0, m1, 0x5410), __byte_perm(m0, m1, 0x7632));
        mm = max_bf2(mm, __shfl_xor_sync(0xffffffffu, mm, 1));
        mm = max_bf2(mm, __shfl_xor_sync(0xffffffffu, mm, 2));
        #pragma unroll
        for (int nt = 0; nt < NK; nt++) {
            if (nt < NK - 1) pa[nt][0] = pack_bf16(exd(bf_lo(sp[nt][0]), bf_lo(mm)), exd(bf_hi(sp[nt][0]), bf_lo(mm)));
            pa[nt][1] = pack_bf16(exd(bf_lo(sp[nt][1]), bf_hi(mm)), exd(bf_hi(sp[nt][1]), bf_hi(mm)));
        }
    }
    tok_loadv<MT, MT ? T_VPRE : 8, 8>(tok, eh, lane, bv);
    wait_v();
    constexpr int NQ = MT ? 2 : 4;
    float o[NQ][4][4], l[4] = {0.f, 0.f, 0.f, 0.f};
    const uint32_t ONE = 0x3F803F80u;
    mma16816r(l, pa[1][0], pa[1][1], pa[2][0], pa[2][1], ONE, ONE);
    if (MT) mma16816r(l, pa[3 % NK][0], pa[3 % NK][1], pa[4 % NK][0], pa[4 % NK][1], ONE, ONE);
    mma1688(l, pa[0][0], pa[0][1], ONE);
    #pragma unroll
    for (int j = 0; j < NQ; j++) {
        uint32_t bm[4];
        ldsm_x4(bm, exl + 4096 + (MT ? eh * 1024 : 0) + 512 * j);
        #pragma unroll
        for (int n = 0; n < 4; n++) {
            o[j][n][0] = o[j][n][1] = o[j][n][2] = o[j][n][3] = 0.f;
            if (MT) mma16816r(o[j][n], pa[1][0], pa[1][1], pa[2][0], pa[2][1], bv[4 * j + n][0], bv[4 * j + n][1]);
            else mma16816r(o[j][n], pa[1][0], pa[1][1], pa[2][0], pa[2][1], bv[2 * j + (n >> 1)][2 * (n & 1)], bv[2 * j + (n >> 1)][2 * (n & 1) + 1]);
        }
        if (MT) {
            #pragma unroll
            for (int n = 0; n < 4; n++) mma16816r(o[j][n], pa[3 % NK][0], pa[3 % NK][1], pa[4 % NK][0], pa[4 % NK][1], bv[4 * j + n][2], bv[4 * j + n][3]);
        }
        #pragma unroll
        for (int n = 0; n < 4; n++) mma1688(o[j][n], pa[0][0], pa[0][1], bm[n]);
    }
    #pragma unroll
    for (int j = 0; j < NQ; j++) asm volatile("" : "+f"(o[j][0][0]), "+f"(o[j][1][0]), "+f"(o[j][2][0]), "+f"(o[j][3][0]));
    asm volatile("" : "+f"(l[0]), "+f"(l[2]));
    wait_x();
    bar_arrive_p(12, 384, !vb);
    pace();
    const float i0 = rcp_approx(l[0]), i1 = rcp_approx(l[2]);
    const uint32_t oa = ost + ((mi & 1) * 8 + r8) * 128 + (((mi >> 1) ^ r8) << 4);
    #pragma unroll
    for (int j = 0; j < NQ; j++) {
        stsm_x4((oa ^ ((j & 1) << 6)) + (j >> 1) * 4096, pack_bf16(o[j][0][0] * i0, o[j][0][1] * i0), pack_bf16(o[j][0][2] * i1, o[j][0][3] * i1), pack_bf16(o[j][1][0] * i0, o[j][1][1] * i0), pack_bf16(o[j][1][2] * i1, o[j][1][3] * i1));
        stsm_x4((oa ^ (((j & 1) << 6) | 32)) + (j >> 1) * 4096, pack_bf16(o[j][2][0] * i0, o[j][2][1] * i0), pack_bf16(o[j][2][2] * i1, o[j][2][3] * i1), pack_bf16(o[j][3][0] * i0, o[j][3][1] * i0), pack_bf16(o[j][3][2] * i1, o[j][3][3] * i1));
    }
}

template<int OA, int OB>
__device__ __forceinline__ void send_tile(float c0, float c1, float c2, float c3, uint32_t a, uint32_t b, uint32_t l16) {
    const uint32_t hi = (uint32_t)((uint64_t)g_acc >> 32);
    asm volatile("{\n.reg .pred q, pl, ph;\n.reg .b64 pa, pb;\n.reg .b32 t, w0, w1, w2;\n.reg .f32 x, y, z;\n"
                 "and.b32 t, %7, 0x30;\nsetp.eq.u32 q, t, 0;\nand.b32 t, %7, 0x70;\nsetp.eq.u32 ph, t, 0;\nxor.pred pl, q, ph;\n"
                 "selp.f32 x, 0f00010000, %4, pl;\nselp.f32 y, 0f00010000, %6, ph;\nselp.f32 z, %6, %4, ph;\n"
                 "cvt.rn.bf16x2.f32 w0, x, %3;\ncvt.rn.bf16x2.f32 w1, y, %5;\ncvt.rn.bf16x2.f32 w2, 0f00010000, z;\n"
                 "mov.b64 pa, {%0, %2};\nmov.b64 pb, {%1, %2};\n"
                 "red.relaxed.gpu.global.add.noftz.bf16x2 [pa+%8], w0;\nred.relaxed.gpu.global.add.noftz.bf16x2 [pa+%10], w1;\n@q red.relaxed.gpu.global.add.noftz.bf16x2 [pb+%9], w2;\n}\n"
        :: "r"(a), "r"(b), "r"(hi), "f"(c0), "f"(c1), "f"(c2), "f"(c3), "r"(l16), "n"(OA), "n"(OB), "n"(OA + 256) : "memory");
}
__device__ __forceinline__ uint32_t send_ua(uint32_t tile) { return (uint32_t)(uint64_t)g_acc + tile * 1024; }
__device__ __forceinline__ uint32_t send_ub(uint32_t tile) { return (uint32_t)(uint64_t)g_acc + ACC_X + (tile >> 1) * 1024 + (tile & 1) * 256; }
__device__ __forceinline__ void lds_il(float& il, float& ih, uint32_t a) {
    uint32_t x, y; asm volatile("ldmatrix.sync.aligned.m8n8.x2.shared.b16 {%0,%1}, [%2];" : "=r"(x), "=r"(y) : "r"(a) : "memory");
    il = __uint_as_float(x); ih = __uint_as_float(y);
}
template<bool AUX>
__device__ __forceinline__ void stage_w(const uint32_t (&wo)[8][4], uint32_t ol, uint32_t tile, uint32_t so, uint32_t l16, uint32_t nv, uint32_t ila) {
    float il, ih;
    uint32_t b[4][4], sa, sx;
    float c[2][4];
    auto addr = [&] {
        const uint32_t ll = AUX ? l16 : l16 | (__float_as_uint(c[0][0]) & nv);
        sa = (ll >> 2) + (send_ua(tile) + so); sx = (ll >> 4) + (send_ub(tile) + so);
    };
    ldsm16_t(b, ol);
    lds_il(il, ih, ila);
    if (AUX) addr(); else sched_fence<0>(nv);
    #pragma unroll
    for (int i = 0; i < 2; i++) c[i][0] = c[i][1] = c[i][2] = c[i][3] = 0.f;
    #pragma unroll
    for (int j = 0; j < 4; j++) {
        if (!AUX && j == 3) addr();
        mma16816(c[0], wo[2 * j], b[j][0], b[j][1]); mma16816(c[1], wo[2 * j + 1], b[j][2], b[j][3]);
    }
    if (AUX) { asm volatile("" : "+f"(c[0][0]), "+f"(c[1][0])); sched_fence<4>(nv); bar_arrive(12, 384); }
    send_tile<0, 0>((c[0][0] + c[1][0]) * il, (c[0][1] + c[1][1]) * ih, (c[0][2] + c[1][2]) * il, (c[0][3] + c[1][3]) * ih, sa, sx, l16);
}
__device__ __forceinline__ void wgmma_n16(float (&d)[8], const uint32_t (&a)[4], uint64_t desc) {
    asm volatile("{\n.reg .pred p;\nsetp.ne.b32 p, 1, 0;\n"
        "wgmma.mma_async.sync.aligned.m64n16k16.f32.bf16.bf16 {%0,%1,%2,%3,%4,%5,%6,%7}, {%8,%9,%10,%11}, %12, p, 1, 1, 0;\n}\n"
        : "+f"(d[0]), "+f"(d[1]), "+f"(d[2]), "+f"(d[3]), "+f"(d[4]), "+f"(d[5]), "+f"(d[6]), "+f"(d[7])
        : "r"(a[0]), "r"(a[1]), "r"(a[2]), "r"(a[3]), "l"(desc));
}

template<int N> __device__ __forceinline__ void code_pad(uint32_t nv) {
    if (N && nv == 0x7fffffe0u + N % 16) {
        float v = __uint_as_float(nv);
        #pragma unroll
        for (int i = 0; i < N; i++) asm volatile("fma.rn.f32 %0, %0, %0, %0;" : "+f"(v));
        sts32_p(0u, __float_as_uint(v), nv);
    }
}
#define PAD_T0 4
#define PAD_T1 0
#define PAD_S 287
#define PAD_P 96
#define BAR_PRO 1
#define BAR_MEM 2
#define BAR_P   3
#define BAR_PRJ 4
#define BAR_VGO 7
#define BAR_X0  7
#define BAR_S   9
#define BAR_P2  10
#define BAR_O   11
#define BAR_V   12
#define VGO_AT 9
#define TP_N 36
#define REG_P 200
#define WO_PRE 3
#define WO_REP 2
#define PRE_W 4
#ifndef M_RES
#define M_RES 5
#endif
#ifndef M_LAG
#define M_LAG 2
#endif
#ifndef M_ARR
#define M_ARR -1
#endif
#define G1_0 256
#define G1_NS 1152

__global__ void __cluster_dims__(3, 1, 1) __launch_bounds__(CH_THREADS, 1)
chain_kernel(const __grid_constant__ CUtensorMap tmx, const __grid_constant__ CUtensorMap tmq, const __grid_constant__ CUtensorMap tmk,
             const __grid_constant__ CUtensorMap tmv, const __grid_constant__ CUtensorMap tmo,
             const __grid_constant__ CUtensorMap tma, const __grid_constant__ CUtensorMap tmb, const bf16* __restrict__ mem0, const uint32_t nv_) {
    extern __shared__ __align__(1024) unsigned char smem[];
    const uint32_t sb = smem_u32(smem);
    const int tid = threadIdx.x, lane = tid & 31;
    const int warp = __shfl_sync(0xffffffffu, tid >> 5, 0);
    const uint32_t nv = __shfl_sync(0xffffffffu, nv_ * tid, 0);
    const int h = blockIdx.x / 3, r = blockIdx.x % 3;
    const int mi = lane >> 3, r8 = lane & 7;
    const uint32_t bX = sb + SM_BAR, bTOK = bX + 16, bEX = bX + 40, bW = bX + 64, bEV = bX + 104, bFREE = bX + 32, bMEM = bX + 56;
    const int nqk = r < 2 ? 6 : 4;
    if ((sb & 0xFFFFFFu) != SB_OFF) __trap();
    asm volatile("griddepcontrol.launch_dependents;");
    if (tid == 0 && blockIdx.x == 0) GT(40, 0);

    auto load_w = [&](int lo, int hi) {
        #pragma unroll 1
        for (int i = lo; i < hi; i++) {
            const int blk = i >> 2, j = i & 3;
            if (i < 48) {
                const int m = r < 2 ? (j < 3 ? r : 2) : (j < 2 ? j : 2), p = r < 2 ? (j < 3 ? j : r) : (j < 2 ? 3 : j);
                asm volatile("cp.async.bulk.tensor.2d.shared::cluster.global.mbarrier::complete_tx::bytes [%0], [%1, {%3, %4}], [%2];"
                    :: "r"(sb + i * 3072), "l"(m == 0 ? &tmq : (m == 1 ? &tmk : &tmv)), "r"(bW + (blk < 3 ? 0 : (blk < 6 ? 8 : (blk < 10 ? 16 : 24)))), "r"(h * DH + p * 32), "r"(blk * 48) : "memory");
            } else asm volatile("cp.async.bulk.tensor.2d.shared::cluster.global.mbarrier::complete_tx::bytes [%0], [%1, {%3, %4}], [%2];"
                :: "r"(sb + SM_WO + (i - 48) * 8192), "l"(&tmo), "r"(bW + 32), "r"(192 * r + 32 * (i - 48)), "r"(h * DH) : "memory");
        }
    };
    if (tid == 352) {
        #pragma unroll
        for (int i = 0; i < 15; i++) mbar_init(bX + 8 * i, (i == 5 || i == 6) ? 1 + nqk : (i >= 13 ? 9 - nqk : 1));
        asm volatile("fence.mbarrier_init.release.cluster;" ::: "memory");
        mbar_expect_tx(bW, 36864); mbar_expect_tx(bW + 8, 36864); mbar_expect_tx(bW + 16, 49152); mbar_expect_tx(bW + 24, 24576); mbar_expect_tx(bW + 32, 49152);
        load_w(0, 2 * PRE_W);
    }
    if (tid < 4) asm volatile("prefetch.param.tensormap [%0];" :: "l"(__cvta_generic_to_grid_constant(tid == 0 ? &tmo : (tid == 1 ? &tmx : (tid == 2 ? &tma : &tmb)))) : "memory");
    const unsigned epoch = ld_relaxed32(&g_epoch);
    __syncthreads();
    const uint32_t pw0 = ((mi >> 1) * 8 + r8) * 64 + (((2 * (warp & 1) + (mi & 1)) ^ (r8 >> 1)) << 4);
    auto tok_publish = [&](int tb, int k) {
        const uint32_t src = sb + SM_TOK + tb * TOKBUF + r * 8192, bar = bTOK + 8 * tb;
        if (k == 1) asm volatile("{\n.reg .pred p;\nelect.sync _|p, 0xffffffff;\n@p mbarrier.arrive.expect_tx.shared.b64 _, [%0], 16384;\n}\n" :: "r"(bar) : "memory");
        asm volatile("{\n.reg .pred p;\nelect.sync _|p, 0xffffffff;\n"
                     "@p cp.async.bulk.shared::cluster.shared::cta.mbarrier::complete_tx::bytes [%0], [%1], 8192, [%2];\n}\n"
            :: "r"(mapa_u32(src, (r + k) % 3)), "r"(src), "r"(mapa_u32(bar, (r + k) % 3)) : "memory");
    };
    if (warp < 8) {
        asm volatile("setmaxnreg.inc.sync.aligned.u32 %0;" :: "n"(REG_P));
        uint32_t wf[36][4];
        const uint32_t wl = sb + (warp >> 1) * 3072 + pw0;
        float ta0[16], ta1[16];
        auto tp_part = [&](auto lo, auto hi) {
            wg_fence();
            #pragma unroll
            for (int i = lo.value; i < hi.value; i++) {
                if (i == 0) wgmma_n32<0>(ta0, wf[0], desc_from(DESC_LO(SM_X))); else wgmma_n32<1>(ta0, wf[i], desc_from(DESC_LO(SM_X) + (i >> 2) * 256 + (i & 3) * 2));
            }
            #pragma unroll
            for (int i = lo.value; i < hi.value; i++) {
                if (i == 0) wgmma_n32<0>(ta1, wf[0], desc_from(DESC_LO(SM_X + XBUF))); else wgmma_n32<1>(ta1, wf[i], desc_from(DESC_LO(SM_X + XBUF) + (i >> 2) * 256 + (i & 3) * 2));
            }
            wg_commit();
        };
        if (tid == 32) load_w(2 * PRE_W, 40);
        if (tid == 0) GT(41 + blockIdx.x % 3, 7);
        code_pad<PAD_P>(nv);
        mbar_wait(bW, 0);
        #pragma unroll
        for (int i = 0; i < 9; i++) ldsm_x4_t(wf[i], wl + (i / 3) * 12288 + (i % 3) * 1024);
        fence_async_smem(); bar_arrive(BAR_X0, 288);
        mbar_wait(bW + 8, 0);
        #pragma unroll
        for (int i = 9; i < 18; i++) ldsm_x4_t(wf[i], wl + (i / 3) * 12288 + (i % 3) * 1024);
        fence_async_smem(); bar_arrive(BAR_X0 + 1, 288);
        mbar_wait(bX, 0); mbar_wait(bX + 8, 0);
        tp_part(ic<0>(), ic<18>());
        wg_wait0();
        sts128(sb + SM_PARK + tid * 16, make_uint4(wf[0][0], wf[0][1], wf[0][2], wf[0][3]));
        mbar_wait(bW + 16, 0);
        #pragma unroll
        for (int i = 18; i < 30; i++) ldsm_x4_t(wf[i], wl + (i / 3) * 12288 + (i % 3) * 1024);
        tp_part(ic<18>(), ic<30>());
        mbar_wait(bW + 24, 0);
        if (tid == 0) GT(41 + blockIdx.x % 3, 0);
        wg_wait0();
        #pragma unroll
        for (int i = 30; i < 36; i++) ldsm_x4_t(wf[i], wl + (i / 3) * 12288 + (i % 3) * 1024);
        fence_async_smem();
        cluster_arrive_rx();
        tp_part(ic<30>(), ic<36>());
        if (tid == 0) GT(41 + blockIdx.x % 3, 2);
        const uint32_t pw = pin(pw0);
        auto tp_store = [&](const float (&acc)[16], uint32_t off) {
            const uint32_t ta = pw + launder(sb + off + (warp >> 1) * 2048);
            stsm_x4_t(ta, pack_bf16(acc[0], acc[1]), pack_bf16(acc[2], acc[3]), pack_bf16(acc[4], acc[5]), pack_bf16(acc[6], acc[7]));
            stsm_x4_t(ta + 1024, pack_bf16(acc[8], acc[9]), pack_bf16(acc[10], acc[11]), pack_bf16(acc[12], acc[13]), pack_bf16(acc[14], acc[15]));
        };
        cluster_wait();
        wg_wait0();
        tp_store(ta0, SM_TOK + r * 8192);
        if (warp == 0) { bar_sync(BAR_PRJ, 256); fence_async_smem(); tok_publish(0, 1); tok_publish(0, 2); } else bar_arrive(BAR_PRJ, 256);
        tp_store(ta1, SM_TOK + TOKBUF + r * 8192);
        { const uint4 v = lds128(sb + SM_PARK + tid * 16); wf[0][0] = v.x; wf[0][1] = v.y; wf[0][2] = v.z; wf[0][3] = v.w; sts32_p(v.x, v.y, nv); }
        if (tid == 0) GT(41 + blockIdx.x % 3, 4);
        const uint32_t l16 = pin(lane * 16), sbl = sb + l16, l4w = pin(sb + warp * 256 + lane * 4);
        uint32_t wo[8][4];
        const int exo = r < 2 ? (warp < 6 ? r * 2048 : 4096 + (2 * r - 6) * 256) : (warp < 2 ? 6 * 256 : (warp < 4 ? 2048 + 4 * 256 : 4096));
        const bool isqk = warp < nqk;
        const uint32_t exbar = isqk ? bEX : bEV;
        uint32_t vf[2][4];
        auto prep = [&](int s) {
            const uint32_t va = pw + launder(sb + SM_TOK + (s & 1) * TOKBUF + BLK_V(warp >> 1));
            mbar_wait(bTOK + 8 * (s & 1), (s >> 1) & 1);
            ldsm_x4_t(vf[0], va); ldsm_x4_t(vf[1], va + 1024);
            sts32_p(vf[0][0], vf[1][0], nv);
        };
        prep(0);
        bar_sync(BAR_MEM, 352);
        for (int s = 0; ; s++) {
            const int par = s & 1;
            const uint32_t wa = pw + launder(sb + SM_WO + (warp >> 1) * 8192);
            const uint32_t exu = launder(SM_EX + par * EXBUF);
            {
                float acc[4][4];
                #pragma unroll
                for (int i = 0; i < 4; i++) { acc[i][0] = acc[i][1] = acc[i][2] = acc[i][3] = 0.f; }
                bar_sync_p(BAR_VGO, 256, isqk);
                #pragma unroll
                for (int i2 = 0; i2 < 18; i2++) {
                    uint32_t b[4];
                    ldsm_x4_t(b, sbl + SM_MEM + i2 * 512);
                    if (i2 == VGO_AT) bar_arrive_p(BAR_VGO, 256, !isqk);
                    mma16816(acc[(2 * i2) & 3], wf[2 * i2], b[0], b[1]);
                    mma16816(acc[(2 * i2 + 1) & 3], wf[2 * i2 + 1], b[2], b[3]);
                }
                float q[4];
                #pragma unroll
                for (int i = 0; i < 4; i++) q[i] = (acc[0][i] + acc[1][i]) + (acc[2][i] + acc[3][i]);
                const uint32_t lo = pack_bf16(q[0], q[1]), hi = pack_bf16(q[2], q[3]);
                const uint32_t exl = l4w + launder(exu + exo), bar = exbar + par * 8;
                #pragma unroll
                for (int k = 1; k < 3; k++) {
                    const uint32_t exd = mapa_u32(exl, (r + k) % 3), exb = mapa_u32(bar, (r + k) % 3);
                    st_async32(exd, lo, exb); st_async32(exd + 128, hi, exb);
                }
                sts32(exl, lo); sts32(exl + 128, hi);
                __syncwarp();
                asm volatile("{\n.reg .pred p;\nelect.sync _|p, 0xffffffff;\n@p mbarrier.arrive.shared.b64 _, [%0];\n}\n" :: "r"(bar) : "memory");
                if (s < NSEG - 1) bar_sync_p(BAR_PRO, 32 * nqk, !isqk);
            }
            if (__builtin_expect(s == NSEG - 1, 0)) break;
            if (__builtin_expect(s == 0, 0)) mbar_wait(bW + 32, 0);
            #pragma unroll
            for (int i = 0; i < WO_PRE; i++) ldsm_x4_t(wo[i], wa + i * 1024);
            #pragma unroll
            for (int k = 0; k < WO_REP; k++) mbar_wait(bEX + 8 * par, (s >> 1) & 1);
            #pragma unroll
            for (int i = WO_PRE; i < 8; i++) ldsm_x4_t(wo[i], wa + i * 1024);
            mbar_wait(bEV + 8 * par, (s >> 1) & 1);
            const uint32_t vm0 = lds32(l4w + exu + 4096), vm1 = lds32(l4w + exu + 4096 + 128);
            const uint32_t big = bar_red_or(BAR_P, 352, 0u);
            uint32_t pb[4]; ldsm_x4_t(pb, sbl + SM_P);
            uint32_t pm = ldsm_x1_t(sbl + SM_P + 512);
            float o0[4] = {0.f, 0.f, 0.f, 0.f}, o1[4] = {0.f, 0.f, 0.f, 0.f}, o2[4] = {0.f, 0.f, 0.f, 0.f};
            if (__builtin_expect(big, 0)) {
                bar_sync(BAR_P2, 352);
                ldsm_x4_t(pb, sbl + SM_P); pm = ldsm_x1_t(sbl + SM_P + 512);
            }
            mma16816(o0, vf[0], pb[0], pb[1]);
            mma16816(o1, vf[1], pb[2], pb[3]);
            mma1688(o2, vm0, vm1, pm);
            uint32_t oa = pm;
            #pragma unroll
            for (int i = 0; i < 8; i++) oa ^= wo[i][0];
            oa = l4w | (oa & nv);
            sts32(oa + SM_O, pack_bf16((o0[0] + o1[0]) + o2[0], (o0[1] + o1[1]) + o2[1]));
            sts32(oa + SM_O + 128, pack_bf16((o0[2] + o1[2]) + o2[2], (o0[3] + o1[3]) + o2[3]));
            const uint32_t xd = uni(DESC_LO(SM_X) + par * (XBUF >> 4));
            bar_sync(BAR_O, 352);
            stage_w<false>(wo, sbl + SM_O, 12 * r + warp, SLOT_OFF(s + 1), l16, nv, sbl + SM_IL);
            STAMP(warp);
            bar_sync(BAR_V, 384);
            wg_fence();
            STAMP(12);
            #pragma unroll
            for (int i = 0; i < TP_N; i++) {
                if (i == 0) wgmma_n32<0>(ta1, wf[0], desc_from(xd));
                else wgmma_n32<1>(ta1, wf[i], desc_from(xd + (i >> 2) * 256 + (i & 3) * 2));
            }
            wg_commit();
            prep(s + 1);
            wg_wait0();
            tp_store(ta1, SM_TOK + par * TOKBUF + r * 8192);
            STAMP(13 + (warp >> 2));
            bar_sync(BAR_MEM, 352);
        }
        {
            const uint32_t tag = ld_relaxed32(&g_init[blockIdx.x]) & 1u, lq = l16 | (tag & nv), pq = pw | (tag & nv);
            uint4* d0 = &g_last[12 * r + warp][0][h][lq >> 4];
            uint4* d1 = &g_last[12 * r + 8 + (warp & 3)][warp >> 2][h][lq >> 4];
            st_relaxed128(d0, make_uint4(tag ^ 1, 0, 0, 0)); st_relaxed128(d0 + 1024, make_uint4(tag ^ 1, 0, 0, 0)); st_relaxed128(d1, make_uint4(tag ^ 1, 0, 0, 0));
            uint32_t wx[8][4];
            #pragma unroll
            for (int i = 0; i < 8; i++) { ldsm_x4_t(wo[i], pq + sb + SM_WO + (warp >> 1) * 8192 + i * 1024); ldsm_x4_t(wx[i], pq + sb + SM_WO + (4 + ((warp >> 1) & 1)) * 8192 + i * 1024); }
            float c2[8];
            #pragma unroll
            for (int i = 0; i < 8; i++) c2[i] = 0.f;
            const uint32_t od = uni(DESC_LO(SM_OST) + (warp >> 2) * 128);
            mbar_wait(bMEM, 1);
            wg_fence();
            #pragma unroll
            for (int i = 0; i < 8; i++) {
                if (i == 0) wgmma_n32<0>(ta1, wo[0], desc_from(DESC_LO(SM_OST)));
                else wgmma_n32<1>(ta1, wo[i], desc_from(DESC_LO(SM_OST) + (i >> 2) * 256 + (i & 3) * 2));
            }
            wg_commit();
            #pragma unroll
            for (int i = 0; i < 8; i++) wgmma_n16(c2, wx[i], desc_from(od + (i >> 2) * 256 + (i & 3) * 2));
            wg_commit();
            auto put = [&](uint4* d, const float* c) { st_relaxed128(d, make_uint4((pack_bf16(c[0], c[1]) & ~1u) | tag, pack_bf16(c[2], c[3]), pack_bf16(c[4], c[5]), pack_bf16(c[6], c[7]))); };
            asm volatile("wgmma.wait_group.sync.aligned 1;" ::: "memory");
            #pragma unroll
            for (int i = 0; i < 16; i++) asm volatile("" : "+f"(ta1[i]) :: "memory");
            put(d0, ta1); put(d0 + 1024, ta1 + 8);
            wg_wait0();
            #pragma unroll
            for (int i = 0; i < 8; i++) asm volatile("" : "+f"(c2[i]) :: "memory");
            put(d1, c2);
            if (tid == 0 && blockIdx.x == 0) GT(40, NSEG);
        }
        cluster_arrive(); cluster_wait();
    } else {
        asm volatile("setmaxnreg.dec.sync.aligned.u32 %0;" :: "n"(504 - 2 * REG_P));
        const int a = warp - 8;
        const uint32_t sbl = sb + lane * 16;
        if (a < 3) {
            const uint32_t zs = 3 * blockIdx.x + (r8 >> 1);
            const uint32_t zoff = (r8 < 6 ? (zs >> 3) * 1024 + ((zs >> 2) & 1) * 256 + (zs & 3) * 32 : ACC_X + (blockIdx.x >> 1) * 1024 + (blockIdx.x & 1) * 256) + (lane & 1) * 16;
            const uint32_t zskip = r8 >= 6 && blockIdx.x >= 36;
            if (a == 1) {
                st_relaxed128_p((uint4*)(g_acc + zoff + SLOT_OFF(mi)), make_uint4(0, 0, 0, 0), zskip);
                __threadfence();
                __syncwarp();
                if (lane == 0) st_relaxed32(&g_init[blockIdx.x], epoch);
            }
            {
                #pragma unroll
                for (int i = 0; i < 6; i++) {
                    const int c = tid - 256 + 96 * i;
                    const unsigned short* m = (const unsigned short*)mem0 + c;
                    uint4 v;
                    v.x = m[0] | ((uint32_t)m[DM] << 16); v.y = m[2 * DM] | ((uint32_t)m[3 * DM] << 16);
                    v.z = m[4 * DM] | ((uint32_t)m[5 * DM] << 16); v.w = m[6 * DM] | ((uint32_t)m[7 * DM] << 16);
                    sts128(sb + SM_MEM + c * 16, v);
                }
                sts32(sb + SM_TG, 0u);
            }
            asm volatile("barrier.cluster.arrive.release.aligned;" ::: "memory");
            { int it = 0; while (__any_sync(0xffffffffu, ld_relaxed32(&g_init[a * 32 + lane]) != epoch) && ++it < SPIN_LIMIT) {} }
            __threadfence();
            const uint32_t kl0 = (a < 2 ? SM_TOK + (16 * a + (mi & 1) * 8 + r8) * 64 + (((mi >> 1) ^ (r8 >> 1)) << 4) : SM_EX + 2048 + ((((mi & 1) << 1) | (mi >> 1)) * 8 + r8) * 16);
            const uint32_t l16 = pin(lane * 16);
            uint32_t kf[8][4], wo[8][4];
            auto load_k = [&](int tb, uint32_t kl) {
                const uint32_t ka = kl + launder(sb + tb * TOKBUF);
                #pragma unroll
                for (int kk = 0; kk < 8; kk++) ldsm_x4(kf[kk], (ka ^ ((kk & 1) << 5)) + BLK_K(kk >> 1));
            };
            code_pad<PAD_S>(nv);
            cluster_wait();
            if (a == 0 && lane == 0) { mbar_expect_tx(bEX, 4096 - 256 * nqk); mbar_expect_tx(bEV, 256 * nqk); }
            if (a < 2) bar_arrive(BAR_MEM, 352); else bar_sync(BAR_MEM, 352);
            mbar_wait(bW + 32, 0);
            #pragma unroll
            for (int i = 0; i < 8; i++) ldsm_x4_t(wo[i], pw0 + sb + SM_WO + (warp >> 1) * 8192 + i * 1024);
            sts128(sbl + SM_STASH + a * 1024 + 512, make_uint4(kl0, (pw0 ^ 32) + sb + SM_WO + 5 * 8192, zoff | ((zskip || lane >= 8) << 31), 0u));
            sts128(sbl + SM_STASH + a * 1024, make_uint4(a * 12288 + (lane >> 4) * 1024 + (mi & 1) * 256 + r8 * 16, ACC_X + a * 6144 + (lane >> 4) * 1024 + (mi & 1) * 256 + r8 * 4,
                                                         ((lane ^ mi) & 1) ? 0u : ~0u, sb + SM_MEM + a * 3072 + mi * 256 + r8 * 16 + (r8 & 1 ? 2 : 130)));
            const uint32_t stash = l16 + uni(sb + SM_STASH + a * 1024);
            #pragma unroll
            for (int i = 0; i < 8; i++) ldsm_x4_t(kf[i], (pw0 ^ 32) + sb + SM_WO + 5 * 8192 + i * 1024);
            if (a < 2) { mbar_wait(bTOK, 0); load_k(0, kl0); }
            __syncwarp();
            int sn = 0;
            #pragma unroll 1
            while (sn < NSEG - 1) {
              uint32_t bad;
              #pragma unroll 1
              do {
                const int s = sn, par = s & 1;
                const uint32_t exu = launder(sb + par * EXBUF);
                const uint32_t exl = l16 + exu + SM_EX;
                const uint32_t t0 = gtime_lo();
                STAMP(15); STAMPV(31, t0);
                if (a == 2) st_relaxed32_p(&g_ts[blockIdx.x], (t0 & ~31u) | (s & 31), l16);
                if (a == 1) {
                    const uint32_t z = lds32(stash + 520);
                    st_relaxed128_p((uint4*)(g_acc + (z + SLOT_OFF(s + 3))), make_uint4(0, 0, 0, 0), z >> 31);
                }
                if (a == 0 && l16 == 0) { mbar_expect_tx(bEX + 8 * (par ^ 1), 4096 - 256 * nqk); mbar_expect_tx(bEV + 8 * (par ^ 1), 256 * nqk); }
                auto first_half = [&](auto role) {
                constexpr bool M = role.value;
                uint32_t sl, sh, kl = 0;
                if (M) {
                    fence_async_smem();
                    if (l16 == 0) {
                        asm volatile("cp.async.bulk.global.shared::cta.bulk_group [%0], [%1], 8192;\ncp.async.bulk.commit_group;"
                            :: "l"(g_tokx[blockIdx.x]), "r"(sb + SM_TOK + (par ^ 1) * TOKBUF + r * 8192) : "memory");
                        mbar_expect_tx(bTOK + 8 * (par ^ 1), 16384); mbar_expect_tx(bMEM, 10368);
                        if (s == 0) mbar_expect_tx(bX, XBUF);
                        if (s + 3 < NSEG) mbar_expect_tx(bX + 8 * (par ^ 1), XBUF);
                    }
                    __syncwarp();
                    if (s > 0 && s + 2 < NSEG) mbar_wait(bX + 8 * par, ((s >> 1) & 1) ^ 1);
                    asm volatile("cp.async.bulk.wait_group 0;" ::: "memory");
                    kl = lds32(stash + 512);
                }
                const uint32_t pst = (launder(l16) >> 2) + launder(sb + SM_P + a * 256);
                if (!M) {
                    uint32_t x = kf[0][0];
                    #pragma unroll
                    for (int i = 1; i < 8; i++) x ^= kf[i][0];
                    sts32_p(pst, x, nv);
                }
                mbar_wait(bEX + 8 * par, (s >> 1) & 1);
                float c[4][4];
                #pragma unroll
                for (int j = 0; j < 4; j++) { c[j][0] = c[j][1] = c[j][2] = c[j][3] = 0.f; }
                if (!M) {
                    uint32_t b[4][4];
                    ldsm16_t(b, exl);
                    #pragma unroll
                    for (int j = 0; j < 4; j++) { mma16816(c[(2 * j) & 3], kf[2 * j], b[j][0], b[j][1]); mma16816(c[(2 * j + 1) & 3], kf[2 * j + 1], b[j][2], b[j][3]); }
                    sl = scale_bf2(pack_bf16((c[0][0] + c[1][0]) + (c[2][0] + c[3][0]), (c[0][1] + c[1][1]) + (c[2][1] + c[3][1])));
                    sh = scale_bf2(pack_bf16((c[0][2] + c[1][2]) + (c[2][2] + c[3][2]), (c[0][3] + c[1][3]) + (c[2][3] + c[3][3])));
                } else {
                    uint32_t k[4][4], b[4][4];
                    #pragma unroll
                    for (int j = 0; j < 4; j++) { ldsm_x4_t(k[j], kl + exu + 512 * j); ldsm_x4_t(b[j], exl + 512 * j); }
                    #pragma unroll
                    for (int j = 0; j < 4; j++) { mma16816(c[2 * (j & 1)], k[j], b[j][0], b[j][1]); mma16816(c[2 * (j & 1) + 1], k[j], b[j][2], b[j][3]); }
                    asm volatile("{\n.reg .pred p;\nelect.sync _|p, 0xffffffff;\n"
                                 "@p cp.async.bulk.shared::cluster.global.mbarrier::complete_tx::bytes.multicast::cluster [%0], [%1], 8192, [%2], %3;\n}\n"
                        :: "r"(sb + SM_TOK + (par ^ 1) * TOKBUF + r * 8192), "l"(g_tokx[blockIdx.x]), "r"(bTOK + 8 * (par ^ 1)), "h"((unsigned short)(7 ^ (1 << r))) : "memory");
                    sh = sl = scale_bf2(pack_bf16((c[0][0] + c[1][2]) + (c[2][0] + c[3][2]), (c[0][1] + c[1][3]) + (c[2][1] + c[3][3])));
                }
                sts32(pst, exp_bf2(sl));
                if (!M) sts32(pst + 128, exp_bf2(sh));
                const uint32_t big = bar_red_or(BAR_P, 352, ((maxabs_bf2(sl, sh) & 0x7fff7fffu) + 0x3ddf3ddfu) & 0x80008000u);
                auto denom = [&] {
                    uint32_t pb[4]; ldsm_x4_t(pb, l16 + sb + SM_P);
                    const uint32_t pm = ldsm_x1_t(l16 + sb + SM_P + 512), ONE = 0x3F803F80u;
                    float l0[4] = {0.f, 0.f, 0.f, 0.f}, l1[4] = {0.f, 0.f, 0.f, 0.f}, l2[4] = {0.f, 0.f, 0.f, 0.f};
                    mma16816r(l0, ONE, ONE, ONE, ONE, pb[0], pb[1]);
                    mma16816r(l1, ONE, ONE, ONE, ONE, pb[2], pb[3]);
                    mma1688(l2, ONE, ONE, pm);
                    const float dl = (l0[0] + l1[0]) + l2[0], dh = (l0[1] + l1[1]) + l2[1];
                    sts32(pst + (SM_IL - SM_P) - a * 128, __float_as_uint(rcp_approx(a ? dh : dl)));
                };
                if (!M) { denom(); bar_sync_p(BAR_O, 352, big); }
                if (__builtin_expect(big, 0)) {
                    uint32_t m2 = max_bf2(sl, sh);
                    m2 = max_bf2(m2, __shfl_xor_sync(0xffffffffu, m2, 4));
                    m2 = max_bf2(m2, __shfl_xor_sync(0xffffffffu, m2, 8));
                    m2 = max_bf2(m2, __shfl_xor_sync(0xffffffffu, m2, 16));
                    const uint32_t lq = l16 | (m2 & nv);
                    if (lq < 64) sts32(lq + sb + SM_P + 768 + a * 4, m2);
                    bar_sync(BAR_S, 96);
                    const uint4 m = lds128(sb + SM_P + 768 + (lq & 0x30));
                    m2 = max_bf2(max_bf2(m.x, m.y), m.z);
                    const float ml = bf_lo(m2), mh = bf_hi(m2);
                    sts32(pst, pack_bf16(exd(bf_lo(sl), ml), exd(bf_hi(sl), mh)));
                    if (!M) sts32(pst + 128, pack_bf16(exd(bf_lo(sh), ml), exd(bf_hi(sh), mh)));
                    bar_sync(BAR_P2, 352);
                    if (!M) { denom(); bar_sync(BAR_O, 352); }
                }
                const uint32_t ll = launder(l16), so = SLOT_OFF(launder(s) + 1);
                if (!M) stage_w<true>(wo, l16 + sb + SM_O, 12 * r + warp, so, ll, nv, l16 + sb + SM_IL);
                else {
                    const uint32_t w2 = lds32(stash + 516);
                    #pragma unroll
                    for (int i = M_RES; i < 8; i++) ldsm_x4_t(kf[i], w2 + i * 1024);
                    const uint32_t sa = launder((ll >> 2) + (send_ua(12 * r + 10) + so)), sx = launder((ll >> 4) + (send_ub(12 * r + 10) + so));
                    bar_sync_p(BAR_O, 352, (kf[5][0] ^ kf[6][0] ^ kf[7][0] ^ sa ^ sx) & nv);
                    #pragma unroll
                    for (int k = 0; k < M_LAG; k++) mbar_wait(bEX + 8 * par, (s >> 1) & 1);
                    float il, ih;
                    #pragma unroll
                    for (int i = 0; i < 4; i++) c[i][0] = c[i][1] = c[i][2] = c[i][3] = 0.f;
                    uint32_t b[4][4];
                    #pragma unroll
                    for (int j = 0; j < 4; j++) ldsm_x4_t(b[j], l16 + sb + SM_O + 512 * (3 - j));
                    lds_il(il, ih, l16 + sb + SM_IL);
                    sched_fence<11>(nv);
                    #pragma unroll
                    for (int j = 0; j < 4; j++) {
                        mma16816(c[0], wo[6 - 2 * j], b[j][0], b[j][1]); mma16816(c[2], kf[6 - 2 * j], b[j][0], b[j][1]);
                        mma16816(c[1], wo[7 - 2 * j], b[j][2], b[j][3]); mma16816(c[3], kf[7 - 2 * j], b[j][2], b[j][3]);
                        if (j == M_ARR) { asm volatile("" : "+f"(c[0][0]), "+f"(c[1][0]), "+f"(c[2][0]), "+f"(c[3][0])); sched_fence<10>(nv); bar_arrive(BAR_V, 384); }
                        if (j == 3 && M_ARR < 0) bar_arrive(BAR_V, 384);
                    }
                    send_tile<0, 0>((c[0][0] + c[1][0]) * il, (c[0][1] + c[1][1]) * ih, (c[0][2] + c[1][2]) * il, (c[0][3] + c[1][3]) * ih, sa, sx, ll);
                    send_tile<1024, 256>((c[2][0] + c[3][0]) * il, (c[2][1] + c[3][1]) * ih, (c[2][2] + c[3][2]) * il, (c[2][3] + c[3][3]) * ih, sa, sx, ll);
                }
                };
                if (a < 2) first_half(ic<0>()); else first_half(ic<1>());
                STAMP(warp);
                {
                    const uint32_t cd = lds32(stash + 12), xa = (launder(l16) >> 2) + launder(sb + SM_XT + a * 384);
                    if (a < 2) { const uint32_t kl = lds32(stash + 512); mbar_wait(bTOK + 8 * (par ^ 1), ((s + 1) >> 1) & 1); load_k(par ^ 1, kl); }
                    else {
                        STAMP(16 + a);
                        uint32_t tg;
                        asm volatile("{\n.reg .pred p, q;\n.reg .b64 w;\n.reg .b32 t, u, d, n;\nmov.b32 n, 100000;\n"
                                     "WT_%=:\nld.volatile.shared.u32 %0, [%1];\nmov.u64 w, %%globaltimer;\nmov.b64 {t, u}, w;\nsub.s32 n, n, 1;\nsetp.gt.s32 q, n, 0;\nor.b32 t, t, 1;\nxor.b32 t, t, %2;\n"
                                     "sub.s32 d, t, %0;\nand.b32 d, d, 0x80000001;\nsetp.ne.and.u32 p, d, 0, q;\n@p bra.uni WT_%=;\n}\n" : "=r"(tg) : "r"(sb + SM_TG + (l16 >> 16)), "r"(par + (l16 >> 16)) : "memory");
                        asm volatile("{\n.reg .pred p;\nelect.sync _|p, 0xffffffff;\n"
                                     "@p cp.async.bulk.tensor.3d.shared::cluster.global.mbarrier::complete_tx::bytes.multicast::cluster [%0], [%1, {%3, %4, %5}], [%2], %9;\n"
                                     "@p cp.async.bulk.tensor.3d.shared::cluster.global.mbarrier::complete_tx::bytes.multicast::cluster [%6], [%7, {%3, %4, %8}], [%2], %9;\n}\n"
                            :: "r"(sb + SM_MEM + r * 3072), "l"(&tma), "r"(bMEM), "r"((par ^ 1) * 32), "r"((s + 1) & 2), "r"(12 * r), "r"(sb + SM_XT + r * 384), "l"(&tmb), "r"(ACC_X / 1024 + 6 * r), "h"((unsigned short)7) : "memory");
                        STAMPV(30, tg);
                    }
                    STAMP(19 + a);
                    mbar_wait(bMEM, par);
                    uint32_t x[3], k[3];
                    #pragma unroll
                    for (int j = 0; j < 3; j++) { x[j] = lds32(xa + 128 * j); k[j] = lds32(cd - 2 + 1024 * j); }
                    #pragma unroll
                    for (int j = 0; j < 3; j++) sts16(cd + 1024 * j, (uint16_t)x[j]);
                    bad = __any_sync(0xffffffffu, !((x[0] & x[1] & x[2]) & (k[0] & k[1] & k[2]) & (ACC_FULL << 16)));
                    STAMP(22 + a); STAMPV(27 + a, bad);
                    bar_sync_p(BAR_MEM, 352, bad);
                }
              } while (++sn < NSEG - 1 && !bad);
                {
                    if (bad) {
                        uint32_t c = nv, cx;
                        const uint32_t lq = l16 | (lds32(stash + 524) & nv), so = SLOT_OFF(sn);
                        const uint4 ad = lds128(stash);
                        const unsigned char* pm = launder_p(g_acc + (ad.x + so));
                        const unsigned char* px = launder_p(g_acc + (ad.y + so));
                        int it = 0;
                        do {
                            const uint32_t again = ~(c & __shfl_xor_sync(0xffffffffu, c, 1)) & (ACC_FULL << 16);
                            uint4 u[6]; uint32_t x[3];
                            #pragma unroll
                            for (int j = 0; j < 6; j++) { u[j] = make_uint4(~0u, ~0u, ~0u, ~0u); ld_relaxed128_p(u[j], (const uint4*)(pm + 2048 * j), again); }
                            #pragma unroll
                            for (int j = 0; j < 3; j++) x[j] = ld_relaxed32((const uint32_t*)(px + 2048 * j));
                            c = ~0u;
                            #pragma unroll
                            for (int j = 0; j < 6; j++) {
                                if (again) sts128(lq + sb + SM_MEM + a * 3072 + 512 * j, u[j]);
                                c &= u[j].x;
                            }
                            __syncwarp();
                            #pragma unroll
                            for (int j = 0; j < 3; j++) sts16(ad.w + 1024 * j, (uint16_t)x[j]);
                            c |= ad.z;
                            cx = x[0] & x[1] & x[2];
                        } while (__any_sync(0xffffffffu, !(c & cx & (ACC_FULL << 16))) && ++it < SPIN_LIMIT);
                        bar_sync(BAR_MEM, 352);
                    }
                }
            }
        } else {
            cluster_arrive_rx();
            const uint32_t l16 = pin(lane * 16);
            bf16* dst = g_otok + h * 4096 + (r ? 1024 : 0) + (r == 2 ? 2048 : 0);
            {
                #pragma unroll
                for (int sg = 0; sg < 2; sg++) {
                    bar_sync(BAR_X0 + sg, 288);
                    if (lane == 0) {
                        mbar_expect_tx(bX + 8 * sg, XBUF);
                        #pragma unroll
                        for (int c = 0; c < 3; c++)
                            asm volatile("cp.async.bulk.tensor.3d.shared::cluster.global.mbarrier::complete_tx::bytes [%0], [%1, {%3, %4, %5}], [%2];"
                                :: "r"(sb + SM_X + sg * XBUF + c * 12288), "l"(&tmx), "r"(bX + 8 * sg), "r"(0), "r"(sg * SEG), "r"(3 * c) : "memory");
                    }
                    __syncwarp();
                }
                if (lane == 0) load_w(40, 54);
                __syncwarp();
                cluster_wait();
            }
            __syncwarp();
            auto t_loop = [&](auto mtile) {
            constexpr int MT = mtile.value;
            uint32_t q[8][4], sp[5][2], pa[5][2], bv[8][4], rng;
            const uint32_t ost = sb + SM_OST + (MT ? 4096 * r - 2048 : 0);
            code_pad<MT ? PAD_T1 : PAD_T0>(nv);
            auto issue_x = [&](int sg) {
                asm volatile("{\n.reg .pred p, q;\nelect.sync _|p, 0xffffffff;\nsetp.eq.and.u32 q, %5, 3, p;\n"
                             "@p cp.async.bulk.tensor.3d.shared::cluster.global.mbarrier::complete_tx::bytes.multicast::cluster [%0], [%1, {%3, %4, %5}], [%2], %6;\n"
                             "@q cp.async.bulk.tensor.3d.shared::cluster.global.mbarrier::complete_tx::bytes.multicast::cluster [%7], [%1, {%3, %4, %3}], [%2], %6;\n}\n"
                    :: "r"(sb + SM_X + (sg & 1) * XBUF + r * 12288), "l"(&tmx), "r"(bX + 8 * (sg & 1)), "r"(0), "r"(sg * SEG), "r"(3 * r), "h"((unsigned short)7), "r"(sb + SM_X + (sg & 1) * XBUF) : "memory");
            };
            mbar_wait(bTOK, 0);
            if (MT) { issue_x(2); issue_x(3); }
            #pragma unroll 1
            for (int s = 0; ; s++) {
                const int par = s & 1;
                mbar_wait(bTOK + 8 * par, (s >> 1) & 1);
                const uint32_t tok = launder(sb + SM_TOK + par * TOKBUF), exl = l16 + launder(sb + SM_EX + par * EXBUF);
                tok_part1<MT>(tok, MT ? r - 1 : 0, launder(l16) >> 4, q, sp, pa, bv, rng, [&] {
                    if (s > 0) {
                        if (lane == 0) {
                            asm volatile("cp.async.bulk.wait_group 0;" ::: "memory");
                            st_relaxed32(&g_prog[blockIdx.x], epoch << 8 | s);
                        }
                        __syncwarp();
                        if (lane == 0 && blockIdx.x == 0) GT(40, s);
                    }
                    sched_fence<6 + MT>(nv); });
                STAMP(25);
                mbar_wait(bEX + 8 * par, (s >> 1) & 1);
                STAMP(26);
                auto duty = [&] { if (s + 1 < NSEG) {
                    asm volatile("{\n.reg .pred p;\nelect.sync _|p, 0xffffffff;\n"
                                 "@p cp.async.bulk.shared::cluster.global.mbarrier::complete_tx::bytes [%0], [%1], 384, [%2];\n"
                                 "@p mbarrier.arrive.expect_tx.shared.b64 _, [%2], 384;\n}\n"
                        :: "r"(sb + SM_TS), "l"(g_ts), "r"(bFREE) : "memory");
                    if (MT && s > 0 && s + 3 < NSEG) issue_x(s + 3);
                } };
                auto pace = [&] { if (s + 1 < NSEG) {
                    const uint32_t lo = min(launder(l16), 368u), b = (gtime_lo() & ~31u) - 0x01000000u + s + (lo >> 16);
                    const uint32_t c = (b & ~31u) + (G1_NS + (s == 0 ? G1_0 : 0)) + (par ^ 1);
                    mbar_wait(bFREE, par);
                    uint4 ts = lds128(sb + SM_TS + lo);
                    int it = 0; uint32_t m;
                    while (true) {
                        m = __reduce_max_sync(0xffffffffu, max(max(__funnelshift_r(ts.x - b, ts.x - b, 5), __funnelshift_r(ts.y - b, ts.y - b, 5)), max(__funnelshift_r(ts.z - b, ts.z - b, 5), __funnelshift_r(ts.w - b, ts.w - b, 5))));
                        if (__builtin_expect(m < 0x00100000u, 1) || ++it >= 64) break;
                        ts = ld_relaxed128((const uint4*)((const char*)g_ts + lo));
                    }
                    asm volatile("st.volatile.shared.u32 [%0], %1;" :: "r"(sb + SM_TG), "r"(c + (min(m, 0x00080000u) << 5)) : "memory");
                } };
                auto wait_v = [&] { mbar_wait(bEV + 8 * par, (s >> 1) & 1); };
                auto wait_x = [&] { if (__builtin_expect(s == 0, 0)) mbar_wait(bX, 1); };
                tok_part2<MT>(tok, exl, ost, MT ? r - 1 : 0, launder(l16) >> 4, q, sp, pa, bv, rng, s < NSEG - 1, wait_v, duty, pace, wait_x);
                STAMP(11);
                fence_async_smem();
                __syncwarp();
                if (s == NSEG - 1) break;
                if (lane == 0) {
                    asm volatile("cp.async.bulk.global.shared::cta.bulk_group [%0], [%1], 2048;" :: "l"(dst), "r"(ost) : "memory");
                    if (!MT) asm volatile("cp.async.bulk.global.shared::cta.bulk_group [%0], [%1], 2048;" :: "l"(dst + 2048), "r"(ost + 4096) : "memory");
                    asm volatile("cp.async.bulk.commit_group;" ::: "memory");
                }
                __syncwarp();
                dst += SEG * NH * DH;
            }
            if (lane == 0) {
                #pragma unroll
                for (int k = 0; k < (MT ? 2 : 4); k++) {
                    const uint32_t src = ost + (k >> 1) * 4096, rk = (r + 1 + (k & 1)) % 3;
                    asm volatile("cp.async.bulk.shared::cluster.shared::cta.mbarrier::complete_tx::bytes [%0], [%1], 2048, [%2];" :: "r"(mapa_u32(src, rk)), "r"(src), "r"(mapa_u32(bMEM, rk)) : "memory");
                }
                mbar_expect_tx(bMEM, MT ? 6144 : 4096);
            }
            __syncwarp();
            };
            if (r == 0) t_loop(ic<0>()); else t_loop(ic<1>());
        }
        cluster_arrive(); cluster_wait();
    }
}
#define SD_THREADS 384
#define SD_CTAS  36
#define BT_RS    4624
#define SD_BT    0
#define SD_STG   74752
#define SD_EF    (SD_STG + 57344)
#define SD_BC    (SD_STG)
#define KSLOTS   5
#define BC_BYTES 10240
#define BC_LBO   1280
#define SD_KP    (SD_STG + 90112)
#define SD_Q0    205824
#define SD_Q1    (SD_STG + 111616)
#define SD_OST   (SD_Q0 + 8192)
#define SD_XCH   (SD_Q0 + 10240)
#define LSEG     (NSEG - 1)
#define SD_BAR   224256
#define SD_TOTAL 224768
#define SD_SPIN  (1 << 22)
#define PART_SLOTS 8
#define SD_WOP 300
#define SD_GO 0
#define SD_REG 200
#define SD_WAIT 6000
#define SD_P2 150
#define SD_P3 600
#define SD_GAP 0
#define SD_RUSH 44
#define SD_P1 300

__device__ uint4 g_part[SD_CTAS][PART_SLOTS][4][8][32];
__device__ __align__(16) unsigned int g_gate[S_LEN];

struct cplx { float r, i; };
__device__ __forceinline__ cplx cmul(cplx a, cplx b) { cplx c; c.r = fmaf(a.r, b.r, -a.i * b.i); c.i = fmaf(a.r, b.i, a.i * b.r); return c; }
__device__ __forceinline__ cplx cexp_(float xr, float xi) {
    const float m = ex2(xr * 1.4426950408889634f);
    const float k = rintf(xi * 0.15915494309189535f);
    const float r = fmaf(k, 1.7484555314695172e-7f, fmaf(k, -6.2831854820251465f, xi));
    cplx o; o.r = m * __cosf(r); o.i = m * __sinf(r); return o;
}
__device__ __forceinline__ void mma_f16(float (&c)[4], const uint32_t (&a)[4], uint32_t b0, uint32_t b1) {
    asm("mma.sync.aligned.m16n8k16.row.col.f32.f16.f16.f32 {%0,%1,%2,%3}, {%4,%5,%6,%7}, {%8,%9}, {%0,%1,%2,%3};"
        : "+f"(c[0]), "+f"(c[1]), "+f"(c[2]), "+f"(c[3]) : "r"(a[0]), "r"(a[1]), "r"(a[2]), "r"(a[3]), "r"(b0), "r"(b1));
}
__device__ __forceinline__ uint32_t mul_bf2(uint32_t a, uint32_t b) { uint32_t r; asm("mul.rn.bf16x2 %0, %1, %2;" : "=r"(r) : "r"(a), "r"(b)); return r; }
__device__ __forceinline__ void mbar_wait_long(uint32_t a, uint32_t parity) { int it = 0; while (!mbar_try(a, parity) && ++it < SD_SPIN) {} }
__device__ __forceinline__ uint16_t lds16(uint32_t a) { uint16_t v; asm volatile("ld.shared.u16 %0, [%1];" : "=h"(v) : "r"(a) : "memory"); return v; }
__device__ __forceinline__ void wg_wait1() { asm volatile("wgmma.wait_group.sync.aligned 1;" ::: "memory"); }
__device__ __forceinline__ void tma2d(uint32_t dst, const CUtensorMap* tm, uint32_t bar, int c0, int c1) {
    asm volatile("cp.async.bulk.tensor.2d.shared::cluster.global.mbarrier::complete_tx::bytes [%0], [%1, {%3, %4}], [%2];"
        :: "r"(dst), "l"(tm), "r"(bar), "r"(c0), "r"(c1) : "memory");
}
__device__ __forceinline__ uint32_t add_bf2(uint32_t a, uint32_t b) { uint32_t r; asm("add.rn.bf16x2 %0, %1, %2;" : "=r"(r) : "r"(a), "r"(b)); return r; }
__device__ __forceinline__ void wgmma_conv(float (&d)[32], uint32_t a0, uint32_t a1, uint32_t a2, uint32_t a3, uint64_t desc) {
    asm volatile("{\n.reg .pred p;\nsetp.ne.b32 p, 1, 0;\n"
        "wgmma.mma_async.sync.aligned.m64n64k16.f32.bf16.bf16 {%0,%1,%2,%3,%4,%5,%6,%7,%8,%9,%10,%11,%12,%13,%14,%15,%16,%17,%18,%19,%20,%21,%22,%23,%24,%25,%26,%27,%28,%29,%30,%31}, {%32,%33,%34,%35}, %36, p, 1, 1, 0;\n}\n"
        : "+f"(d[0]), "+f"(d[1]), "+f"(d[2]), "+f"(d[3]), "+f"(d[4]), "+f"(d[5]), "+f"(d[6]), "+f"(d[7]), "+f"(d[8]), "+f"(d[9]), "+f"(d[10]), "+f"(d[11]), "+f"(d[12]), "+f"(d[13]), "+f"(d[14]), "+f"(d[15]), "+f"(d[16]), "+f"(d[17]), "+f"(d[18]), "+f"(d[19]), "+f"(d[20]), "+f"(d[21]), "+f"(d[22]), "+f"(d[23]), "+f"(d[24]), "+f"(d[25]), "+f"(d[26]), "+f"(d[27]), "+f"(d[28]), "+f"(d[29]), "+f"(d[30]), "+f"(d[31])
        : "r"(a0), "r"(a1), "r"(a2), "r"(a3), "l"(desc));
}
__device__ __forceinline__ void wgmma_conv(float (&d)[24], uint32_t a0, uint32_t a1, uint32_t a2, uint32_t a3, uint64_t desc) {
    asm volatile("{\n.reg .pred p;\nsetp.ne.b32 p, 1, 0;\n"
        "wgmma.mma_async.sync.aligned.m64n48k16.f32.bf16.bf16 {%0,%1,%2,%3,%4,%5,%6,%7,%8,%9,%10,%11,%12,%13,%14,%15,%16,%17,%18,%19,%20,%21,%22,%23}, {%24,%25,%26,%27}, %28, p, 1, 1, 0;\n}\n"
        : "+f"(d[0]), "+f"(d[1]), "+f"(d[2]), "+f"(d[3]), "+f"(d[4]), "+f"(d[5]), "+f"(d[6]), "+f"(d[7]), "+f"(d[8]), "+f"(d[9]), "+f"(d[10]), "+f"(d[11]), "+f"(d[12]), "+f"(d[13]), "+f"(d[14]), "+f"(d[15]), "+f"(d[16]), "+f"(d[17]), "+f"(d[18]), "+f"(d[19]), "+f"(d[20]), "+f"(d[21]), "+f"(d[22]), "+f"(d[23])
        : "r"(a0), "r"(a1), "r"(a2), "r"(a3), "l"(desc));
}
__device__ __forceinline__ void wgmma_conv(float (&d)[16], uint32_t a0, uint32_t a1, uint32_t a2, uint32_t a3, uint64_t desc) {
    asm volatile("{\n.reg .pred p;\nsetp.ne.b32 p, 1, 0;\n"
        "wgmma.mma_async.sync.aligned.m64n32k16.f32.bf16.bf16 {%0,%1,%2,%3,%4,%5,%6,%7,%8,%9,%10,%11,%12,%13,%14,%15}, {%16,%17,%18,%19}, %20, p, 1, 1, 0;\n}\n"
        : "+f"(d[0]), "+f"(d[1]), "+f"(d[2]), "+f"(d[3]), "+f"(d[4]), "+f"(d[5]), "+f"(d[6]), "+f"(d[7]), "+f"(d[8]), "+f"(d[9]), "+f"(d[10]), "+f"(d[11]), "+f"(d[12]), "+f"(d[13]), "+f"(d[14]), "+f"(d[15])
        : "r"(a0), "r"(a1), "r"(a2), "r"(a3), "l"(desc));
}
__device__ __forceinline__ void wgmma_conv(float (&d)[8], uint32_t a0, uint32_t a1, uint32_t a2, uint32_t a3, uint64_t desc) {
    asm volatile("{\n.reg .pred p;\nsetp.ne.b32 p, 1, 0;\n"
        "wgmma.mma_async.sync.aligned.m64n16k16.f32.bf16.bf16 {%0,%1,%2,%3,%4,%5,%6,%7}, {%8,%9,%10,%11}, %12, p, 1, 1, 0;\n}\n"
        : "+f"(d[0]), "+f"(d[1]), "+f"(d[2]), "+f"(d[3]), "+f"(d[4]), "+f"(d[5]), "+f"(d[6]), "+f"(d[7])
        : "r"(a0), "r"(a1), "r"(a2), "r"(a3), "l"(desc));
}
template<int NR> __device__ __forceinline__ void conv_mma(float (&acc)[NR], const uint32_t (&R)[16], uint32_t dlo) {
    #pragma unroll
    for (int q = 0; q < 4; q++)
        wgmma_conv(acc, R[4 * q], R[4 * q + 1], R[4 * q + 2], R[4 * q + 3], (uint64_t)(dlo + (2 * (3 - q)) * (BC_LBO >> 4)) | ((uint64_t)8 << 32));
}
__device__ __forceinline__ void conv_ld(uint32_t (&R)[16], uint32_t a) {
    #pragma unroll
    for (int q = 0; q < 4; q++) { const uint2 u = lds64(a + 64 * (2 * q + 1)); R[4 * q] = u.x; R[4 * q + 1] = u.y; }
}
__device__ __forceinline__ void conv_fix(uint32_t (&R)[16], uint32_t& carry) {
    #pragma unroll
    for (int q = 0; q < 4; q++) {
        asm volatile("mov.b32 %0, %1;" : "=r"(R[4 * q + 2]) : "r"(q ? R[4 * q - 3] : carry));
        asm volatile("mov.b32 %0, %1;" : "=r"(R[4 * q + 3]) : "r"(R[4 * q]));
    }
    asm volatile("mov.b32 %0, %1;" : "=r"(carry) : "r"(R[13]));
}
template<int A> __device__ __forceinline__ void conv_group(float (&acc)[32 - 8 * A], uint32_t (&R)[4][16], uint32_t& carry, uint32_t pb, uint32_t dlo) {
    #pragma unroll
    for (int e = 0; e < 8; e += 2) {
        const int dl = 8 * A + e;
        conv_fix(R[dl & 3], carry); conv_fix(R[(dl + 1) & 3], carry);
        wg_fence(); conv_mma(acc, R[dl & 3], dlo + 16 - 2 * e); conv_mma(acc, R[(dl + 1) & 3], dlo + 14 - 2 * e); wg_commit();
        wg_wait1();
        if (dl + 2 < 32) { conv_ld(R[(dl + 2) & 3], pb + (dl + 2) * 512); conv_ld(R[(dl + 3) & 3], pb + (dl + 3) * 512); }
    }
}

__global__ void __launch_bounds__(SD_THREADS, 1)
side_kernel(const __grid_constant__ CUtensorMap tmw, const bf16* __restrict__ x,
            const bf16* __restrict__ log_A_real, const bf16* __restrict__ A_imag, const bf16* __restrict__ C_real, const bf16* __restrict__ C_imag,
            const bf16* __restrict__ log_dt, const bf16* __restrict__ D_skip, const bf16* __restrict__ gate_w, bf16* __restrict__ out, const int npass) {
    extern __shared__ __align__(1024) unsigned char smem[];
    const uint32_t sb = smem_u32(smem);
    const int tid = threadIdx.x, lane = tid & 31;
    const int warp = __shfl_sync(0xffffffffu, tid >> 5, 0);
    const int g = lane >> 2, t = lane & 3, mi = lane >> 3, r8 = lane & 7;
    const bool sh = blockIdx.x < 32;
    const int d0 = blockIdx.x * 16;
    const uint32_t b0_ = sb + SD_BAR, bKF = b0_ + 384, bKE = bKF + 8 * KSLOTS, bWO = b0_ + 48, bFULL = b0_ + 56, bEMPTY = b0_ + 88, bEPI = b0_ + 120, bPRT = b0_ + 152, bGO = b0_ + 184, bCH = b0_ + 256;
    const unsigned epoch = ld_relaxed32(&g_epoch);
    if (tid == 0) GT(blockIdx.x, 0);
    if (tid == 0) {
        for (int i = 0; i < 2 * KSLOTS; i++) mbar_init(bKF + 8 * i, 128);
        mbar_init(bWO, 1);
        for (int i = 0; i < 16; i++) mbar_init(bCH + 8 * i, 1);
        for (int i = 0; i < 4; i++) { mbar_init(bFULL + 8 * i, 1); mbar_init(bEMPTY + 8 * i, sh ? 8 : 4); mbar_init(bEPI + 8 * i, 4); mbar_init(bPRT + 8 * i, 8); }
        sts32(bGO, epoch);
        asm volatile("fence.mbarrier_init.release.cluster;" ::: "memory");
    }
    for (int i = tid; i < KSLOTS * 8 * 16; i += SD_THREADS) sts128(sb + SD_BC + (i >> 4) * BC_LBO + (i & 15) * 16, make_uint4(0, 0, 0, 0));
    if (tid < 128) sts64(sb + ((tid & 64) ? SD_Q1 : SD_Q0) + (tid & 63) * 8, 0u, 0u);
    fence_async_smem();
    __syncthreads();

    if (warp < 8) {
        asm volatile("setmaxnreg.inc.sync.aligned.u32 %0;" :: "n"(SD_REG));
        const int wg = warp >> 2, w = warp & 3, t128 = tid & 127;
        if (SD_WAIT) __nanosleep(SD_WAIT);
        {
            #pragma unroll 1
            for (int i = 0; i < 4; i++) {
                const int tp = tid + 256 * i;
                const bf16* xp = x + (size_t)(2 * tp) * DM + d0;
                const uint4 v0 = __ldg((const uint4*)xp), v1 = __ldg((const uint4*)(xp + 8)), v2 = __ldg((const uint4*)(xp + DM)), v3 = __ldg((const uint4*)(xp + DM + 8));
                const uint32_t a = sb + SD_BT + (tp >> 5) * 144 + (tp & 31) * 4;
                const uint32_t lo[8] = {v0.x, v0.y, v0.z, v0.w, v1.x, v1.y, v1.z, v1.w};
                const uint32_t hi[8] = {v2.x, v2.y, v2.z, v2.w, v3.x, v3.y, v3.z, v3.w};
                #pragma unroll
                for (int j = 0; j < 8; j++) { sts32(a + (2 * j) * BT_RS, __byte_perm(lo[j], hi[j], 0x5410)); sts32(a + (2 * j + 1) * BT_RS, __byte_perm(lo[j], hi[j], 0x7632)); }
                if (SD_GAP) __nanosleep(SD_GAP);
            }
        }
        bar_sync(1, 256);
        if (tid == 0) GT(blockIdx.x, 65);
        const uint32_t pa = sb + (wg ? SD_Q1 : SD_Q0);
        const uint32_t pb = pa + (72 + 16 * w - 56 + g - 2 * t) * 8;
        for (int c = wg; c < 16; c += 2) {
            const uint32_t bt = sb + SD_BT + c * BT_RS;
            bar_sync(2 + wg, 128);
            #pragma unroll
            for (int it = 0; it < 9; it++) {
                const int k = it < 8 ? t128 + 128 * it : t128 - 4;
                if (it < 8 || t128 < 4) {
                    auto word = [&](int j) { return j >= 0 ? lds32(bt + (j >> 5) * 144 + (j & 31) * 4) : 0u; };
                    const uint32_t c0 = word(k), p0 = word(k - 1), c1 = word(k + 4), p1 = word(k + 3);
                    sts128(pa + (72 + 2 * k) * 8, make_uint4(__byte_perm(c0, p0, 0x7610), __byte_perm(c1, p1, 0x7610), __byte_perm(c0, c0, 0x1032), __byte_perm(c1, c1, 0x1032)));
                }
            }
            bar_sync(2 + wg, 128);
            const int slot = c % KSLOTS;
            float acc[32];
            #pragma unroll
            for (int i = 0; i < 32; i++) acc[i] = 0.f;
            uint32_t R[4][16];
            uint32_t carry = lds32(pb);
            conv_ld(R[0], pb); conv_ld(R[1], pb + 512);
            const uint32_t dlo = (((sb + SD_BC + slot * BC_BYTES) & 0x3FFFF) >> 4) | ((BC_LBO >> 4) << 16);
            mbar_wait_long(bKF + 8 * slot, (c / KSLOTS) & 1);
            const float ds = bf(D_skip[d0 + c]);
            auto fin = [&](const float* a8, int q0) {
                #pragma unroll
                for (int q = 0; q < 2; q++)
                    #pragma unroll
                    for (int hh = 0; hh < 2; hh++) {
                        const uint32_t a = bt + (4 * (q0 + q) + t) * 144 + (16 * w + g + 8 * hh) * 2;
                        const float u = __uint_as_float((uint32_t)lds16(a) << 16);
                        const float y = rbf(a8[4 * q + 2 * hh] + a8[4 * q + 2 * hh + 1]);
                        sts16(a, (uint16_t)(pack_bf16(y + rbf(u * ds), 0.f) & 0xffff));
                    }
            };
            float a1[24], a2[16], a3[8];
            conv_group<0>(acc, R, carry, pb, dlo);
            wg_wait0();
            #pragma unroll
            for (int i = 0; i < 24; i++) asm volatile("mov.b32 %0, %1;" : "=f"(a1[i]) : "f"(acc[8 + i]));
            fin(acc, 0);
            conv_group<1>(a1, R, carry, pb, dlo);
            wg_wait0();
            #pragma unroll
            for (int i = 0; i < 16; i++) asm volatile("mov.b32 %0, %1;" : "=f"(a2[i]) : "f"(a1[8 + i]));
            fin(a1, 2);
            conv_group<2>(a2, R, carry, pb, dlo);
            wg_wait0();
            #pragma unroll
            for (int i = 0; i < 8; i++) asm volatile("mov.b32 %0, %1;" : "=f"(a3[i]) : "f"(a2[8 + i]));
            fin(a2, 4);
            conv_group<3>(a3, R, carry, pb, dlo);
            wg_wait0();
            mbar_arrive(bKE + 8 * slot);
            fin(a3, 6);
        }
        fence_async_smem();
        __syncthreads();
        const uint32_t stg = sb + SD_STG + wg * 65536;
        uint32_t wf[32][4];
        if (tid == 0) GT(blockIdx.x, 66);
        mbar_wait_long(bWO, 0);
        #pragma unroll
        for (int i = 0; i < 32; i++)
            ldsm_x4_t(wf[i], stg + (i * 16 + (mi >> 1) * 8 + r8) * 128 + (((2 * w + (mi & 1)) ^ r8) << 4));
        { uint32_t x = 0;
          #pragma unroll
          for (int i = 0; i < 32; i++) x |= wf[i][0];
          asm volatile("" :: "r"(x) : "memory"); }
        __syncwarp();
        if (lane == 0) {
            mbar_arrive(bEMPTY + 16 * wg); mbar_arrive(bEMPTY + 16 * wg + 8);
            if (sh) { mbar_arrive(bEMPTY + 16 * (wg ^ 1)); mbar_arrive(bEMPTY + 16 * (wg ^ 1) + 8); }
        }
        uint4* dst = sh ? &g_part[(blockIdx.x & ~7) + 4 * wg + w][0][0][blockIdx.x & 7][lane] : &g_part[32 + w][0][0][2 * (blockIdx.x - 32) + wg][lane];
        const uint32_t dl0 = (((sb + SD_STG) & 0x3FFFF) >> 4) | 0x10000u;
        auto seg = [&](int s) {
            const int bi = sh ? s & 3 : 2 * wg + (s & 1), bp = (sh ? s >> 2 : s >> 1) & 1;
            const uint32_t xd = uni(dl0 + bi * 2048);
            float acc[16];
            #pragma unroll
            for (int i = 0; i < 32; i++) {
                if ((i & 15) == 0) { mbar_wait_long(bCH + 32 * bi + (i >> 1), bp); wg_fence(); }
                if (i == 0) wgmma_n32<0>(acc, wf[i], desc_from(xd));
                else wgmma_n32<1>(acc, wf[i], desc_from(xd + (i >> 2) * 256 + (i & 3) * 2));
            }
            wg_commit();
            if (s >= PART_SLOTS / 2) mbar_wait_long(bEPI + 8 * (s & 3), ((s - 4) >> 2) & 1);
            const uint32_t ph = ((s / PART_SLOTS) & 1) ^ 1;
            uint4* p = dst + (s % PART_SLOTS) * (4 * 8 * 32);
            wg_wait0();
            #pragma unroll
            for (int j = 0; j < 4; j++)
                st_relaxed128(p + 256 * j, make_uint4((__float_as_uint(acc[4 * j]) & ~1u) | ph, __float_as_uint(acc[4 * j + 1]), __float_as_uint(acc[4 * j + 2]), __float_as_uint(acc[4 * j + 3])));
            if (tid == 0 && s == LSEG - 1) GT(blockIdx.x, 71);
            __syncwarp();
            if (lane == 0) { mbar_arrive(bEMPTY + 8 * bi); mbar_arrive(bPRT + 8 * (s & 3)); }
        };
        #pragma unroll 1
        for (int pass = 0; pass < npass; pass++) {
            if (pass) {
                #pragma unroll 1
                for (int s = 0; s < LSEG; s++) seg(s);
            }
            uint32_t tq; asm volatile("mov.u32 %0, %%tid.x;" : "=r"(tq));
            const uint4* p = &g_last[blockIdx.x][0][0][0] + (tq >> 5) * 256 + (tq & 31);
            const uint32_t tag = lds32(bGO) & 1u;
            uint4 v[8]; int it = 0;
            #pragma unroll
            for (int i = 0; i < 8; i++) v[i] = make_uint4(tag ^ pass, 0, 0, 0);
            while (true) {
                #pragma unroll
                for (int i = 0; i < 8; i++) ld_relaxed128_p(v[i], p + 32 * i, (v[i].x ^ tag) & 1u);
                uint32_t any = 0;
                #pragma unroll
                for (int i = 0; i < 8; i++) any |= v[i].x ^ tag;
                if (!__any_sync(0xffffffffu, any & 1u) || ++it >= SD_SPIN) break;
            }
            float a[8];
            #pragma unroll
            for (int i = 0; i < 8; i++) a[i] = 0.f;
            #pragma unroll
            for (int i = 0; i < 8; i++) { a[0] += bf_lo(v[i].x); a[1] += bf_hi(v[i].x); a[2] += bf_lo(v[i].y); a[3] += bf_hi(v[i].y); a[4] += bf_lo(v[i].z); a[5] += bf_hi(v[i].z); a[6] += bf_lo(v[i].w); a[7] += bf_hi(v[i].w); }
            const uint32_t xa = sb + SD_XCH + (tq >> 7) * 4096 + (tq & 127) * 16;
            sts128(xa, make_uint4(__float_as_uint(a[0]), __float_as_uint(a[1]), __float_as_uint(a[2]), __float_as_uint(a[3])));
            sts128(xa + 2048, make_uint4(__float_as_uint(a[4]), __float_as_uint(a[5]), __float_as_uint(a[6]), __float_as_uint(a[7])));
            bar_arrive_p(6, 320, !pass);
        }
        mbar_wait_long(bEPI + 8 * (LSEG & 3), ((LSEG - 4) >> 2) & 1);
        #pragma unroll
        for (int j = 0; j < 4; j++) st_relaxed128(dst + (LSEG % PART_SLOTS) * (4 * 8 * 32) + 256 * j, make_uint4(((LSEG / PART_SLOTS) & 1) ^ 1, 0, 0, 0));
    } else {
        asm volatile("setmaxnreg.dec.sync.aligned.u32 %0;" :: "n"(504 - 2 * SD_REG));
        const int w = warp - 8, n = tid - 256;
        bf16 p_la = log_A_real[d0 * NS + n], p_ai = A_imag[d0 * NS + n], p_cr = C_real[d0 * NS + n], p_ci = C_imag[d0 * NS + n], p_dt = log_dt[d0];
        const uint32_t ef = sb + SD_EF + w * 8192;
        const uint32_t efl = ef + lane * 4;
        uint32_t goff[8];
        #pragma unroll
        for (int i = 0; i < 16; i++) {
            const int l = 64 * lane + 8 * (w + 4 * (i >> 3)) + (i & 7);
            const int p = (int)rbf((float)l);
            const int a = p >> 7, b = (p >> 3) & 15, c = p & 7;
            const int row = p < 256 ? 8 * a + c : (p < 512 ? 16 + 4 * (a - 2) + (c >> 1) : (p < 1024 ? 24 + 2 * (a - 4) + (c >> 2) : 24 + a));
            const uint32_t off = row * 72 + b * 4;
            if (i & 1) goff[i >> 1] |= off << 16; else goff[i >> 1] = off;
        }
        for (int c = 0; c < 16; c++) {
            const float dt = rbf(expf(bf(p_dt)));
            const float xr = -rbf(expf(bf(p_la))) * dt, xi = bf(p_ai) * dt;
            cplx C; C.r = 2.f * bf(p_cr) * dt; C.i = 2.f * bf(p_ci) * dt;
            if (c + 1 < 16) {
                const int o = (d0 + c + 1) * NS + n;
                p_la = log_A_real[o]; p_ai = A_imag[o]; p_cr = C_real[o]; p_ci = C_imag[o]; p_dt = log_dt[d0 + c + 1];
            }
            const uint32_t mexp = min(max(__reduce_max_sync(0xffffffffu, __float_as_uint(fmaxf(fabsf(C.r), fabsf(C.i)))) & 0x7f800000u, 0x01000000u), 0x7e000000u);
            const float unsc = __uint_as_float(mexp), sc = __uint_as_float(0x7f000000u - mexp);
            C.r *= sc; C.i *= sc;
            #define EADDR(r) ((efl ^ (((r) & 7) << 4)) + (r) * 128)
            {
                cplx f[16];
                f[1] = cexp_(8.f * xr, -8.f * xi);
                f[2] = cmul(f[1], f[1]); f[3] = cmul(f[2], f[1]); f[4] = cmul(f[2], f[2]); f[5] = cmul(f[4], f[1]); f[6] = cmul(f[4], f[2]); f[7] = cmul(f[4], f[3]);
                f[8] = cmul(f[4], f[4]);
                #pragma unroll
                for (int b = 9; b < 16; b++) f[b] = cmul(f[8], f[b - 8]);
                sts32(EADDR(0) + 6144, 0x00003c00u);
                #pragma unroll
                for (int b = 1; b < 16; b++) sts32(EADDR(b) + 6144, pack_f16(f[b].r, f[b].i));
            }
            {
                cplx G[17], wc[8];
                G[1] = cexp_(128.f * xr, 128.f * xi);
                wc[1] = cexp_(xr, xi);
                G[2] = cmul(G[1], G[1]); G[4] = cmul(G[2], G[2]); G[8] = cmul(G[4], G[4]);
                wc[2] = cmul(wc[1], wc[1]); wc[3] = cmul(wc[2], wc[1]); wc[4] = cmul(wc[2], wc[2]); wc[5] = cmul(wc[4], wc[1]); wc[6] = cmul(wc[4], wc[2]); wc[7] = cmul(wc[4], wc[3]);
                cplx CG[17];
                CG[0] = C; CG[1] = cmul(C, G[1]); CG[2] = cmul(C, G[2]); CG[3] = cmul(CG[1], G[2]);
                #pragma unroll
                for (int a = 0; a < 4; a++) CG[4 + a] = cmul(CG[a], G[4]);
                #pragma unroll
                for (int a = 0; a < 9; a++) CG[8 + a] = cmul(CG[a], G[8]);
                #pragma unroll
                for (int r = 0; r < 41; r++) {
                    const int a = r < 16 ? (r >> 3) : (r < 24 ? 2 + ((r >> 2) & 1) : (r < 32 ? 4 + ((r >> 1) & 3) : r - 24));
                    const int cc = r < 16 ? (r & 7) : (r < 24 ? 2 * (r & 3) : (r < 32 ? 4 * (r & 1) : 0));
                    const cplx e = cc ? cmul(CG[a], wc[cc]) : CG[a];
                    sts32(EADDR(r), pack_f16(e.r, e.i));
                }
            }
            __syncwarp();
            float acc[3][2][4];
            #pragma unroll
            for (int i = 0; i < 3; i++)
                #pragma unroll
                for (int j = 0; j < 2; j++) { acc[i][j][0] = acc[i][j][1] = acc[i][j][2] = acc[i][j][3] = 0.f; }
            #pragma unroll
            for (int ks = 0; ks < 4; ks++) {
                uint32_t bq[4];
                ldsm_x4(bq, ef + 6144 + ((mi >> 1) * 8 + r8) * 128 + (((2 * ks + (mi & 1)) ^ r8) << 4));
                #pragma unroll
                for (int mt = 0; mt < 3; mt++) {
                    uint32_t aq[4];
                    ldsm_x4(aq, ef + (16 * mt + (mi & 1) * 8 + r8) * 128 + (((2 * ks + (mi >> 1)) ^ r8) << 4));
                    mma_f16(acc[mt][0], aq, bq[0], bq[1]);
                    mma_f16(acc[mt][1], aq, bq[2], bq[3]);
                }
            }
            const uint32_t kp = sb + SD_KP;
            #pragma unroll
            for (int mt = 0; mt < 3; mt++)
                #pragma unroll
                for (int nt = 0; nt < 2; nt++) {
                    const uint32_t a = kp + w * 3072 + (16 * mt + g) * 64 + nt * 32 + t * 8;
                    sts64(a, __float_as_uint(acc[mt][nt][0] * unsc), __float_as_uint(acc[mt][nt][1] * unsc));
                    sts64(a + 512, __float_as_uint(acc[mt][nt][2] * unsc), __float_as_uint(acc[mt][nt][3] * unsc));
                }
            bar_sync(4, 128);
            #pragma unroll
            for (int i = 0; i < 3; i++) {
                const uint32_t a = kp + (n + 128 * i) * 8;
                const uint2 v0 = lds64(a), v1 = lds64(a + 3072), v2 = lds64(a + 6144), v3 = lds64(a + 9216);
                sts64(a + 12288 + ((n >> 3) + 16 * i) * 8, __float_as_uint((__uint_as_float(v0.x) + __uint_as_float(v1.x)) + (__uint_as_float(v2.x) + __uint_as_float(v3.x))),
                                 __float_as_uint((__uint_as_float(v0.y) + __uint_as_float(v1.y)) + (__uint_as_float(v2.y) + __uint_as_float(v3.y))));
            }
            bar_sync(4, 128);
            const int slot = c % KSLOTS;
            float kv[16];
            #pragma unroll
            for (int e = 0; e < 8; e++) { kv[2 * e] = __uint_as_float(lds32(kp + 12288 + (goff[e] & 0xffff))); kv[2 * e + 1] = __uint_as_float(lds32(kp + 12288 + (goff[e] >> 16))); }
            if (c >= KSLOTS) mbar_wait_long(bKE + 8 * slot, (c / KSLOTS - 1) & 1);
            #pragma unroll
            for (int it = 0; it < 2; it++) {
                uint32_t hi[4], lo[4];
                #pragma unroll
                for (int e = 0; e < 4; e++) {
                    const float k0 = kv[8 * it + 2 * e], k1 = kv[8 * it + 2 * e + 1];
                    hi[e] = pack_bf16(k0, k1);
                    lo[e] = pack_bf16(k0 - bf_lo(hi[e]), k1 - bf_hi(hi[e]));
                }
                const uint32_t a = sb + SD_BC + slot * BC_BYTES + (w + 4 * it) * BC_LBO + (16 + 2 * lane) * 16;
                sts128(a, make_uint4(hi[0], hi[1], hi[2], hi[3]));
                sts128(a + 16, make_uint4(lo[0], lo[1], lo[2], lo[3]));
            }
            fence_async_smem();
            mbar_arrive(bKF + 8 * slot);
        }
        {
            uint32_t gw[9];
            #pragma unroll
            for (int j = 0; j < 9; j++) gw[j] = __ldg((const uint32_t*)gate_w + lane + 32 * j);
            float z = 0.f;
            #pragma unroll 1
            for (int i0 = 0; i0 < 15; i0 += 5) {
                uint32_t xv[5][9];
                #pragma unroll
                for (int i = 0; i < 5; i++) {
                    const int tk = min(blockIdx.x * 57 + w + 4 * (i0 + i), S_LEN - 1);
                    #pragma unroll
                    for (int j = 0; j < 9; j++) xv[i][j] = __ldg((const uint32_t*)(x + (size_t)tk * DM) + lane + 32 * j);
                }
                #pragma unroll
                for (int i = 0; i < 5; i++) {
                    float acc = 0.f;
                    #pragma unroll
                    for (int j = 0; j < 9; j++) { const uint32_t m = mul_bf2(xv[i][j], gw[j]); acc += bf_lo(m) + bf_hi(m); }
                    #pragma unroll
                    for (int o = 16; o; o >>= 1) acc += __shfl_xor_sync(0xffffffffu, acc, o);
                    if (lane == i0 + i) z = rbf(acc);
                }
            }
            const int li = w + 4 * lane, tk = blockIdx.x * 57 + li;
            if (li < 57 && tk < S_LEN) st_relaxed32(&g_gate[tk], pack_bf16(1.f / (1.f + expf(-z)), 0.f) | (epoch << 16));
        }
        if (tid == 256) GT(blockIdx.x, 67);
        fence_async_smem();
        __syncthreads();
            const uint32_t ost = sb + SD_OST + w * 512;
            const uint4* const pl = &g_part[blockIdx.x][0][0][0][lane];
            bf16* const ol = out + (size_t)(lane >> 1) * DM + d0 + 8 * (lane & 1);
            auto finish = [&](auto nu_, int u, auto& sm, bool store) {
                constexpr int NU = nu_.value;
                #pragma unroll
                for (int k = 0; k < NU; k++) {
                    const int t0 = 8 * (u + k) + 2 * t;
                    const uint2 gt = lds64(sb + SD_Q0 + t0 * 4);
                    const uint32_t ba = sb + SD_BT + g * BT_RS + (t0 >> 6) * 144 + (t0 & 63) * 2;
                    const uint32_t b0 = lds32(ba), b1 = lds32(ba + 8 * BT_RS);
                    const uint32_t gg = __byte_perm(gt.x, gt.y, 0x5410), mm = pack_bf16(1.f - bf_lo(gg), 1.f - bf_hi(gg));
                    const uint32_t r0 = add_bf2(mul_bf2(gg, sm[k][0]), mul_bf2(mm, b0)), r1 = add_bf2(mul_bf2(gg, sm[k][1]), mul_bf2(mm, b1));
                    asm volatile("stmatrix.sync.aligned.m8n8.x2.trans.shared.b16 [%0], {%1,%2};" :: "r"(ost + k * 256 + r8 * 32 + (mi & 1) * 16), "r"(r0), "r"(r1) : "memory");
                }
                __syncwarp();
                if (store && lane < 16 * NU) *(uint4*)(ol + (size_t)(8 * u) * DM) = lds128(ost + lane * 16);
                __syncwarp();
            };
            auto units = [&](auto nu_, int u, int end) {
              constexpr int NU = nu_.value;
              uint4 v[8 * NU];
              auto fetch = [&](int u, bool block) {
                const int s = u >> 2;
                uint32_t early;
                asm volatile("{\n.reg .pred p;\nmbarrier.test_wait.parity.shared::cta.b64 p, [%1], %2;\nselp.u32 %0, 1, 0, p;\n}\n" : "=r"(early) : "r"(bPRT + 8 * (s & 3)), "r"((s >> 2) & 1) : "memory");
                if (!early) {
                    if (!block) return false;
                    mbar_wait_long(bPRT + 8 * (s & 3), (s >> 2) & 1);
                    delay_clk(s < LSEG - 2 ? SD_P1 : SD_P2);
                } else if (SD_P3 && s < SD_RUSH) delay_clk(SD_P3);
                const uint4* p = pl + (u & (4 * PART_SLOTS - 1)) * 256;
                #pragma unroll
                for (int i = 0; i < 8 * NU; i++) v[i] = ld_relaxed128(p + 32 * i);
                return true;
              };
              fetch(u, true);
              #pragma unroll 1
              while (true) {
                const int s = u >> 2;
                const uint32_t phm = ((s / PART_SLOTS) & 1) - 1;
                int it = 0;
                while (true) {
                    uint32_t all = ~0u, any = 0;
                    #pragma unroll
                    for (int i = 0; i < 8 * NU; i++) { all &= v[i].x; any |= v[i].x; }
                    if (!__any_sync(0xffffffffu, ((all ^ phm) | (any ^ phm)) & 1u) || ++it >= SD_SPIN) break;
                    if (it > 1 && s < LSEG - 2) __nanosleep(200);
                    const uint4* p = pl + (u & (4 * PART_SLOTS - 1)) * 256;
                    #pragma unroll
                    for (int i = 0; i < 8 * NU; i++) ld_relaxed128_p(v[i], p + 32 * i, (v[i].x ^ phm) & 1u);
                }
                if (lane < NU) mbar_arrive(bEPI + 8 * (s & 3));
                uint32_t sm[NU][2];
                #pragma unroll
                for (int k = 0; k < NU; k++) {
                    float a0 = __uint_as_float(v[8 * k].x), a1 = __uint_as_float(v[8 * k].y), a2 = __uint_as_float(v[8 * k].z), a3 = __uint_as_float(v[8 * k].w);
                    #pragma unroll
                    for (int i = 1; i < 8; i++) { a0 += __uint_as_float(v[8 * k + i].x); a1 += __uint_as_float(v[8 * k + i].y); a2 += __uint_as_float(v[8 * k + i].z); a3 += __uint_as_float(v[8 * k + i].w); }
                    sm[k][0] = pack_bf16(a0, a1); sm[k][1] = pack_bf16(a2, a3);
                }
                const int nu = u + 3 * NU;
                const bool pre = nu < end && fetch(nu, false);
                finish(nu_, u, sm, true);
                if (lane == 0 && ((u + NU - 1) & 3) == 3) GT(blockIdx.x, 1 + s);
                if (nu >= end) break;
                if (!pre) fetch(nu, true);
                u = nu;
              }
            };
        #pragma unroll 1
        for (int pass = w & 1 ? 0 : 1; pass < npass; pass++) {
        if (pass) {
        if (w == 0) {
            if (lane == 0) {
                mbar_expect_tx(bWO, 131072);
                #pragma unroll 1
                for (int q = 0; q < 16; q++) {
                    tma2d(sb + SD_STG + q * 8192, &tmw, bWO, sh ? 128 * (blockIdx.x >> 3) + 64 * (q >> 3) : 512, sh ? 512 * (blockIdx.x & 7) + 64 * (q & 7) : 1024 * (blockIdx.x - 32) + 64 * q);
                    if (SD_WOP) delay_clk(SD_WOP);
                }
            }
            bar_sync(5, 128);
            const int ke0 = sh ? blockIdx.x & 7 : 2 * (blockIdx.x - 32);
            const unsigned int* f = &g_prog[12 * ke0 + (lane < (sh ? 12 : 24) ? lane : 0)];
            int avail = 0;
            #pragma unroll 1
            for (int s = 0; s < LSEG; s++) {
                if (s >= avail) {
                    int it = 0;
                    while (true) {
                        uint32_t v;
                        asm volatile("ld.acquire.gpu.global.u32 %0, [%1];" : "=r"(v) : "l"(f) : "memory");
                        avail = __reduce_min_sync(0xffffffffu, (v >> 8) == (epoch & 0xffffffu) ? v & 255u : 0u);
                        if (avail > s || ++it >= SD_SPIN) break;
                        if (s < LSEG - 1) __nanosleep(64);
                    }
                    asm volatile("fence.proxy.async.global;" ::: "memory");
                    if (lane == 0 && s == LSEG - 1) GT(blockIdx.x, 70);
                }
                if (lane == 0 && s == 2 && blockIdx.x == 0) st_relaxed32(&g_epoch, epoch + 1);
                const int b0 = sh ? s & 3 : s & 1, bp = (sh ? s >> 2 : s >> 1) & 1;
                const bf16* src = g_otok + (size_t)s * (SEG * NH * DH) + ke0 * 16384;
                mbar_wait_long(bEMPTY + 8 * b0, bp);
                if (!sh) mbar_wait_long(bEMPTY + 16 + 8 * b0, bp);
                #pragma unroll
                for (int hc = 0; hc < 2; hc++)
                    asm volatile("{\n.reg .pred p, q;\nelect.sync _|p, 0xffffffff;\nsetp.eq.and.u32 q, %6, 0, p;\n"
                                 "@p mbarrier.arrive.expect_tx.shared.b64 _, [%2], 16384;\n"
                                 "@p cp.async.bulk.shared::cluster.global.mbarrier::complete_tx::bytes [%0], [%1], 16384, [%2];\n"
                                 "@q mbarrier.arrive.expect_tx.shared.b64 _, [%5], 16384;\n"
                                 "@q cp.async.bulk.shared::cluster.global.mbarrier::complete_tx::bytes [%3], [%4], 16384, [%5];\n}\n"
                        :: "r"(sb + SD_STG + b0 * 32768 + hc * 16384), "l"(src + hc * 8192), "r"(bCH + 32 * b0 + 8 * hc),
                           "r"(sb + SD_STG + (b0 + 2) * 32768 + hc * 16384), "l"(src + 16384 + hc * 8192), "r"(bCH + 32 * (b0 + 2) + 8 * hc), "r"((uint32_t)sh) : "memory");
            }
        } else {
            if (w == 3) {
                for (int i = 0; i < 16; i += 8) {
                    uint4 v[8]; uint32_t miss = 0xffu; int it = 0;
                    const uint32_t tag = epoch & 0xffffu;
                    #pragma unroll
                    for (int j = 0; j < 8; j++) v[j] = make_uint4(0, 0, 0, 0);
                    do {
                        #pragma unroll
                        for (int j = 0; j < 8; j++) ld_relaxed128_p(v[j], (const uint4*)g_gate + (i + j) * 32 + lane, miss & (1u << j));
                        miss = 0;
                        #pragma unroll
                        for (int j = 0; j < 8; j++) miss |= (uint32_t)((v[j].x >> 16) != tag || (v[j].y >> 16) != tag || (v[j].z >> 16) != tag || (v[j].w >> 16) != tag) << j;
                    } while (__any_sync(0xffffffffu, miss) && ++it < SD_SPIN);
                    #pragma unroll
                    for (int j = 0; j < 8; j++) sts128(sb + SD_Q0 + ((i + j) * 32 + lane) * 16, v[j]);
                }
            }
            bar_sync(5, 128);
        }
        if (w) units(ic<2>(), 2 * (w - 1), 4 * LSEG);
        }
        if (w < 2) {
            bar_sync_p(6, 320, !pass);
            uint32_t sm[2][2];
            #pragma unroll
            for (int k = 0; k < 2; k++) {
                float a0 = 0.f, a1 = 0.f, a2 = 0.f, a3 = 0.f;
                #pragma unroll
                for (int i = 0; i < 4; i++) { const uint4 v = lds128(sb + SD_XCH + w * 4096 + k * 2048 + i * 512 + lane * 16); a0 += __uint_as_float(v.x); a1 += __uint_as_float(v.y); a2 += __uint_as_float(v.z); a3 += __uint_as_float(v.w); }
                sm[k][0] = pack_bf16(a0, a1); sm[k][1] = pack_bf16(a2, a3);
            }
            finish(ic<2>(), 4 * LSEG + 2 * w, sm, pass);
            if (lane == 0 && w == 1) GT(blockIdx.x, 1 + LSEG);
        }
        }
    }
    if (tid == 256) GT(blockIdx.x, 72);
}

extern "C" void kernel_launch(void* const* d_in, const int* in_sizes, int n_in, void* d_out, int out_size) {
    const bf16* x = (const bf16*)d_in[0];
    const bf16* mem0 = (const bf16*)d_in[1];
    const bf16* Wq = (const bf16*)d_in[2];
    const bf16* Wk = (const bf16*)d_in[3];
    const bf16* Wv = (const bf16*)d_in[4];
    const bf16* Wo = (const bf16*)d_in[5];
    const bf16* log_A_real = (const bf16*)d_in[8];
    const bf16* A_imag = (const bf16*)d_in[9];
    const bf16* C_real = (const bf16*)d_in[10];
    const bf16* C_imag = (const bf16*)d_in[11];
    const bf16* log_dt = (const bf16*)d_in[12];
    const bf16* D_skip = (const bf16*)d_in[13];
    const bf16* gate_w = (const bf16*)d_in[14];
    bf16* out = (bf16*)d_out;
    typedef CUresult (*EncFn)(CUtensorMap*, CUtensorMapDataType, cuuint32_t, void*, const cuuint64_t*, const cuuint64_t*, const cuuint32_t*, const cuuint32_t*,
                              CUtensorMapInterleave, CUtensorMapSwizzle, CUtensorMapL2promotion, CUtensorMapFloatOOBfill);
    static EncFn enc = nullptr;
    if (!enc) { void* fn = nullptr; cudaDriverEntryPointQueryResult qr; cudaGetDriverEntryPoint("cuTensorMapEncodeTiled", &fn, cudaEnableDefault, &qr); enc = (EncFn)fn; }
    auto mk = [&](CUtensorMap* tm, const void* ptr, uint64_t cols, uint64_t rows, uint32_t bc, uint32_t br) {
        cuuint64_t gdim[2] = {cols, rows}; cuuint64_t gstr[1] = {cols * 2}; cuuint32_t box[2] = {bc, br}; cuuint32_t estr[2] = {1, 1};
        enc(tm, CU_TENSOR_MAP_DATA_TYPE_BFLOAT16, 2, (void*)ptr, gdim, gstr, box, estr, CU_TENSOR_MAP_INTERLEAVE_NONE, bc == 64 ? CU_TENSOR_MAP_SWIZZLE_128B : CU_TENSOR_MAP_SWIZZLE_64B,
            CU_TENSOR_MAP_L2_PROMOTION_L2_256B, CU_TENSOR_MAP_FLOAT_OOB_FILL_NONE);
    };
    static bool attr_done = false;
    if (!attr_done) {
        cudaFuncSetAttribute(chain_kernel, cudaFuncAttributeMaxDynamicSharedMemorySize, SM_TOTAL);
        cudaFuncSetAttribute(side_kernel, cudaFuncAttributeMaxDynamicSharedMemorySize, SD_TOTAL);
        attr_done = true;
    }
    CUtensorMap tmx, tma, tmb, tmw, tmq, tmk, tmv, tmo;
    {
        cuuint64_t gdim[3] = {64, S_LEN, DM / 64}; cuuint64_t gstr[2] = {DM * 2, 128}; cuuint32_t box[3] = {64, SEG, 3}; cuuint32_t estr[3] = {1, 1, 1};
        enc(&tmx, CU_TENSOR_MAP_DATA_TYPE_BFLOAT16, 3, (void*)x, gdim, gstr, box, estr, CU_TENSOR_MAP_INTERLEAVE_NONE, CU_TENSOR_MAP_SWIZZLE_128B,
            CU_TENSOR_MAP_L2_PROMOTION_L2_256B, CU_TENSOR_MAP_FLOAT_OOB_FILL_NONE);
    }
    static void* acc = nullptr;
    if (!acc) cudaGetSymbolAddress(&acc, g_acc);
    for (int w = 0; w < 2; w++) {
        cuuint64_t gdim[3] = {64, 4, 64}; cuuint64_t gstr[2] = {256, 1024}; cuuint32_t box[3] = {w ? 8u : 32u, 2, w ? 6u : 12u}; cuuint32_t estr[3] = {1, 1, 1};
        enc(w ? &tmb : &tma, CU_TENSOR_MAP_DATA_TYPE_UINT32, 3, acc, gdim, gstr, box, estr, CU_TENSOR_MAP_INTERLEAVE_NONE, CU_TENSOR_MAP_SWIZZLE_NONE,
            CU_TENSOR_MAP_L2_PROMOTION_NONE, CU_TENSOR_MAP_FLOAT_OOB_FILL_NONE);
    }
    mk(&tmw, Wo, DM, NH * DH, 64, 64);
    mk(&tmo, Wo, DM, NH * DH, 32, 128);
    mk(&tmq, Wq, NH * DH, DM, 32, 48); mk(&tmk, Wk, NH * DH, DM, 32, 48); mk(&tmv, Wv, NH * DH, DM, 32, 48);
    chain_kernel<<<96, CH_THREADS, SM_TOTAL>>>(tmx, tmq, tmk, tmv, tmo, tma, tmb, mem0, 0u);
    cudaLaunchConfig_t cfg = {};
    cfg.gridDim = dim3(SD_CTAS); cfg.blockDim = dim3(SD_THREADS); cfg.dynamicSmemBytes = SD_TOTAL; cfg.stream = cudaStreamPerThread;
    cudaLaunchAttribute at[1];
    at[0].id = cudaLaunchAttributeProgrammaticStreamSerialization; at[0].val.programmaticStreamSerializationAllowed = 1;
    cfg.attrs = at; cfg.numAttrs = 1;
    cudaLaunchKernelEx(&cfg, side_kernel, tmw, x, log_A_real, A_imag, C_real, C_imag, log_dt, D_skip, gate_w, out, 2);
}
```

```cpp
#include <cuda_runtime.h>
#include <cuda.h>
#include <cuda_bf16.h>
#include <stdint.h>

#define S_LEN 2048
#define DM 576
#define NH 32
#define DH 128
#define NMEM 8
#define SEG 32
#define NSEG 64
#define LQ 40
#define NS 128

typedef __nv_bfloat16 bf16;

__device__ __forceinline__ float bf(bf16 v) { return __bfloat162float(v); }
__device__ __forceinline__ bf16 tobf(float v) { return __float2bfloat16_rn(v); }
__device__ __forceinline__ float rbf(float v) { return __bfloat162float(__float2bfloat16_rn(v)); }

#define CH_THREADS 384
#define SPIN_LIMIT (1 << 17)
#define SM_X     0
#define XBUF     36864
#define SM_TOK   73728
#define TOKBUF   24576
#define SM_STASH 139264
#define SM_TS    (SM_STASH + 3072)
#define SM_WO    147456
#define SM_MEM   196608
#define SM_EX    205824
#define EXBUF    6144
#define SM_P     218112
#define SM_OST   122880
#define SM_PARK  219136
#define SM_O     223232
#define SM_XT    225280
#define SM_BAR   228352
#define SM_IL    (SM_BAR + 128)
#define SM_TG    (SM_IL + 256)
#define SM_TOTAL (SM_TG + 64)

#define ACC_X    36864
#define ACC_FULL 0x0020u
#define SLOT_OFF(sl) ((((sl) & 1) << 7) | (((sl) & 2) << 8))
__device__ __align__(65536) unsigned char g_acc[65536];
__device__ unsigned int g_init[96];
__device__ __align__(1024) uint4 g_last[36][2][32][32];
__device__ unsigned int g_epoch = 1;
__device__ __align__(128) unsigned int g_ts[128];
__device__ __align__(1024) bf16 g_otok[S_LEN * NH * DH];
__device__ __align__(1024) unsigned char g_tokx[96][8192];
__device__ __align__(128) unsigned int g_prog[96];
#define STAMP(i)
#define STAMPV(i, v)
#define GT(b, i)
#define PT(i)
#define STAMPB(i)

__device__ __forceinline__ uint32_t smem_u32(const void* p) { return (uint32_t)__cvta_generic_to_shared(p); }
__device__ __forceinline__ void ldsm_x4(uint32_t (&r)[4], uint32_t addr) {
    asm volatile("ldmatrix.sync.aligned.m8n8.x4.shared.b16 {%0,%1,%2,%3}, [%4];" : "=r"(r[0]), "=r"(r[1]), "=r"(r[2]), "=r"(r[3]) : "r"(addr) : "memory");
}
__device__ __forceinline__ void ldsm_x4_p(uint32_t (&r)[4], uint32_t addr, uint32_t skip) {
    asm volatile("{\n.reg .pred p;\nsetp.eq.u32 p, %5, 0;\n@p ldmatrix.sync.aligned.m8n8.x4.shared.b16 {%0,%1,%2,%3}, [%4];\n}\n" : "+r"(r[0]), "+r"(r[1]), "+r"(r[2]), "+r"(r[3]) : "r"(addr), "r"(skip) : "memory");
}
__device__ __forceinline__ void ldsm_x4_t(uint32_t (&r)[4], uint32_t addr) {
    asm volatile("ldmatrix.sync.aligned.m8n8.x4.trans.shared.b16 {%0,%1,%2,%3}, [%4];" : "=r"(r[0]), "=r"(r[1]), "=r"(r[2]), "=r"(r[3]) : "r"(addr) : "memory");
}
__device__ __forceinline__ uint32_t ldsm_x1_t(uint32_t addr) {
    uint32_t r; asm volatile("ldmatrix.sync.aligned.m8n8.x1.trans.shared.b16 {%0}, [%1];" : "=r"(r) : "r"(addr) : "memory"); return r;
}
__device__ __forceinline__ void ldsm_x2_t(uint32_t& r0, uint32_t& r1, uint32_t addr) {
    asm volatile("ldmatrix.sync.aligned.m8n8.x2.trans.shared.b16 {%0,%1}, [%2];" : "=r"(r0), "=r"(r1) : "r"(addr) : "memory");
}
__device__ __forceinline__ void stsm_x4(uint32_t addr, uint32_t r0, uint32_t r1, uint32_t r2, uint32_t r3) {
    asm volatile("stmatrix.sync.aligned.m8n8.x4.shared.b16 [%0], {%1,%2,%3,%4};" :: "r"(addr), "r"(r0), "r"(r1), "r"(r2), "r"(r3) : "memory");
}
__device__ __forceinline__ void stsm_x4_t(uint32_t addr, uint32_t r0, uint32_t r1, uint32_t r2, uint32_t r3) {
    asm volatile("stmatrix.sync.aligned.m8n8.x4.trans.shared.b16 [%0], {%1,%2,%3,%4};" :: "r"(addr), "r"(r0), "r"(r1), "r"(r2), "r"(r3) : "memory");
}
__device__ __forceinline__ void mma16816(float (&c)[4], const uint32_t (&a)[4], uint32_t b0, uint32_t b1) {
    asm("mma.sync.aligned.m16n8k16.row.col.f32.bf16.bf16.f32 {%0,%1,%2,%3}, {%4,%5,%6,%7}, {%8,%9}, {%0,%1,%2,%3};"
        : "+f"(c[0]), "+f"(c[1]), "+f"(c[2]), "+f"(c[3]) : "r"(a[0]), "r"(a[1]), "r"(a[2]), "r"(a[3]), "r"(b0), "r"(b1));
}
__device__ __forceinline__ void mma16816r(float (&c)[4], uint32_t a0, uint32_t a1, uint32_t a2, uint32_t a3, uint32_t b0, uint32_t b1) {
    asm("mma.sync.aligned.m16n8k16.row.col.f32.bf16.bf16.f32 {%0,%1,%2,%3}, {%4,%5,%6,%7}, {%8,%9}, {%0,%1,%2,%3};"
        : "+f"(c[0]), "+f"(c[1]), "+f"(c[2]), "+f"(c[3]) : "r"(a0), "r"(a1), "r"(a2), "r"(a3), "r"(b0), "r"(b1));
}
__device__ __forceinline__ void mma1688(float (&c)[4], uint32_t a0, uint32_t a1, uint32_t b0) {
    asm("mma.sync.aligned.m16n8k8.row.col.f32.bf16.bf16.f32 {%0,%1,%2,%3}, {%4,%5}, {%6}, {%0,%1,%2,%3};"
        : "+f"(c[0]), "+f"(c[1]), "+f"(c[2]), "+f"(c[3]) : "r"(a0), "r"(a1), "r"(b0));
}
__device__ __forceinline__ uint32_t pack_bf16(float lo, float hi) {
    uint32_t r; asm("cvt.rn.bf16x2.f32 %0, %1, %2;" : "=r"(r) : "f"(hi), "f"(lo)); return r;
}
__device__ __forceinline__ float bf_lo(uint32_t v) { return __uint_as_float(v << 16); }
__device__ __forceinline__ float bf_hi(uint32_t v) { return __uint_as_float(v & 0xffff0000u); }
__device__ __forceinline__ uint32_t max_bf2(uint32_t a, uint32_t b) { uint32_t r; asm("max.bf16x2 %0, %1, %2;" : "=r"(r) : "r"(a), "r"(b)); return r; }
__device__ __forceinline__ uint32_t maxabs_bf2(uint32_t a, uint32_t b) { uint32_t r; asm("max.NaN.xorsign.abs.bf16x2 %0, %1, %2;" : "=r"(r) : "r"(a), "r"(b)); return r; }
__device__ __forceinline__ float ex2(float x) { float r; asm("ex2.approx.ftz.f32 %0, %1;" : "=f"(r) : "f"(x)); return r; }
__device__ __forceinline__ void ld_relaxed128_p(uint4& v, const uint4* p, uint32_t pred) {
    asm volatile("{\n.reg .pred p;\nsetp.ne.u32 p, %5, 0;\n@p ld.relaxed.gpu.global.v4.u32 {%0,%1,%2,%3}, [%4];\n}\n" : "+r"(v.x), "+r"(v.y), "+r"(v.z), "+r"(v.w) : "l"(p), "r"(pred) : "memory");
}
__device__ __forceinline__ uint4 ld_relaxed128(const uint4* p) { uint4 v; asm volatile("ld.relaxed.gpu.global.v4.u32 {%0,%1,%2,%3}, [%4];" : "=r"(v.x), "=r"(v.y), "=r"(v.z), "=r"(v.w) : "l"(p) : "memory"); return v; }
__device__ __forceinline__ uint32_t ld_relaxed32(const uint32_t* p) { uint32_t v; asm volatile("ld.relaxed.gpu.global.u32 %0, [%1];" : "=r"(v) : "l"(p) : "memory"); return v; }
__device__ __forceinline__ void st_relaxed128(uint4* p, uint4 v) { asm volatile("st.relaxed.gpu.global.v4.u32 [%0], {%1,%2,%3,%4};" :: "l"(p), "r"(v.x), "r"(v.y), "r"(v.z), "r"(v.w) : "memory"); }
__device__ __forceinline__ void st_relaxed32(uint32_t* p, uint32_t v) { asm volatile("st.relaxed.gpu.global.u32 [%0], %1;" :: "l"(p), "r"(v) : "memory"); }
__device__ __forceinline__ void st_relaxed128_p(uint4* p, uint4 v, uint32_t skip) {
    asm volatile("{\n.reg .pred p;\nsetp.eq.u32 p, %5, 0;\n@p st.relaxed.gpu.global.v4.u32 [%0], {%1,%2,%3,%4};\n}\n" :: "l"(p), "r"(v.x), "r"(v.y), "r"(v.z), "r"(v.w), "r"(skip) : "memory");
}
__device__ __forceinline__ void st_relaxed64_p(void* p, uint32_t x, uint32_t y, uint32_t skip) {
    asm volatile("{\n.reg .pred p;\n.reg .b64 v;\nsetp.eq.u32 p, %3, 0;\nmov.b64 v, {%1,%2};\n@p st.relaxed.gpu.global.b64 [%0], v;\n}\n" :: "l"(p), "r"(x), "r"(y), "r"(skip) : "memory");
}
__device__ __forceinline__ void ld_relaxed64_p(uint2& v, const void* p, uint32_t pred) {
    asm volatile("{\n.reg .pred p;\n.reg .b64 v;\nsetp.ne.u32 p, %3, 0;\nmov.b64 v, {%0,%1};\n@p ld.relaxed.gpu.global.b64 v, [%2];\nmov.b64 {%0,%1}, v;\n}\n" : "+r"(v.x), "+r"(v.y) : "l"(p), "r"(pred) : "memory");
}
__device__ __forceinline__ uint2 ld_relaxed64(const void* p) {
    uint2 v; asm volatile("{\n.reg .b64 v;\nld.relaxed.gpu.global.b64 v, [%2];\nmov.b64 {%0,%1}, v;\n}\n" : "=r"(v.x), "=r"(v.y) : "l"(p) : "memory"); return v;
}
__device__ __forceinline__ void st_relaxed32_p(void* p, uint32_t v, uint32_t skip) {
    asm volatile("{\n.reg .pred p;\nsetp.eq.u32 p, %2, 0;\n@p st.relaxed.gpu.global.u32 [%0], %1;\n}\n" :: "l"(p), "r"(v), "r"(skip) : "memory");
}
__device__ __forceinline__ void bar_arrive_p(int id, int n, uint32_t skip) {
    asm volatile("{\n.reg .pred p;\nsetp.eq.u32 p, %2, 0;\n@p bar.arrive %0, %1;\n}\n" :: "r"(id), "r"(n), "r"(skip) : "memory");
}
__device__ __forceinline__ void bar_sync_p(int id, int n, uint32_t skip) {
    asm volatile("{\n.reg .pred p;\nsetp.eq.u32 p, %2, 0;\n@p bar.sync %0, %1;\n}\n" :: "r"(id), "r"(n), "r"(skip) : "memory");
}
__device__ __forceinline__ uint32_t movm(uint32_t x) { uint32_t r; asm volatile("movmatrix.sync.aligned.m8n8.trans.b16 %0, %1;" : "=r"(r) : "r"(x)); return r; }
__device__ __forceinline__ void sts32_p(uint32_t a, uint32_t v, uint32_t doit) {
    asm volatile("{\n.reg .pred p;\nsetp.ne.u32 p, %2, 0;\n@p st.shared.u32 [%0], %1;\n}\n" :: "r"(a), "r"(v), "r"(doit) : "memory");
}
__device__ __forceinline__ uint32_t pin(uint32_t x) { return __shfl_sync(0xffffffffu, x, threadIdx.x & 31); }
__device__ __forceinline__ void ldsm16_t(uint32_t (&b)[4][4], uint32_t a) {
    asm volatile("ldmatrix.sync.aligned.m8n8.x4.trans.shared.b16 {%0,%1,%2,%3}, [%16];\n"
                 "ldmatrix.sync.aligned.m8n8.x4.trans.shared.b16 {%4,%5,%6,%7}, [%16+512];\n"
                 "ldmatrix.sync.aligned.m8n8.x4.trans.shared.b16 {%8,%9,%10,%11}, [%16+1024];\n"
                 "ldmatrix.sync.aligned.m8n8.x4.trans.shared.b16 {%12,%13,%14,%15}, [%16+1536];\n"
        : "=r"(b[0][0]), "=r"(b[0][1]), "=r"(b[0][2]), "=r"(b[0][3]), "=r"(b[1][0]), "=r"(b[1][1]), "=r"(b[1][2]), "=r"(b[1][3]),
          "=r"(b[2][0]), "=r"(b[2][1]), "=r"(b[2][2]), "=r"(b[2][3]), "=r"(b[3][0]), "=r"(b[3][1]), "=r"(b[3][2]), "=r"(b[3][3]) : "r"(a) : "memory");
}
template<int ID> __device__ __forceinline__ void sched_fence(uint32_t never) { while (never == 0x7fffff00u + ID) { asm volatile("nanosleep.u32 64;" ::: "memory"); } }
__device__ __forceinline__ uint32_t opaque_u() { uint32_t v; asm volatile("mov.u32 %0, %%nsmid;" : "=r"(v)); return v; }
__device__ __forceinline__ uint32_t bar_red_or(int id, int n, uint32_t v) {
    uint32_t r; asm volatile("{\n.reg .pred p, q;\nsetp.ne.u32 p, %3, 0;\nbar.red.or.pred q, %1, %2, p;\nselp.u32 %0, 1, 0, q;\n}\n" : "=r"(r) : "r"(id), "r"(n), "r"(v) : "memory"); return r;
}
template<class T> __device__ __forceinline__ T* launder_p(T* p) { asm volatile("" : "+l"(p)); return p; }
__device__ __forceinline__ uint32_t mapa_u32(uint32_t addr, uint32_t rank) { uint32_t d; asm("mapa.shared::cluster.u32 %0, %1, %2;" : "=r"(d) : "r"(addr), "r"(rank)); return d; }
__device__ __forceinline__ uint32_t mapa_v(uint32_t addr, uint32_t rank) { uint32_t d; asm volatile("mapa.shared::cluster.u32 %0, %1, %2;" : "=r"(d) : "r"(addr), "r"(rank)); return d; }
__device__ __forceinline__ void st_async32(uint32_t addr, uint32_t v, uint32_t mbar) { asm volatile("st.async.shared::cluster.mbarrier::complete_tx::bytes.u32 [%0], %1, [%2];" :: "r"(addr), "r"(v), "r"(mbar) : "memory"); }
__device__ __forceinline__ void cluster_arrive() { asm volatile("barrier.cluster.arrive.release.aligned;" ::: "memory"); }
__device__ __forceinline__ void cluster_wait() { asm volatile("barrier.cluster.wait.acquire.aligned;" ::: "memory"); }
__device__ __forceinline__ void cp_async16(uint32_t dst, const void* src) { asm volatile("cp.async.cg.shared.global [%0], [%1], 16;" :: "r"(dst), "l"(src) : "memory"); }
__device__ __forceinline__ void cp_async_commit() { asm volatile("cp.async.commit_group;" ::: "memory"); }
template<int N> __device__ __forceinline__ void cp_async_wait() { asm volatile("cp.async.wait_group %0;" :: "n"(N) : "memory"); }
__device__ __forceinline__ void cp_async_wait0() { asm volatile("cp.async.wait_group 0;" ::: "memory"); }
__device__ __forceinline__ void mbar_init(uint32_t a, uint32_t cnt) { asm volatile("mbarrier.init.shared.b64 [%0], %1;" :: "r"(a), "r"(cnt) : "memory"); }
__device__ __forceinline__ void mbar_expect_tx(uint32_t a, uint32_t bytes) { asm volatile("mbarrier.arrive.expect_tx.shared.b64 _, [%0], %1;" :: "r"(a), "r"(bytes) : "memory"); }
__device__ __forceinline__ bool mbar_try(uint32_t a, uint32_t parity) {
    uint32_t ok; asm volatile("{\n.reg .pred p;\nmbarrier.try_wait.parity.shared::cta.b64 p, [%1], %2;\nselp.u32 %0, 1, 0, p;\n}\n" : "=r"(ok) : "r"(a), "r"(parity) : "memory"); return ok;
}
__device__ __forceinline__ void mbar_wait(uint32_t a, uint32_t parity) { int it = 0; bool more; do { more = ++it < SPIN_LIMIT; } while (!mbar_try(a, parity) && more); }
__device__ __forceinline__ void bar_sync(int id, int n) { asm volatile("bar.sync %0, %1;" :: "r"(id), "r"(n) : "memory"); }
__device__ __forceinline__ void bar_arrive(int id, int n) { asm volatile("bar.arrive %0, %1;" :: "r"(id), "r"(n) : "memory"); }
__device__ __forceinline__ void fence_async_smem() { asm volatile("fence.proxy.async.shared::cta;" ::: "memory"); }
__device__ __forceinline__ void sts32(uint32_t a, uint32_t v) { asm volatile("st.shared.u32 [%0], %1;" :: "r"(a), "r"(v) : "memory"); }
__device__ __forceinline__ void sts128(uint32_t a, uint4 v) { asm volatile("st.shared.v4.u32 [%0], {%1,%2,%3,%4};" :: "r"(a), "r"(v.x), "r"(v.y), "r"(v.z), "r"(v.w) : "memory"); }
__device__ __forceinline__ uint4 lds128(uint32_t a) { uint4 v; asm volatile("ld.shared.v4.u32 {%0,%1,%2,%3}, [%4];" : "=r"(v.x), "=r"(v.y), "=r"(v.z), "=r"(v.w) : "r"(a) : "memory"); return v; }
__device__ __forceinline__ uint32_t lds32(uint32_t a) { uint32_t v; asm volatile("ld.shared.u32 %0, [%1];" : "=r"(v) : "r"(a) : "memory"); return v; }
__device__ __forceinline__ uint32_t gtime_lo() { uint32_t t; asm volatile("mov.u32 %0, %globaltimer_lo;" : "=r"(t)); return t; }
__device__ __forceinline__ void wait_gtime(uint32_t tg) {
    asm volatile("{\n.reg .pred p, q;\n.reg .b64 t;\n.reg .b32 lo, hi, d, n;\nmov.b32 n, 300;\n"
                 "WG_%=:\nmov.u64 t, %%globaltimer;\nmov.b64 {lo, hi}, t;\nsub.s32 d, lo, %0;\nsub.s32 n, n, 1;\n"
                 "setp.gt.s32 q, n, 0;\nsetp.lt.and.s32 p, d, 0, q;\n@p bra.uni WG_%=;\n}\n" :: "r"(tg) : "memory");
}
__device__ __forceinline__ void delay_clk(int d) { uint32_t t0 = clock(); while ((int)(clock() - t0) < d) {} }

__device__ __forceinline__ uint64_t desc128(uint32_t addr) {
    return (uint64_t)((addr & 0x3FFFF) >> 4) | ((uint64_t)1 << 16) | ((uint64_t)64 << 32) | ((uint64_t)1 << 62);
}
template<int accum> __device__ __forceinline__ void wgmma_n32(float (&d)[16], const uint32_t (&a)[4], uint64_t desc) {
    if (accum) {
        asm volatile("{\n.reg .pred p;\nsetp.ne.b32 p, 1, 0;\n"
            "wgmma.mma_async.sync.aligned.m64n32k16.f32.bf16.bf16 {%0,%1,%2,%3,%4,%5,%6,%7,%8,%9,%10,%11,%12,%13,%14,%15}, {%16,%17,%18,%19}, %20, p, 1, 1, 0;\n}\n"
            : "+f"(d[0]), "+f"(d[1]), "+f"(d[2]), "+f"(d[3]), "+f"(d[4]), "+f"(d[5]), "+f"(d[6]), "+f"(d[7]),
              "+f"(d[8]), "+f"(d[9]), "+f"(d[10]), "+f"(d[11]), "+f"(d[12]), "+f"(d[13]), "+f"(d[14]), "+f"(d[15])
            : "r"(a[0]), "r"(a[1]), "r"(a[2]), "r"(a[3]), "l"(desc));
    } else {
        asm volatile("{\n.reg .pred p;\nsetp.ne.b32 p, 0, 0;\n"
            "wgmma.mma_async.sync.aligned.m64n32k16.f32.bf16.bf16 {%0,%1,%2,%3,%4,%5,%6,%7,%8,%9,%10,%11,%12,%13,%14,%15}, {%16,%17,%18,%19}, %20, p, 1, 1, 0;\n}\n"
            : "=f"(d[0]), "=f"(d[1]), "=f"(d[2]), "=f"(d[3]), "=f"(d[4]), "=f"(d[5]), "=f"(d[6]), "=f"(d[7]),
              "=f"(d[8]), "=f"(d[9]), "=f"(d[10]), "=f"(d[11]), "=f"(d[12]), "=f"(d[13]), "=f"(d[14]), "=f"(d[15])
            : "r"(a[0]), "r"(a[1]), "r"(a[2]), "r"(a[3]), "l"(desc));
    }
}
__device__ __forceinline__ float rcp_approx(float x) { float r; asm("rcp.approx.ftz.f32 %0, %1;" : "=f"(r) : "f"(x)); return r; }
__device__ __forceinline__ void wg_fence() { asm volatile("wgmma.fence.sync.aligned;" ::: "memory"); }
__device__ __forceinline__ void wg_commit() { asm volatile("wgmma.commit_group.sync.aligned;" ::: "memory"); }
__device__ __forceinline__ void wg_wait0() { asm volatile("wgmma.wait_group.sync.aligned 0;" ::: "memory"); }

#define SCALE_HI 0x3db53db5u
#define SCALE_LO 0x371e371eu
#define LOG2E 1.4426950408889634f
#define NEG_BIG2 0xce6ece6eu
__device__ __forceinline__ uint32_t scale_bf2(uint32_t x) {
    uint32_t t, r;
    asm("mul.rn.bf16x2 %0, %1, %2;" : "=r"(t) : "r"(x), "r"(SCALE_LO));
    asm("fma.rn.bf16x2 %0, %1, %2, %3;" : "=r"(r) : "r"(x), "r"(SCALE_HI), "r"(t));
    return r;
}
__device__ __forceinline__ void cluster_arrive_rx() { asm volatile("barrier.cluster.arrive.relaxed.aligned;" ::: "memory"); }
__device__ __forceinline__ uint32_t launder(uint32_t x) { asm volatile("" : "+r"(x)); return x; }
__device__ __forceinline__ void mbar_arrive(uint32_t a) { asm volatile("mbarrier.arrive.shared.b64 _, [%0];" :: "r"(a) : "memory"); }
__device__ __forceinline__ void mbar_wait_cl(uint32_t a, uint32_t parity) {
    int it = 0; uint32_t ok;
    do { asm volatile("{\n.reg .pred p;\nmbarrier.try_wait.parity.acquire.cluster.shared::cta.b64 p, [%1], %2;\nselp.u32 %0, 1, 0, p;\n}\n" : "=r"(ok) : "r"(a), "r"(parity) : "memory"); } while (!ok && ++it < SPIN_LIMIT);
}
__device__ __forceinline__ uint64_t desc_from(uint32_t lo) { return (uint64_t)lo | ((uint64_t)0x40000040u << 32); }
#define SB_OFF 1024u
#define DESC_LO(off) ((((SB_OFF + (uint32_t)(off)) & 0x3FFFFu) >> 4) | 0x10000u)
template<int N> struct ic { static constexpr int value = N; };
__device__ __forceinline__ uint32_t uni(uint32_t x) { return __shfl_sync(0xffffffffu, x, 0); }

__device__ __forceinline__ uint32_t pack_f16(float lo, float hi) { uint32_t r; asm("cvt.rn.f16x2.f32 %0, %1, %2;" : "=r"(r) : "f"(hi), "f"(lo)); return r; }
__device__ __forceinline__ void sts16(uint32_t a, uint16_t v) { asm volatile("st.shared.u16 [%0], %1;" :: "r"(a), "h"(v) : "memory"); }
__device__ __forceinline__ void sts64(uint32_t a, uint32_t x, uint32_t y) { asm volatile("st.shared.v2.u32 [%0], {%1,%2};" :: "r"(a), "r"(x), "r"(y) : "memory"); }
__device__ __forceinline__ void ld_relaxed32_p(uint32_t& v, const void* p, uint32_t pred) {
    asm volatile("{\n.reg .pred p;\nsetp.ne.u32 p, %2, 0;\n@p ld.relaxed.gpu.global.u32 %0, [%1];\n}\n" : "+r"(v) : "l"(p), "r"(pred) : "memory");
}
__device__ __forceinline__ uint2 lds64(uint32_t a) { uint2 v; asm volatile("ld.shared.v2.u32 {%0,%1}, [%2];" : "=r"(v.x), "=r"(v.y) : "r"(a) : "memory"); return v; }
__device__ __forceinline__ void mbar_wait2(uint32_t a, uint32_t pa, uint32_t b, uint32_t pb) {
    int it = 0; uint32_t ok;
    do { asm volatile("{\n.reg .pred p, q;\nmbarrier.try_wait.parity.shared::cta.b64 p, [%1], %2;\nmbarrier.try_wait.parity.shared::cta.b64 q, [%3], %4;\nand.pred p, p, q;\nselp.u32 %0, 1, 0, p;\n}\n"
                      : "=r"(ok) : "r"(a), "r"(pa), "r"(b), "r"(pb) : "memory"); } while (!ok && ++it < SPIN_LIMIT);
}
__device__ __forceinline__ float exd(float s, float m) { return ex2(__fmul_rn(__fsub_rn(s, m), LOG2E)); }
__device__ __forceinline__ uint32_t gtime_after(uint32_t z) {
    uint32_t t = 0; asm volatile("{\n.reg .pred p;\nsetp.eq.u32 p, %1, 0;\n@p mov.u32 %0, %%globaltimer_lo;\n}\n" : "+r"(t) : "r"(z)); return t;
}
__device__ __forceinline__ uint32_t ld_acquire32(const uint32_t* p) { uint32_t v; asm volatile("ld.acquire.gpu.global.u32 %0, [%1];" : "=r"(v) : "l"(p) : "memory"); return v; }
#define T_KPRE 3
#define BLK_Q(p) (((p) < 3 ? (p) : 8) * 2048)
#define BLK_K(p) (((p) < 3 ? 4 + (p) : 9) * 2048)
#define BLK_V(p) (((p) < 2 ? 3 + 4 * (p) : 8 + (p)) * 2048)
__device__ __forceinline__ uint32_t exp_bf2(uint32_t s) { return pack_bf16(ex2(bf_lo(s) * LOG2E), ex2(bf_hi(s) * LOG2E)); }
template<int MT, int LO, int HI>
__device__ __forceinline__ void tok_loadv(uint32_t tok, int eh, int lane, uint32_t (&bv)[8][4]) {
    const int r8 = lane & 7;
    const uint32_t va = MT ? tok + lane * 64 + ((r8 >> 1) << 4) : tok + (lane & 15) * 64 + (((lane >> 4) ^ (r8 >> 1)) << 4);
    const uint32_t o0 = eh ? BLK_V(2) : BLK_V(0), o1 = eh ? BLK_V(3) : BLK_V(1);
    #pragma unroll
    for (int n = LO; n < HI; n++) { if (MT) ldsm_x4_t(bv[n], (va ^ ((n & 3) << 4)) + (n < 4 ? o0 : o1)); else ldsm_x4_t(bv[n], (va ^ ((n & 1) << 5)) + BLK_V(n >> 1)); }
}
#define T_VPRE 4
template<int MT, class F>
__device__ __forceinline__ void tok_part1(uint32_t tok, int eh, int lane, uint32_t (&q)[8][4], uint32_t (&sp)[5][2], uint32_t (&pa)[5][2], uint32_t (&bv)[8][4], uint32_t& rng, F&& hold) {
    float e[5][4];
    constexpr int NK = MT ? 5 : 3;
    const int g = lane >> 2, t = lane & 3, mi = lane >> 3, r8 = lane & 7;
    #pragma unroll
    for (int nt = 1; nt < NK; nt++) { e[nt][0] = e[nt][1] = e[nt][2] = e[nt][3] = 0.f; }
    const uint32_t qa = tok + (16 * MT + (mi & 1) * 8 + r8) * 64 + (((mi >> 1) ^ (r8 >> 1)) << 4);
    const uint32_t ka = tok + r8 * 64 + ((mi ^ (r8 >> 1)) << 4);
    uint32_t b[4][NK][4];
    constexpr int PRE = MT ? T_KPRE : 4;
    #pragma unroll
    for (int k2 = 0; k2 < 4; k2++) {
        ldsm_x4(q[2 * k2], qa + BLK_Q(k2)); ldsm_x4(q[2 * k2 + 1], (qa ^ 32) + BLK_Q(k2));
        if (k2 < PRE) {
            #pragma unroll
            for (int nt = 1; nt < NK; nt++) ldsm_x4(b[k2][nt], ka + BLK_K(k2) + (nt - 1) * 512);
        }
    }
    hold();
    #pragma unroll
    for (int k2 = 0; k2 < 4; k2++) {
        if (k2 >= PRE) {
            #pragma unroll
            for (int nt = 1; nt < NK; nt++) ldsm_x4(b[k2][nt], ka + BLK_K(k2) + (nt - 1) * 512);
        }
        #pragma unroll
        for (int nt = 1; nt < NK; nt++) mma16816(e[nt], q[2 * k2], b[k2][nt][0], b[k2][nt][1]);
        #pragma unroll
        for (int nt = 1; nt < NK; nt++) mma16816(e[nt], q[2 * k2 + 1], b[k2][nt][2], b[k2][nt][3]);
    }
    #pragma unroll
    for (int nt = 1; nt < NK; nt++) asm volatile("" : "+f"(e[nt][0]), "+f"(e[nt][1]), "+f"(e[nt][2]), "+f"(e[nt][3]));
    #pragma unroll
    for (int nt = 1; nt < NK; nt++) {
        sp[nt][0] = nt < NK - 1 ? scale_bf2(pack_bf16(e[nt][0], e[nt][1])) : NEG_BIG2; sp[nt][1] = scale_bf2(pack_bf16(e[nt][2], e[nt][3]));
        rng = maxabs_bf2(nt == 1 ? sp[1][0] : (nt < NK - 1 ? maxabs_bf2(rng, sp[nt][0]) : rng), sp[nt][1]);
    }
    const uint32_t keep = (2 * t <= g ? 0x0000ffffu : 0u) | (2 * t + 1 <= g ? 0xffff0000u : 0u);
    sp[NK - 2][0] = (sp[NK - 2][0] & keep) | (NEG_BIG2 & ~keep);
    sp[NK - 1][1] = (sp[NK - 1][1] & keep) | (NEG_BIG2 & ~keep);
    #pragma unroll
    for (int nt = 1; nt < NK; nt++) { pa[nt][0] = nt < NK - 1 ? exp_bf2(sp[nt][0]) : 0u; pa[nt][1] = exp_bf2(sp[nt][1]); }
    tok_loadv<MT, 0, MT ? T_VPRE : 8>(tok, eh, lane, bv);
}
template<int MT, class F, class G, class H, class I>
__device__ __forceinline__ void tok_part2(uint32_t tok, uint32_t exl, uint32_t ost, int eh, int lane, const uint32_t (&q)[8][4], uint32_t (&sp)[5][2], uint32_t (&pa)[5][2], uint32_t (&bv)[8][4], uint32_t rng, bool vb,
                                          F&& wait_v, G&& duty, H&& pace, I&& wait_x) {
    constexpr int NK = MT ? 5 : 3;
    const int mi = lane >> 3, r8 = lane & 7;
    {
        float c[4][4];
        uint32_t b[4][4];
        ldsm16_t(b, exl + 2048);
        duty();
        #pragma unroll
        for (int j = 0; j < 4; j++) { c[j][0] = c[j][1] = c[j][2] = c[j][3] = 0.f; }
        #pragma unroll
        for (int k2 = 0; k2 < 4; k2++) { mma16816(c[(2 * k2) & 3], q[2 * k2], b[k2][0], b[k2][1]); mma16816(c[(2 * k2 + 1) & 3], q[2 * k2 + 1], b[k2][2], b[k2][3]); }
        sp[0][0] = scale_bf2(pack_bf16((c[0][0] + c[1][0]) + (c[2][0] + c[3][0]), (c[0][1] + c[1][1]) + (c[2][1] + c[3][1])));
        sp[0][1] = scale_bf2(pack_bf16((c[0][2] + c[1][2]) + (c[2][2] + c[3][2]), (c[0][3] + c[1][3]) + (c[2][3] + c[3][3])));
    }
    pa[0][0] = exp_bf2(sp[0][0]); pa[0][1] = exp_bf2(sp[0][1]);
    rng = maxabs_bf2(maxabs_bf2(rng, sp[0][0]), sp[0][1]);
    if (__builtin_expect(__any_sync(0xffffffffu, ((rng & 0x7fff7fffu) + 0x3ddf3ddfu) & 0x80008000u), 0)) {
        uint32_t m0 = sp[0][0], m1 = sp[0][1];
        #pragma unroll
        for (int nt = 1; nt < NK; nt++) { if (nt < NK - 1) m0 = max_bf2(m0, sp[nt][0]); m1 = max_bf2(m1, sp[nt][1]); }
        uint32_t mm = max_bf2(__byte_perm(m0, m1, 0x5410), __byte_perm(m0, m1, 0x7632));
        mm = max_bf2(mm, __shfl_xor_sync(0xffffffffu, mm, 1));
        mm = max_bf2(mm, __shfl_xor_sync(0xffffffffu, mm, 2));
        #pragma unroll
        for (int nt = 0; nt < NK; nt++) {
            if (nt < NK - 1) pa[nt][0] = pack_bf16(exd(bf_lo(sp[nt][0]), bf_lo(mm)), exd(bf_hi(sp[nt][0]), bf_lo(mm)));
            pa[nt][1] = pack_bf16(exd(bf_lo(sp[nt][1]), bf_hi(mm)), exd(bf_hi(sp[nt][1]), bf_hi(mm)));
        }
    }
    tok_loadv<MT, MT ? T_VPRE : 8, 8>(tok, eh, lane, bv);
    wait_v();
    constexpr int NQ = MT ? 2 : 4;
    float o[NQ][4][4], l[4] = {0.f, 0.f, 0.f, 0.f};
    const uint32_t ONE = 0x3F803F80u;
    mma16816r(l, pa[1][0], pa[1][1], pa[2][0], pa[2][1], ONE, ONE);
    if (MT) mma16816r(l, pa[3 % NK][0], pa[3 % NK][1], pa[4 % NK][0], pa[4 % NK][1], ONE, ONE);
    mma1688(l, pa[0][0], pa[0][1], ONE);
    #pragma unroll
    for (int j = 0; j < NQ; j++) {
        uint32_t bm[4];
        ldsm_x4(bm, exl + 4096 + (MT ? eh * 1024 : 0) + 512 * j);
        #pragma unroll
        for (int n = 0; n < 4; n++) {
            o[j][n][0] = o[j][n][1] = o[j][n][2] = o[j][n][3] = 0.f;
            if (MT) mma16816r(o[j][n], pa[1][0], pa[1][1], pa[2][0], pa[2][1], bv[4 * j + n][0], bv[4 * j + n][1]);
            else mma16816r(o[j][n], pa[1][0], pa[1][1], pa[2][0], pa[2][1], bv[2 * j + (n >> 1)][2 * (n & 1)], bv[2 * j + (n >> 1)][2 * (n & 1) + 1]);
        }
        if (MT) {
            #pragma unroll
            for (int n = 0; n < 4; n++) mma16816r(o[j][n], pa[3 % NK][0], pa[3 % NK][1], pa[4 % NK][0], pa[4 % NK][1], bv[4 * j + n][2], bv[4 * j + n][3]);
        }
        #pragma unroll
        for (int n = 0; n < 4; n++) mma1688(o[j][n], pa[0][0], pa[0][1], bm[n]);
    }
    #pragma unroll
    for (int j = 0; j < NQ; j++) asm volatile("" : "+f"(o[j][0][0]), "+f"(o[j][1][0]), "+f"(o[j][2][0]), "+f"(o[j][3][0]));
    asm volatile("" : "+f"(l[0]), "+f"(l[2]));
    wait_x();
    bar_arrive_p(12, 384, !vb);
    pace();
    const float i0 = rcp_approx(l[0]), i1 = rcp_approx(l[2]);
    const uint32_t oa = ost + ((mi & 1) * 8 + r8) * 128 + (((mi >> 1) ^ r8) << 4);
    #pragma unroll
    for (int j = 0; j < NQ; j++) {
        stsm_x4((oa ^ ((j & 1) << 6)) + (j >> 1) * 4096, pack_bf16(o[j][0][0] * i0, o[j][0][1] * i0), pack_bf16(o[j][0][2] * i1, o[j][0][3] * i1), pack_bf16(o[j][1][0] * i0, o[j][1][1] * i0), pack_bf16(o[j][1][2] * i1, o[j][1][3] * i1));
        stsm_x4((oa ^ (((j & 1) << 6) | 32)) + (j >> 1) * 4096, pack_bf16(o[j][2][0] * i0, o[j][2][1] * i0), pack_bf16(o[j][2][2] * i1, o[j][2][3] * i1), pack_bf16(o[j][3][0] * i0, o[j][3][1] * i0), pack_bf16(o[j][3][2] * i1, o[j][3][3] * i1));
    }
}

template<int OA>
__device__ __forceinline__ uint32_t send_main(float c0, float c1, float c2, float c3, uint32_t a, uint32_t l16) {
    uint32_t w2;
    asm volatile("{\n.reg .pred q, pl, ph;\n.reg .b64 pa;\n.reg .b32 t, w0, w1;\n.reg .f32 x, y, z;\n"
                 "and.b32 t, %7, 0x30;\nsetp.eq.u32 q, t, 0;\nand.b32 t, %7, 0x70;\nsetp.eq.u32 ph, t, 0;\nxor.pred pl, q, ph;\n"
                 "selp.f32 x, 0f00010000, %4, pl;\nselp.f32 y, 0f00010000, %6, ph;\nselp.f32 z, %6, %4, ph;\n"
                 "cvt.rn.bf16x2.f32 w0, x, %3;\ncvt.rn.bf16x2.f32 w1, y, %5;\ncvt.rn.bf16x2.f32 %0, 0f00010000, z;\n"
                 "mov.b64 pa, {%1, %2};\n"
                 "red.relaxed.gpu.global.add.noftz.bf16x2 [pa+%8], w0;\nred.relaxed.gpu.global.add.noftz.bf16x2 [pa+%9], w1;\n}\n"
        : "=r"(w2) : "r"(a), "r"((uint32_t)((uint64_t)g_acc >> 32)), "f"(c0), "f"(c1), "f"(c2), "f"(c3), "r"(l16), "n"(OA), "n"(OA + 256) : "memory");
    return w2;
}
template<int OB>
__device__ __forceinline__ void send_extra(uint32_t w2, uint32_t b, uint32_t l16) {
    asm volatile("{\n.reg .pred q;\n.reg .b64 pb;\n.reg .b32 t;\nand.b32 t, %3, 0x30;\nsetp.eq.u32 q, t, 0;\nmov.b64 pb, {%0, %1};\n"
                 "@q red.relaxed.gpu.global.add.noftz.bf16x2 [pb+%4], %2;\n}\n"
        :: "r"(b), "r"((uint32_t)((uint64_t)g_acc >> 32)), "r"(w2), "r"(l16), "n"(OB) : "memory");
}
#define X_AT 0
__device__ __forceinline__ uint32_t send_ua(uint32_t tile) { return (uint32_t)(uint64_t)g_acc + tile * 1024; }
__device__ __forceinline__ uint32_t send_ub(uint32_t tile) { return (uint32_t)(uint64_t)g_acc + ACC_X + (tile >> 1) * 1024 + (tile & 1) * 256; }
__device__ __forceinline__ void lds_il(float& il, float& ih, uint32_t a) {
    uint32_t x, y; asm volatile("ldmatrix.sync.aligned.m8n8.x2.shared.b16 {%0,%1}, [%2];" : "=r"(x), "=r"(y) : "r"(a) : "memory");
    il = __uint_as_float(x); ih = __uint_as_float(y);
}
template<bool AUX>
__device__ __forceinline__ uint32_t stage_w(const uint32_t (&wo)[8][4], uint32_t ol, uint32_t tile, uint32_t so, uint32_t l16, uint32_t nv, uint32_t ila, uint32_t& sx) {
    float il, ih;
    uint32_t b[4][4], sa;
    float c[2][4];
    auto addr = [&] {
        const uint32_t ll = AUX ? l16 : l16 | (__float_as_uint(c[0][0]) & nv);
        sa = (ll >> 2) + (send_ua(tile) + so); sx = (ll >> 4) + (send_ub(tile) + so);
    };
    ldsm16_t(b, ol);
    lds_il(il, ih, ila);
    if (AUX) addr(); else sched_fence<0>(nv);
    #pragma unroll
    for (int i = 0; i < 2; i++) c[i][0] = c[i][1] = c[i][2] = c[i][3] = 0.f;
    #pragma unroll
    for (int j = 0; j < 4; j++) {
        if (!AUX && j == 3) addr();
        mma16816(c[0], wo[2 * j], b[j][0], b[j][1]); mma16816(c[1], wo[2 * j + 1], b[j][2], b[j][3]);
    }
    if (AUX) { asm volatile("" : "+f"(c[0][0]), "+f"(c[1][0])); sched_fence<4>(nv); bar_arrive(12, 384); }
    return send_main<0>((c[0][0] + c[1][0]) * il, (c[0][1] + c[1][1]) * ih, (c[0][2] + c[1][2]) * il, (c[0][3] + c[1][3]) * ih, sa, l16);
}
__device__ __forceinline__ void wgmma_n16(float (&d)[8], const uint32_t (&a)[4], uint64_t desc) {
    asm volatile("{\n.reg .pred p;\nsetp.ne.b32 p, 1, 0;\n"
        "wgmma.mma_async.sync.aligned.m64n16k16.f32.bf16.bf16 {%0,%1,%2,%3,%4,%5,%6,%7}, {%8,%9,%10,%11}, %12, p, 1, 1, 0;\n}\n"
        : "+f"(d[0]), "+f"(d[1]), "+f"(d[2]), "+f"(d[3]), "+f"(d[4]), "+f"(d[5]), "+f"(d[6]), "+f"(d[7])
        : "r"(a[0]), "r"(a[1]), "r"(a[2]), "r"(a[3]), "l"(desc));
}

template<int N> __device__ __forceinline__ void code_pad(uint32_t nv) {
    if (N && nv == 0x7fffffe0u + N % 16) {
        float v = __uint_as_float(nv);
        #pragma unroll
        for (int i = 0; i < N; i++) asm volatile("fma.rn.f32 %0, %0, %0, %0;" : "+f"(v));
        sts32_p(0u, __float_as_uint(v), nv);
    }
}
#define PAD_T0 0
#define PAD_T1 0
#define PAD_S 0
#define PAD_P 0
#define BAR_PRO 1
#define BAR_MEM 2
#define BAR_P   3
#define BAR_PRJ 4
#define BAR_VGO 7
#define BAR_X0  7
#define BAR_S   9
#define BAR_P2  10
#define BAR_O   11
#define BAR_V   12
#define VGO_AT 9
#define TP_N 36
#define REG_P 200
#define WO_PRE 3
#define WO_REP 2
#define X_FIRST 0
#ifndef M_RES
#define M_RES 5
#endif
#ifndef M_LAG
#define M_LAG 2
#endif
#ifndef M_ARR
#define M_ARR -1
#endif
#define G1_0 256
#define G1_NS 1152

__global__ void __cluster_dims__(3, 1, 1) __launch_bounds__(CH_THREADS, 1)
chain_kernel(const __grid_constant__ CUtensorMap tmx, const __grid_constant__ CUtensorMap tmq, const __grid_constant__ CUtensorMap tmk,
             const __grid_constant__ CUtensorMap tmv, const __grid_constant__ CUtensorMap tmo,
             const __grid_constant__ CUtensorMap tma, const __grid_constant__ CUtensorMap tmb, const bf16* __restrict__ mem0, const uint32_t nv_) {
    extern __shared__ __align__(1024) unsigned char smem[];
    const uint32_t sb = smem_u32(smem);
    const int tid = threadIdx.x, lane = tid & 31;
    const int warp = __shfl_sync(0xffffffffu, tid >> 5, 0);
    const uint32_t nv = __shfl_sync(0xffffffffu, nv_ * tid, 0);
    const int h = blockIdx.x / 3, r = blockIdx.x % 3;
    const int mi = lane >> 3, r8 = lane & 7;
    const uint32_t bX = sb + SM_BAR, bTOK = bX + 16, bEX = bX + 40, bW = bX + 64, bEV = bX + 104, bFREE = bX + 32, bMEM = bX + 56, bWA = bX + 120;
    const int nqk = r < 2 ? 6 : 4;
    if (lane == 0 && warp < 7) asm volatile("prefetch.param.tensormap [%0];" :: "l"(__cvta_generic_to_grid_constant(&tmx) + 128 * warp) : "memory");
    if ((sb & 0xFFFFFFu) != SB_OFF) __trap();
    asm volatile("griddepcontrol.launch_dependents;");
    if (tid == 0 && blockIdx.x == 0) GT(40, 0);
    if (tid == 0) PT(0);

    #define W_STG(g, j) ((g) == 2 && (j) == 3 ? SM_EX : SM_TOK + ((g) % 3) * 36864 + (j) * 9216)
    auto load_w = [&](int g) {
        #pragma unroll
        for (int j = 0; j < 4; j++) {
            const int m = r < 2 ? (j < 3 ? r : 2) : (j < 2 ? j : 2), p = r < 2 ? (j < 3 ? j : r) : (j < 2 ? 3 : j);
            asm volatile("cp.async.bulk.tensor.2d.shared::cluster.global.mbarrier::complete_tx::bytes [%0], [%1, {%3, %4}], [%2];"
                :: "r"(sb + W_STG(g, j)), "l"(m == 0 ? &tmq : (m == 1 ? &tmk : &tmv)), "r"(bW + 8 * g), "r"(h * DH + p * 32), "r"(g * 144) : "memory");
        }
    };
    auto load_wo = [&](int lo, int hi, uint32_t bar) {
        #pragma unroll
        for (int i = lo; i < hi; i++)
            asm volatile("cp.async.bulk.tensor.2d.shared::cluster.global.mbarrier::complete_tx::bytes [%0], [%1, {%3, %4}], [%2];"
                :: "r"(sb + SM_WO + i * 8192), "l"(&tmo), "r"(bar), "r"(192 * r + 32 * i), "r"(h * DH) : "memory");
    };
    if (warp == 11) {
        if (lane == 0) {
            #pragma unroll
            for (int g = 0; g < 3; g++) mbar_init(bW + 8 * g, 1);
            mbar_init(bX, 1); mbar_init(bX + 8, 1);
            asm volatile("fence.mbarrier_init.release.cluster;" ::: "memory");
        }
        __syncwarp();
        bar_arrive(0, 384);
        if (lane == 0) {
            #pragma unroll 1
            for (int g = 0; g < 3; g++) {
                PT(1 + g);
                mbar_expect_tx(bW + 8 * g, 36864);
                if (X_FIRST == 0) load_w(g);
                if (g < 2) {
                    mbar_expect_tx(bX + 8 * g, XBUF);
                    #pragma unroll
                    for (int c = 0; c < 3; c++)
                        asm volatile("cp.async.bulk.tensor.3d.shared::cluster.global.mbarrier::complete_tx::bytes [%0], [%1, {%3, %4, %5}], [%2];"
                            :: "r"(sb + SM_X + g * XBUF + c * 12288), "l"(&tmx), "r"(bX + 8 * g), "r"(0), "r"(g * SEG), "r"(3 * c) : "memory");
                }
                if (X_FIRST) load_w(g);
            }
            PT(4);
        }
        __syncwarp();
    }
    const uint32_t zs = 3 * blockIdx.x + (r8 >> 1);
    const uint32_t zoff = (r8 < 6 ? (zs >> 3) * 1024 + ((zs >> 2) & 1) * 256 + (zs & 3) * 32 : ACC_X + (blockIdx.x >> 1) * 1024 + (blockIdx.x & 1) * 256) + (lane & 1) * 16;
    const uint32_t zskip = r8 >= 6 && blockIdx.x >= 36;
    if (warp == 9) {
        bar_arrive(0, 384);
        const unsigned ep = ld_relaxed32(&g_epoch);
        unsigned long long o0 = 0, o1 = 0;
        if (!zskip) {
            asm volatile("atom.relaxed.gpu.global.exch.b64 %0, [%1], 0;" : "=l"(o0) : "l"(g_acc + zoff + SLOT_OFF(mi)) : "memory");
            asm volatile("atom.relaxed.gpu.global.exch.b64 %0, [%1], 0;" : "=l"(o1) : "l"(g_acc + zoff + SLOT_OFF(mi) + 8) : "memory");
        }
        const uint32_t done = __reduce_or_sync(0xffffffffu, (uint32_t)(o0 | o1) & nv);
        if (lane == 0) asm volatile("st.relaxed.gpu.global.u32 [%0], %1;" :: "l"(&g_init[blockIdx.x]), "r"(ep + done) : "memory");
    }
    if (tid == 320) {
        #pragma unroll
        for (int i = 2; i < 16; i++) if (i < 8 || i > 10) mbar_init(bX + 8 * i, (i == 5 || i == 6) ? 1 + nqk : (i == 13 || i == 14 ? 9 - nqk : 1));
        asm volatile("fence.mbarrier_init.release.cluster;" ::: "memory");
        mbar_expect_tx(bW + 24, 36864); mbar_expect_tx(bW + 32, 32768); mbar_expect_tx(bWA, 16384);
        sts32(sb + SM_TG, 0u);
    }
    if (warp != 11 && warp != 9) bar_sync(0, 384);
    const uint32_t pw0 = ((mi >> 1) * 8 + r8) * 64 + (((2 * (warp & 1) + (mi & 1)) ^ (r8 >> 1)) << 4);
    auto tok_publish = [&](int tb, int k) {
        const uint32_t src = sb + SM_TOK + tb * TOKBUF + r * 8192, bar = bTOK + 8 * tb;
        if (k == 1) asm volatile("{\n.reg .pred p;\nelect.sync _|p, 0xffffffff;\n@p mbarrier.arrive.expect_tx.shared.b64 _, [%0], 16384;\n}\n" :: "r"(bar) : "memory");
        asm volatile("{\n.reg .pred p;\nelect.sync _|p, 0xffffffff;\n"
                     "@p cp.async.bulk.shared::cluster.shared::cta.mbarrier::complete_tx::bytes [%0], [%1], 8192, [%2];\n}\n"
            :: "r"(mapa_u32(src, (r + k) % 3)), "r"(src), "r"(mapa_u32(bar, (r + k) % 3)) : "memory");
    };
    if (warp < 8) {
        asm volatile("setmaxnreg.inc.sync.aligned.u32 %0;" :: "n"(REG_P));
        uint32_t wf[36][4];
        float ta0[16], ta1[16];
        auto group = [&](auto gg) {
            constexpr int g = gg.value;
            const uint32_t wl = sb + pw0 + W_STG(g, warp >> 1);
            mbar_wait(bW + 8 * g, 0);
            if (tid == 0) PT(5 + g);
            if (g) wg_wait0();
            if (g == 1) sts128(sb + SM_PARK + tid * 16, make_uint4(wf[0][0], wf[0][1], wf[0][2], wf[0][3]));
            #pragma unroll
            for (int i = 0; i < 9; i++) ldsm_x4_t(wf[9 * g + i], wl + i * 1024);
            if (g != 1) fence_async_smem();
            if (g == 0) { bar_arrive(BAR_X0, 288); mbar_wait(bX, 0); mbar_wait(bX + 8, 0); if (tid == 0) PT(9); }
            if (g == 2) bar_arrive(BAR_X0 + 1, 288);
            if (g == 3) cluster_arrive_rx();
            wg_fence();
            #pragma unroll
            for (int i = 9 * g; i < 9 * g + 9; i++) {
                if (i == 0) wgmma_n32<0>(ta0, wf[0], desc_from(DESC_LO(SM_X))); else wgmma_n32<1>(ta0, wf[i], desc_from(DESC_LO(SM_X) + (i >> 2) * 256 + (i & 3) * 2));
            }
            if (g == 3) wg_commit();
            #pragma unroll
            for (int i = 9 * g; i < 9 * g + 9; i++) {
                if (i == 0) wgmma_n32<0>(ta1, wf[0], desc_from(DESC_LO(SM_X + XBUF))); else wgmma_n32<1>(ta1, wf[i], desc_from(DESC_LO(SM_X + XBUF) + (i >> 2) * 256 + (i & 3) * 2));
            }
            wg_commit();
        };
        if (tid == 0) PT(10);
        code_pad<PAD_P>(nv);
        group(ic<0>()); group(ic<1>()); group(ic<2>()); group(ic<3>());
        if (tid == 0) PT(11);
        const uint32_t pw = pin(pw0);
        auto tp_store = [&](const float (&acc)[16], uint32_t off) {
            const uint32_t ta = pw + launder(sb + off + (warp >> 1) * 2048);
            stsm_x4_t(ta, pack_bf16(acc[0], acc[1]), pack_bf16(acc[2], acc[3]), pack_bf16(acc[4], acc[5]), pack_bf16(acc[6], acc[7]));
            stsm_x4_t(ta + 1024, pack_bf16(acc[8], acc[9]), pack_bf16(acc[10], acc[11]), pack_bf16(acc[12], acc[13]), pack_bf16(acc[14], acc[15]));
        };
        cluster_wait();
        wg_wait0();
        tp_store(ta0, SM_TOK + r * 8192);
        if (warp == 0) { bar_sync(BAR_PRJ, 256); fence_async_smem(); tok_publish(0, 1); tok_publish(0, 2); } else bar_arrive(BAR_PRJ, 256);
        tp_store(ta1, SM_TOK + TOKBUF + r * 8192);
        { const uint4 v = lds128(sb + SM_PARK + tid * 16); wf[0][0] = v.x; wf[0][1] = v.y; wf[0][2] = v.z; wf[0][3] = v.w; sts32_p(v.x, v.y, nv); }
        if (tid == 0) PT(12);
        const uint32_t l16 = pin(lane * 16), sbl = sb + l16, l4w = pin(sb + warp * 256 + lane * 4);
        uint32_t wo[8][4];
        const int exo = r < 2 ? (warp < 6 ? r * 2048 : 4096 + (2 * r - 6) * 256) : (warp < 2 ? 6 * 256 : (warp < 4 ? 2048 + 4 * 256 : 4096));
        const bool isqk = warp < nqk;
        const uint32_t exbar = isqk ? bEX : bEV;
        uint32_t vf[2][4];
        auto prep = [&](int s) {
            const uint32_t va = pw + launder(sb + SM_TOK + (s & 1) * TOKBUF + BLK_V(warp >> 1));
            mbar_wait(bTOK + 8 * (s & 1), (s >> 1) & 1);
            ldsm_x4_t(vf[0], va); ldsm_x4_t(vf[1], va + 1024);
            sts32_p(vf[0][0], vf[1][0], nv);
        };
        prep(0);
        if (tid == 0) PT(13);
        bar_sync(BAR_MEM, 352);
        for (int s = 0; ; s++) {
            const int par = s & 1;
            const uint32_t wa = pw + launder(sb + SM_WO + (warp >> 1) * 8192);
            const uint32_t exu = launder(SM_EX + par * EXBUF);
            {
                float acc[4][4];
                #pragma unroll
                for (int i = 0; i < 4; i++) { acc[i][0] = acc[i][1] = acc[i][2] = acc[i][3] = 0.f; }
                bar_sync_p(BAR_VGO, 256, isqk);
                #pragma unroll
                for (int i2 = 0; i2 < 18; i2++) {
                    uint32_t b[4];
                    ldsm_x4_t(b, sbl + SM_MEM + i2 * 512);
                    if (i2 == VGO_AT) bar_arrive_p(BAR_VGO, 256, !isqk);
                    mma16816(acc[(2 * i2) & 3], wf[2 * i2], b[0], b[1]);
                    mma16816(acc[(2 * i2 + 1) & 3], wf[2 * i2 + 1], b[2], b[3]);
                }
                float q[4];
                #pragma unroll
                for (int i = 0; i < 4; i++) q[i] = (acc[0][i] + acc[1][i]) + (acc[2][i] + acc[3][i]);
                const uint32_t lo = pack_bf16(q[0], q[1]), hi = pack_bf16(q[2], q[3]);
                const uint32_t exl = l4w + launder(exu + exo), bar = exbar + par * 8;
                #pragma unroll
                for (int k = 1; k < 3; k++) {
                    const uint32_t exd = mapa_u32(exl, (r + k) % 3), exb = mapa_u32(bar, (r + k) % 3);
                    st_async32(exd, lo, exb); st_async32(exd + 128, hi, exb);
                }
                sts32(exl, lo); sts32(exl + 128, hi);
                __syncwarp();
                asm volatile("{\n.reg .pred p;\nelect.sync _|p, 0xffffffff;\n@p mbarrier.arrive.shared.b64 _, [%0];\n}\n" :: "r"(bar) : "memory");
                if (s < NSEG - 1) bar_sync_p(BAR_PRO, 32 * nqk, !isqk);
            }
            if (__builtin_expect(s == NSEG - 1, 0)) break;
            if (__builtin_expect(s == 0, 0)) mbar_wait(bW + 32, 0);
            #pragma unroll
            for (int i = 0; i < WO_PRE; i++) ldsm_x4_t(wo[i], wa + i * 1024);
            #pragma unroll
            for (int k = 0; k < WO_REP; k++) mbar_wait(bEX + 8 * par, (s >> 1) & 1);
            #pragma unroll
            for (int i = WO_PRE; i < 8; i++) ldsm_x4_t(wo[i], wa + i * 1024);
            mbar_wait(bEV + 8 * par, (s >> 1) & 1);
            const uint32_t vm0 = lds32(l4w + exu + 4096), vm1 = lds32(l4w + exu + 4096 + 128);
            const uint32_t big = bar_red_or(BAR_P, 352, 0u);
            uint32_t pb[4]; ldsm_x4_t(pb, sbl + SM_P);
            uint32_t pm = ldsm_x1_t(sbl + SM_P + 512);
            float o0[4] = {0.f, 0.f, 0.f, 0.f}, o1[4] = {0.f, 0.f, 0.f, 0.f}, o2[4] = {0.f, 0.f, 0.f, 0.f};
            if (__builtin_expect(big, 0)) {
                bar_sync(BAR_P2, 352);
                ldsm_x4_t(pb, sbl + SM_P); pm = ldsm_x1_t(sbl + SM_P + 512);
            }
            mma16816(o0, vf[0], pb[0], pb[1]);
            mma16816(o1, vf[1], pb[2], pb[3]);
            mma1688(o2, vm0, vm1, pm);
            uint32_t oa = pm;
            #pragma unroll
            for (int i = 0; i < 8; i++) oa ^= wo[i][0];
            oa = l4w | (oa & nv);
            sts32(oa + SM_O, pack_bf16((o0[0] + o1[0]) + o2[0], (o0[1] + o1[1]) + o2[1]));
            sts32(oa + SM_O + 128, pack_bf16((o0[2] + o1[2]) + o2[2], (o0[3] + o1[3]) + o2[3]));
            const uint32_t xd = uni(DESC_LO(SM_X) + par * (XBUF >> 4));
            bar_sync(BAR_O, 352);
            uint32_t sx;
            const uint32_t w2 = stage_w<false>(wo, sbl + SM_O, 12 * r + warp, SLOT_OFF(s + 1), l16, nv, sbl + SM_IL, sx);
            if (X_AT == 0) send_extra<0>(w2, sx, l16);
            STAMP(warp);
            bar_sync(BAR_V, 384);
            wg_fence();
            STAMP(12);
            #pragma unroll
            for (int i = 0; i < TP_N; i++) {
                if (X_AT && i == X_AT) send_extra<0>(w2, sx, l16);
                if (i == 0) wgmma_n32<0>(ta1, wf[0], desc_from(xd));
                else wgmma_n32<1>(ta1, wf[i], desc_from(xd + (i >> 2) * 256 + (i & 3) * 2));
            }
            wg_commit();
            prep(s + 1);
            wg_wait0();
            tp_store(ta1, SM_TOK + par * TOKBUF + r * 8192);
            STAMP(13 + (warp >> 2));
            bar_sync(BAR_MEM, 352);
        }
        {
            const uint32_t tag = ld_relaxed32(&g_init[blockIdx.x]) & 1u, lq = l16 | (tag & nv), pq = pw | (tag & nv);
            uint4* d0 = &g_last[12 * r + warp][0][h][lq >> 4];
            uint4* d1 = &g_last[12 * r + 8 + (warp & 3)][warp >> 2][h][lq >> 4];
            st_relaxed128(d0, make_uint4(tag ^ 1, 0, 0, 0)); st_relaxed128(d0 + 1024, make_uint4(tag ^ 1, 0, 0, 0)); st_relaxed128(d1, make_uint4(tag ^ 1, 0, 0, 0));
            uint32_t wx[8][4];
            #pragma unroll
            for (int i = 0; i < 8; i++) { ldsm_x4_t(wo[i], pq + sb + SM_WO + (warp >> 1) * 8192 + i * 1024); ldsm_x4_t(wx[i], pq + sb + SM_WO + (4 + ((warp >> 1) & 1)) * 8192 + i * 1024); }
            float c2[8];
            #pragma unroll
            for (int i = 0; i < 8; i++) c2[i] = 0.f;
            const uint32_t od = uni(DESC_LO(SM_OST) + (warp >> 2) * 128);
            mbar_wait(bMEM, 1);
            wg_fence();
            #pragma unroll
            for (int i = 0; i < 8; i++) {
                if (i == 0) wgmma_n32<0>(ta1, wo[0], desc_from(DESC_LO(SM_OST)));
                else wgmma_n32<1>(ta1, wo[i], desc_from(DESC_LO(SM_OST) + (i >> 2) * 256 + (i & 3) * 2));
            }
            wg_commit();
            #pragma unroll
            for (int i = 0; i < 8; i++) wgmma_n16(c2, wx[i], desc_from(od + (i >> 2) * 256 + (i & 3) * 2));
            wg_commit();
            auto put = [&](uint4* d, const float* c) { st_relaxed128(d, make_uint4((pack_bf16(c[0], c[1]) & ~1u) | tag, pack_bf16(c[2], c[3]), pack_bf16(c[4], c[5]), pack_bf16(c[6], c[7]))); };
            asm volatile("wgmma.wait_group.sync.aligned 1;" ::: "memory");
            #pragma unroll
            for (int i = 0; i < 16; i++) asm volatile("" : "+f"(ta1[i]) :: "memory");
            put(d0, ta1); put(d0 + 1024, ta1 + 8);
            wg_wait0();
            #pragma unroll
            for (int i = 0; i < 8; i++) asm volatile("" : "+f"(c2[i]) :: "memory");
            put(d1, c2);
            if (tid == 0 && blockIdx.x == 0) GT(40, NSEG);
        }
        cluster_arrive(); cluster_wait();
    } else {
        asm volatile("setmaxnreg.dec.sync.aligned.u32 %0;" :: "n"(504 - 2 * REG_P));
        const int a = warp - 8;
        const unsigned epoch = ld_relaxed32(&g_epoch);
        const uint32_t sbl = sb + lane * 16;
        if (a < 3) {
            cluster_arrive_rx();
            {
                uint32_t v[3][8];
                #pragma unroll
                for (int k = 0; k < 3; k++)
                    #pragma unroll
                    for (int i = 0; i < 8; i++) v[k][i] = __ldg((const uint32_t*)mem0 + (tid - 256 + 96 * k) + i * (DM / 2));
                #pragma unroll
                for (int k = 0; k < 3; k++) {
                    const uint32_t d = sb + SM_MEM + (tid - 256 + 96 * k) * 32;
                    sts128(d, make_uint4(__byte_perm(v[k][0], v[k][1], 0x5410), __byte_perm(v[k][2], v[k][3], 0x5410), __byte_perm(v[k][4], v[k][5], 0x5410), __byte_perm(v[k][6], v[k][7], 0x5410)));
                    sts128(d + 16, make_uint4(__byte_perm(v[k][0], v[k][1], 0x7632), __byte_perm(v[k][2], v[k][3], 0x7632), __byte_perm(v[k][4], v[k][5], 0x7632), __byte_perm(v[k][6], v[k][7], 0x7632)));
                }
            }
            { int it = 0; while (__any_sync(0xffffffffu, ld_acquire32(&g_init[a * 32 + lane]) != epoch) && ++it < SPIN_LIMIT) {} }
            const uint32_t kl0 = (a < 2 ? SM_TOK + (16 * a + (mi & 1) * 8 + r8) * 64 + (((mi >> 1) ^ (r8 >> 1)) << 4) : SM_EX + 2048 + ((((mi & 1) << 1) | (mi >> 1)) * 8 + r8) * 16);
            const uint32_t l16 = pin(lane * 16);
            uint32_t kf[8][4], wo[8][4];
            auto load_k = [&](int tb, uint32_t kl) {
                const uint32_t ka = kl + launder(sb + tb * TOKBUF);
                #pragma unroll
                for (int kk = 0; kk < 8; kk++) ldsm_x4(kf[kk], (ka ^ ((kk & 1) << 5)) + BLK_K(kk >> 1));
            };
            code_pad<PAD_S>(nv);
            if (tid == 288) PT(14);
            cluster_wait();
            if (a == 0 && lane == 0) { mbar_expect_tx(bEX, 4096 - 256 * nqk); mbar_expect_tx(bEV, 256 * nqk); }
            if (a < 2) bar_arrive(BAR_MEM, 352); else bar_sync(BAR_MEM, 352);
            mbar_wait(bWA, 0);
            #pragma unroll
            for (int i = 0; i < 8; i++) ldsm_x4_t(wo[i], pw0 + sb + SM_WO + (warp >> 1) * 8192 + i * 1024);
            sts128(sbl + SM_STASH + a * 1024 + 512, make_uint4(kl0, (pw0 ^ 32) + sb + SM_WO + 5 * 8192, zoff | ((zskip || lane >= 8) << 31), 0u));
            sts128(sbl + SM_STASH + a * 1024, make_uint4(a * 12288 + (lane >> 4) * 1024 + (mi & 1) * 256 + r8 * 16, ACC_X + a * 6144 + (lane >> 4) * 1024 + (mi & 1) * 256 + r8 * 4,
                                                         ((lane ^ mi) & 1) ? 0u : ~0u, sb + SM_MEM + a * 3072 + mi * 256 + r8 * 16 + (r8 & 1 ? 2 : 130)));
            const uint32_t stash = l16 + uni(sb + SM_STASH + a * 1024);
            #pragma unroll
            for (int i = 0; i < 8; i++) ldsm_x4_t(kf[i], (pw0 ^ 32) + sb + SM_WO + 5 * 8192 + i * 1024);
            if (a < 2) { mbar_wait(bTOK, 0); load_k(0, kl0); }
            __syncwarp();
            int sn = 0;
            #pragma unroll 1
            while (sn < NSEG - 1) {
              uint32_t bad;
              #pragma unroll 1
              do {
                const int s = sn, par = s & 1;
                const uint32_t exu = launder(sb + par * EXBUF);
                const uint32_t exl = l16 + exu + SM_EX;
                const uint32_t t0 = gtime_lo();
                STAMP(15); STAMPV(31, t0);
                if (a == 2) st_relaxed32_p(&g_ts[blockIdx.x], (t0 & ~31u) | (s & 31), l16);
                if (a == 1) {
                    const uint32_t z = lds32(stash + 520);
                    st_relaxed128_p((uint4*)(g_acc + (z + SLOT_OFF(s + 3))), make_uint4(0, 0, 0, 0), z >> 31);
                }
                if (a == 0 && l16 == 0) { mbar_expect_tx(bEX + 8 * (par ^ 1), 4096 - 256 * nqk); mbar_expect_tx(bEV + 8 * (par ^ 1), 256 * nqk); }
                auto first_half = [&](auto role) {
                constexpr bool M = role.value;
                uint32_t sl, sh, kl = 0;
                if (M) {
                    fence_async_smem();
                    if (l16 == 0) {
                        asm volatile("cp.async.bulk.global.shared::cta.bulk_group [%0], [%1], 8192;\ncp.async.bulk.commit_group;"
                            :: "l"(g_tokx[blockIdx.x]), "r"(sb + SM_TOK + (par ^ 1) * TOKBUF + r * 8192) : "memory");
                        mbar_expect_tx(bTOK + 8 * (par ^ 1), 16384); mbar_expect_tx(bMEM, 10368);
                        if (s == 0) mbar_expect_tx(bX, XBUF);
                        if (s + 3 < NSEG) mbar_expect_tx(bX + 8 * (par ^ 1), XBUF);
                    }
                    __syncwarp();
                    if (s > 0 && s + 2 < NSEG) mbar_wait(bX + 8 * par, ((s >> 1) & 1) ^ 1);
                    asm volatile("cp.async.bulk.wait_group 0;" ::: "memory");
                    kl = lds32(stash + 512);
                }
                const uint32_t pst = (launder(l16) >> 2) + launder(sb + SM_P + a * 256);
                if (!M) {
                    uint32_t x = kf[0][0];
                    #pragma unroll
                    for (int i = 1; i < 8; i++) x ^= kf[i][0];
                    sts32_p(pst, x, nv);
                }
                mbar_wait(bEX + 8 * par, (s >> 1) & 1);
                float c[4][4];
                #pragma unroll
                for (int j = 0; j < 4; j++) { c[j][0] = c[j][1] = c[j][2] = c[j][3] = 0.f; }
                if (!M) {
                    uint32_t b[4][4];
                    ldsm16_t(b, exl);
                    #pragma unroll
                    for (int j = 0; j < 4; j++) { mma16816(c[(2 * j) & 3], kf[2 * j], b[j][0], b[j][1]); mma16816(c[(2 * j + 1) & 3], kf[2 * j + 1], b[j][2], b[j][3]); }
                    sl = scale_bf2(pack_bf16((c[0][0] + c[1][0]) + (c[2][0] + c[3][0]), (c[0][1] + c[1][1]) + (c[2][1] + c[3][1])));
                    sh = scale_bf2(pack_bf16((c[0][2] + c[1][2]) + (c[2][2] + c[3][2]), (c[0][3] + c[1][3]) + (c[2][3] + c[3][3])));
                } else {
                    uint32_t k[4][4], b[4][4];
                    #pragma unroll
                    for (int j = 0; j < 4; j++) { ldsm_x4_t(k[j], kl + exu + 512 * j); ldsm_x4_t(b[j], exl + 512 * j); }
                    #pragma unroll
                    for (int j = 0; j < 4; j++) { mma16816(c[2 * (j & 1)], k[j], b[j][0], b[j][1]); mma16816(c[2 * (j & 1) + 1], k[j], b[j][2], b[j][3]); }
                    asm volatile("{\n.reg .pred p;\nelect.sync _|p, 0xffffffff;\n"
                                 "@p cp.async.bulk.shared::cluster.global.mbarrier::complete_tx::bytes.multicast::cluster [%0], [%1], 8192, [%2], %3;\n}\n"
                        :: "r"(sb + SM_TOK + (par ^ 1) * TOKBUF + r * 8192), "l"(g_tokx[blockIdx.x]), "r"(bTOK + 8 * (par ^ 1)), "h"((unsigned short)(7 ^ (1 << r))) : "memory");
                    sh = sl = scale_bf2(pack_bf16((c[0][0] + c[1][2]) + (c[2][0] + c[3][2]), (c[0][1] + c[1][3]) + (c[2][1] + c[3][3])));
                }
                sts32(pst, exp_bf2(sl));
                if (!M) sts32(pst + 128, exp_bf2(sh));
                const uint32_t big = bar_red_or(BAR_P, 352, ((maxabs_bf2(sl, sh) & 0x7fff7fffu) + 0x3ddf3ddfu) & 0x80008000u);
                auto denom = [&] {
                    uint32_t pb[4]; ldsm_x4_t(pb, l16 + sb + SM_P);
                    const uint32_t pm = ldsm_x1_t(l16 + sb + SM_P + 512), ONE = 0x3F803F80u;
                    float l0[4] = {0.f, 0.f, 0.f, 0.f}, l1[4] = {0.f, 0.f, 0.f, 0.f}, l2[4] = {0.f, 0.f, 0.f, 0.f};
                    mma16816r(l0, ONE, ONE, ONE, ONE, pb[0], pb[1]);
                    mma16816r(l1, ONE, ONE, ONE, ONE, pb[2], pb[3]);
                    mma1688(l2, ONE, ONE, pm);
                    const float dl = (l0[0] + l1[0]) + l2[0], dh = (l0[1] + l1[1]) + l2[1];
                    sts32(pst + (SM_IL - SM_P) - a * 128, __float_as_uint(rcp_approx(a ? dh : dl)));
                };
                if (!M) { denom(); bar_sync_p(BAR_O, 352, big); }
                if (__builtin_expect(big, 0)) {
                    uint32_t m2 = max_bf2(sl, sh);
                    m2 = max_bf2(m2, __shfl_xor_sync(0xffffffffu, m2, 4));
                    m2 = max_bf2(m2, __shfl_xor_sync(0xffffffffu, m2, 8));
                    m2 = max_bf2(m2, __shfl_xor_sync(0xffffffffu, m2, 16));
                    const uint32_t lq = l16 | (m2 & nv);
                    if (lq < 64) sts32(lq + sb + SM_P + 768 + a * 4, m2);
                    bar_sync(BAR_S, 96);
                    const uint4 m = lds128(sb + SM_P + 768 + (lq & 0x30));
                    m2 = max_bf2(max_bf2(m.x, m.y), m.z);
                    const float ml = bf_lo(m2), mh = bf_hi(m2);
                    sts32(pst, pack_bf16(exd(bf_lo(sl), ml), exd(bf_hi(sl), mh)));
                    if (!M) sts32(pst + 128, pack_bf16(exd(bf_lo(sh), ml), exd(bf_hi(sh), mh)));
                    bar_sync(BAR_P2, 352);
                    if (!M) { denom(); bar_sync(BAR_O, 352); }
                }
                const uint32_t ll = launder(l16), so = SLOT_OFF(launder(s) + 1);
                if (!M) { uint32_t sx; const uint32_t w2 = stage_w<true>(wo, l16 + sb + SM_O, 12 * r + warp, so, ll, nv, l16 + sb + SM_IL, sx); send_extra<0>(w2, sx, ll); }
                else {
                    const uint32_t w2 = lds32(stash + 516);
                    #pragma unroll
                    for (int i = M_RES; i < 8; i++) ldsm_x4_t(kf[i], w2 + i * 1024);
                    const uint32_t sa = launder((ll >> 2) + (send_ua(12 * r + 10) + so)), sx = launder((ll >> 4) + (send_ub(12 * r + 10) + so));
                    bar_sync_p(BAR_O, 352, (kf[5][0] ^ kf[6][0] ^ kf[7][0] ^ sa ^ sx) & nv);
                    #pragma unroll
                    for (int k = 0; k < M_LAG; k++) mbar_wait(bEX + 8 * par, (s >> 1) & 1);
                    float il, ih;
                    #pragma unroll
                    for (int i = 0; i < 4; i++) c[i][0] = c[i][1] = c[i][2] = c[i][3] = 0.f;
                    uint32_t b[4][4];
                    #pragma unroll
                    for (int j = 0; j < 4; j++) ldsm_x4_t(b[j], l16 + sb + SM_O + 512 * (3 - j));
                    lds_il(il, ih, l16 + sb + SM_IL);
                    sched_fence<11>(nv);
                    #pragma unroll
                    for (int j = 0; j < 4; j++) {
                        mma16816(c[0], wo[6 - 2 * j], b[j][0], b[j][1]); mma16816(c[2], kf[6 - 2 * j], b[j][0], b[j][1]);
                        mma16816(c[1], wo[7 - 2 * j], b[j][2], b[j][3]); mma16816(c[3], kf[7 - 2 * j], b[j][2], b[j][3]);
                        if (j == M_ARR) { asm volatile("" : "+f"(c[0][0]), "+f"(c[1][0]), "+f"(c[2][0]), "+f"(c[3][0])); sched_fence<10>(nv); bar_arrive(BAR_V, 384); }
                        if (j == 3 && M_ARR < 0) bar_arrive(BAR_V, 384);
                    }
                    const uint32_t x0 = send_main<0>((c[0][0] + c[1][0]) * il, (c[0][1] + c[1][1]) * ih, (c[0][2] + c[1][2]) * il, (c[0][3] + c[1][3]) * ih, sa, ll);
                    const uint32_t x1 = send_main<1024>((c[2][0] + c[3][0]) * il, (c[2][1] + c[3][1]) * ih, (c[2][2] + c[3][2]) * il, (c[2][3] + c[3][3]) * ih, sa, ll);
                    send_extra<0>(x0, sx, ll); send_extra<256>(x1, sx, ll);
                }
                };
                if (a < 2) first_half(ic<0>()); else first_half(ic<1>());
                STAMP(warp);
                {
                    const uint32_t cd = lds32(stash + 12), xa = (launder(l16) >> 2) + launder(sb + SM_XT + a * 384);
                    if (a < 2) { const uint32_t kl = lds32(stash + 512); mbar_wait(bTOK + 8 * (par ^ 1), ((s + 1) >> 1) & 1); load_k(par ^ 1, kl); }
                    else {
                        STAMP(16 + a);
                        uint32_t tg;
                        asm volatile("{\n.reg .pred p, q;\n.reg .b64 w;\n.reg .b32 t, u, d, n;\nmov.b32 n, 100000;\n"
                                     "WT_%=:\nld.volatile.shared.u32 %0, [%1];\nmov.u64 w, %%globaltimer;\nmov.b64 {t, u}, w;\nsub.s32 n, n, 1;\nsetp.gt.s32 q, n, 0;\nor.b32 t, t, 1;\nxor.b32 t, t, %2;\n"
                                     "sub.s32 d, t, %0;\nand.b32 d, d, 0x80000001;\nsetp.ne.and.u32 p, d, 0, q;\n@p bra.uni WT_%=;\n}\n" : "=r"(tg) : "r"(sb + SM_TG + (l16 >> 16)), "r"(par + (l16 >> 16)) : "memory");
                        asm volatile("{\n.reg .pred p;\nelect.sync _|p, 0xffffffff;\n"
                                     "@p cp.async.bulk.tensor.3d.shared::cluster.global.mbarrier::complete_tx::bytes.multicast::cluster [%0], [%1, {%3, %4, %5}], [%2], %9;\n"
                                     "@p cp.async.bulk.tensor.3d.shared::cluster.global.mbarrier::complete_tx::bytes.multicast::cluster [%6], [%7, {%3, %4, %8}], [%2], %9;\n}\n"
                            :: "r"(sb + SM_MEM + r * 3072), "l"(&tma), "r"(bMEM), "r"((par ^ 1) * 32), "r"((s + 1) & 2), "r"(12 * r), "r"(sb + SM_XT + r * 384), "l"(&tmb), "r"(ACC_X / 1024 + 6 * r), "h"((unsigned short)7) : "memory");
                        STAMPV(30, tg);
                    }
                    STAMP(19 + a);
                    mbar_wait(bMEM, par);
                    uint32_t x[3], k[3];
                    #pragma unroll
                    for (int j = 0; j < 3; j++) { x[j] = lds32(xa + 128 * j); k[j] = lds32(cd - 2 + 1024 * j); }
                    #pragma unroll
                    for (int j = 0; j < 3; j++) sts16(cd + 1024 * j, (uint16_t)x[j]);
                    bad = __any_sync(0xffffffffu, !((x[0] & x[1] & x[2]) & (k[0] & k[1] & k[2]) & (ACC_FULL << 16)));
                    STAMP(22 + a); STAMPV(27 + a, bad);
                    bar_sync_p(BAR_MEM, 352, bad);
                }
              } while (++sn < NSEG - 1 && !bad);
                {
                    if (bad) {
                        uint32_t c = nv, cx;
                        const uint32_t lq = l16 | (lds32(stash + 524) & nv), so = SLOT_OFF(sn);
                        const uint4 ad = lds128(stash);
                        const unsigned char* pm = launder_p(g_acc + (ad.x + so));
                        const unsigned char* px = launder_p(g_acc + (ad.y + so));
                        int it = 0;
                        do {
                            const uint32_t again = ~(c & __shfl_xor_sync(0xffffffffu, c, 1)) & (ACC_FULL << 16);
                            uint4 u[6]; uint32_t x[3];
                            #pragma unroll
                            for (int j = 0; j < 6; j++) { u[j] = make_uint4(~0u, ~0u, ~0u, ~0u); ld_relaxed128_p(u[j], (const uint4*)(pm + 2048 * j), again); }
                            #pragma unroll
                            for (int j = 0; j < 3; j++) x[j] = ld_relaxed32((const uint32_t*)(px + 2048 * j));
                            c = ~0u;
                            #pragma unroll
                            for (int j = 0; j < 6; j++) {
                                if (again) sts128(lq + sb + SM_MEM + a * 3072 + 512 * j, u[j]);
                                c &= u[j].x;
                            }
                            __syncwarp();
                            #pragma unroll
                            for (int j = 0; j < 3; j++) sts16(ad.w + 1024 * j, (uint16_t)x[j]);
                            c |= ad.z;
                            cx = x[0] & x[1] & x[2];
                        } while (__any_sync(0xffffffffu, !(c & cx & (ACC_FULL << 16))) && ++it < SPIN_LIMIT);
                        bar_sync(BAR_MEM, 352);
                    }
                }
            }
        } else {
            cluster_arrive_rx();
            const uint32_t l16 = pin(lane * 16);
            bf16* dst = g_otok + h * 4096 + (r ? 1024 : 0) + (r == 2 ? 2048 : 0);
            {
                bar_sync(BAR_X0, 288);
                if (lane == 0) { load_w(3); load_wo(4, 6, bWA); }
                __syncwarp();
                bar_sync(BAR_X0 + 1, 288);
                if (lane == 0) { load_wo(0, 4, bW + 32);
 }
                __syncwarp();
                cluster_wait();
            }
            __syncwarp();
            auto t_loop = [&](auto mtile) {
            constexpr int MT = mtile.value;
            uint32_t q[8][4], sp[5][2], pa[5][2], bv[8][4], rng;
            const uint32_t ost = sb + SM_OST + (MT ? 4096 * r - 2048 : 0);
            code_pad<MT ? PAD_T1 : PAD_T0>(nv);
            auto issue_x = [&](int sg) {
                asm volatile("{\n.reg .pred p, q;\nelect.sync _|p, 0xffffffff;\nsetp.eq.and.u32 q, %5, 3, p;\n"
                             "@p cp.async.bulk.tensor.3d.shared::cluster.global.mbarrier::complete_tx::bytes.multicast::cluster [%0], [%1, {%3, %4, %5}], [%2], %6;\n"
                             "@q cp.async.bulk.tensor.3d.shared::cluster.global.mbarrier::complete_tx::bytes.multicast::cluster [%7], [%1, {%3, %4, %3}], [%2], %6;\n}\n"
                    :: "r"(sb + SM_X + (sg & 1) * XBUF + r * 12288), "l"(&tmx), "r"(bX + 8 * (sg & 1)), "r"(0), "r"(sg * SEG), "r"(3 * r), "h"((unsigned short)7), "r"(sb + SM_X + (sg & 1) * XBUF) : "memory");
            };
            mbar_wait(bTOK, 0);
            if (MT) { issue_x(2); issue_x(3); }
            #pragma unroll 1
            for (int s = 0; ; s++) {
                const int par = s & 1;
                mbar_wait(bTOK + 8 * par, (s >> 1) & 1);
                const uint32_t tok = launder(sb + SM_TOK + par * TOKBUF), exl = l16 + launder(sb + SM_EX + par * EXBUF);
                tok_part1<MT>(tok, MT ? r - 1 : 0, launder(l16) >> 4, q, sp, pa, bv, rng, [&] {
                    if (s > 0) {
                        if (lane == 0) {
                            asm volatile("cp.async.bulk.wait_group 0;" ::: "memory");
                            st_relaxed32(&g_prog[blockIdx.x], epoch << 8 | s);
                        }
                        __syncwarp();
                        if (lane == 0 && blockIdx.x == 0) GT(40, s);
                    }
                    sched_fence<6 + MT>(nv); });
                STAMP(25);
                mbar_wait(bEX + 8 * par, (s >> 1) & 1);
                STAMP(26);
                auto duty = [&] { if (s + 1 < NSEG) {
                    asm volatile("{\n.reg .pred p;\nelect.sync _|p, 0xffffffff;\n"
                                 "@p cp.async.bulk.shared::cluster.global.mbarrier::complete_tx::bytes [%0], [%1], 384, [%2];\n"
                                 "@p mbarrier.arrive.expect_tx.shared.b64 _, [%2], 384;\n}\n"
                        :: "r"(sb + SM_TS), "l"(g_ts), "r"(bFREE) : "memory");
                    if (MT && s > 0 && s + 3 < NSEG) issue_x(s + 3);
                } };
                auto pace = [&] { if (s + 1 < NSEG) {
                    const uint32_t lo = min(launder(l16), 368u), b = (gtime_lo() & ~31u) - 0x01000000u + s + (lo >> 16);
                    const uint32_t c = (b & ~31u) + (G1_NS + (s == 0 ? G1_0 : 0)) + (par ^ 1);
                    mbar_wait(bFREE, par);
                    uint4 ts = lds128(sb + SM_TS + lo);
                    int it = 0; uint32_t m;
                    while (true) {
                        m = __reduce_max_sync(0xffffffffu, max(max(__funnelshift_r(ts.x - b, ts.x - b, 5), __funnelshift_r(ts.y - b, ts.y - b, 5)), max(__funnelshift_r(ts.z - b, ts.z - b, 5), __funnelshift_r(ts.w - b, ts.w - b, 5))));
                        if (__builtin_expect(m < 0x00100000u, 1) || ++it >= 64) break;
                        ts = ld_relaxed128((const uint4*)((const char*)g_ts + lo));
                    }
                    asm volatile("st.volatile.shared.u32 [%0], %1;" :: "r"(sb + SM_TG), "r"(c + (min(m, 0x00080000u) << 5)) : "memory");
                } };
                auto wait_v = [&] { mbar_wait(bEV + 8 * par, (s >> 1) & 1); };
                auto wait_x = [&] { if (__builtin_expect(s == 0, 0)) mbar_wait(bX, 1); };
                tok_part2<MT>(tok, exl, ost, MT ? r - 1 : 0, launder(l16) >> 4, q, sp, pa, bv, rng, s < NSEG - 1, wait_v, duty, pace, wait_x);
                STAMP(11);
                fence_async_smem();
                __syncwarp();
                if (s == NSEG - 1) break;
                if (lane == 0) {
                    asm volatile("cp.async.bulk.global.shared::cta.bulk_group [%0], [%1], 2048;" :: "l"(dst), "r"(ost) : "memory");
                    if (!MT) asm volatile("cp.async.bulk.global.shared::cta.bulk_group [%0], [%1], 2048;" :: "l"(dst + 2048), "r"(ost + 4096) : "memory");
                    asm volatile("cp.async.bulk.commit_group;" ::: "memory");
                }
                __syncwarp();
                dst += SEG * NH * DH;
            }
            if (lane == 0) {
                #pragma unroll
                for (int k = 0; k < (MT ? 2 : 4); k++) {
                    const uint32_t src = ost + (k >> 1) * 4096, rk = (r + 1 + (k & 1)) % 3;
                    asm volatile("cp.async.bulk.shared::cluster.shared::cta.mbarrier::complete_tx::bytes [%0], [%1], 2048, [%2];" :: "r"(mapa_u32(src, rk)), "r"(src), "r"(mapa_u32(bMEM, rk)) : "memory");
                }
                mbar_expect_tx(bMEM, MT ? 6144 : 4096);
            }
            __syncwarp();
            };
            if (r == 0) t_loop(ic<0>()); else t_loop(ic<1>());
        }
        cluster_arrive(); cluster_wait();
    }
}
#define SD_THREADS 384
#define SD_CTAS  36
#define BT_RS    4624
#define SD_BT    0
#define SD_STG   74752
#define SD_EF    (SD_STG + 57344)
#define SD_BC    (SD_STG)
#define KSLOTS   5
#define BC_BYTES 10240
#define BC_LBO   1280
#define SD_KP    (SD_STG + 90112)
#define SD_Q0    205824
#define SD_Q1    (SD_STG + 111616)
#define SD_OST   (SD_Q0 + 8192)
#define SD_XCH   (SD_Q0 + 10240)
#define LSEG     (NSEG - 1)
#define SD_BAR   224256
#define SD_TOTAL 224768
#define SD_SPIN  (1 << 22)
#define PART_SLOTS 8
#define SD_WOP 300
#define SD_GO 0
#define SD_REG 200
#define SD_WAIT 6000
#define SD_P2 150
#define SD_P3 600
#define SD_GAP 0
#define SD_RUSH 44
#define SD_P1 300

__device__ uint4 g_part[SD_CTAS][PART_SLOTS][4][8][32];
__device__ __align__(16) unsigned int g_gate[S_LEN];

struct cplx { float r, i; };
__device__ __forceinline__ cplx cmul(cplx a, cplx b) { cplx c; c.r = fmaf(a.r, b.r, -a.i * b.i); c.i = fmaf(a.r, b.i, a.i * b.r); return c; }
__device__ __forceinline__ cplx cexp_(float xr, float xi) {
    const float m = ex2(xr * 1.4426950408889634f);
    const float k = rintf(xi * 0.15915494309189535f);
    const float r = fmaf(k, 1.7484555314695172e-7f, fmaf(k, -6.2831854820251465f, xi));
    cplx o; o.r = m * __cosf(r); o.i = m * __sinf(r); return o;
}
__device__ __forceinline__ void mma_f16(float (&c)[4], const uint32_t (&a)[4], uint32_t b0, uint32_t b1) {
    asm("mma.sync.aligned.m16n8k16.row.col.f32.f16.f16.f32 {%0,%1,%2,%3}, {%4,%5,%6,%7}, {%8,%9}, {%0,%1,%2,%3};"
        : "+f"(c[0]), "+f"(c[1]), "+f"(c[2]), "+f"(c[3]) : "r"(a[0]), "r"(a[1]), "r"(a[2]), "r"(a[3]), "r"(b0), "r"(b1));
}
__device__ __forceinline__ uint32_t mul_bf2(uint32_t a, uint32_t b) { uint32_t r; asm("mul.rn.bf16x2 %0, %1, %2;" : "=r"(r) : "r"(a), "r"(b)); return r; }
__device__ __forceinline__ void mbar_wait_long(uint32_t a, uint32_t parity) { int it = 0; bool more; do { more = ++it < SD_SPIN; } while (!mbar_try(a, parity) && more); }
__device__ __forceinline__ uint32_t lop3_and(uint32_t a, uint32_t b, uint32_t c) { uint32_t r; asm("lop3.b32 %0, %1, %2, %3, 0x80;" : "=r"(r) : "r"(a), "r"(b), "r"(c)); return r; }
__device__ __forceinline__ uint32_t lop3_or(uint32_t a, uint32_t b, uint32_t c) { uint32_t r; asm("lop3.b32 %0, %1, %2, %3, 0xfe;" : "=r"(r) : "r"(a), "r"(b), "r"(c)); return r; }
__device__ __forceinline__ uint16_t lds16(uint32_t a) { uint16_t v; asm volatile("ld.shared.u16 %0, [%1];" : "=h"(v) : "r"(a) : "memory"); return v; }
__device__ __forceinline__ void wg_wait1() { asm volatile("wgmma.wait_group.sync.aligned 1;" ::: "memory"); }
__device__ __forceinline__ void tma2d(uint32_t dst, const CUtensorMap* tm, uint32_t bar, int c0, int c1) {
    asm volatile("cp.async.bulk.tensor.2d.shared::cluster.global.mbarrier::complete_tx::bytes [%0], [%1, {%3, %4}], [%2];"
        :: "r"(dst), "l"(tm), "r"(bar), "r"(c0), "r"(c1) : "memory");
}
__device__ __forceinline__ uint32_t add_bf2(uint32_t a, uint32_t b) { uint32_t r; asm("add.rn.bf16x2 %0, %1, %2;" : "=r"(r) : "r"(a), "r"(b)); return r; }
__device__ __forceinline__ void wgmma_conv(float (&d)[32], uint32_t a0, uint32_t a1, uint32_t a2, uint32_t a3, uint64_t desc) {
    asm volatile("{\n.reg .pred p;\nsetp.ne.b32 p, 1, 0;\n"
        "wgmma.mma_async.sync.aligned.m64n64k16.f32.bf16.bf16 {%0,%1,%2,%3,%4,%5,%6,%7,%8,%9,%10,%11,%12,%13,%14,%15,%16,%17,%18,%19,%20,%21,%22,%23,%24,%25,%26,%27,%28,%29,%30,%31}, {%32,%33,%34,%35}, %36, p, 1, 1, 0;\n}\n"
        : "+f"(d[0]), "+f"(d[1]), "+f"(d[2]), "+f"(d[3]), "+f"(d[4]), "+f"(d[5]), "+f"(d[6]), "+f"(d[7]), "+f"(d[8]), "+f"(d[9]), "+f"(d[10]), "+f"(d[11]), "+f"(d[12]), "+f"(d[13]), "+f"(d[14]), "+f"(d[15]), "+f"(d[16]), "+f"(d[17]), "+f"(d[18]), "+f"(d[19]), "+f"(d[20]), "+f"(d[21]), "+f"(d[22]), "+f"(d[23]), "+f"(d[24]), "+f"(d[25]), "+f"(d[26]), "+f"(d[27]), "+f"(d[28]), "+f"(d[29]), "+f"(d[30]), "+f"(d[31])
        : "r"(a0), "r"(a1), "r"(a2), "r"(a3), "l"(desc));
}
__device__ __forceinline__ void wgmma_conv(float (&d)[24], uint32_t a0, uint32_t a1, uint32_t a2, uint32_t a3, uint64_t desc) {
    asm volatile("{\n.reg .pred p;\nsetp.ne.b32 p, 1, 0;\n"
        "wgmma.mma_async.sync.aligned.m64n48k16.f32.bf16.bf16 {%0,%1,%2,%3,%4,%5,%6,%7,%8,%9,%10,%11,%12,%13,%14,%15,%16,%17,%18,%19,%20,%21,%22,%23}, {%24,%25,%26,%27}, %28, p, 1, 1, 0;\n}\n"
        : "+f"(d[0]), "+f"(d[1]), "+f"(d[2]), "+f"(d[3]), "+f"(d[4]), "+f"(d[5]), "+f"(d[6]), "+f"(d[7]), "+f"(d[8]), "+f"(d[9]), "+f"(d[10]), "+f"(d[11]), "+f"(d[12]), "+f"(d[13]), "+f"(d[14]), "+f"(d[15]), "+f"(d[16]), "+f"(d[17]), "+f"(d[18]), "+f"(d[19]), "+f"(d[20]), "+f"(d[21]), "+f"(d[22]), "+f"(d[23])
        : "r"(a0), "r"(a1), "r"(a2), "r"(a3), "l"(desc));
}
__device__ __forceinline__ void wgmma_conv(float (&d)[16], uint32_t a0, uint32_t a1, uint32_t a2, uint32_t a3, uint64_t desc) {
    asm volatile("{\n.reg .pred p;\nsetp.ne.b32 p, 1, 0;\n"
        "wgmma.mma_async.sync.aligned.m64n32k16.f32.bf16.bf16 {%0,%1,%2,%3,%4,%5,%6,%7,%8,%9,%10,%11,%12,%13,%14,%15}, {%16,%17,%18,%19}, %20, p, 1, 1, 0;\n}\n"
        : "+f"(d[0]), "+f"(d[1]), "+f"(d[2]), "+f"(d[3]), "+f"(d[4]), "+f"(d[5]), "+f"(d[6]), "+f"(d[7]), "+f"(d[8]), "+f"(d[9]), "+f"(d[10]), "+f"(d[11]), "+f"(d[12]), "+f"(d[13]), "+f"(d[14]), "+f"(d[15])
        : "r"(a0), "r"(a1), "r"(a2), "r"(a3), "l"(desc));
}
__device__ __forceinline__ void wgmma_conv(float (&d)[8], uint32_t a0, uint32_t a1, uint32_t a2, uint32_t a3, uint64_t desc) {
    asm volatile("{\n.reg .pred p;\nsetp.ne.b32 p, 1, 0;\n"
        "wgmma.mma_async.sync.aligned.m64n16k16.f32.bf16.bf16 {%0,%1,%2,%3,%4,%5,%6,%7}, {%8,%9,%10,%11}, %12, p, 1, 1, 0;\n}\n"
        : "+f"(d[0]), "+f"(d[1]), "+f"(d[2]), "+f"(d[3]), "+f"(d[4]), "+f"(d[5]), "+f"(d[6]), "+f"(d[7])
        : "r"(a0), "r"(a1), "r"(a2), "r"(a3), "l"(desc));
}
template<int NR> __device__ __forceinline__ void conv_mma(float (&acc)[NR], const uint32_t (&R)[16], uint32_t dlo) {
    #pragma unroll
    for (int q = 0; q < 4; q++)
        wgmma_conv(acc, R[4 * q], R[4 * q + 1], R[4 * q + 2], R[4 * q + 3], (uint64_t)(dlo + (2 * (3 - q)) * (BC_LBO >> 4)) | ((uint64_t)8 << 32));
}
__device__ __forceinline__ void conv_ld(uint32_t (&R)[16], uint32_t a) {
    #pragma unroll
    for (int q = 0; q < 4; q++) { const uint2 u = lds64(a + 64 * (2 * q + 1)); R[4 * q] = u.x; R[4 * q + 1] = u.y; }
}
__device__ __forceinline__ void conv_fix(uint32_t (&R)[16], uint32_t& carry) {
    #pragma unroll
    for (int q = 0; q < 4; q++) {
        asm volatile("mov.b32 %0, %1;" : "=r"(R[4 * q + 2]) : "r"(q ? R[4 * q - 3] : carry));
        asm volatile("mov.b32 %0, %1;" : "=r"(R[4 * q + 3]) : "r"(R[4 * q]));
    }
    asm volatile("mov.b32 %0, %1;" : "=r"(carry) : "r"(R[13]));
}
template<int A> __device__ __forceinline__ void conv_group(float (&acc)[32 - 8 * A], uint32_t (&R)[4][16], uint32_t& carry, uint32_t pb, uint32_t dlo) {
    #pragma unroll
    for (int e = 0; e < 8; e += 2) {
        const int dl = 8 * A + e;
        conv_fix(R[dl & 3], carry); conv_fix(R[(dl + 1) & 3], carry);
        wg_fence(); conv_mma(acc, R[dl & 3], dlo + 16 - 2 * e); conv_mma(acc, R[(dl + 1) & 3], dlo + 14 - 2 * e); wg_commit();
        wg_wait1();
        if (dl + 2 < 32) { conv_ld(R[(dl + 2) & 3], pb + (dl + 2) * 512); conv_ld(R[(dl + 3) & 3], pb + (dl + 3) * 512); }
    }
}

__global__ void __launch_bounds__(SD_THREADS, 1)
side_kernel(const __grid_constant__ CUtensorMap tmw, const bf16* __restrict__ x,
            const bf16* __restrict__ log_A_real, const bf16* __restrict__ A_imag, const bf16* __restrict__ C_real, const bf16* __restrict__ C_imag,
            const bf16* __restrict__ log_dt, const bf16* __restrict__ D_skip, const bf16* __restrict__ gate_w, bf16* __restrict__ out, const int npass) {
    extern __shared__ __align__(1024) unsigned char smem[];
    const uint32_t sb = smem_u32(smem);
    const int tid = threadIdx.x, lane = tid & 31;
    const int warp = __shfl_sync(0xffffffffu, tid >> 5, 0);
    const int g = lane >> 2, t = lane & 3, mi = lane >> 3, r8 = lane & 7;
    const bool sh = blockIdx.x < 32;
    const int d0 = blockIdx.x * 16;
    const uint32_t b0_ = sb + SD_BAR, bKF = b0_ + 384, bKE = bKF + 8 * KSLOTS, bWO = b0_ + 48, bFULL = b0_ + 56, bEMPTY = b0_ + 88, bEPI = b0_ + 120, bPRT = b0_ + 152, bGO = b0_ + 184, bCH = b0_ + 256;
    const unsigned epoch = ld_relaxed32(&g_epoch);
    if (tid == 0) GT(blockIdx.x, 0);
    if (tid == 0) {
        for (int i = 0; i < 2 * KSLOTS; i++) mbar_init(bKF + 8 * i, 128);
        mbar_init(bWO, 1);
        for (int i = 0; i < 16; i++) mbar_init(bCH + 8 * i, 1);
        for (int i = 0; i < 4; i++) { mbar_init(bFULL + 8 * i, 1); mbar_init(bEMPTY + 8 * i, sh ? 8 : 4); mbar_init(bEPI + 8 * i, 4); mbar_init(bPRT + 8 * i, 8); }
        sts32(bGO, epoch);
        asm volatile("fence.mbarrier_init.release.cluster;" ::: "memory");
    }
    for (int i = tid; i < KSLOTS * 8 * 16; i += SD_THREADS) sts128(sb + SD_BC + (i >> 4) * BC_LBO + (i & 15) * 16, make_uint4(0, 0, 0, 0));
    if (tid < 128) sts64(sb + ((tid & 64) ? SD_Q1 : SD_Q0) + (tid & 63) * 8, 0u, 0u);
    fence_async_smem();
    __syncthreads();

    if (warp < 8) {
        asm volatile("setmaxnreg.inc.sync.aligned.u32 %0;" :: "n"(SD_REG));
        const int wg = warp >> 2, w = warp & 3, t128 = tid & 127;
        if (SD_WAIT) __nanosleep(SD_WAIT);
        {
            #pragma unroll 1
            for (int i = 0; i < 4; i++) {
                const int tp = tid + 256 * i;
                const bf16* xp = x + (size_t)(2 * tp) * DM + d0;
                const uint4 v0 = __ldg((const uint4*)xp), v1 = __ldg((const uint4*)(xp + 8)), v2 = __ldg((const uint4*)(xp + DM)), v3 = __ldg((const uint4*)(xp + DM + 8));
                const uint32_t a = sb + SD_BT + (tp >> 5) * 144 + (tp & 31) * 4;
                const uint32_t lo[8] = {v0.x, v0.y, v0.z, v0.w, v1.x, v1.y, v1.z, v1.w};
                const uint32_t hi[8] = {v2.x, v2.y, v2.z, v2.w, v3.x, v3.y, v3.z, v3.w};
                #pragma unroll
                for (int j = 0; j < 8; j++) { sts32(a + (2 * j) * BT_RS, __byte_perm(lo[j], hi[j], 0x5410)); sts32(a + (2 * j + 1) * BT_RS, __byte_perm(lo[j], hi[j], 0x7632)); }
                if (SD_GAP) __nanosleep(SD_GAP);
            }
        }
        bar_sync(1, 256);
        if (tid == 0) GT(blockIdx.x, 65);
        const uint32_t pa = sb + (wg ? SD_Q1 : SD_Q0);
        const uint32_t pb = pa + (72 + 16 * w - 56 + g - 2 * t) * 8;
        for (int c = wg; c < 16; c += 2) {
            const uint32_t bt = sb + SD_BT + c * BT_RS;
            bar_sync(2 + wg, 128);
            #pragma unroll
            for (int it = 0; it < 9; it++) {
                const int k = it < 8 ? t128 + 128 * it : t128 - 4;
                if (it < 8 || t128 < 4) {
                    auto word = [&](int j) { return j >= 0 ? lds32(bt + (j >> 5) * 144 + (j & 31) * 4) : 0u; };
                    const uint32_t c0 = word(k), p0 = word(k - 1), c1 = word(k + 4), p1 = word(k + 3);
                    sts128(pa + (72 + 2 * k) * 8, make_uint4(__byte_perm(c0, p0, 0x7610), __byte_perm(c1, p1, 0x7610), __byte_perm(c0, c0, 0x1032), __byte_perm(c1, c1, 0x1032)));
                }
            }
            bar_sync(2 + wg, 128);
            const int slot = c % KSLOTS;
            float acc[32];
            #pragma unroll
            for (int i = 0; i < 32; i++) acc[i] = 0.f;
            uint32_t R[4][16];
            uint32_t carry = lds32(pb);
            conv_ld(R[0], pb); conv_ld(R[1], pb + 512);
            const uint32_t dlo = (((sb + SD_BC + slot * BC_BYTES) & 0x3FFFF) >> 4) | ((BC_LBO >> 4) << 16);
            mbar_wait_long(bKF + 8 * slot, (c / KSLOTS) & 1);
            const float ds = bf(D_skip[d0 + c]);
            auto fin = [&](const float* a8, int q0) {
                #pragma unroll
                for (int q = 0; q < 2; q++)
                    #pragma unroll
                    for (int hh = 0; hh < 2; hh++) {
                        const uint32_t a = bt + (4 * (q0 + q) + t) * 144 + (16 * w + g + 8 * hh) * 2;
                        const float u = __uint_as_float((uint32_t)lds16(a) << 16);
                        const float y = rbf(a8[4 * q + 2 * hh] + a8[4 * q + 2 * hh + 1]);
                        sts16(a, (uint16_t)(pack_bf16(y + rbf(u * ds), 0.f) & 0xffff));
                    }
            };
            float a1[24], a2[16], a3[8];
            conv_group<0>(acc, R, carry, pb, dlo);
            wg_wait0();
            #pragma unroll
            for (int i = 0; i < 24; i++) asm volatile("mov.b32 %0, %1;" : "=f"(a1[i]) : "f"(acc[8 + i]));
            fin(acc, 0);
            conv_group<1>(a1, R, carry, pb, dlo);
            wg_wait0();
            #pragma unroll
            for (int i = 0; i < 16; i++) asm volatile("mov.b32 %0, %1;" : "=f"(a2[i]) : "f"(a1[8 + i]));
            fin(a1, 2);
            conv_group<2>(a2, R, carry, pb, dlo);
            wg_wait0();
            #pragma unroll
            for (int i = 0; i < 8; i++) asm volatile("mov.b32 %0, %1;" : "=f"(a3[i]) : "f"(a2[8 + i]));
            fin(a2, 4);
            conv_group<3>(a3, R, carry, pb, dlo);
            wg_wait0();
            mbar_arrive(bKE + 8 * slot);
            fin(a3, 6);
        }
        fence_async_smem();
        __syncthreads();
        const uint32_t stg = sb + SD_STG + wg * 65536;
        uint32_t wf[32][4];
        if (tid == 0) GT(blockIdx.x, 66);
        mbar_wait_long(bWO, 0);
        #pragma unroll
        for (int i = 0; i < 32; i++)
            ldsm_x4_t(wf[i], stg + (i * 16 + (mi >> 1) * 8 + r8) * 128 + (((2 * w + (mi & 1)) ^ r8) << 4));
        { uint32_t x = 0;
          #pragma unroll
          for (int i = 0; i < 32; i++) x |= wf[i][0];
          asm volatile("" :: "r"(x) : "memory"); }
        __syncwarp();
        if (lane == 0) {
            mbar_arrive(bEMPTY + 16 * wg); mbar_arrive(bEMPTY + 16 * wg + 8);
            if (sh) { mbar_arrive(bEMPTY + 16 * (wg ^ 1)); mbar_arrive(bEMPTY + 16 * (wg ^ 1) + 8); }
        }
        uint4* dst = sh ? &g_part[(blockIdx.x & ~7) + 4 * wg + w][0][0][blockIdx.x & 7][lane] : &g_part[32 + w][0][0][2 * (blockIdx.x - 32) + wg][lane];
        const uint32_t dl0 = (((sb + SD_STG) & 0x3FFFF) >> 4) | 0x10000u;
        const uint32_t bu = uni(b0_), shu = uni(sh), wgu = uni(wg), dlu = uni(dl0);
        auto seg = [&](int s, float (&acc)[16]) {
            const uint32_t bi = shu ? s & 3 : 2 * wgu + (s & 1), bp = (shu ? s >> 2 : s >> 1) & 1;
            const uint32_t xd = dlu + bi * 2048;
            #pragma unroll
            for (int i = 0; i < 32; i++) {
                if ((i & 15) == 0) { mbar_wait_long(bu + 256 + 32 * bi + (i >> 1), bp); wg_fence(); }
                if (i == 0) wgmma_n32<0>(acc, wf[i], desc_from(xd));
                else wgmma_n32<1>(acc, wf[i], desc_from(xd + (i >> 2) * 256 + (i & 3) * 2));
            }
            wg_commit();
            if (s >= PART_SLOTS / 2) mbar_wait_long(bu + 120 + 8 * (s & 3), ((s - 4) >> 2) & 1);
            const uint32_t ph = ((s / PART_SLOTS) & 1) ^ 1;
            uint4* p = dst + (s % PART_SLOTS) * (4 * 8 * 32);
            wg_wait0();
            #pragma unroll
            for (int j = 0; j < 4; j++)
                st_relaxed128(p + 256 * j, make_uint4((__float_as_uint(acc[4 * j]) & ~1u) | ph, __float_as_uint(acc[4 * j + 1]), __float_as_uint(acc[4 * j + 2]), __float_as_uint(acc[4 * j + 3])));
            if (tid == 0 && s == LSEG - 1) GT(blockIdx.x, 71);
            asm volatile("{\n.reg .pred p;\nelect.sync _|p, 0xffffffff;\n@p mbarrier.arrive.shared.b64 _, [%0];\n@p mbarrier.arrive.shared.b64 _, [%1];\n}\n" :: "r"(bu + 88 + 8 * bi), "r"(bu + 152 + 8 * (s & 3)) : "memory");
        };
        #pragma unroll 1
        for (int pass = 0; pass < npass; pass++) {
            if (pass) {
                float acc0[16], acc1[16];
                #pragma unroll 1
                for (int s = 0; ; s += 2) { seg(s, acc0); if (s + 1 >= LSEG) break; seg(s + 1, acc1); }
            }
            uint32_t tq; asm volatile("mov.u32 %0, %%tid.x;" : "=r"(tq));
            const uint4* p = &g_last[blockIdx.x][0][0][0] + (tq >> 5) * 256 + (tq & 31);
            const uint32_t tag = lds32(bGO) & 1u;
            uint4 v[8]; int it = 0;
            #pragma unroll
            for (int i = 0; i < 8; i++) v[i] = make_uint4(tag ^ pass, 0, 0, 0);
            while (true) {
                #pragma unroll
                for (int i = 0; i < 8; i++) ld_relaxed128_p(v[i], p + 32 * i, (v[i].x ^ tag) & 1u);
                uint32_t any = 0;
                #pragma unroll
                for (int i = 0; i < 8; i++) any |= v[i].x ^ tag;
                if (!__any_sync(0xffffffffu, any & 1u) || ++it >= SD_SPIN) break;
            }
            float a[8];
            #pragma unroll
            for (int i = 0; i < 8; i++) a[i] = 0.f;
            #pragma unroll
            for (int i = 0; i < 8; i++) { a[0] += bf_lo(v[i].x); a[1] += bf_hi(v[i].x); a[2] += bf_lo(v[i].y); a[3] += bf_hi(v[i].y); a[4] += bf_lo(v[i].z); a[5] += bf_hi(v[i].z); a[6] += bf_lo(v[i].w); a[7] += bf_hi(v[i].w); }
            const uint32_t xa = sb + SD_XCH + (tq >> 7) * 4096 + (tq & 127) * 16;
            sts128(xa, make_uint4(__float_as_uint(a[0]), __float_as_uint(a[1]), __float_as_uint(a[2]), __float_as_uint(a[3])));
            sts128(xa + 2048, make_uint4(__float_as_uint(a[4]), __float_as_uint(a[5]), __float_as_uint(a[6]), __float_as_uint(a[7])));
            bar_arrive_p(6, 320, !pass);
        }
        mbar_wait_long(bEPI + 8 * (LSEG & 3), ((LSEG - 4) >> 2) & 1);
        #pragma unroll
        for (int j = 0; j < 4; j++) st_relaxed128(dst + (LSEG % PART_SLOTS) * (4 * 8 * 32) + 256 * j, make_uint4(((LSEG / PART_SLOTS) & 1) ^ 1, 0, 0, 0));
    } else {
        asm volatile("setmaxnreg.dec.sync.aligned.u32 %0;" :: "n"(504 - 2 * SD_REG));
        const int w = warp - 8, n = tid - 256;
        bf16 p_la = log_A_real[d0 * NS + n], p_ai = A_imag[d0 * NS + n], p_cr = C_real[d0 * NS + n], p_ci = C_imag[d0 * NS + n], p_dt = log_dt[d0];
        const uint32_t ef = sb + SD_EF + w * 8192;
        const uint32_t efl = ef + lane * 4;
        uint32_t goff[8];
        #pragma unroll
        for (int i = 0; i < 16; i++) {
            const int l = 64 * lane + 8 * (w + 4 * (i >> 3)) + (i & 7);
            const int p = (int)rbf((float)l);
            const int a = p >> 7, b = (p >> 3) & 15, c = p & 7;
            const int row = p < 256 ? 8 * a + c : (p < 512 ? 16 + 4 * (a - 2) + (c >> 1) : (p < 1024 ? 24 + 2 * (a - 4) + (c >> 2) : 24 + a));
            const uint32_t off = row * 72 + b * 4;
            if (i & 1) goff[i >> 1] |= off << 16; else goff[i >> 1] = off;
        }
        for (int c = 0; c < 16; c++) {
            const float dt = rbf(expf(bf(p_dt)));
            const float xr = -rbf(expf(bf(p_la))) * dt, xi = bf(p_ai) * dt;
            cplx C; C.r = 2.f * bf(p_cr) * dt; C.i = 2.f * bf(p_ci) * dt;
            if (c + 1 < 16) {
                const int o = (d0 + c + 1) * NS + n;
                p_la = log_A_real[o]; p_ai = A_imag[o]; p_cr = C_real[o]; p_ci = C_imag[o]; p_dt = log_dt[d0 + c + 1];
            }
            const uint32_t mexp = min(max(__reduce_max_sync(0xffffffffu, __float_as_uint(fmaxf(fabsf(C.r), fabsf(C.i)))) & 0x7f800000u, 0x01000000u), 0x7e000000u);
            const float unsc = __uint_as_float(mexp), sc = __uint_as_float(0x7f000000u - mexp);
            C.r *= sc; C.i *= sc;
            #define EADDR(r) ((efl ^ (((r) & 7) << 4)) + (r) * 128)
            {
                cplx f[16];
                f[1] = cexp_(8.f * xr, -8.f * xi);
                f[2] = cmul(f[1], f[1]); f[3] = cmul(f[2], f[1]); f[4] = cmul(f[2], f[2]); f[5] = cmul(f[4], f[1]); f[6] = cmul(f[4], f[2]); f[7] = cmul(f[4], f[3]);
                f[8] = cmul(f[4], f[4]);
                #pragma unroll
                for (int b = 9; b < 16; b++) f[b] = cmul(f[8], f[b - 8]);
                sts32(EADDR(0) + 6144, 0x00003c00u);
                #pragma unroll
                for (int b = 1; b < 16; b++) sts32(EADDR(b) + 6144, pack_f16(f[b].r, f[b].i));
            }
            {
                cplx G[17], wc[8];
                G[1] = cexp_(128.f * xr, 128.f * xi);
                wc[1] = cexp_(xr, xi);
                G[2] = cmul(G[1], G[1]); G[4] = cmul(G[2], G[2]); G[8] = cmul(G[4], G[4]);
                wc[2] = cmul(wc[1], wc[1]); wc[3] = cmul(wc[2], wc[1]); wc[4] = cmul(wc[2], wc[2]); wc[5] = cmul(wc[4], wc[1]); wc[6] = cmul(wc[4], wc[2]); wc[7] = cmul(wc[4], wc[3]);
                cplx CG[17];
                CG[0] = C; CG[1] = cmul(C, G[1]); CG[2] = cmul(C, G[2]); CG[3] = cmul(CG[1], G[2]);
                #pragma unroll
                for (int a = 0; a < 4; a++) CG[4 + a] = cmul(CG[a], G[4]);
                #pragma unroll
                for (int a = 0; a < 9; a++) CG[8 + a] = cmul(CG[a], G[8]);
                #pragma unroll
                for (int r = 0; r < 41; r++) {
                    const int a = r < 16 ? (r >> 3) : (r < 24 ? 2 + ((r >> 2) & 1) : (r < 32 ? 4 + ((r >> 1) & 3) : r - 24));
                    const int cc = r < 16 ? (r & 7) : (r < 24 ? 2 * (r & 3) : (r < 32 ? 4 * (r & 1) : 0));
                    const cplx e = cc ? cmul(CG[a], wc[cc]) : CG[a];
                    sts32(EADDR(r), pack_f16(e.r, e.i));
                }
            }
            __syncwarp();
            float acc[3][2][4];
            #pragma unroll
            for (int i = 0; i < 3; i++)
                #pragma unroll
                for (int j = 0; j < 2; j++) { acc[i][j][0] = acc[i][j][1] = acc[i][j][2] = acc[i][j][3] = 0.f; }
            #pragma unroll
            for (int ks = 0; ks < 4; ks++) {
                uint32_t bq[4];
                ldsm_x4(bq, ef + 6144 + ((mi >> 1) * 8 + r8) * 128 + (((2 * ks + (mi & 1)) ^ r8) << 4));
                #pragma unroll
                for (int mt = 0; mt < 3; mt++) {
                    uint32_t aq[4];
                    ldsm_x4(aq, ef + (16 * mt + (mi & 1) * 8 + r8) * 128 + (((2 * ks + (mi >> 1)) ^ r8) << 4));
                    mma_f16(acc[mt][0], aq, bq[0], bq[1]);
                    mma_f16(acc[mt][1], aq, bq[2], bq[3]);
                }
            }
            const uint32_t kp = sb + SD_KP;
            #pragma unroll
            for (int mt = 0; mt < 3; mt++)
                #pragma unroll
                for (int nt = 0; nt < 2; nt++) {
                    const uint32_t a = kp + w * 3072 + (16 * mt + g) * 64 + nt * 32 + t * 8;
                    sts64(a, __float_as_uint(acc[mt][nt][0] * unsc), __float_as_uint(acc[mt][nt][1] * unsc));
                    sts64(a + 512, __float_as_uint(acc[mt][nt][2] * unsc), __float_as_uint(acc[mt][nt][3] * unsc));
                }
            bar_sync(4, 128);
            #pragma unroll
            for (int i = 0; i < 3; i++) {
                const uint32_t a = kp + (n + 128 * i) * 8;
                const uint2 v0 = lds64(a), v1 = lds64(a + 3072), v2 = lds64(a + 6144), v3 = lds64(a + 9216);
                sts64(a + 12288 + ((n >> 3) + 16 * i) * 8, __float_as_uint((__uint_as_float(v0.x) + __uint_as_float(v1.x)) + (__uint_as_float(v2.x) + __uint_as_float(v3.x))),
                                 __float_as_uint((__uint_as_float(v0.y) + __uint_as_float(v1.y)) + (__uint_as_float(v2.y) + __uint_as_float(v3.y))));
            }
            bar_sync(4, 128);
            const int slot = c % KSLOTS;
            float kv[16];
            #pragma unroll
            for (int e = 0; e < 8; e++) { kv[2 * e] = __uint_as_float(lds32(kp + 12288 + (goff[e] & 0xffff))); kv[2 * e + 1] = __uint_as_float(lds32(kp + 12288 + (goff[e] >> 16))); }
            if (c >= KSLOTS) mbar_wait_long(bKE + 8 * slot, (c / KSLOTS - 1) & 1);
            #pragma unroll
            for (int it = 0; it < 2; it++) {
                uint32_t hi[4], lo[4];
                #pragma unroll
                for (int e = 0; e < 4; e++) {
                    const float k0 = kv[8 * it + 2 * e], k1 = kv[8 * it + 2 * e + 1];
                    hi[e] = pack_bf16(k0, k1);
                    lo[e] = pack_bf16(k0 - bf_lo(hi[e]), k1 - bf_hi(hi[e]));
                }
                const uint32_t a = sb + SD_BC + slot * BC_BYTES + (w + 4 * it) * BC_LBO + (16 + 2 * lane) * 16;
                sts128(a, make_uint4(hi[0], hi[1], hi[2], hi[3]));
                sts128(a + 16, make_uint4(lo[0], lo[1], lo[2], lo[3]));
            }
            fence_async_smem();
            mbar_arrive(bKF + 8 * slot);
        }
        {
            uint32_t gw[9];
            #pragma unroll
            for (int j = 0; j < 9; j++) gw[j] = __ldg((const uint32_t*)gate_w + lane + 32 * j);
            float z = 0.f;
            #pragma unroll 1
            for (int i0 = 0; i0 < 15; i0 += 5) {
                uint32_t xv[5][9];
                #pragma unroll
                for (int i = 0; i < 5; i++) {
                    const int tk = min(blockIdx.x * 57 + w + 4 * (i0 + i), S_LEN - 1);
                    #pragma unroll
                    for (int j = 0; j < 9; j++) xv[i][j] = __ldg((const uint32_t*)(x + (size_t)tk * DM) + lane + 32 * j);
                }
                #pragma unroll
                for (int i = 0; i < 5; i++) {
                    float acc = 0.f;
                    #pragma unroll
                    for (int j = 0; j < 9; j++) { const uint32_t m = mul_bf2(xv[i][j], gw[j]); acc += bf_lo(m) + bf_hi(m); }
                    #pragma unroll
                    for (int o = 16; o; o >>= 1) acc += __shfl_xor_sync(0xffffffffu, acc, o);
                    if (lane == i0 + i) z = rbf(acc);
                }
            }
            const int li = w + 4 * lane, tk = blockIdx.x * 57 + li;
            if (li < 57 && tk < S_LEN) st_relaxed32(&g_gate[tk], pack_bf16(1.f / (1.f + expf(-z)), 0.f) | (epoch << 16));
        }
        if (tid == 256) GT(blockIdx.x, 67);
        fence_async_smem();
        __syncthreads();
            const uint32_t ost = sb + SD_OST + w * 512;
            const uint4* const pl = &g_part[blockIdx.x][0][0][0][lane];
            bf16* const ol = out + (size_t)(lane >> 1) * DM + d0 + 8 * (lane & 1);
            const uint32_t ga = sb + SD_Q0 + t * 8, bb = sb + SD_BT + g * BT_RS + t * 4, oa = ost + r8 * 32 + (mi & 1) * 16 + (mi >> 1) * 256;
            uint32_t gg[2], mb[2][2];
            auto gates = [&](int u) {
                #pragma unroll
                for (int k = 0; k < 2; k++) {
                    const uint2 gt = lds64(ga + (u + k) * 32);
                    const uint32_t ba = bb + (u >> 3) * 144 + ((u & 7) + k) * 16;
                    gg[k] = __byte_perm(gt.x, gt.y, 0x5410);
                    const uint32_t mm = pack_bf16(1.f - bf_lo(gg[k]), 1.f - bf_hi(gg[k]));
                    mb[k][0] = mul_bf2(mm, lds32(ba)); mb[k][1] = mul_bf2(mm, lds32(ba + 8 * BT_RS));
                }
            };
            auto finish = [&](int u, const uint32_t (&sm)[2][2], uint32_t store) {
                stsm_x4_t(oa, add_bf2(mul_bf2(gg[0], sm[0][0]), mb[0][0]), add_bf2(mul_bf2(gg[0], sm[0][1]), mb[0][1]), add_bf2(mul_bf2(gg[1], sm[1][0]), mb[1][0]), add_bf2(mul_bf2(gg[1], sm[1][1]), mb[1][1]));
                __syncwarp();
                const uint4 o = lds128(ost + lane * 16);
                asm volatile("{\n.reg .pred p;\nsetp.ne.u32 p, %5, 0;\n@p st.global.v4.u32 [%0], {%1,%2,%3,%4};\n}\n" :: "l"(ol + (size_t)u * (8 * DM)), "r"(o.x), "r"(o.y), "r"(o.z), "r"(o.w), "r"(store) : "memory");
                __syncwarp();
            };
            auto units = [&](int u, int end) {
              uint4 v[16];
              auto fetch = [&](int u, bool block) {
                const int s = u >> 2;
                uint32_t early;
                asm volatile("{\n.reg .pred p;\nmbarrier.test_wait.parity.shared::cta.b64 p, [%1], %2;\nselp.u32 %0, 1, 0, p;\n}\n" : "=r"(early) : "r"(bPRT + 8 * (s & 3)), "r"((s >> 2) & 1) : "memory");
                if (!early) {
                    if (!block) return false;
                    mbar_wait_long(bPRT + 8 * (s & 3), (s >> 2) & 1);
                    delay_clk(s < LSEG - 2 ? SD_P1 : SD_P2);
                } else if (SD_P3 && s < SD_RUSH) delay_clk(SD_P3);
                const uint4* p = pl + (u & (4 * PART_SLOTS - 1)) * 256;
                #pragma unroll
                for (int i = 0; i < 16; i++) v[i] = ld_relaxed128(p + 32 * i);
                return true;
              };
              fetch(u, true);
              #pragma unroll 1
              while (true) {
                const int s = u >> 2;
                const uint32_t phm = ((s / PART_SLOTS) & 1) - 1;
                gates(u);
                int it = 0;
                while (true) {
                    uint32_t all = ~0u, any = 0;
                    #pragma unroll
                    for (int i = 0; i < 16; i += 2) { all = lop3_and(all, v[i].x, v[i + 1].x); any = lop3_or(any, v[i].x, v[i + 1].x); }
                    if (!__any_sync(0xffffffffu, ((all ^ phm) | (any ^ phm)) & 1u) || ++it >= SD_SPIN) break;
                    if (it > 1 && s < LSEG - 2) __nanosleep(200);
                    const uint4* p = pl + (u & (4 * PART_SLOTS - 1)) * 256;
                    #pragma unroll
                    for (int i = 0; i < 16; i++) ld_relaxed128_p(v[i], p + 32 * i, (v[i].x ^ phm) & 1u);
                }
                if (lane < 2) mbar_arrive(bEPI + 8 * (s & 3));
                uint32_t sm[2][2];
                #pragma unroll
                for (int k = 0; k < 2; k++) {
                    float a0 = __uint_as_float(v[8 * k].x), a1 = __uint_as_float(v[8 * k].y), a2 = __uint_as_float(v[8 * k].z), a3 = __uint_as_float(v[8 * k].w);
                    #pragma unroll
                    for (int i = 1; i < 8; i++) { a0 += __uint_as_float(v[8 * k + i].x); a1 += __uint_as_float(v[8 * k + i].y); a2 += __uint_as_float(v[8 * k + i].z); a3 += __uint_as_float(v[8 * k + i].w); }
                    sm[k][0] = pack_bf16(a0, a1); sm[k][1] = pack_bf16(a2, a3);
                }
                const int nu = u + 6;
                const bool pre = nu < end && fetch(nu, false);
                finish(u, sm, 1u);
                if (lane == 0 && (u & 2)) GT(blockIdx.x, 1 + s);
                if (nu >= end) break;
                if (!pre) fetch(nu, true);
                u = nu;
              }
            };
        #pragma unroll 1
        for (int pass = w & 1 ? 0 : 1; pass < npass; pass++) {
        if (pass) {
        if (w == 0) {
            if (lane == 0) {
                mbar_expect_tx(bWO, 131072);
                #pragma unroll 1
                for (int q = 0; q < 16; q++) {
                    tma2d(sb + SD_STG + q * 8192, &tmw, bWO, sh ? 128 * (blockIdx.x >> 3) + 64 * (q >> 3) : 512, sh ? 512 * (blockIdx.x & 7) + 64 * (q & 7) : 1024 * (blockIdx.x - 32) + 64 * q);
                    if (SD_WOP) delay_clk(SD_WOP);
                }
            }
            bar_sync(5, 128);
            const int ke0 = sh ? blockIdx.x & 7 : 2 * (blockIdx.x - 32);
            const unsigned int* f = &g_prog[12 * ke0 + (lane < (sh ? 12 : 24) ? lane : 0)];
            int avail = 0;
            #pragma unroll 1
            for (int s = 0; s < LSEG; s++) {
                if (s >= avail) {
                    int it = 0;
                    while (true) {
                        uint32_t v;
                        asm volatile("ld.acquire.gpu.global.u32 %0, [%1];" : "=r"(v) : "l"(f) : "memory");
                        avail = __reduce_min_sync(0xffffffffu, (v >> 8) == (epoch & 0xffffffu) ? v & 255u : 0u);
                        if (avail > s || ++it >= SD_SPIN) break;
                        if (s < LSEG - 1) __nanosleep(64);
                    }
                    asm volatile("fence.proxy.async.global;" ::: "memory");
                    if (lane == 0 && s == LSEG - 1) GT(blockIdx.x, 70);
                }
                if (lane == 0 && s == 2 && blockIdx.x == 0) st_relaxed32(&g_epoch, epoch + 1);
                const int b0 = sh ? s & 3 : s & 1, bp = (sh ? s >> 2 : s >> 1) & 1;
                const bf16* src = g_otok + (size_t)s * (SEG * NH * DH) + ke0 * 16384;
                mbar_wait_long(bEMPTY + 8 * b0, bp);
                if (!sh) mbar_wait_long(bEMPTY + 16 + 8 * b0, bp);
                #pragma unroll
                for (int hc = 0; hc < 2; hc++)
                    asm volatile("{\n.reg .pred p, q;\nelect.sync _|p, 0xffffffff;\nsetp.eq.and.u32 q, %6, 0, p;\n"
                                 "@p mbarrier.arrive.expect_tx.shared.b64 _, [%2], 16384;\n"
                                 "@p cp.async.bulk.shared::cluster.global.mbarrier::complete_tx::bytes [%0], [%1], 16384, [%2];\n"
                                 "@q mbarrier.arrive.expect_tx.shared.b64 _, [%5], 16384;\n"
                                 "@q cp.async.bulk.shared::cluster.global.mbarrier::complete_tx::bytes [%3], [%4], 16384, [%5];\n}\n"
                        :: "r"(sb + SD_STG + b0 * 32768 + hc * 16384), "l"(src + hc * 8192), "r"(bCH + 32 * b0 + 8 * hc),
                           "r"(sb + SD_STG + (b0 + 2) * 32768 + hc * 16384), "l"(src + 16384 + hc * 8192), "r"(bCH + 32 * (b0 + 2) + 8 * hc), "r"((uint32_t)sh) : "memory");
            }
        } else {
            if (w == 3) {
                for (int i = 0; i < 16; i += 8) {
                    uint4 v[8]; uint32_t miss = 0xffu; int it = 0;
                    const uint32_t tag = epoch & 0xffffu;
                    #pragma unroll
                    for (int j = 0; j < 8; j++) v[j] = make_uint4(0, 0, 0, 0);
                    do {
                        #pragma unroll
                        for (int j = 0; j < 8; j++) ld_relaxed128_p(v[j], (const uint4*)g_gate + (i + j) * 32 + lane, miss & (1u << j));
                        miss = 0;
                        #pragma unroll
                        for (int j = 0; j < 8; j++) miss |= (uint32_t)((v[j].x >> 16) != tag || (v[j].y >> 16) != tag || (v[j].z >> 16) != tag || (v[j].w >> 16) != tag) << j;
                    } while (__any_sync(0xffffffffu, miss) && ++it < SD_SPIN);
                    #pragma unroll
                    for (int j = 0; j < 8; j++) sts128(sb + SD_Q0 + ((i + j) * 32 + lane) * 16, v[j]);
                }
            }
            bar_sync(5, 128);
        }
        if (w) units(2 * (w - 1), 4 * LSEG);
        }
        if (w < 2) {
            gates(4 * LSEG + 2 * w);
            bar_sync_p(6, 320, !pass);
            uint32_t sm[2][2];
            #pragma unroll
            for (int k = 0; k < 2; k++) {
                float a0 = 0.f, a1 = 0.f, a2 = 0.f, a3 = 0.f;
                #pragma unroll
                for (int i = 0; i < 4; i++) { const uint4 v = lds128(sb + SD_XCH + w * 4096 + k * 2048 + i * 512 + lane * 16); a0 += __uint_as_float(v.x); a1 += __uint_as_float(v.y); a2 += __uint_as_float(v.z); a3 += __uint_as_float(v.w); }
                sm[k][0] = pack_bf16(a0, a1); sm[k][1] = pack_bf16(a2, a3);
            }
            finish(4 * LSEG + 2 * w, sm, pass);
            if (lane == 0 && w == 1) GT(blockIdx.x, 1 + LSEG);
        }
        }
    }
    if (tid == 256) GT(blockIdx.x, 72);
}

extern "C" void kernel_launch(void* const* d_in, const int* in_sizes, int n_in, void* d_out, int out_size) {
    const bf16* x = (const bf16*)d_in[0];
    const bf16* mem0 = (const bf16*)d_in[1];
    const bf16* Wq = (const bf16*)d_in[2];
    const bf16* Wk = (const bf16*)d_in[3];
    const bf16* Wv = (const bf16*)d_in[4];
    const bf16* Wo = (const bf16*)d_in[5];
    const bf16* log_A_real = (const bf16*)d_in[8];
    const bf16* A_imag = (const bf16*)d_in[9];
    const bf16* C_real = (const bf16*)d_in[10];
    const bf16* C_imag = (const bf16*)d_in[11];
    const bf16* log_dt = (const bf16*)d_in[12];
    const bf16* D_skip = (const bf16*)d_in[13];
    const bf16* gate_w = (const bf16*)d_in[14];
    bf16* out = (bf16*)d_out;
    typedef CUresult (*EncFn)(CUtensorMap*, CUtensorMapDataType, cuuint32_t, void*, const cuuint64_t*, const cuuint64_t*, const cuuint32_t*, const cuuint32_t*,
                              CUtensorMapInterleave, CUtensorMapSwizzle, CUtensorMapL2promotion, CUtensorMapFloatOOBfill);
    static EncFn enc = nullptr;
    if (!enc) { void* fn = nullptr; cudaDriverEntryPointQueryResult qr; cudaGetDriverEntryPoint("cuTensorMapEncodeTiled", &fn, cudaEnableDefault, &qr); enc = (EncFn)fn; }
    auto mk = [&](CUtensorMap* tm, const void* ptr, uint64_t cols, uint64_t rows, uint32_t bc, uint32_t br) {
        cuuint64_t gdim[2] = {cols, rows}; cuuint64_t gstr[1] = {cols * 2}; cuuint32_t box[2] = {bc, br}; cuuint32_t estr[2] = {1, 1};
        enc(tm, CU_TENSOR_MAP_DATA_TYPE_BFLOAT16, 2, (void*)ptr, gdim, gstr, box, estr, CU_TENSOR_MAP_INTERLEAVE_NONE, bc == 64 ? CU_TENSOR_MAP_SWIZZLE_128B : CU_TENSOR_MAP_SWIZZLE_64B,
            CU_TENSOR_MAP_L2_PROMOTION_L2_256B, CU_TENSOR_MAP_FLOAT_OOB_FILL_NONE);
    };
    static bool attr_done = false;
    if (!attr_done) {
        cudaFuncSetAttribute(chain_kernel, cudaFuncAttributeMaxDynamicSharedMemorySize, SM_TOTAL);
        cudaFuncSetAttribute(side_kernel, cudaFuncAttributeMaxDynamicSharedMemorySize, SD_TOTAL);
        attr_done = true;
    }
    CUtensorMap tmx, tma, tmb, tmw, tmq, tmk, tmv, tmo;
    {
        cuuint64_t gdim[3] = {64, S_LEN, DM / 64}; cuuint64_t gstr[2] = {DM * 2, 128}; cuuint32_t box[3] = {64, SEG, 3}; cuuint32_t estr[3] = {1, 1, 1};
        enc(&tmx, CU_TENSOR_MAP_DATA_TYPE_BFLOAT16, 3, (void*)x, gdim, gstr, box, estr, CU_TENSOR_MAP_INTERLEAVE_NONE, CU_TENSOR_MAP_SWIZZLE_128B,
            CU_TENSOR_MAP_L2_PROMOTION_L2_256B, CU_TENSOR_MAP_FLOAT_OOB_FILL_NONE);
    }
    static void* acc = nullptr;
    if (!acc) cudaGetSymbolAddress(&acc, g_acc);
    for (int w = 0; w < 2; w++) {
        cuuint64_t gdim[3] = {64, 4, 64}; cuuint64_t gstr[2] = {256, 1024}; cuuint32_t box[3] = {w ? 8u : 32u, 2, w ? 6u : 12u}; cuuint32_t estr[3] = {1, 1, 1};
        enc(w ? &tmb : &tma, CU_TENSOR_MAP_DATA_TYPE_UINT32, 3, acc, gdim, gstr, box, estr, CU_TENSOR_MAP_INTERLEAVE_NONE, CU_TENSOR_MAP_SWIZZLE_NONE,
            CU_TENSOR_MAP_L2_PROMOTION_NONE, CU_TENSOR_MAP_FLOAT_OOB_FILL_NONE);
    }
    mk(&tmw, Wo, DM, NH * DH, 64, 64);
    mk(&tmo, Wo, DM, NH * DH, 32, 128);
    mk(&tmq, Wq, NH * DH, DM, 32, 144); mk(&tmk, Wk, NH * DH, DM, 32, 144); mk(&tmv, Wv, NH * DH, DM, 32, 144);
    chain_kernel<<<96, CH_THREADS, SM_TOTAL>>>(tmx, tmq, tmk, tmv, tmo, tma, tmb, mem0, 0u);
    cudaLaunchConfig_t cfg = {};
    cfg.gridDim = dim3(SD_CTAS); cfg.blockDim = dim3(SD_THREADS); cfg.dynamicSmemBytes = SD_TOTAL; cfg.stream = cudaStreamPerThread;
    cudaLaunchAttribute at[1];
    at[0].id = cudaLaunchAttributeProgrammaticStreamSerialization; at[0].val.programmaticStreamSerializationAllowed = 1;
    cfg.attrs = at; cfg.numAttrs = 1;
    cudaLaunchKernelEx(&cfg, side_kernel, tmw, x, log_A_real, A_imag, C_real, C_imag, log_dt, D_skip, gate_w, out, 2);
}
```

```cpp
#include <cuda_runtime.h>
#include <cuda.h>
#include <cuda_bf16.h>
#include <stdint.h>

#define S_LEN 2048
#define DM 576
#define NH 32
#define DH 128
#define NMEM 8
#define SEG 32
#define NSEG 64
#define LQ 40
#define NS 128

typedef __nv_bfloat16 bf16;

__device__ __forceinline__ float bf(bf16 v) { return __bfloat162float(v); }
__device__ __forceinline__ bf16 tobf(float v) { return __float2bfloat16_rn(v); }
__device__ __forceinline__ float rbf(float v) { return __bfloat162float(__float2bfloat16_rn(v)); }

#define CH_THREADS 384
#define SPIN_LIMIT (1 << 17)
#define SM_X     0
#define XBUF     36864
#define SM_TOK   73728
#define TOKBUF   24576
#define SM_STASH 139264
#define SM_TS    (SM_STASH + 3072)
#define SM_WO    147456
#define SM_MEM   196608
#define SM_EX    205824
#define EXBUF    6144
#define SM_P     218112
#define SM_OST   122880
#define SM_PARK  219136
#define SM_O     223232
#define SM_XT    225280
#define SM_BAR   228352
#define SM_IL    (SM_BAR + 128)
#define SM_TG    (SM_IL + 256)
#define SM_TOTAL (SM_TG + 64)

#define ACC_X    36864
#define ACC_FULL 0x0020u
#define SLOT_OFF(sl) ((((sl) & 1) << 7) | (((sl) & 2) << 8))
__device__ __align__(65536) unsigned char g_acc[65536];
__device__ unsigned int g_init[96];
__device__ __align__(1024) uint4 g_last[36][2][32][32];
__device__ unsigned int g_epoch = 1;
__device__ __align__(128) unsigned int g_ts[128];
__device__ __align__(1024) bf16 g_otok[S_LEN * NH * DH];
__device__ __align__(1024) unsigned char g_tokx[96][8192];
__device__ __align__(128) unsigned int g_prog[96];
#define STAMP(i)
#define STAMPV(i, v)
#define GT(b, i)
#define PT(i)
#define STAMPB(i)

__device__ __forceinline__ uint32_t smem_u32(const void* p) { return (uint32_t)__cvta_generic_to_shared(p); }
__device__ __forceinline__ void ldsm_x4(uint32_t (&r)[4], uint32_t addr) {
    asm volatile("ldmatrix.sync.aligned.m8n8.x4.shared.b16 {%0,%1,%2,%3}, [%4];" : "=r"(r[0]), "=r"(r[1]), "=r"(r[2]), "=r"(r[3]) : "r"(addr) : "memory");
}
__device__ __forceinline__ void ldsm_x4_p(uint32_t (&r)[4], uint32_t addr, uint32_t skip) {
    asm volatile("{\n.reg .pred p;\nsetp.eq.u32 p, %5, 0;\n@p ldmatrix.sync.aligned.m8n8.x4.shared.b16 {%0,%1,%2,%3}, [%4];\n}\n" : "+r"(r[0]), "+r"(r[1]), "+r"(r[2]), "+r"(r[3]) : "r"(addr), "r"(skip) : "memory");
}
__device__ __forceinline__ void ldsm_x4_t(uint32_t (&r)[4], uint32_t addr) {
    asm volatile("ldmatrix.sync.aligned.m8n8.x4.trans.shared.b16 {%0,%1,%2,%3}, [%4];" : "=r"(r[0]), "=r"(r[1]), "=r"(r[2]), "=r"(r[3]) : "r"(addr) : "memory");
}
__device__ __forceinline__ uint32_t ldsm_x1_t(uint32_t addr) {
    uint32_t r; asm volatile("ldmatrix.sync.aligned.m8n8.x1.trans.shared.b16 {%0}, [%1];" : "=r"(r) : "r"(addr) : "memory"); return r;
}
__device__ __forceinline__ void ldsm_x2_t(uint32_t& r0, uint32_t& r1, uint32_t addr) {
    asm volatile("ldmatrix.sync.aligned.m8n8.x2.trans.shared.b16 {%0,%1}, [%2];" : "=r"(r0), "=r"(r1) : "r"(addr) : "memory");
}
__device__ __forceinline__ void stsm_x4(uint32_t addr, uint32_t r0, uint32_t r1, uint32_t r2, uint32_t r3) {
    asm volatile("stmatrix.sync.aligned.m8n8.x4.shared.b16 [%0], {%1,%2,%3,%4};" :: "r"(addr), "r"(r0), "r"(r1), "r"(r2), "r"(r3) : "memory");
}
__device__ __forceinline__ void stsm_x4_t(uint32_t addr, uint32_t r0, uint32_t r1, uint32_t r2, uint32_t r3) {
    asm volatile("stmatrix.sync.aligned.m8n8.x4.trans.shared.b16 [%0], {%1,%2,%3,%4};" :: "r"(addr), "r"(r0), "r"(r1), "r"(r2), "r"(r3) : "memory");
}
__device__ __forceinline__ void mma16816(float (&c)[4], const uint32_t (&a)[4], uint32_t b0, uint32_t b1) {
    asm("mma.sync.aligned.m16n8k16.row.col.f32.bf16.bf16.f32 {%0,%1,%2,%3}, {%4,%5,%6,%7}, {%8,%9}, {%0,%1,%2,%3};"
        : "+f"(c[0]), "+f"(c[1]), "+f"(c[2]), "+f"(c[3]) : "r"(a[0]), "r"(a[1]), "r"(a[2]), "r"(a[3]), "r"(b0), "r"(b1));
}
__device__ __forceinline__ void mma16816r(float (&c)[4], uint32_t a0, uint32_t a1, uint32_t a2, uint32_t a3, uint32_t b0, uint32_t b1) {
    asm("mma.sync.aligned.m16n8k16.row.col.f32.bf16.bf16.f32 {%0,%1,%2,%3}, {%4,%5,%6,%7}, {%8,%9}, {%0,%1,%2,%3};"
        : "+f"(c[0]), "+f"(c[1]), "+f"(c[2]), "+f"(c[3]) : "r"(a0), "r"(a1), "r"(a2), "r"(a3), "r"(b0), "r"(b1));
}
__device__ __forceinline__ void mma1688(float (&c)[4], uint32_t a0, uint32_t a1, uint32_t b0) {
    asm("mma.sync.aligned.m16n8k8.row.col.f32.bf16.bf16.f32 {%0,%1,%2,%3}, {%4,%5}, {%6}, {%0,%1,%2,%3};"
        : "+f"(c[0]), "+f"(c[1]), "+f"(c[2]), "+f"(c[3]) : "r"(a0), "r"(a1), "r"(b0));
}
__device__ __forceinline__ uint32_t pack_bf16(float lo, float hi) {
    uint32_t r; asm("cvt.rn.bf16x2.f32 %0, %1, %2;" : "=r"(r) : "f"(hi), "f"(lo)); return r;
}
__device__ __forceinline__ float bf_lo(uint32_t v) { return __uint_as_float(v << 16); }
__device__ __forceinline__ float bf_hi(uint32_t v) { return __uint_as_float(v & 0xffff0000u); }
__device__ __forceinline__ uint32_t max_bf2(uint32_t a, uint32_t b) { uint32_t r; asm("max.bf16x2 %0, %1, %2;" : "=r"(r) : "r"(a), "r"(b)); return r; }
__device__ __forceinline__ uint32_t maxabs_bf2(uint32_t a, uint32_t b) { uint32_t r; asm("max.NaN.xorsign.abs.bf16x2 %0, %1, %2;" : "=r"(r) : "r"(a), "r"(b)); return r; }
__device__ __forceinline__ float ex2(float x) { float r; asm("ex2.approx.ftz.f32 %0, %1;" : "=f"(r) : "f"(x)); return r; }
__device__ __forceinline__ void ld_relaxed128_p(uint4& v, const uint4* p, uint32_t pred) {
    asm volatile("{\n.reg .pred p;\nsetp.ne.u32 p, %5, 0;\n@p ld.relaxed.gpu.global.v4.u32 {%0,%1,%2,%3}, [%4];\n}\n" : "+r"(v.x), "+r"(v.y), "+r"(v.z), "+r"(v.w) : "l"(p), "r"(pred) : "memory");
}
__device__ __forceinline__ uint4 ld_relaxed128(const uint4* p) { uint4 v; asm volatile("ld.relaxed.gpu.global.v4.u32 {%0,%1,%2,%3}, [%4];" : "=r"(v.x), "=r"(v.y), "=r"(v.z), "=r"(v.w) : "l"(p) : "memory"); return v; }
__device__ __forceinline__ uint32_t ld_relaxed32(const uint32_t* p) { uint32_t v; asm volatile("ld.relaxed.gpu.global.u32 %0, [%1];" : "=r"(v) : "l"(p) : "memory"); return v; }
__device__ __forceinline__ void st_relaxed128(uint4* p, uint4 v) { asm volatile("st.relaxed.gpu.global.v4.u32 [%0], {%1,%2,%3,%4};" :: "l"(p), "r"(v.x), "r"(v.y), "r"(v.z), "r"(v.w) : "memory"); }
__device__ __forceinline__ void st_relaxed32(uint32_t* p, uint32_t v) { asm volatile("st.relaxed.gpu.global.u32 [%0], %1;" :: "l"(p), "r"(v) : "memory"); }
__device__ __forceinline__ void st_relaxed128_p(uint4* p, uint4 v, uint32_t skip) {
    asm volatile("{\n.reg .pred p;\nsetp.eq.u32 p, %5, 0;\n@p st.relaxed.gpu.global.v4.u32 [%0], {%1,%2,%3,%4};\n}\n" :: "l"(p), "r"(v.x), "r"(v.y), "r"(v.z), "r"(v.w), "r"(skip) : "memory");
}
__device__ __forceinline__ void st_relaxed64_p(void* p, uint32_t x, uint32_t y, uint32_t skip) {
    asm volatile("{\n.reg .pred p;\n.reg .b64 v;\nsetp.eq.u32 p, %3, 0;\nmov.b64 v, {%1,%2};\n@p st.relaxed.gpu.global.b64 [%0], v;\n}\n" :: "l"(p), "r"(x), "r"(y), "r"(skip) : "memory");
}
__device__ __forceinline__ void ld_relaxed64_p(uint2& v, const void* p, uint32_t pred) {
    asm volatile("{\n.reg .pred p;\n.reg .b64 v;\nsetp.ne.u32 p, %3, 0;\nmov.b64 v, {%0,%1};\n@p ld.relaxed.gpu.global.b64 v, [%2];\nmov.b64 {%0,%1}, v;\n}\n" : "+r"(v.x), "+r"(v.y) : "l"(p), "r"(pred) : "memory");
}
__device__ __forceinline__ uint2 ld_relaxed64(const void* p) {
    uint2 v; asm volatile("{\n.reg .b64 v;\nld.relaxed.gpu.global.b64 v, [%2];\nmov.b64 {%0,%1}, v;\n}\n" : "=r"(v.x), "=r"(v.y) : "l"(p) : "memory"); return v;
}
__device__ __forceinline__ void st_relaxed32_p(void* p, uint32_t v, uint32_t skip) {
    asm volatile("{\n.reg .pred p;\nsetp.eq.u32 p, %2, 0;\n@p st.relaxed.gpu.global.u32 [%0], %1;\n}\n" :: "l"(p), "r"(v), "r"(skip) : "memory");
}
__device__ __forceinline__ void bar_arrive_p(int id, int n, uint32_t skip) {
    asm volatile("{\n.reg .pred p;\nsetp.eq.u32 p, %2, 0;\n@p bar.arrive %0, %1;\n}\n" :: "r"(id), "r"(n), "r"(skip) : "memory");
}
__device__ __forceinline__ void bar_sync_p(int id, int n, uint32_t skip) {
    asm volatile("{\n.reg .pred p;\nsetp.eq.u32 p, %2, 0;\n@p bar.sync %0, %1;\n}\n" :: "r"(id), "r"(n), "r"(skip) : "memory");
}
__device__ __forceinline__ uint32_t movm(uint32_t x) { uint32_t r; asm volatile("movmatrix.sync.aligned.m8n8.trans.b16 %0, %1;" : "=r"(r) : "r"(x)); return r; }
__device__ __forceinline__ void sts32_p(uint32_t a, uint32_t v, uint32_t doit) {
    asm volatile("{\n.reg .pred p;\nsetp.ne.u32 p, %2, 0;\n@p st.shared.u32 [%0], %1;\n}\n" :: "r"(a), "r"(v), "r"(doit) : "memory");
}
__device__ __forceinline__ uint32_t pin(uint32_t x) { return __shfl_sync(0xffffffffu, x, threadIdx.x & 31); }
__device__ __forceinline__ void ldsm16_t(uint32_t (&b)[4][4], uint32_t a) {
    asm volatile("ldmatrix.sync.aligned.m8n8.x4.trans.shared.b16 {%0,%1,%2,%3}, [%16];\n"
                 "ldmatrix.sync.aligned.m8n8.x4.trans.shared.b16 {%4,%5,%6,%7}, [%16+512];\n"
                 "ldmatrix.sync.aligned.m8n8.x4.trans.shared.b16 {%8,%9,%10,%11}, [%16+1024];\n"
                 "ldmatrix.sync.aligned.m8n8.x4.trans.shared.b16 {%12,%13,%14,%15}, [%16+1536];\n"
        : "=r"(b[0][0]), "=r"(b[0][1]), "=r"(b[0][2]), "=r"(b[0][3]), "=r"(b[1][0]), "=r"(b[1][1]), "=r"(b[1][2]), "=r"(b[1][3]),
          "=r"(b[2][0]), "=r"(b[2][1]), "=r"(b[2][2]), "=r"(b[2][3]), "=r"(b[3][0]), "=r"(b[3][1]), "=r"(b[3][2]), "=r"(b[3][3]) : "r"(a) : "memory");
}
template<int ID> __device__ __forceinline__ void sched_fence(uint32_t never) { while (never == 0x7fffff00u + ID) { asm volatile("nanosleep.u32 64;" ::: "memory"); } }
__device__ __forceinline__ uint32_t opaque_u() { uint32_t v; asm volatile("mov.u32 %0, %%nsmid;" : "=r"(v)); return v; }
__device__ __forceinline__ uint32_t bar_red_or(int id, int n, uint32_t v) {
    uint32_t r; asm volatile("{\n.reg .pred p, q;\nsetp.ne.u32 p, %3, 0;\nbar.red.or.pred q, %1, %2, p;\nselp.u32 %0, 1, 0, q;\n}\n" : "=r"(r) : "r"(id), "r"(n), "r"(v) : "memory"); return r;
}
template<class T> __device__ __forceinline__ T* launder_p(T* p) { asm volatile("" : "+l"(p)); return p; }
__device__ __forceinline__ uint32_t mapa_u32(uint32_t addr, uint32_t rank) { uint32_t d; asm("mapa.shared::cluster.u32 %0, %1, %2;" : "=r"(d) : "r"(addr), "r"(rank)); return d; }
__device__ __forceinline__ uint32_t mapa_v(uint32_t addr, uint32_t rank) { uint32_t d; asm volatile("mapa.shared::cluster.u32 %0, %1, %2;" : "=r"(d) : "r"(addr), "r"(rank)); return d; }
__device__ __forceinline__ void st_async32(uint32_t addr, uint32_t v, uint32_t mbar) { asm volatile("st.async.shared::cluster.mbarrier::complete_tx::bytes.u32 [%0], %1, [%2];" :: "r"(addr), "r"(v), "r"(mbar) : "memory"); }
__device__ __forceinline__ void cluster_arrive() { asm volatile("barrier.cluster.arrive.release.aligned;" ::: "memory"); }
__device__ __forceinline__ void cluster_wait() { asm volatile("barrier.cluster.wait.acquire.aligned;" ::: "memory"); }
__device__ __forceinline__ void cp_async16(uint32_t dst, const void* src) { asm volatile("cp.async.cg.shared.global [%0], [%1], 16;" :: "r"(dst), "l"(src) : "memory"); }
__device__ __forceinline__ void cp_async_commit() { asm volatile("cp.async.commit_group;" ::: "memory"); }
template<int N> __device__ __forceinline__ void cp_async_wait() { asm volatile("cp.async.wait_group %0;" :: "n"(N) : "memory"); }
__device__ __forceinline__ void cp_async_wait0() { asm volatile("cp.async.wait_group 0;" ::: "memory"); }
__device__ __forceinline__ void mbar_init(uint32_t a, uint32_t cnt) { asm volatile("mbarrier.init.shared.b64 [%0], %1;" :: "r"(a), "r"(cnt) : "memory"); }
__device__ __forceinline__ void mbar_expect_tx(uint32_t a, uint32_t bytes) { asm volatile("mbarrier.arrive.expect_tx.shared.b64 _, [%0], %1;" :: "r"(a), "r"(bytes) : "memory"); }
__device__ __forceinline__ bool mbar_try(uint32_t a, uint32_t parity) {
    uint32_t ok; asm volatile("{\n.reg .pred p;\nmbarrier.try_wait.parity.shared::cta.b64 p, [%1], %2;\nselp.u32 %0, 1, 0, p;\n}\n" : "=r"(ok) : "r"(a), "r"(parity) : "memory"); return ok;
}
__device__ __forceinline__ void mbar_wait(uint32_t a, uint32_t parity) { int it = 0; bool more; do { more = ++it < SPIN_LIMIT; } while (!mbar_try(a, parity) && more); }
__device__ __forceinline__ void bar_sync(int id, int n) { asm volatile("bar.sync %0, %1;" :: "r"(id), "r"(n) : "memory"); }
__device__ __forceinline__ void bar_arrive(int id, int n) { asm volatile("bar.arrive %0, %1;" :: "r"(id), "r"(n) : "memory"); }
__device__ __forceinline__ void fence_async_smem() { asm volatile("fence.proxy.async.shared::cta;" ::: "memory"); }
__device__ __forceinline__ void sts32(uint32_t a, uint32_t v) { asm volatile("st.shared.u32 [%0], %1;" :: "r"(a), "r"(v) : "memory"); }
__device__ __forceinline__ void sts128(uint32_t a, uint4 v) { asm volatile("st.shared.v4.u32 [%0], {%1,%2,%3,%4};" :: "r"(a), "r"(v.x), "r"(v.y), "r"(v.z), "r"(v.w) : "memory"); }
__device__ __forceinline__ uint4 lds128(uint32_t a) { uint4 v; asm volatile("ld.shared.v4.u32 {%0,%1,%2,%3}, [%4];" : "=r"(v.x), "=r"(v.y), "=r"(v.z), "=r"(v.w) : "r"(a) : "memory"); return v; }
__device__ __forceinline__ uint32_t lds32(uint32_t a) { uint32_t v; asm volatile("ld.shared.u32 %0, [%1];" : "=r"(v) : "r"(a) : "memory"); return v; }
__device__ __forceinline__ uint32_t gtime_lo() { uint32_t t; asm volatile("mov.u32 %0, %globaltimer_lo;" : "=r"(t)); return t; }
__device__ __forceinline__ void wait_gtime(uint32_t tg) {
    asm volatile("{\n.reg .pred p, q;\n.reg .b64 t;\n.reg .b32 lo, hi, d, n;\nmov.b32 n, 300;\n"
                 "WG_%=:\nmov.u64 t, %%globaltimer;\nmov.b64 {lo, hi}, t;\nsub.s32 d, lo, %0;\nsub.s32 n, n, 1;\n"
                 "setp.gt.s32 q, n, 0;\nsetp.lt.and.s32 p, d, 0, q;\n@p bra.uni WG_%=;\n}\n" :: "r"(tg) : "memory");
}
__device__ __forceinline__ void delay_clk(int d) { uint32_t t0 = clock(); while ((int)(clock() - t0) < d) {} }

__device__ __forceinline__ uint64_t desc128(uint32_t addr) {
    return (uint64_t)((addr & 0x3FFFF) >> 4) | ((uint64_t)1 << 16) | ((uint64_t)64 << 32) | ((uint64_t)1 << 62);
}
template<int accum> __device__ __forceinline__ void wgmma_n32(float (&d)[16], const uint32_t (&a)[4], uint64_t desc) {
    if (accum) {
        asm volatile("{\n.reg .pred p;\nsetp.ne.b32 p, 1, 0;\n"
            "wgmma.mma_async.sync.aligned.m64n32k16.f32.bf16.bf16 {%0,%1,%2,%3,%4,%5,%6,%7,%8,%9,%10,%11,%12,%13,%14,%15}, {%16,%17,%18,%19}, %20, p, 1, 1, 0;\n}\n"
            : "+f"(d[0]), "+f"(d[1]), "+f"(d[2]), "+f"(d[3]), "+f"(d[4]), "+f"(d[5]), "+f"(d[6]), "+f"(d[7]),
              "+f"(d[8]), "+f"(d[9]), "+f"(d[10]), "+f"(d[11]), "+f"(d[12]), "+f"(d[13]), "+f"(d[14]), "+f"(d[15])
            : "r"(a[0]), "r"(a[1]), "r"(a[2]), "r"(a[3]), "l"(desc));
    } else {
        asm volatile("{\n.reg .pred p;\nsetp.ne.b32 p, 0, 0;\n"
            "wgmma.mma_async.sync.aligned.m64n32k16.f32.bf16.bf16 {%0,%1,%2,%3,%4,%5,%6,%7,%8,%9,%10,%11,%12,%13,%14,%15}, {%16,%17,%18,%19}, %20, p, 1, 1, 0;\n}\n"
            : "=f"(d[0]), "=f"(d[1]), "=f"(d[2]), "=f"(d[3]), "=f"(d[4]), "=f"(d[5]), "=f"(d[6]), "=f"(d[7]),
              "=f"(d[8]), "=f"(d[9]), "=f"(d[10]), "=f"(d[11]), "=f"(d[12]), "=f"(d[13]), "=f"(d[14]), "=f"(d[15])
            : "r"(a[0]), "r"(a[1]), "r"(a[2]), "r"(a[3]), "l"(desc));
    }
}
__device__ __forceinline__ float rcp_approx(float x) { float r; asm("rcp.approx.ftz.f32 %0, %1;" : "=f"(r) : "f"(x)); return r; }
__device__ __forceinline__ void wg_fence() { asm volatile("wgmma.fence.sync.aligned;" ::: "memory"); }
__device__ __forceinline__ void wg_commit() { asm volatile("wgmma.commit_group.sync.aligned;" ::: "memory"); }
__device__ __forceinline__ void wg_wait0() { asm volatile("wgmma.wait_group.sync.aligned 0;" ::: "memory"); }

#define SCALE_HI 0x3db53db5u
#define SCALE_LO 0x371e371eu
#define LOG2E 1.4426950408889634f
#define NEG_BIG2 0xce6ece6eu
__device__ __forceinline__ uint32_t scale_bf2(uint32_t x) {
    uint32_t t, r;
    asm("mul.rn.bf16x2 %0, %1, %2;" : "=r"(t) : "r"(x), "r"(SCALE_LO));
    asm("fma.rn.bf16x2 %0, %1, %2, %3;" : "=r"(r) : "r"(x), "r"(SCALE_HI), "r"(t));
    return r;
}
__device__ __forceinline__ void cluster_arrive_rx() { asm volatile("barrier.cluster.arrive.relaxed.aligned;" ::: "memory"); }
__device__ __forceinline__ uint32_t launder(uint32_t x) { asm volatile("" : "+r"(x)); return x; }
__device__ __forceinline__ void mbar_arrive(uint32_t a) { asm volatile("mbarrier.arrive.shared.b64 _, [%0];" :: "r"(a) : "memory"); }
__device__ __forceinline__ void mbar_wait_cl(uint32_t a, uint32_t parity) {
    int it = 0; uint32_t ok;
    do { asm volatile("{\n.reg .pred p;\nmbarrier.try_wait.parity.acquire.cluster.shared::cta.b64 p, [%1], %2;\nselp.u32 %0, 1, 0, p;\n}\n" : "=r"(ok) : "r"(a), "r"(parity) : "memory"); } while (!ok && ++it < SPIN_LIMIT);
}
__device__ __forceinline__ uint64_t desc_from(uint32_t lo) { return (uint64_t)lo | ((uint64_t)0x40000040u << 32); }
#define SB_OFF 1024u
#define DESC_LO(off) ((((SB_OFF + (uint32_t)(off)) & 0x3FFFFu) >> 4) | 0x10000u)
template<int N> struct ic { static constexpr int value = N; };
__device__ __forceinline__ uint32_t uni(uint32_t x) { return __shfl_sync(0xffffffffu, x, 0); }

__device__ __forceinline__ uint32_t pack_f16(float lo, float hi) { uint32_t r; asm("cvt.rn.f16x2.f32 %0, %1, %2;" : "=r"(r) : "f"(hi), "f"(lo)); return r; }
__device__ __forceinline__ void sts16(uint32_t a, uint16_t v) { asm volatile("st.shared.u16 [%0], %1;" :: "r"(a), "h"(v) : "memory"); }
__device__ __forceinline__ void sts64(uint32_t a, uint32_t x, uint32_t y) { asm volatile("st.shared.v2.u32 [%0], {%1,%2};" :: "r"(a), "r"(x), "r"(y) : "memory"); }
__device__ __forceinline__ void ld_relaxed32_p(uint32_t& v, const void* p, uint32_t pred) {
    asm volatile("{\n.reg .pred p;\nsetp.ne.u32 p, %2, 0;\n@p ld.relaxed.gpu.global.u32 %0, [%1];\n}\n" : "+r"(v) : "l"(p), "r"(pred) : "memory");
}
__device__ __forceinline__ uint2 lds64(uint32_t a) { uint2 v; asm volatile("ld.shared.v2.u32 {%0,%1}, [%2];" : "=r"(v.x), "=r"(v.y) : "r"(a) : "memory"); return v; }
__device__ __forceinline__ void mbar_wait2(uint32_t a, uint32_t pa, uint32_t b, uint32_t pb) {
    int it = 0; uint32_t ok;
    do { asm volatile("{\n.reg .pred p, q;\nmbarrier.try_wait.parity.shared::cta.b64 p, [%1], %2;\nmbarrier.try_wait.parity.shared::cta.b64 q, [%3], %4;\nand.pred p, p, q;\nselp.u32 %0, 1, 0, p;\n}\n"
                      : "=r"(ok) : "r"(a), "r"(pa), "r"(b), "r"(pb) : "memory"); } while (!ok && ++it < SPIN_LIMIT);
}
__device__ __forceinline__ float exd(float s, float m) { return ex2(__fmul_rn(__fsub_rn(s, m), LOG2E)); }
__device__ __forceinline__ uint32_t gtime_after(uint32_t z) {
    uint32_t t = 0; asm volatile("{\n.reg .pred p;\nsetp.eq.u32 p, %1, 0;\n@p mov.u32 %0, %%globaltimer_lo;\n}\n" : "+r"(t) : "r"(z)); return t;
}
__device__ __forceinline__ uint32_t ld_acquire32(const uint32_t* p) { uint32_t v; asm volatile("ld.acquire.gpu.global.u32 %0, [%1];" : "=r"(v) : "l"(p) : "memory"); return v; }
#define T_KPRE 3
#define BLK_Q(p) (((p) < 3 ? (p) : 8) * 2048)
#define BLK_K(p) (((p) < 3 ? 4 + (p) : 9) * 2048)
#define BLK_V(p) (((p) < 2 ? 3 + 4 * (p) : 8 + (p)) * 2048)
__device__ __forceinline__ uint32_t exp_bf2(uint32_t s) { return pack_bf16(ex2(bf_lo(s) * LOG2E), ex2(bf_hi(s) * LOG2E)); }
template<int MT, int LO, int HI>
__device__ __forceinline__ void tok_loadv(uint32_t tok, int eh, int lane, uint32_t (&bv)[8][4]) {
    const int r8 = lane & 7;
    const uint32_t va = MT ? tok + lane * 64 + ((r8 >> 1) << 4) : tok + (lane & 15) * 64 + (((lane >> 4) ^ (r8 >> 1)) << 4);
    const uint32_t o0 = eh ? BLK_V(2) : BLK_V(0), o1 = eh ? BLK_V(3) : BLK_V(1);
    #pragma unroll
    for (int n = LO; n < HI; n++) { if (MT) ldsm_x4_t(bv[n], (va ^ ((n & 3) << 4)) + (n < 4 ? o0 : o1)); else ldsm_x4_t(bv[n], (va ^ ((n & 1) << 5)) + BLK_V(n >> 1)); }
}
#define T_VPRE 4
template<int MT, class F>
__device__ __forceinline__ void tok_part1(uint32_t tok, int eh, int lane, uint32_t (&q)[8][4], uint32_t (&sp)[5][2], uint32_t (&pa)[5][2], uint32_t (&bv)[8][4], uint32_t& rng, F&& hold) {
    float e[5][4];
    constexpr int NK = MT ? 5 : 3;
    const int g = lane >> 2, t = lane & 3, mi = lane >> 3, r8 = lane & 7;
    #pragma unroll
    for (int nt = 1; nt < NK; nt++) { e[nt][0] = e[nt][1] = e[nt][2] = e[nt][3] = 0.f; }
    const uint32_t qa = tok + (16 * MT + (mi & 1) * 8 + r8) * 64 + (((mi >> 1) ^ (r8 >> 1)) << 4);
    const uint32_t ka = tok + r8 * 64 + ((mi ^ (r8 >> 1)) << 4);
    uint32_t b[4][NK][4];
    constexpr int PRE = MT ? T_KPRE : 4;
    #pragma unroll
    for (int k2 = 0; k2 < 4; k2++) {
        ldsm_x4(q[2 * k2], qa + BLK_Q(k2)); ldsm_x4(q[2 * k2 + 1], (qa ^ 32) + BLK_Q(k2));
        if (k2 < PRE) {
            #pragma unroll
            for (int nt = 1; nt < NK; nt++) ldsm_x4(b[k2][nt], ka + BLK_K(k2) + (nt - 1) * 512);
        }
    }
    hold();
    #pragma unroll
    for (int k2 = 0; k2 < 4; k2++) {
        if (k2 >= PRE) {
            #pragma unroll
            for (int nt = 1; nt < NK; nt++) ldsm_x4(b[k2][nt], ka + BLK_K(k2) + (nt - 1) * 512);
        }
        #pragma unroll
        for (int nt = 1; nt < NK; nt++) mma16816(e[nt], q[2 * k2], b[k2][nt][0], b[k2][nt][1]);
        #pragma unroll
        for (int nt = 1; nt < NK; nt++) mma16816(e[nt], q[2 * k2 + 1], b[k2][nt][2], b[k2][nt][3]);
    }
    #pragma unroll
    for (int nt = 1; nt < NK; nt++) asm volatile("" : "+f"(e[nt][0]), "+f"(e[nt][1]), "+f"(e[nt][2]), "+f"(e[nt][3]));
    #pragma unroll
    for (int nt = 1; nt < NK; nt++) {
        sp[nt][0] = nt < NK - 1 ? scale_bf2(pack_bf16(e[nt][0], e[nt][1])) : NEG_BIG2; sp[nt][1] = scale_bf2(pack_bf16(e[nt][2], e[nt][3]));
        rng = maxabs_bf2(nt == 1 ? sp[1][0] : (nt < NK - 1 ? maxabs_bf2(rng, sp[nt][0]) : rng), sp[nt][1]);
    }
    const uint32_t keep = (2 * t <= g ? 0x0000ffffu : 0u) | (2 * t + 1 <= g ? 0xffff0000u : 0u);
    sp[NK - 2][0] = (sp[NK - 2][0] & keep) | (NEG_BIG2 & ~keep);
    sp[NK - 1][1] = (sp[NK - 1][1] & keep) | (NEG_BIG2 & ~keep);
    #pragma unroll
    for (int nt = 1; nt < NK; nt++) { pa[nt][0] = nt < NK - 1 ? exp_bf2(sp[nt][0]) : 0u; pa[nt][1] = exp_bf2(sp[nt][1]); }
    tok_loadv<MT, 0, MT ? T_VPRE : 8>(tok, eh, lane, bv);
}
template<int MT, class F, class G, class H, class I>
__device__ __forceinline__ void tok_part2(uint32_t tok, uint32_t exl, uint32_t ost, int eh, int lane, const uint32_t (&q)[8][4], uint32_t (&sp)[5][2], uint32_t (&pa)[5][2], uint32_t (&bv)[8][4], uint32_t rng, bool vb,
                                          F&& wait_v, G&& duty, H&& pace, I&& wait_x) {
    constexpr int NK = MT ? 5 : 3;
    const int mi = lane >> 3, r8 = lane & 7;
    {
        float c[4][4];
        uint32_t b[4][4];
        ldsm16_t(b, exl + 2048);
        duty();
        #pragma unroll
        for (int j = 0; j < 4; j++) { c[j][0] = c[j][1] = c[j][2] = c[j][3] = 0.f; }
        #pragma unroll
        for (int k2 = 0; k2 < 4; k2++) { mma16816(c[(2 * k2) & 3], q[2 * k2], b[k2][0], b[k2][1]); mma16816(c[(2 * k2 + 1) & 3], q[2 * k2 + 1], b[k2][2], b[k2][3]); }
        sp[0][0] = scale_bf2(pack_bf16((c[0][0] + c[1][0]) + (c[2][0] + c[3][0]), (c[0][1] + c[1][1]) + (c[2][1] + c[3][1])));
        sp[0][1] = scale_bf2(pack_bf16((c[0][2] + c[1][2]) + (c[2][2] + c[3][2]), (c[0][3] + c[1][3]) + (c[2][3] + c[3][3])));
    }
    pa[0][0] = exp_bf2(sp[0][0]); pa[0][1] = exp_bf2(sp[0][1]);
    rng = maxabs_bf2(maxabs_bf2(rng, sp[0][0]), sp[0][1]);
    if (__builtin_expect(__any_sync(0xffffffffu, ((rng & 0x7fff7fffu) + 0x3ddf3ddfu) & 0x80008000u), 0)) {
        uint32_t m0 = sp[0][0], m1 = sp[0][1];
        #pragma unroll
        for (int nt = 1; nt < NK; nt++) { if (nt < NK - 1) m0 = max_bf2(m0, sp[nt][0]); m1 = max_bf2(m1, sp[nt][1]); }
        uint32_t mm = max_bf2(__byte_perm(m0, m1, 0x5410), __byte_perm(m0, m1, 0x7632));
        mm = max_bf2(mm, __shfl_xor_sync(0xffffffffu, mm, 1));
        mm = max_bf2(mm, __shfl_xor_sync(0xffffffffu, mm, 2));
        #pragma unroll
        for (int nt = 0; nt < NK; nt++) {
            if (nt < NK - 1) pa[nt][0] = pack_bf16(exd(bf_lo(sp[nt][0]), bf_lo(mm)), exd(bf_hi(sp[nt][0]), bf_lo(mm)));
            pa[nt][1] = pack_bf16(exd(bf_lo(sp[nt][1]), bf_hi(mm)), exd(bf_hi(sp[nt][1]), bf_hi(mm)));
        }
    }
    tok_loadv<MT, MT ? T_VPRE : 8, 8>(tok, eh, lane, bv);
    wait_v();
    constexpr int NQ = MT ? 2 : 4;
    float o[NQ][4][4], l[4] = {0.f, 0.f, 0.f, 0.f};
    const uint32_t ONE = 0x3F803F80u;
    mma16816r(l, pa[1][0], pa[1][1], pa[2][0], pa[2][1], ONE, ONE);
    if (MT) mma16816r(l, pa[3 % NK][0], pa[3 % NK][1], pa[4 % NK][0], pa[4 % NK][1], ONE, ONE);
    mma1688(l, pa[0][0], pa[0][1], ONE);
    #pragma unroll
    for (int j = 0; j < NQ; j++) {
        uint32_t bm[4];
        ldsm_x4(bm, exl + 4096 + (MT ? eh * 1024 : 0) + 512 * j);
        #pragma unroll
        for (int n = 0; n < 4; n++) {
            o[j][n][0] = o[j][n][1] = o[j][n][2] = o[j][n][3] = 0.f;
            if (MT) mma16816r(o[j][n], pa[1][0], pa[1][1], pa[2][0], pa[2][1], bv[4 * j + n][0], bv[4 * j + n][1]);
            else mma16816r(o[j][n], pa[1][0], pa[1][1], pa[2][0], pa[2][1], bv[2 * j + (n >> 1)][2 * (n & 1)], bv[2 * j + (n >> 1)][2 * (n & 1) + 1]);
        }
        if (MT) {
            #pragma unroll
            for (int n = 0; n < 4; n++) mma16816r(o[j][n], pa[3 % NK][0], pa[3 % NK][1], pa[4 % NK][0], pa[4 % NK][1], bv[4 * j + n][2], bv[4 * j + n][3]);
        }
        #pragma unroll
        for (int n = 0; n < 4; n++) mma1688(o[j][n], pa[0][0], pa[0][1], bm[n]);
    }
    #pragma unroll
    for (int j = 0; j < NQ; j++) asm volatile("" : "+f"(o[j][0][0]), "+f"(o[j][1][0]), "+f"(o[j][2][0]), "+f"(o[j][3][0]));
    asm volatile("" : "+f"(l[0]), "+f"(l[2]));
    wait_x();
    bar_arrive_p(12, 384, !vb);
    pace();
    const float i0 = rcp_approx(l[0]), i1 = rcp_approx(l[2]);
    const uint32_t oa = ost + ((mi & 1) * 8 + r8) * 128 + (((mi >> 1) ^ r8) << 4);
    #pragma unroll
    for (int j = 0; j < NQ; j++) {
        stsm_x4((oa ^ ((j & 1) << 6)) + (j >> 1) * 4096, pack_bf16(o[j][0][0] * i0, o[j][0][1] * i0), pack_bf16(o[j][0][2] * i1, o[j][0][3] * i1), pack_bf16(o[j][1][0] * i0, o[j][1][1] * i0), pack_bf16(o[j][1][2] * i1, o[j][1][3] * i1));
        stsm_x4((oa ^ (((j & 1) << 6) | 32)) + (j >> 1) * 4096, pack_bf16(o[j][2][0] * i0, o[j][2][1] * i0), pack_bf16(o[j][2][2] * i1, o[j][2][3] * i1), pack_bf16(o[j][3][0] * i0, o[j][3][1] * i0), pack_bf16(o[j][3][2] * i1, o[j][3][3] * i1));
    }
}

template<int OA>
__device__ __forceinline__ uint32_t send_main(float c0, float c1, float c2, float c3, uint32_t a, uint32_t l16) {
    uint32_t w2;
    asm volatile("{\n.reg .pred q, pl, ph;\n.reg .b64 pa;\n.reg .b32 t, w0, w1;\n.reg .f32 x, y, z;\n"
                 "and.b32 t, %7, 0x30;\nsetp.eq.u32 q, t, 0;\nand.b32 t, %7, 0x70;\nsetp.eq.u32 ph, t, 0;\nxor.pred pl, q, ph;\n"
                 "selp.f32 x, 0f00010000, %4, pl;\nselp.f32 y, 0f00010000, %6, ph;\nselp.f32 z, %6, %4, ph;\n"
                 "cvt.rn.bf16x2.f32 w0, x, %3;\ncvt.rn.bf16x2.f32 w1, y, %5;\ncvt.rn.bf16x2.f32 %0, 0f00010000, z;\n"
                 "mov.b64 pa, {%1, %2};\n"
                 "red.relaxed.gpu.global.add.noftz.bf16x2 [pa+%8], w0;\nred.relaxed.gpu.global.add.noftz.bf16x2 [pa+%9], w1;\n}\n"
        : "=r"(w2) : "r"(a), "r"((uint32_t)((uint64_t)g_acc >> 32)), "f"(c0), "f"(c1), "f"(c2), "f"(c3), "r"(l16), "n"(OA), "n"(OA + 256) : "memory");
    return w2;
}
template<int OB>
__device__ __forceinline__ void send_extra(uint32_t w2, uint32_t b, uint32_t l16) {
    asm volatile("{\n.reg .pred q;\n.reg .b64 pb;\n.reg .b32 t;\nand.b32 t, %3, 0x30;\nsetp.eq.u32 q, t, 0;\nmov.b64 pb, {%0, %1};\n"
                 "@q red.relaxed.gpu.global.add.noftz.bf16x2 [pb+%4], %2;\n}\n"
        :: "r"(b), "r"((uint32_t)((uint64_t)g_acc >> 32)), "r"(w2), "r"(l16), "n"(OB) : "memory");
}
#define X_AT 0
__device__ __forceinline__ uint32_t send_ua(uint32_t tile) { return (uint32_t)(uint64_t)g_acc + tile * 1024; }
__device__ __forceinline__ uint32_t send_ub(uint32_t tile) { return (uint32_t)(uint64_t)g_acc + ACC_X + (tile >> 1) * 1024 + (tile & 1) * 256; }
__device__ __forceinline__ void lds_il(float& il, float& ih, uint32_t a) {
    uint32_t x, y; asm volatile("ldmatrix.sync.aligned.m8n8.x2.shared.b16 {%0,%1}, [%2];" : "=r"(x), "=r"(y) : "r"(a) : "memory");
    il = __uint_as_float(x); ih = __uint_as_float(y);
}
template<bool AUX>
__device__ __forceinline__ uint32_t stage_w(const uint32_t (&wo)[8][4], uint32_t ol, uint32_t tile, uint32_t so, uint32_t l16, uint32_t nv, uint32_t ila, uint32_t& sx) {
    float il, ih;
    uint32_t b[4][4], sa;
    float c[2][4];
    auto addr = [&] {
        const uint32_t ll = AUX ? l16 : l16 | (__float_as_uint(c[0][0]) & nv);
        sa = (ll >> 2) + (send_ua(tile) + so); sx = (ll >> 4) + (send_ub(tile) + so);
    };
    ldsm16_t(b, ol);
    lds_il(il, ih, ila);
    if (AUX) addr(); else sched_fence<0>(nv);
    #pragma unroll
    for (int i = 0; i < 2; i++) c[i][0] = c[i][1] = c[i][2] = c[i][3] = 0.f;
    #pragma unroll
    for (int j = 0; j < 4; j++) {
        if (!AUX && j == 3) addr();
        mma16816(c[0], wo[2 * j], b[j][0], b[j][1]); mma16816(c[1], wo[2 * j + 1], b[j][2], b[j][3]);
    }
    if (AUX) { asm volatile("" : "+f"(c[0][0]), "+f"(c[1][0])); sched_fence<4>(nv); bar_arrive(12, 384); }
    return send_main<0>((c[0][0] + c[1][0]) * il, (c[0][1] + c[1][1]) * ih, (c[0][2] + c[1][2]) * il, (c[0][3] + c[1][3]) * ih, sa, l16);
}
__device__ __forceinline__ void wgmma_n16(float (&d)[8], const uint32_t (&a)[4], uint64_t desc) {
    asm volatile("{\n.reg .pred p;\nsetp.ne.b32 p, 1, 0;\n"
        "wgmma.mma_async.sync.aligned.m64n16k16.f32.bf16.bf16 {%0,%1,%2,%3,%4,%5,%6,%7}, {%8,%9,%10,%11}, %12, p, 1, 1, 0;\n}\n"
        : "+f"(d[0]), "+f"(d[1]), "+f"(d[2]), "+f"(d[3]), "+f"(d[4]), "+f"(d[5]), "+f"(d[6]), "+f"(d[7])
        : "r"(a[0]), "r"(a[1]), "r"(a[2]), "r"(a[3]), "l"(desc));
}

template<int N> __device__ __forceinline__ void code_pad(uint32_t nv) {
    if (N && nv == 0x7fffffe0u + N % 16) {
        float v = __uint_as_float(nv);
        #pragma unroll
        for (int i = 0; i < N; i++) asm volatile("fma.rn.f32 %0, %0, %0, %0;" : "+f"(v));
        sts32_p(0u, __float_as_uint(v), nv);
    }
}
#define PAD_T0 4
#define PAD_T1 0
#define PAD_S 355
#define PAD_P 132
#define BAR_PRO 1
#define BAR_MEM 2
#define BAR_P   3
#define BAR_PRJ 4
#define BAR_VGO 7
#define BAR_X0  7
#define BAR_S   9
#define BAR_P2  10
#define BAR_O   11
#define BAR_V   12
#define VGO_AT 9
#define TP_N 36
#define REG_P 200
#define WO_PRE 3
#define WO_REP 2
#define X_FIRST 0
#define VF0 1
#define X_PF 0
#ifndef M_RES
#define M_RES 5
#endif
#ifndef M_LAG
#define M_LAG 2
#endif
#ifndef M_ARR
#define M_ARR -1
#endif
#define G1_0 128
#define G1_NS 1152

__global__ void __cluster_dims__(3, 1, 1) __launch_bounds__(CH_THREADS, 1)
chain_kernel(const __grid_constant__ CUtensorMap tmx, const __grid_constant__ CUtensorMap tmq, const __grid_constant__ CUtensorMap tmk,
             const __grid_constant__ CUtensorMap tmv, const __grid_constant__ CUtensorMap tmo,
             const __grid_constant__ CUtensorMap tma, const __grid_constant__ CUtensorMap tmb, const bf16* __restrict__ mem0, const uint32_t nv_) {
    extern __shared__ __align__(1024) unsigned char smem[];
    const uint32_t sb = smem_u32(smem);
    const int tid = threadIdx.x, lane = tid & 31;
    const int warp = __shfl_sync(0xffffffffu, tid >> 5, 0);
    const uint32_t nv = __shfl_sync(0xffffffffu, nv_ * tid, 0);
    const int h = blockIdx.x / 3, r = blockIdx.x % 3;
    const int mi = lane >> 3, r8 = lane & 7;
    const uint32_t bX = sb + SM_BAR, bTOK = bX + 16, bEX = bX + 40, bW = bX + 64, bEV = bX + 104, bFREE = bX + 32, bMEM = bX + 56, bWA = bX + 120;
    const int nqk = r < 2 ? 6 : 4;
    if (lane == 0 && warp < 7) asm volatile("prefetch.param.tensormap [%0];" :: "l"(__cvta_generic_to_grid_constant(&tmx) + 128 * warp) : "memory");
    if ((sb & 0xFFFFFFu) != SB_OFF) __trap();
    asm volatile("griddepcontrol.launch_dependents;");
    if (tid == 0 && blockIdx.x == 0) GT(40, 0);
    if (tid == 0) PT(0);

    #define W_STG(g, j) ((g) == 2 && (j) == 3 ? SM_EX : SM_TOK + ((g) % 3) * 36864 + (j) * 9216)
    auto load_w = [&](int g) {
        #pragma unroll
        for (int j = 0; j < 4; j++) {
            const int m = r < 2 ? (j < 3 ? r : 2) : (j < 2 ? j : 2), p = r < 2 ? (j < 3 ? j : r) : (j < 2 ? 3 : j);
            asm volatile("cp.async.bulk.tensor.2d.shared::cluster.global.mbarrier::complete_tx::bytes [%0], [%1, {%3, %4}], [%2];"
                :: "r"(sb + W_STG(g, j)), "l"(m == 0 ? &tmq : (m == 1 ? &tmk : &tmv)), "r"(bW + 8 * g), "r"(h * DH + p * 32), "r"(g * 144) : "memory");
        }
    };
    auto load_wo = [&](int lo, int hi, uint32_t bar) {
        #pragma unroll
        for (int i = lo; i < hi; i++)
            asm volatile("cp.async.bulk.tensor.2d.shared::cluster.global.mbarrier::complete_tx::bytes [%0], [%1, {%3, %4}], [%2];"
                :: "r"(sb + SM_WO + i * 8192), "l"(&tmo), "r"(bar), "r"(192 * r + 32 * i), "r"(h * DH) : "memory");
    };
    if (warp == 11) {
        if (lane == 0) {
            #pragma unroll
            for (int g = 0; g < 3; g++) mbar_init(bW + 8 * g, 1);
            mbar_init(bX, 1); mbar_init(bX + 8, 1);
            asm volatile("fence.mbarrier_init.release.cluster;" ::: "memory");
        }
        __syncwarp();
        bar_arrive(0, 384);
        if (lane == 0) {
            #pragma unroll 1
            for (int g = 0; g < 3; g++) {
                PT(1 + g);
                mbar_expect_tx(bW + 8 * g, 36864);
                if (X_FIRST == 0) load_w(g);
                if (g < 2) {
                    mbar_expect_tx(bX + 8 * g, XBUF);
                    #pragma unroll
                    for (int c = 0; c < 3; c++)
                        asm volatile("cp.async.bulk.tensor.3d.shared::cluster.global.mbarrier::complete_tx::bytes [%0], [%1, {%3, %4, %5}], [%2];"
                            :: "r"(sb + SM_X + g * XBUF + c * 12288), "l"(&tmx), "r"(bX + 8 * g), "r"(0), "r"(g * SEG), "r"(3 * c) : "memory");
                }
                if (X_FIRST) load_w(g);
            }
            PT(4);
        }
        __syncwarp();
    }
    const uint32_t zs = 3 * blockIdx.x + (r8 >> 1);
    const uint32_t zoff = (r8 < 6 ? (zs >> 3) * 1024 + ((zs >> 2) & 1) * 256 + (zs & 3) * 32 : ACC_X + (blockIdx.x >> 1) * 1024 + (blockIdx.x & 1) * 256) + (lane & 1) * 16;
    const uint32_t zskip = r8 >= 6 && blockIdx.x >= 36;
    if (warp == 9) {
        bar_arrive(0, 384);
        const unsigned ep = ld_relaxed32(&g_epoch);
        unsigned long long o0 = 0, o1 = 0;
        if (!zskip) {
            asm volatile("atom.relaxed.gpu.global.exch.b64 %0, [%1], 0;" : "=l"(o0) : "l"(g_acc + zoff + SLOT_OFF(mi)) : "memory");
            asm volatile("atom.relaxed.gpu.global.exch.b64 %0, [%1], 0;" : "=l"(o1) : "l"(g_acc + zoff + SLOT_OFF(mi) + 8) : "memory");
        }
        const uint32_t done = __reduce_or_sync(0xffffffffu, (uint32_t)(o0 | o1) & nv);
        if (lane == 0) asm volatile("st.relaxed.gpu.global.u32 [%0], %1;" :: "l"(&g_init[blockIdx.x]), "r"(ep + done) : "memory");
    }
    if (tid == 320) {
        #pragma unroll
        for (int i = 2; i < 16; i++) if (i < 8 || i > 10) mbar_init(bX + 8 * i, (i == 5 || i == 6) ? 1 + nqk : (i == 13 || i == 14 ? 9 - nqk : 1));
        asm volatile("fence.mbarrier_init.release.cluster;" ::: "memory");
        mbar_expect_tx(bW + 24, 36864); mbar_expect_tx(bW + 32, 32768); mbar_expect_tx(bWA, 16384);
        sts32(sb + SM_TG, 0u);
    }
    if (warp != 11 && warp != 9) bar_sync(0, 384);
    const uint32_t pw0 = ((mi >> 1) * 8 + r8) * 64 + (((2 * (warp & 1) + (mi & 1)) ^ (r8 >> 1)) << 4);
    auto tok_publish = [&](int tb, int k) {
        const uint32_t src = sb + SM_TOK + tb * TOKBUF + r * 8192, bar = bTOK + 8 * tb;
        if (k == 1) asm volatile("{\n.reg .pred p;\nelect.sync _|p, 0xffffffff;\n@p mbarrier.arrive.expect_tx.shared.b64 _, [%0], 16384;\n}\n" :: "r"(bar) : "memory");
        asm volatile("{\n.reg .pred p;\nelect.sync _|p, 0xffffffff;\n"
                     "@p cp.async.bulk.shared::cluster.shared::cta.mbarrier::complete_tx::bytes [%0], [%1], 8192, [%2];\n}\n"
            :: "r"(mapa_u32(src, (r + k) % 3)), "r"(src), "r"(mapa_u32(bar, (r + k) % 3)) : "memory");
    };
    if (warp < 8) {
        asm volatile("setmaxnreg.inc.sync.aligned.u32 %0;" :: "n"(REG_P));
        uint32_t wf[36][4];
        float ta0[16], ta1[16];
        auto group = [&](auto gg) {
            constexpr int g = gg.value;
            const uint32_t wl = sb + pw0 + W_STG(g, warp >> 1);
            mbar_wait(bW + 8 * g, 0);
            if (tid == 0) PT(5 + g);
            if (g) wg_wait0();
            if (g == 1) sts128(sb + SM_PARK + tid * 16, make_uint4(wf[0][0], wf[0][1], wf[0][2], wf[0][3]));
            #pragma unroll
            for (int i = 0; i < 9; i++) ldsm_x4_t(wf[9 * g + i], wl + i * 1024);
            if (g != 1) fence_async_smem();
            if (g == 0) { bar_arrive(BAR_X0, 288); mbar_wait(bX, 0); mbar_wait(bX + 8, 0); if (tid == 0) PT(9); }
            if (g == 2) bar_arrive(BAR_X0 + 1, 288);
            if (g == 3) cluster_arrive_rx();
            wg_fence();
            #pragma unroll
            for (int i = 9 * g; i < 9 * g + 9; i++) {
                if (i == 0) wgmma_n32<0>(ta0, wf[0], desc_from(DESC_LO(SM_X))); else wgmma_n32<1>(ta0, wf[i], desc_from(DESC_LO(SM_X) + (i >> 2) * 256 + (i & 3) * 2));
            }
            if (g == 3) wg_commit();
            #pragma unroll
            for (int i = 9 * g; i < 9 * g + 9; i++) {
                if (i == 0) wgmma_n32<0>(ta1, wf[0], desc_from(DESC_LO(SM_X + XBUF))); else wgmma_n32<1>(ta1, wf[i], desc_from(DESC_LO(SM_X + XBUF) + (i >> 2) * 256 + (i & 3) * 2));
            }
            wg_commit();
        };
        if (tid == 0) PT(10);
        code_pad<PAD_P>(nv);
        group(ic<0>()); group(ic<1>()); group(ic<2>()); group(ic<3>());
        if (tid == 0) PT(11);
        const uint32_t pw = pin(pw0);
        auto tp_store = [&](const float (&acc)[16], uint32_t off) {
            const uint32_t ta = pw + launder(sb + off + (warp >> 1) * 2048);
            stsm_x4_t(ta, pack_bf16(acc[0], acc[1]), pack_bf16(acc[2], acc[3]), pack_bf16(acc[4], acc[5]), pack_bf16(acc[6], acc[7]));
            stsm_x4_t(ta + 1024, pack_bf16(acc[8], acc[9]), pack_bf16(acc[10], acc[11]), pack_bf16(acc[12], acc[13]), pack_bf16(acc[14], acc[15]));
        };
        cluster_wait();
        asm volatile("wgmma.wait_group.sync.aligned 1;" ::: "memory");
        #pragma unroll
        for (int i = 0; i < 16; i++) asm volatile("" : "+f"(ta0[i]) :: "memory");
        tp_store(ta0, SM_TOK + r * 8192);
        if (warp == 0) { bar_sync(BAR_PRJ, 256); fence_async_smem(); tok_publish(0, 1); tok_publish(0, 2); } else bar_arrive(BAR_PRJ, 256);
        wg_wait0();
        tp_store(ta1, SM_TOK + TOKBUF + r * 8192);
        { const uint4 v = lds128(sb + SM_PARK + tid * 16); wf[0][0] = v.x; wf[0][1] = v.y; wf[0][2] = v.z; wf[0][3] = v.w; sts32_p(v.x, v.y, nv); }
        if (tid == 0) PT(12);
        const uint32_t l16 = pin(lane * 16), sbl = sb + l16, l4w = pin(sb + warp * 256 + lane * 4);
        uint32_t wo[8][4];
        const int exo = r < 2 ? (warp < 6 ? r * 2048 : 4096 + (2 * r - 6) * 256) : (warp < 2 ? 6 * 256 : (warp < 4 ? 2048 + 4 * 256 : 4096));
        const bool isqk = warp < nqk;
        const uint32_t exbar = isqk ? bEX : bEV;
        uint32_t vf[2][4];
        auto prep = [&](int s) {
            const uint32_t va = pw + launder(sb + SM_TOK + (s & 1) * TOKBUF + BLK_V(warp >> 1));
            mbar_wait(bTOK + 8 * (s & 1), (s >> 1) & 1);
            ldsm_x4_t(vf[0], va); ldsm_x4_t(vf[1], va + 1024);
            sts32_p(vf[0][0], vf[1][0], nv);
        };
        if (VF0) { vf[0][0] = vf[0][1] = vf[0][2] = vf[0][3] = vf[1][0] = vf[1][1] = vf[1][2] = vf[1][3] = nv; } else prep(0);
        if (tid == 0) PT(13);
        bar_sync(BAR_MEM, 352);
        for (int s = 0; ; s++) {
            const int par = s & 1;
            const uint32_t wa = pw + launder(sb + SM_WO + (warp >> 1) * 8192);
            const uint32_t exu = launder(SM_EX + par * EXBUF);
            {
                float acc[4][4];
                #pragma unroll
                for (int i = 0; i < 4; i++) { acc[i][0] = acc[i][1] = acc[i][2] = acc[i][3] = 0.f; }
                bar_sync_p(BAR_VGO, 256, isqk);
                #pragma unroll
                for (int i2 = 0; i2 < 18; i2++) {
                    uint32_t b[4];
                    ldsm_x4_t(b, sbl + SM_MEM + i2 * 512);
                    if (i2 == VGO_AT) bar_arrive_p(BAR_VGO, 256, !isqk);
                    mma16816(acc[(2 * i2) & 3], wf[2 * i2], b[0], b[1]);
                    mma16816(acc[(2 * i2 + 1) & 3], wf[2 * i2 + 1], b[2], b[3]);
                }
                float q[4];
                #pragma unroll
                for (int i = 0; i < 4; i++) q[i] = (acc[0][i] + acc[1][i]) + (acc[2][i] + acc[3][i]);
                const uint32_t lo = pack_bf16(q[0], q[1]), hi = pack_bf16(q[2], q[3]);
                const uint32_t exl = l4w + launder(exu + exo), bar = exbar + par * 8;
                #pragma unroll
                for (int k = 1; k < 3; k++) {
                    const uint32_t exd = mapa_u32(exl, (r + k) % 3), exb = mapa_u32(bar, (r + k) % 3);
                    st_async32(exd, lo, exb); st_async32(exd + 128, hi, exb);
                }
                sts32(exl, lo); sts32(exl + 128, hi);
                __syncwarp();
                asm volatile("{\n.reg .pred p;\nelect.sync _|p, 0xffffffff;\n@p mbarrier.arrive.shared.b64 _, [%0];\n}\n" :: "r"(bar) : "memory");
                if (s < NSEG - 1) bar_sync_p(BAR_PRO, 32 * nqk, !isqk);
            }
            if (__builtin_expect(s == NSEG - 1, 0)) break;
            if (__builtin_expect(s == 0, 0)) { if (VF0) prep(0); mbar_wait(bW + 32, 0); }
            #pragma unroll
            for (int i = 0; i < WO_PRE; i++) ldsm_x4_t(wo[i], wa + i * 1024);
            #pragma unroll
            for (int k = 0; k < WO_REP; k++) mbar_wait(bEX + 8 * par, (s >> 1) & 1);
            #pragma unroll
            for (int i = WO_PRE; i < 8; i++) ldsm_x4_t(wo[i], wa + i * 1024);
            mbar_wait(bEV + 8 * par, (s >> 1) & 1);
            const uint32_t vm0 = lds32(l4w + exu + 4096), vm1 = lds32(l4w + exu + 4096 + 128);
            const uint32_t big = bar_red_or(BAR_P, 352, 0u);
            uint32_t pb[4]; ldsm_x4_t(pb, sbl + SM_P);
            uint32_t pm = ldsm_x1_t(sbl + SM_P + 512);
            float o0[4] = {0.f, 0.f, 0.f, 0.f}, o1[4] = {0.f, 0.f, 0.f, 0.f}, o2[4] = {0.f, 0.f, 0.f, 0.f};
            if (__builtin_expect(big, 0)) {
                bar_sync(BAR_P2, 352);
                ldsm_x4_t(pb, sbl + SM_P); pm = ldsm_x1_t(sbl + SM_P + 512);
            }
            mma16816(o0, vf[0], pb[0], pb[1]);
            mma16816(o1, vf[1], pb[2], pb[3]);
            mma1688(o2, vm0, vm1, pm);
            uint32_t oa = pm;
            #pragma unroll
            for (int i = 0; i < 8; i++) oa ^= wo[i][0];
            oa = l4w | (oa & nv);
            sts32(oa + SM_O, pack_bf16((o0[0] + o1[0]) + o2[0], (o0[1] + o1[1]) + o2[1]));
            sts32(oa + SM_O + 128, pack_bf16((o0[2] + o1[2]) + o2[2], (o0[3] + o1[3]) + o2[3]));
            const uint32_t xd = uni(DESC_LO(SM_X) + par * (XBUF >> 4));
            bar_sync(BAR_O, 352);
            uint32_t sx;
            const uint32_t w2 = stage_w<false>(wo, sbl + SM_O, 12 * r + warp, SLOT_OFF(s + 1), l16, nv, sbl + SM_IL, sx);
            if (X_AT == 0) send_extra<0>(w2, sx, l16);
            STAMP(warp);
            bar_sync(BAR_V, 384);
            wg_fence();
            STAMP(12);
            #pragma unroll
            for (int i = 0; i < TP_N; i++) {
                if (X_AT && i == X_AT) send_extra<0>(w2, sx, l16);
                if (i == 0) wgmma_n32<0>(ta1, wf[0], desc_from(xd));
                else wgmma_n32<1>(ta1, wf[i], desc_from(xd + (i >> 2) * 256 + (i & 3) * 2));
            }
            wg_commit();
            prep(s + 1);
            wg_wait0();
            tp_store(ta1, SM_TOK + par * TOKBUF + r * 8192);
            STAMP(13 + (warp >> 2));
            bar_sync(BAR_MEM, 352);
        }
        {
            const uint32_t tag = ld_relaxed32(&g_init[blockIdx.x]) & 1u, lq = l16 | (tag & nv), pq = pw | (tag & nv);
            uint4* d0 = &g_last[12 * r + warp][0][h][lq >> 4];
            uint4* d1 = &g_last[12 * r + 8 + (warp & 3)][warp >> 2][h][lq >> 4];
            st_relaxed128(d0, make_uint4(tag ^ 1, 0, 0, 0)); st_relaxed128(d0 + 1024, make_uint4(tag ^ 1, 0, 0, 0)); st_relaxed128(d1, make_uint4(tag ^ 1, 0, 0, 0));
            uint32_t wx[8][4];
            #pragma unroll
            for (int i = 0; i < 8; i++) { ldsm_x4_t(wo[i], pq + sb + SM_WO + (warp >> 1) * 8192 + i * 1024); ldsm_x4_t(wx[i], pq + sb + SM_WO + (4 + ((warp >> 1) & 1)) * 8192 + i * 1024); }
            float c2[8];
            #pragma unroll
            for (int i = 0; i < 8; i++) c2[i] = 0.f;
            const uint32_t od = uni(DESC_LO(SM_OST) + (warp >> 2) * 128);
            mbar_wait(bMEM, 1);
            wg_fence();
            #pragma unroll
            for (int i = 0; i < 8; i++) {
                if (i == 0) wgmma_n32<0>(ta1, wo[0], desc_from(DESC_LO(SM_OST)));
                else wgmma_n32<1>(ta1, wo[i], desc_from(DESC_LO(SM_OST) + (i >> 2) * 256 + (i & 3) * 2));
            }
            wg_commit();
            #pragma unroll
            for (int i = 0; i < 8; i++) wgmma_n16(c2, wx[i], desc_from(od + (i >> 2) * 256 + (i & 3) * 2));
            wg_commit();
            auto put = [&](uint4* d, const float* c) { st_relaxed128(d, make_uint4((pack_bf16(c[0], c[1]) & ~1u) | tag, pack_bf16(c[2], c[3]), pack_bf16(c[4], c[5]), pack_bf16(c[6], c[7]))); };
            asm volatile("wgmma.wait_group.sync.aligned 1;" ::: "memory");
            #pragma unroll
            for (int i = 0; i < 16; i++) asm volatile("" : "+f"(ta1[i]) :: "memory");
            put(d0, ta1); put(d0 + 1024, ta1 + 8);
            wg_wait0();
            #pragma unroll
            for (int i = 0; i < 8; i++) asm volatile("" : "+f"(c2[i]) :: "memory");
            put(d1, c2);
            if (tid == 0 && blockIdx.x == 0) GT(40, NSEG);
        }
        cluster_arrive(); cluster_wait();
    } else {
        asm volatile("setmaxnreg.dec.sync.aligned.u32 %0;" :: "n"(504 - 2 * REG_P));
        const int a = warp - 8;
        const unsigned epoch = ld_relaxed32(&g_epoch);
        const uint32_t sbl = sb + lane * 16;
        if (a < 3) {
            cluster_arrive_rx();
            {
                uint32_t v[3][8];
                #pragma unroll
                for (int k = 0; k < 3; k++)
                    #pragma unroll
                    for (int i = 0; i < 8; i++) v[k][i] = __ldg((const uint32_t*)mem0 + (tid - 256 + 96 * k) + i * (DM / 2));
                #pragma unroll
                for (int k = 0; k < 3; k++) {
                    const uint32_t d = sb + SM_MEM + (tid - 256 + 96 * k) * 32;
                    sts128(d, make_uint4(__byte_perm(v[k][0], v[k][1], 0x5410), __byte_perm(v[k][2], v[k][3], 0x5410), __byte_perm(v[k][4], v[k][5], 0x5410), __byte_perm(v[k][6], v[k][7], 0x5410)));
                    sts128(d + 16, make_uint4(__byte_perm(v[k][0], v[k][1], 0x7632), __byte_perm(v[k][2], v[k][3], 0x7632), __byte_perm(v[k][4], v[k][5], 0x7632), __byte_perm(v[k][6], v[k][7], 0x7632)));
                }
            }
            { int it = 0; while (__any_sync(0xffffffffu, ld_acquire32(&g_init[a * 32 + lane]) != epoch) && ++it < SPIN_LIMIT) {} }
            const uint32_t kl0 = (a < 2 ? SM_TOK + (16 * a + (mi & 1) * 8 + r8) * 64 + (((mi >> 1) ^ (r8 >> 1)) << 4) : SM_EX + 2048 + ((((mi & 1) << 1) | (mi >> 1)) * 8 + r8) * 16);
            const uint32_t l16 = pin(lane * 16);
            uint32_t kf[8][4], wo[8][4];
            auto load_k = [&](int tb, uint32_t kl) {
                const uint32_t ka = kl + launder(sb + tb * TOKBUF);
                #pragma unroll
                for (int kk = 0; kk < 8; kk++) ldsm_x4(kf[kk], (ka ^ ((kk & 1) << 5)) + BLK_K(kk >> 1));
            };
            code_pad<PAD_S>(nv);
            if (tid == 288) PT(14);
            cluster_wait();
            if (a == 0 && lane == 0) { mbar_expect_tx(bEX, 4096 - 256 * nqk); mbar_expect_tx(bEV, 256 * nqk); }
            if (a < 2) bar_arrive(BAR_MEM, 352); else bar_sync(BAR_MEM, 352);
            mbar_wait(bWA, 0);
            #pragma unroll
            for (int i = 0; i < 8; i++) ldsm_x4_t(wo[i], pw0 + sb + SM_WO + (warp >> 1) * 8192 + i * 1024);
            sts128(sbl + SM_STASH + a * 1024 + 512, make_uint4(kl0, (pw0 ^ 32) + sb + SM_WO + 5 * 8192, zoff | ((zskip || lane >= 8) << 31), 0u));
            sts128(sbl + SM_STASH + a * 1024, make_uint4(a * 12288 + (lane >> 4) * 1024 + (mi & 1) * 256 + r8 * 16, ACC_X + a * 6144 + (lane >> 4) * 1024 + (mi & 1) * 256 + r8 * 4,
                                                         ((lane ^ mi) & 1) ? 0u : ~0u, sb + SM_MEM + a * 3072 + mi * 256 + r8 * 16 + (r8 & 1 ? 2 : 130)));
            const uint32_t stash = l16 + uni(sb + SM_STASH + a * 1024);
            #pragma unroll
            for (int i = 0; i < 8; i++) ldsm_x4_t(kf[i], (pw0 ^ 32) + sb + SM_WO + 5 * 8192 + i * 1024);
            if (a < 2) { mbar_wait(bTOK, 0); load_k(0, kl0); }
            __syncwarp();
            int sn = 0;
            #pragma unroll 1
            while (sn < NSEG - 1) {
              uint32_t bad;
              #pragma unroll 1
              do {
                const int s = sn, par = s & 1;
                const uint32_t exu = launder(sb + par * EXBUF);
                const uint32_t exl = l16 + exu + SM_EX;
                const uint32_t t0 = gtime_lo();
                STAMP(15); STAMPV(31, t0);
                if (a == 2) st_relaxed32_p(&g_ts[blockIdx.x], (t0 & ~31u) | (s & 31), l16);
                if (a == 1) {
                    const uint32_t z = lds32(stash + 520);
                    st_relaxed128_p((uint4*)(g_acc + (z + SLOT_OFF(s + 3))), make_uint4(0, 0, 0, 0), z >> 31);
                }
                if (a == 0 && l16 == 0) { mbar_expect_tx(bEX + 8 * (par ^ 1), 4096 - 256 * nqk); mbar_expect_tx(bEV + 8 * (par ^ 1), 256 * nqk); }
                auto first_half = [&](auto role) {
                constexpr bool M = role.value;
                uint32_t sl, sh, kl = 0;
                if (M) {
                    fence_async_smem();
                    if (l16 == 0) {
                        asm volatile("cp.async.bulk.global.shared::cta.bulk_group [%0], [%1], 8192;\ncp.async.bulk.commit_group;"
                            :: "l"(g_tokx[blockIdx.x]), "r"(sb + SM_TOK + (par ^ 1) * TOKBUF + r * 8192) : "memory");
                        mbar_expect_tx(bTOK + 8 * (par ^ 1), 16384); mbar_expect_tx(bMEM, 10368);
                        if (s == 0) mbar_expect_tx(bX, XBUF);
                        if (s + 3 < NSEG) mbar_expect_tx(bX + 8 * (par ^ 1), XBUF);
                    }
                    __syncwarp();
                    if (s > 0 && s + 2 < NSEG) mbar_wait(bX + 8 * par, ((s >> 1) & 1) ^ 1);
                    asm volatile("cp.async.bulk.wait_group 0;" ::: "memory");
                    kl = lds32(stash + 512);
                }
                const uint32_t pst = (launder(l16) >> 2) + launder(sb + SM_P + a * 256);
                if (!M) {
                    uint32_t x = kf[0][0];
                    #pragma unroll
                    for (int i = 1; i < 8; i++) x ^= kf[i][0];
                    sts32_p(pst, x, nv);
                }
                mbar_wait(bEX + 8 * par, (s >> 1) & 1);
                float c[4][4];
                #pragma unroll
                for (int j = 0; j < 4; j++) { c[j][0] = c[j][1] = c[j][2] = c[j][3] = 0.f; }
                if (!M) {
                    uint32_t b[4][4];
                    ldsm16_t(b, exl);
                    #pragma unroll
                    for (int j = 0; j < 4; j++) { mma16816(c[(2 * j) & 3], kf[2 * j], b[j][0], b[j][1]); mma16816(c[(2 * j + 1) & 3], kf[2 * j + 1], b[j][2], b[j][3]); }
                    sl = scale_bf2(pack_bf16((c[0][0] + c[1][0]) + (c[2][0] + c[3][0]), (c[0][1] + c[1][1]) + (c[2][1] + c[3][1])));
                    sh = scale_bf2(pack_bf16((c[0][2] + c[1][2]) + (c[2][2] + c[3][2]), (c[0][3] + c[1][3]) + (c[2][3] + c[3][3])));
                } else {
                    uint32_t k[4][4], b[4][4];
                    #pragma unroll
                    for (int j = 0; j < 4; j++) { ldsm_x4_t(k[j], kl + exu + 512 * j); ldsm_x4_t(b[j], exl + 512 * j); }
                    #pragma unroll
                    for (int j = 0; j < 4; j++) { mma16816(c[2 * (j & 1)], k[j], b[j][0], b[j][1]); mma16816(c[2 * (j & 1) + 1], k[j], b[j][2], b[j][3]); }
                    asm volatile("{\n.reg .pred p;\nelect.sync _|p, 0xffffffff;\n"
                                 "@p cp.async.bulk.shared::cluster.global.mbarrier::complete_tx::bytes.multicast::cluster [%0], [%1], 8192, [%2], %3;\n}\n"
                        :: "r"(sb + SM_TOK + (par ^ 1) * TOKBUF + r * 8192), "l"(g_tokx[blockIdx.x]), "r"(bTOK + 8 * (par ^ 1)), "h"((unsigned short)(7 ^ (1 << r))) : "memory");
                    sh = sl = scale_bf2(pack_bf16((c[0][0] + c[1][2]) + (c[2][0] + c[3][2]), (c[0][1] + c[1][3]) + (c[2][1] + c[3][3])));
                }
                sts32(pst, exp_bf2(sl));
                if (!M) sts32(pst + 128, exp_bf2(sh));
                const uint32_t big = bar_red_or(BAR_P, 352, ((maxabs_bf2(sl, sh) & 0x7fff7fffu) + 0x3ddf3ddfu) & 0x80008000u);
                auto denom = [&] {
                    uint32_t pb[4]; ldsm_x4_t(pb, l16 + sb + SM_P);
                    const uint32_t pm = ldsm_x1_t(l16 + sb + SM_P + 512), ONE = 0x3F803F80u;
                    float l0[4] = {0.f, 0.f, 0.f, 0.f}, l1[4] = {0.f, 0.f, 0.f, 0.f}, l2[4] = {0.f, 0.f, 0.f, 0.f};
                    mma16816r(l0, ONE, ONE, ONE, ONE, pb[0], pb[1]);
                    mma16816r(l1, ONE, ONE, ONE, ONE, pb[2], pb[3]);
                    mma1688(l2, ONE, ONE, pm);
                    const float dl = (l0[0] + l1[0]) + l2[0], dh = (l0[1] + l1[1]) + l2[1];
                    sts32(pst + (SM_IL - SM_P) - a * 128, __float_as_uint(rcp_approx(a ? dh : dl)));
                };
                if (!M) { denom(); bar_sync_p(BAR_O, 352, big); }
                if (__builtin_expect(big, 0)) {
                    uint32_t m2 = max_bf2(sl, sh);
                    m2 = max_bf2(m2, __shfl_xor_sync(0xffffffffu, m2, 4));
                    m2 = max_bf2(m2, __shfl_xor_sync(0xffffffffu, m2, 8));
                    m2 = max_bf2(m2, __shfl_xor_sync(0xffffffffu, m2, 16));
                    const uint32_t lq = l16 | (m2 & nv);
                    if (lq < 64) sts32(lq + sb + SM_P + 768 + a * 4, m2);
                    bar_sync(BAR_S, 96);
                    const uint4 m = lds128(sb + SM_P + 768 + (lq & 0x30));
                    m2 = max_bf2(max_bf2(m.x, m.y), m.z);
                    const float ml = bf_lo(m2), mh = bf_hi(m2);
                    sts32(pst, pack_bf16(exd(bf_lo(sl), ml), exd(bf_hi(sl), mh)));
                    if (!M) sts32(pst + 128, pack_bf16(exd(bf_lo(sh), ml), exd(bf_hi(sh), mh)));
                    bar_sync(BAR_P2, 352);
                    if (!M) { denom(); bar_sync(BAR_O, 352); }
                }
                const uint32_t ll = launder(l16), so = SLOT_OFF(launder(s) + 1);
                if (!M) { uint32_t sx; const uint32_t w2 = stage_w<true>(wo, l16 + sb + SM_O, 12 * r + warp, so, ll, nv, l16 + sb + SM_IL, sx); send_extra<0>(w2, sx, ll); }
                else {
                    const uint32_t w2 = lds32(stash + 516);
                    #pragma unroll
                    for (int i = M_RES; i < 8; i++) ldsm_x4_t(kf[i], w2 + i * 1024);
                    const uint32_t sa = launder((ll >> 2) + (send_ua(12 * r + 10) + so)), sx = launder((ll >> 4) + (send_ub(12 * r + 10) + so));
                    bar_sync_p(BAR_O, 352, (kf[5][0] ^ kf[6][0] ^ kf[7][0] ^ sa ^ sx) & nv);
                    #pragma unroll
                    for (int k = 0; k < M_LAG; k++) mbar_wait(bEX + 8 * par, (s >> 1) & 1);
                    float il, ih;
                    #pragma unroll
                    for (int i = 0; i < 4; i++) c[i][0] = c[i][1] = c[i][2] = c[i][3] = 0.f;
                    uint32_t b[4][4];
                    #pragma unroll
                    for (int j = 0; j < 4; j++) ldsm_x4_t(b[j], l16 + sb + SM_O + 512 * (3 - j));
                    lds_il(il, ih, l16 + sb + SM_IL);
                    sched_fence<11>(nv);
                    #pragma unroll
                    for (int j = 0; j < 4; j++) {
                        mma16816(c[0], wo[6 - 2 * j], b[j][0], b[j][1]); mma16816(c[2], kf[6 - 2 * j], b[j][0], b[j][1]);
                        mma16816(c[1], wo[7 - 2 * j], b[j][2], b[j][3]); mma16816(c[3], kf[7 - 2 * j], b[j][2], b[j][3]);
                        if (j == M_ARR) { asm volatile("" : "+f"(c[0][0]), "+f"(c[1][0]), "+f"(c[2][0]), "+f"(c[3][0])); sched_fence<10>(nv); bar_arrive(BAR_V, 384); }
                        if (j == 3 && M_ARR < 0) bar_arrive(BAR_V, 384);
                    }
                    const uint32_t x0 = send_main<0>((c[0][0] + c[1][0]) * il, (c[0][1] + c[1][1]) * ih, (c[0][2] + c[1][2]) * il, (c[0][3] + c[1][3]) * ih, sa, ll);
                    const uint32_t x1 = send_main<1024>((c[2][0] + c[3][0]) * il, (c[2][1] + c[3][1]) * ih, (c[2][2] + c[3][2]) * il, (c[2][3] + c[3][3]) * ih, sa, ll);
                    send_extra<0>(x0, sx, ll); send_extra<256>(x1, sx, ll);
                }
                };
                if (a < 2) first_half(ic<0>()); else first_half(ic<1>());
                STAMP(warp);
                {
                    const uint32_t cd = lds32(stash + 12), xa = (launder(l16) >> 2) + launder(sb + SM_XT + a * 384);
                    if (a < 2) { const uint32_t kl = lds32(stash + 512); mbar_wait(bTOK + 8 * (par ^ 1), ((s + 1) >> 1) & 1); load_k(par ^ 1, kl); }
                    else {
                        STAMP(16 + a);
                        uint32_t tg;
                        asm volatile("{\n.reg .pred p, q;\n.reg .b64 w;\n.reg .b32 t, u, d, n;\nmov.b32 n, 100000;\n"
                                     "WT_%=:\nld.volatile.shared.u32 %0, [%1];\nmov.u64 w, %%globaltimer;\nmov.b64 {t, u}, w;\nsub.s32 n, n, 1;\nsetp.gt.s32 q, n, 0;\nor.b32 t, t, 1;\nxor.b32 t, t, %2;\n"
                                     "sub.s32 d, t, %0;\nand.b32 d, d, 0x80000001;\nsetp.ne.and.u32 p, d, 0, q;\n@p bra.uni WT_%=;\n}\n" : "=r"(tg) : "r"(sb + SM_TG + (l16 >> 16)), "r"(par + (l16 >> 16)) : "memory");
                        asm volatile("{\n.reg .pred p;\nelect.sync _|p, 0xffffffff;\n"
                                     "@p cp.async.bulk.tensor.3d.shared::cluster.global.mbarrier::complete_tx::bytes.multicast::cluster [%0], [%1, {%3, %4, %5}], [%2], %9;\n"
                                     "@p cp.async.bulk.tensor.3d.shared::cluster.global.mbarrier::complete_tx::bytes.multicast::cluster [%6], [%7, {%3, %4, %8}], [%2], %9;\n}\n"
                            :: "r"(sb + SM_MEM + r * 3072), "l"(&tma), "r"(bMEM), "r"((par ^ 1) * 32), "r"((s + 1) & 2), "r"(12 * r), "r"(sb + SM_XT + r * 384), "l"(&tmb), "r"(ACC_X / 1024 + 6 * r), "h"((unsigned short)7) : "memory");
                        STAMPV(30, tg);
                    }
                    STAMP(19 + a);
                    mbar_wait(bMEM, par);
                    uint32_t x[3], k[3];
                    #pragma unroll
                    for (int j = 0; j < 3; j++) { x[j] = lds32(xa + 128 * j); k[j] = lds32(cd - 2 + 1024 * j); }
                    #pragma unroll
                    for (int j = 0; j < 3; j++) sts16(cd + 1024 * j, (uint16_t)x[j]);
                    bad = __any_sync(0xffffffffu, !((x[0] & x[1] & x[2]) & (k[0] & k[1] & k[2]) & (ACC_FULL << 16)));
                    STAMP(22 + a); STAMPV(27 + a, bad);
                    bar_sync_p(BAR_MEM, 352, bad);
                }
              } while (++sn < NSEG - 1 && !bad);
                {
                    if (bad) {
                        uint32_t c = nv, cx;
                        const uint32_t lq = l16 | (lds32(stash + 524) & nv), so = SLOT_OFF(sn);
                        const uint4 ad = lds128(stash);
                        const unsigned char* pm = launder_p(g_acc + (ad.x + so));
                        const unsigned char* px = launder_p(g_acc + (ad.y + so));
                        int it = 0;
                        do {
                            const uint32_t again = ~(c & __shfl_xor_sync(0xffffffffu, c, 1)) & (ACC_FULL << 16);
                            uint4 u[6]; uint32_t x[3];
                            #pragma unroll
                            for (int j = 0; j < 6; j++) { u[j] = make_uint4(~0u, ~0u, ~0u, ~0u); ld_relaxed128_p(u[j], (const uint4*)(pm + 2048 * j), again); }
                            #pragma unroll
                            for (int j = 0; j < 3; j++) x[j] = ld_relaxed32((const uint32_t*)(px + 2048 * j));
                            c = ~0u;
                            #pragma unroll
                            for (int j = 0; j < 6; j++) {
                                if (again) sts128(lq + sb + SM_MEM + a * 3072 + 512 * j, u[j]);
                                c &= u[j].x;
                            }
                            __syncwarp();
                            #pragma unroll
                            for (int j = 0; j < 3; j++) sts16(ad.w + 1024 * j, (uint16_t)x[j]);
                            c |= ad.z;
                            cx = x[0] & x[1] & x[2];
                        } while (__any_sync(0xffffffffu, !(c & cx & (ACC_FULL << 16))) && ++it < SPIN_LIMIT);
                        bar_sync(BAR_MEM, 352);
                    }
                }
            }
        } else {
            cluster_arrive_rx();
            const uint32_t l16 = pin(lane * 16);
            bf16* dst = g_otok + h * 4096 + (r ? 1024 : 0) + (r == 2 ? 2048 : 0);
            {
                bar_sync(BAR_X0, 288);
                if (lane == 0) {
                    load_w(3); load_wo(4, 6, bWA);
                    if (h < X_PF) asm volatile("cp.async.bulk.prefetch.tensor.3d.L2.global [%0, {%1, %2, %3}];" :: "l"(&tmx), "r"(0), "r"((2 + h) * SEG), "r"(3 * r) : "memory");
                }
                __syncwarp();
                bar_sync(BAR_X0 + 1, 288);
                if (lane == 0) { load_wo(0, 4, bW + 32);
 }
                __syncwarp();
                cluster_wait();
            }
            __syncwarp();
            auto t_loop = [&](auto mtile) {
            constexpr int MT = mtile.value;
            uint32_t q[8][4], sp[5][2], pa[5][2], bv[8][4], rng;
            const uint32_t ost = sb + SM_OST + (MT ? 4096 * r - 2048 : 0);
            code_pad<MT ? PAD_T1 : PAD_T0>(nv);
            auto issue_x = [&](int sg) {
                asm volatile("{\n.reg .pred p, q;\nelect.sync _|p, 0xffffffff;\nsetp.eq.and.u32 q, %5, 3, p;\n"
                             "@p cp.async.bulk.tensor.3d.shared::cluster.global.mbarrier::complete_tx::bytes.multicast::cluster [%0], [%1, {%3, %4, %5}], [%2], %6;\n"
                             "@q cp.async.bulk.tensor.3d.shared::cluster.global.mbarrier::complete_tx::bytes.multicast::cluster [%7], [%1, {%3, %4, %3}], [%2], %6;\n}\n"
                    :: "r"(sb + SM_X + (sg & 1) * XBUF + r * 12288), "l"(&tmx), "r"(bX + 8 * (sg & 1)), "r"(0), "r"(sg * SEG), "r"(3 * r), "h"((unsigned short)7), "r"(sb + SM_X + (sg & 1) * XBUF) : "memory");
            };
            mbar_wait(bTOK, 0);
            if (MT) issue_x(2);
            #pragma unroll 1
            for (int s = 0; ; s++) {
                const int par = s & 1;
                mbar_wait(bTOK + 8 * par, (s >> 1) & 1);
                const uint32_t tok = launder(sb + SM_TOK + par * TOKBUF), exl = l16 + launder(sb + SM_EX + par * EXBUF);
                tok_part1<MT>(tok, MT ? r - 1 : 0, launder(l16) >> 4, q, sp, pa, bv, rng, [&] {
                    if (s > 0) {
                        if (lane == 0) {
                            asm volatile("cp.async.bulk.wait_group 0;" ::: "memory");
                            st_relaxed32(&g_prog[blockIdx.x], epoch << 8 | s);
                        }
                        __syncwarp();
                        if (lane == 0 && blockIdx.x == 0) GT(40, s);
                    }
                    sched_fence<6 + MT>(nv); });
                STAMP(25);
                mbar_wait(bEX + 8 * par, (s >> 1) & 1);
                STAMP(26);
                auto duty = [&] { if (s + 1 < NSEG) {
                    asm volatile("{\n.reg .pred p;\nelect.sync _|p, 0xffffffff;\n"
                                 "@p cp.async.bulk.shared::cluster.global.mbarrier::complete_tx::bytes [%0], [%1], 384, [%2];\n"
                                 "@p mbarrier.arrive.expect_tx.shared.b64 _, [%2], 384;\n}\n"
                        :: "r"(sb + SM_TS), "l"(g_ts), "r"(bFREE) : "memory");
                    if (MT && s + 3 < NSEG) issue_x(s + 3);
                } };
                auto pace = [&] { if (s + 1 < NSEG) {
                    const uint32_t lo = min(launder(l16), 368u), b = (gtime_lo() & ~31u) - 0x01000000u + s + (lo >> 16);
                    const uint32_t c = (b & ~31u) + (G1_NS + (s == 0 ? G1_0 : 0)) + (par ^ 1);
                    mbar_wait(bFREE, par);
                    uint4 ts = lds128(sb + SM_TS + lo);
                    int it = 0; uint32_t m;
                    while (true) {
                        m = __reduce_max_sync(0xffffffffu, max(max(__funnelshift_r(ts.x - b, ts.x - b, 5), __funnelshift_r(ts.y - b, ts.y - b, 5)), max(__funnelshift_r(ts.z - b, ts.z - b, 5), __funnelshift_r(ts.w - b, ts.w - b, 5))));
                        if (__builtin_expect(m < 0x00100000u, 1) || ++it >= 64) break;
                        ts = ld_relaxed128((const uint4*)((const char*)g_ts + lo));
                    }
                    asm volatile("st.volatile.shared.u32 [%0], %1;" :: "r"(sb + SM_TG), "r"(c + (min(m, 0x00080000u) << 5)) : "memory");
                } };
                auto wait_v = [&] { mbar_wait(bEV + 8 * par, (s >> 1) & 1); };
                auto wait_x = [&] { if (__builtin_expect(s == 0, 0)) mbar_wait(bX, 1); };
                tok_part2<MT>(tok, exl, ost, MT ? r - 1 : 0, launder(l16) >> 4, q, sp, pa, bv, rng, s < NSEG - 1, wait_v, duty, pace, wait_x);
                STAMP(11);
                fence_async_smem();
                __syncwarp();
                if (s == NSEG - 1) break;
                if (lane == 0) {
                    asm volatile("cp.async.bulk.global.shared::cta.bulk_group [%0], [%1], 2048;" :: "l"(dst), "r"(ost) : "memory");
                    if (!MT) asm volatile("cp.async.bulk.global.shared::cta.bulk_group [%0], [%1], 2048;" :: "l"(dst + 2048), "r"(ost + 4096) : "memory");
                    asm volatile("cp.async.bulk.commit_group;" ::: "memory");
                }
                __syncwarp();
                dst += SEG * NH * DH;
            }
            if (lane == 0) {
                #pragma unroll
                for (int k = 0; k < (MT ? 2 : 4); k++) {
                    const uint32_t src = ost + (k >> 1) * 4096, rk = (r + 1 + (k & 1)) % 3;
                    asm volatile("cp.async.bulk.shared::cluster.shared::cta.mbarrier::complete_tx::bytes [%0], [%1], 2048, [%2];" :: "r"(mapa_u32(src, rk)), "r"(src), "r"(mapa_u32(bMEM, rk)) : "memory");
                }
                mbar_expect_tx(bMEM, MT ? 6144 : 4096);
            }
            __syncwarp();
            };
            if (r == 0) t_loop(ic<0>()); else t_loop(ic<1>());
        }
        cluster_arrive(); cluster_wait();
    }
}
#define SD_THREADS 384
#define SD_CTAS  36
#define BT_RS    4624
#define SD_BT    0
#define SD_STG   74752
#define SD_EF    (SD_STG + 57344)
#define SD_BC    (SD_STG)
#define KSLOTS   5
#define BC_BYTES 10240
#define BC_LBO   1280
#define SD_KP    (SD_STG + 90112)
#define SD_Q0    205824
#define SD_Q1    (SD_STG + 111616)
#define SD_OST   (SD_Q0 + 8192)
#define SD_XCH   (SD_Q0 + 10240)
#define LSEG     (NSEG - 1)
#define SD_BAR   224256
#define SD_TOTAL 224768
#define SD_SPIN  (1 << 22)
#define PART_SLOTS 8
#define SD_WOP 300
#define SD_GO 0
#define SD_REG 200
#define SD_WAIT 6000
#define SD_P2 150
#define SD_P3 600
#define SD_GAP 0
#define SD_RUSH 44
#define SD_P1 300

__device__ uint4 g_part[SD_CTAS][PART_SLOTS][4][8][32];
__device__ __align__(16) unsigned int g_gate[S_LEN];

struct cplx { float r, i; };
__device__ __forceinline__ cplx cmul(cplx a, cplx b) { cplx c; c.r = fmaf(a.r, b.r, -a.i * b.i); c.i = fmaf(a.r, b.i, a.i * b.r); return c; }
__device__ __forceinline__ cplx cexp_(float xr, float xi) {
    const float m = ex2(xr * 1.4426950408889634f);
    const float k = rintf(xi * 0.15915494309189535f);
    const float r = fmaf(k, 1.7484555314695172e-7f, fmaf(k, -6.2831854820251465f, xi));
    cplx o; o.r = m * __cosf(r); o.i = m * __sinf(r); return o;
}
__device__ __forceinline__ void mma_f16(float (&c)[4], const uint32_t (&a)[4], uint32_t b0, uint32_t b1) {
    asm("mma.sync.aligned.m16n8k16.row.col.f32.f16.f16.f32 {%0,%1,%2,%3}, {%4,%5,%6,%7}, {%8,%9}, {%0,%1,%2,%3};"
        : "+f"(c[0]), "+f"(c[1]), "+f"(c[2]), "+f"(c[3]) : "r"(a[0]), "r"(a[1]), "r"(a[2]), "r"(a[3]), "r"(b0), "r"(b1));
}
__device__ __forceinline__ uint32_t mul_bf2(uint32_t a, uint32_t b) { uint32_t r; asm("mul.rn.bf16x2 %0, %1, %2;" : "=r"(r) : "r"(a), "r"(b)); return r; }
__device__ __forceinline__ void mbar_wait_long(uint32_t a, uint32_t parity) { int it = 0; bool more; do { more = ++it < SD_SPIN; } while (!mbar_try(a, parity) && more); }
__device__ __forceinline__ uint32_t lop3_and(uint32_t a, uint32_t b, uint32_t c) { uint32_t r; asm("lop3.b32 %0, %1, %2, %3, 0x80;" : "=r"(r) : "r"(a), "r"(b), "r"(c)); return r; }
__device__ __forceinline__ uint32_t lop3_or(uint32_t a, uint32_t b, uint32_t c) { uint32_t r; asm("lop3.b32 %0, %1, %2, %3, 0xfe;" : "=r"(r) : "r"(a), "r"(b), "r"(c)); return r; }
__device__ __forceinline__ uint16_t lds16(uint32_t a) { uint16_t v; asm volatile("ld.shared.u16 %0, [%1];" : "=h"(v) : "r"(a) : "memory"); return v; }
__device__ __forceinline__ void wg_wait1() { asm volatile("wgmma.wait_group.sync.aligned 1;" ::: "memory"); }
__device__ __forceinline__ void tma2d(uint32_t dst, const CUtensorMap* tm, uint32_t bar, int c0, int c1) {
    asm volatile("cp.async.bulk.tensor.2d.shared::cluster.global.mbarrier::complete_tx::bytes [%0], [%1, {%3, %4}], [%2];"
        :: "r"(dst), "l"(tm), "r"(bar), "r"(c0), "r"(c1) : "memory");
}
__device__ __forceinline__ uint32_t add_bf2(uint32_t a, uint32_t b) { uint32_t r; asm("add.rn.bf16x2 %0, %1, %2;" : "=r"(r) : "r"(a), "r"(b)); return r; }
__device__ __forceinline__ void wgmma_conv(float (&d)[32], uint32_t a0, uint32_t a1, uint32_t a2, uint32_t a3, uint64_t desc) {
    asm volatile("{\n.reg .pred p;\nsetp.ne.b32 p, 1, 0;\n"
        "wgmma.mma_async.sync.aligned.m64n64k16.f32.bf16.bf16 {%0,%1,%2,%3,%4,%5,%6,%7,%8,%9,%10,%11,%12,%13,%14,%15,%16,%17,%18,%19,%20,%21,%22,%23,%24,%25,%26,%27,%28,%29,%30,%31}, {%32,%33,%34,%35}, %36, p, 1, 1, 0;\n}\n"
        : "+f"(d[0]), "+f"(d[1]), "+f"(d[2]), "+f"(d[3]), "+f"(d[4]), "+f"(d[5]), "+f"(d[6]), "+f"(d[7]), "+f"(d[8]), "+f"(d[9]), "+f"(d[10]), "+f"(d[11]), "+f"(d[12]), "+f"(d[13]), "+f"(d[14]), "+f"(d[15]), "+f"(d[16]), "+f"(d[17]), "+f"(d[18]), "+f"(d[19]), "+f"(d[20]), "+f"(d[21]), "+f"(d[22]), "+f"(d[23]), "+f"(d[24]), "+f"(d[25]), "+f"(d[26]), "+f"(d[27]), "+f"(d[28]), "+f"(d[29]), "+f"(d[30]), "+f"(d[31])
        : "r"(a0), "r"(a1), "r"(a2), "r"(a3), "l"(desc));
}
__device__ __forceinline__ void wgmma_conv(float (&d)[24], uint32_t a0, uint32_t a1, uint32_t a2, uint32_t a3, uint64_t desc) {
    asm volatile("{\n.reg .pred p;\nsetp.ne.b32 p, 1, 0;\n"
        "wgmma.mma_async.sync.aligned.m64n48k16.f32.bf16.bf16 {%0,%1,%2,%3,%4,%5,%6,%7,%8,%9,%10,%11,%12,%13,%14,%15,%16,%17,%18,%19,%20,%21,%22,%23}, {%24,%25,%26,%27}, %28, p, 1, 1, 0;\n}\n"
        : "+f"(d[0]), "+f"(d[1]), "+f"(d[2]), "+f"(d[3]), "+f"(d[4]), "+f"(d[5]), "+f"(d[6]), "+f"(d[7]), "+f"(d[8]), "+f"(d[9]), "+f"(d[10]), "+f"(d[11]), "+f"(d[12]), "+f"(d[13]), "+f"(d[14]), "+f"(d[15]), "+f"(d[16]), "+f"(d[17]), "+f"(d[18]), "+f"(d[19]), "+f"(d[20]), "+f"(d[21]), "+f"(d[22]), "+f"(d[23])
        : "r"(a0), "r"(a1), "r"(a2), "r"(a3), "l"(desc));
}
__device__ __forceinline__ void wgmma_conv(float (&d)[16], uint32_t a0, uint32_t a1, uint32_t a2, uint32_t a3, uint64_t desc) {
    asm volatile("{\n.reg .pred p;\nsetp.ne.b32 p, 1, 0;\n"
        "wgmma.mma_async.sync.aligned.m64n32k16.f32.bf16.bf16 {%0,%1,%2,%3,%4,%5,%6,%7,%8,%9,%10,%11,%12,%13,%14,%15}, {%16,%17,%18,%19}, %20, p, 1, 1, 0;\n}\n"
        : "+f"(d[0]), "+f"(d[1]), "+f"(d[2]), "+f"(d[3]), "+f"(d[4]), "+f"(d[5]), "+f"(d[6]), "+f"(d[7]), "+f"(d[8]), "+f"(d[9]), "+f"(d[10]), "+f"(d[11]), "+f"(d[12]), "+f"(d[13]), "+f"(d[14]), "+f"(d[15])
        : "r"(a0), "r"(a1), "r"(a2), "r"(a3), "l"(desc));
}
__device__ __forceinline__ void wgmma_conv(float (&d)[8], uint32_t a0, uint32_t a1, uint32_t a2, uint32_t a3, uint64_t desc) {
    asm volatile("{\n.reg .pred p;\nsetp.ne.b32 p, 1, 0;\n"
        "wgmma.mma_async.sync.aligned.m64n16k16.f32.bf16.bf16 {%0,%1,%2,%3,%4,%5,%6,%7}, {%8,%9,%10,%11}, %12, p, 1, 1, 0;\n}\n"
        : "+f"(d[0]), "+f"(d[1]), "+f"(d[2]), "+f"(d[3]), "+f"(d[4]), "+f"(d[5]), "+f"(d[6]), "+f"(d[7])
        : "r"(a0), "r"(a1), "r"(a2), "r"(a3), "l"(desc));
}
template<int NR> __device__ __forceinline__ void conv_mma(float (&acc)[NR], const uint32_t (&R)[16], uint32_t dlo) {
    #pragma unroll
    for (int q = 0; q < 4; q++)
        wgmma_conv(acc, R[4 * q], R[4 * q + 1], R[4 * q + 2], R[4 * q + 3], (uint64_t)(dlo + (2 * (3 - q)) * (BC_LBO >> 4)) | ((uint64_t)8 << 32));
}
__device__ __forceinline__ void conv_ld(uint32_t (&R)[16], uint32_t a) {
    #pragma unroll
    for (int q = 0; q < 4; q++) { const uint2 u = lds64(a + 64 * (2 * q + 1)); R[4 * q] = u.x; R[4 * q + 1] = u.y; }
}
__device__ __forceinline__ void conv_fix(uint32_t (&R)[16], uint32_t& carry) {
    #pragma unroll
    for (int q = 0; q < 4; q++) {
        asm volatile("mov.b32 %0, %1;" : "=r"(R[4 * q + 2]) : "r"(q ? R[4 * q - 3] : carry));
        asm volatile("mov.b32 %0, %1;" : "=r"(R[4 * q + 3]) : "r"(R[4 * q]));
    }
    asm volatile("mov.b32 %0, %1;" : "=r"(carry) : "r"(R[13]));
}
template<int A> __device__ __forceinline__ void conv_group(float (&acc)[32 - 8 * A], uint32_t (&R)[4][16], uint32_t& carry, uint32_t pb, uint32_t dlo) {
    #pragma unroll
    for (int e = 0; e < 8; e += 2) {
        const int dl = 8 * A + e;
        conv_fix(R[dl & 3], carry); conv_fix(R[(dl + 1) & 3], carry);
        wg_fence(); conv_mma(acc, R[dl & 3], dlo + 16 - 2 * e); conv_mma(acc, R[(dl + 1) & 3], dlo + 14 - 2 * e); wg_commit();
        wg_wait1();
        if (dl + 2 < 32) { conv_ld(R[(dl + 2) & 3], pb + (dl + 2) * 512); conv_ld(R[(dl + 3) & 3], pb + (dl + 3) * 512); }
    }
}

__global__ void __launch_bounds__(SD_THREADS, 1)
side_kernel(const __grid_constant__ CUtensorMap tmw, const bf16* __restrict__ x,
            const bf16* __restrict__ log_A_real, const bf16* __restrict__ A_imag, const bf16* __restrict__ C_real, const bf16* __restrict__ C_imag,
            const bf16* __restrict__ log_dt, const bf16* __restrict__ D_skip, const bf16* __restrict__ gate_w, bf16* __restrict__ out, const int npass) {
    extern __shared__ __align__(1024) unsigned char smem[];
    const uint32_t sb = smem_u32(smem);
    const int tid = threadIdx.x, lane = tid & 31;
    const int warp = __shfl_sync(0xffffffffu, tid >> 5, 0);
    const int g = lane >> 2, t = lane & 3, mi = lane >> 3, r8 = lane & 7;
    const bool sh = blockIdx.x < 32;
    const int d0 = blockIdx.x * 16;
    const uint32_t b0_ = sb + SD_BAR, bKF = b0_ + 384, bKE = bKF + 8 * KSLOTS, bWO = b0_ + 48, bFULL = b0_ + 56, bEMPTY = b0_ + 88, bEPI = b0_ + 120, bPRT = b0_ + 152, bGO = b0_ + 184, bCH = b0_ + 256;
    const unsigned epoch = ld_relaxed32(&g_epoch);
    if (tid == 0) GT(blockIdx.x, 0);
    if (tid == 0) {
        for (int i = 0; i < 2 * KSLOTS; i++) mbar_init(bKF + 8 * i, 128);
        mbar_init(bWO, 1);
        for (int i = 0; i < 16; i++) mbar_init(bCH + 8 * i, 1);
        for (int i = 0; i < 4; i++) { mbar_init(bFULL + 8 * i, 1); mbar_init(bEMPTY + 8 * i, sh ? 8 : 4); mbar_init(bEPI + 8 * i, 4); mbar_init(bPRT + 8 * i, 8); }
        sts32(bGO, epoch);
        asm volatile("fence.mbarrier_init.release.cluster;" ::: "memory");
    }
    for (int i = tid; i < KSLOTS * 8 * 16; i += SD_THREADS) sts128(sb + SD_BC + (i >> 4) * BC_LBO + (i & 15) * 16, make_uint4(0, 0, 0, 0));
    if (tid < 128) sts64(sb + ((tid & 64) ? SD_Q1 : SD_Q0) + (tid & 63) * 8, 0u, 0u);
    fence_async_smem();
    __syncthreads();

    if (warp < 8) {
        asm volatile("setmaxnreg.inc.sync.aligned.u32 %0;" :: "n"(SD_REG));
        const int wg = warp >> 2, w = warp & 3, t128 = tid & 127;
        if (SD_WAIT) __nanosleep(SD_WAIT);
        {
            #pragma unroll 1
            for (int i = 0; i < 4; i++) {
                const int tp = tid + 256 * i;
                const bf16* xp = x + (size_t)(2 * tp) * DM + d0;
                const uint4 v0 = __ldg((const uint4*)xp), v1 = __ldg((const uint4*)(xp + 8)), v2 = __ldg((const uint4*)(xp + DM)), v3 = __ldg((const uint4*)(xp + DM + 8));
                const uint32_t a = sb + SD_BT + (tp >> 5) * 144 + (tp & 31) * 4;
                const uint32_t lo[8] = {v0.x, v0.y, v0.z, v0.w, v1.x, v1.y, v1.z, v1.w};
                const uint32_t hi[8] = {v2.x, v2.y, v2.z, v2.w, v3.x, v3.y, v3.z, v3.w};
                #pragma unroll
                for (int j = 0; j < 8; j++) { sts32(a + (2 * j) * BT_RS, __byte_perm(lo[j], hi[j], 0x5410)); sts32(a + (2 * j + 1) * BT_RS, __byte_perm(lo[j], hi[j], 0x7632)); }
                if (SD_GAP) __nanosleep(SD_GAP);
            }
        }
        bar_sync(1, 256);
        if (tid == 0) GT(blockIdx.x, 65);
        const uint32_t pa = sb + (wg ? SD_Q1 : SD_Q0);
        const uint32_t pb = pa + (72 + 16 * w - 56 + g - 2 * t) * 8;
        for (int c = wg; c < 16; c += 2) {
            const uint32_t bt = sb + SD_BT + c * BT_RS;
            bar_sync(2 + wg, 128);
            #pragma unroll
            for (int it = 0; it < 9; it++) {
                const int k = it < 8 ? t128 + 128 * it : t128 - 4;
                if (it < 8 || t128 < 4) {
                    auto word = [&](int j) { return j >= 0 ? lds32(bt + (j >> 5) * 144 + (j & 31) * 4) : 0u; };
                    const uint32_t c0 = word(k), p0 = word(k - 1), c1 = word(k + 4), p1 = word(k + 3);
                    sts128(pa + (72 + 2 * k) * 8, make_uint4(__byte_perm(c0, p0, 0x7610), __byte_perm(c1, p1, 0x7610), __byte_perm(c0, c0, 0x1032), __byte_perm(c1, c1, 0x1032)));
                }
            }
            bar_sync(2 + wg, 128);
            const int slot = c % KSLOTS;
            float acc[32];
            #pragma unroll
            for (int i = 0; i < 32; i++) acc[i] = 0.f;
            uint32_t R[4][16];
            uint32_t carry = lds32(pb);
            conv_ld(R[0], pb); conv_ld(R[1], pb + 512);
            const uint32_t dlo = (((sb + SD_BC + slot * BC_BYTES) & 0x3FFFF) >> 4) | ((BC_LBO >> 4) << 16);
            mbar_wait_long(bKF + 8 * slot, (c / KSLOTS) & 1);
            const float ds = bf(D_skip[d0 + c]);
            auto fin = [&](const float* a8, int q0) {
                #pragma unroll
                for (int q = 0; q < 2; q++)
                    #pragma unroll
                    for (int hh = 0; hh < 2; hh++) {
                        const uint32_t a = bt + (4 * (q0 + q) + t) * 144 + (16 * w + g + 8 * hh) * 2;
                        const float u = __uint_as_float((uint32_t)lds16(a) << 16);
                        const float y = rbf(a8[4 * q + 2 * hh] + a8[4 * q + 2 * hh + 1]);
                        sts16(a, (uint16_t)(pack_bf16(y + rbf(u * ds), 0.f) & 0xffff));
                    }
            };
            float a1[24], a2[16], a3[8];
            conv_group<0>(acc, R, carry, pb, dlo);
            wg_wait0();
            #pragma unroll
            for (int i = 0; i < 24; i++) asm volatile("mov.b32 %0, %1;" : "=f"(a1[i]) : "f"(acc[8 + i]));
            fin(acc, 0);
            conv_group<1>(a1, R, carry, pb, dlo);
            wg_wait0();
            #pragma unroll
            for (int i = 0; i < 16; i++) asm volatile("mov.b32 %0, %1;" : "=f"(a2[i]) : "f"(a1[8 + i]));
            fin(a1, 2);
            conv_group<2>(a2, R, carry, pb, dlo);
            wg_wait0();
            #pragma unroll
            for (int i = 0; i < 8; i++) asm volatile("mov.b32 %0, %1;" : "=f"(a3[i]) : "f"(a2[8 + i]));
            fin(a2, 4);
            conv_group<3>(a3, R, carry, pb, dlo);
            wg_wait0();
            mbar_arrive(bKE + 8 * slot);
            fin(a3, 6);
        }
        fence_async_smem();
        __syncthreads();
        const uint32_t stg = sb + SD_STG + wg * 65536;
        uint32_t wf[32][4];
        if (tid == 0) GT(blockIdx.x, 66);
        mbar_wait_long(bWO, 0);
        #pragma unroll
        for (int i = 0; i < 32; i++)
            ldsm_x4_t(wf[i], stg + (i * 16 + (mi >> 1) * 8 + r8) * 128 + (((2 * w + (mi & 1)) ^ r8) << 4));
        { uint32_t x = 0;
          #pragma unroll
          for (int i = 0; i < 32; i++) x |= wf[i][0];
          asm volatile("" :: "r"(x) : "memory"); }
        __syncwarp();
        if (lane == 0) {
            mbar_arrive(bEMPTY + 16 * wg); mbar_arrive(bEMPTY + 16 * wg + 8);
            if (sh) { mbar_arrive(bEMPTY + 16 * (wg ^ 1)); mbar_arrive(bEMPTY + 16 * (wg ^ 1) + 8); }
        }
        uint4* dst = sh ? &g_part[(blockIdx.x & ~7) + 4 * wg + w][0][0][blockIdx.x & 7][lane] : &g_part[32 + w][0][0][2 * (blockIdx.x - 32) + wg][lane];
        const uint32_t dl0 = (((sb + SD_STG) & 0x3FFFF) >> 4) | 0x10000u;
        const uint32_t bu = uni(b0_), shu = uni(sh), wgu = uni(wg), dlu = uni(dl0);
        auto seg = [&](int s, float (&acc)[16]) {
            const uint32_t bi = shu ? s & 3 : 2 * wgu + (s & 1), bp = (shu ? s >> 2 : s >> 1) & 1;
            const uint32_t xd = dlu + bi * 2048;
            #pragma unroll
            for (int i = 0; i < 32; i++) {
                if ((i & 15) == 0) { mbar_wait_long(bu + 256 + 32 * bi + (i >> 1), bp); wg_fence(); }
                if (i == 0) wgmma_n32<0>(acc, wf[i], desc_from(xd));
                else wgmma_n32<1>(acc, wf[i], desc_from(xd + (i >> 2) * 256 + (i & 3) * 2));
            }
            wg_commit();
            if (s >= PART_SLOTS / 2) mbar_wait_long(bu + 120 + 8 * (s & 3), ((s - 4) >> 2) & 1);
            const uint32_t ph = ((s / PART_SLOTS) & 1) ^ 1;
            uint4* p = dst + (s % PART_SLOTS) * (4 * 8 * 32);
            wg_wait0();
            #pragma unroll
            for (int j = 0; j < 4; j++)
                st_relaxed128(p + 256 * j, make_uint4((__float_as_uint(acc[4 * j]) & ~1u) | ph, __float_as_uint(acc[4 * j + 1]), __float_as_uint(acc[4 * j + 2]), __float_as_uint(acc[4 * j + 3])));
            if (tid == 0 && s == LSEG - 1) GT(blockIdx.x, 71);
            asm volatile("{\n.reg .pred p;\nelect.sync _|p, 0xffffffff;\n@p mbarrier.arrive.shared.b64 _, [%0];\n@p mbarrier.arrive.shared.b64 _, [%1];\n}\n" :: "r"(bu + 88 + 8 * bi), "r"(bu + 152 + 8 * (s & 3)) : "memory");
        };
        #pragma unroll 1
        for (int pass = 0; pass < npass; pass++) {
            if (pass) {
                float acc0[16], acc1[16];
                #pragma unroll 1
                for (int s = 0; ; s += 2) { seg(s, acc0); if (s + 1 >= LSEG) break; seg(s + 1, acc1); }
            }
            uint32_t tq; asm volatile("mov.u32 %0, %%tid.x;" : "=r"(tq));
            const uint4* p = &g_last[blockIdx.x][0][0][0] + (tq >> 5) * 256 + (tq & 31);
            const uint32_t tag = lds32(bGO) & 1u;
            uint4 v[8]; int it = 0;
            #pragma unroll
            for (int i = 0; i < 8; i++) v[i] = make_uint4(tag ^ pass, 0, 0, 0);
            while (true) {
                #pragma unroll
                for (int i = 0; i < 8; i++) ld_relaxed128_p(v[i], p + 32 * i, (v[i].x ^ tag) & 1u);
                uint32_t any = 0;
                #pragma unroll
                for (int i = 0; i < 8; i++) any |= v[i].x ^ tag;
                if (!__any_sync(0xffffffffu, any & 1u) || ++it >= SD_SPIN) break;
            }
            float a[8];
            #pragma unroll
            for (int i = 0; i < 8; i++) a[i] = 0.f;
            #pragma unroll
            for (int i = 0; i < 8; i++) { a[0] += bf_lo(v[i].x); a[1] += bf_hi(v[i].x); a[2] += bf_lo(v[i].y); a[3] += bf_hi(v[i].y); a[4] += bf_lo(v[i].z); a[5] += bf_hi(v[i].z); a[6] += bf_lo(v[i].w); a[7] += bf_hi(v[i].w); }
            const uint32_t xa = sb + SD_XCH + (tq >> 7) * 4096 + (tq & 127) * 16;
            sts128(xa, make_uint4(__float_as_uint(a[0]), __float_as_uint(a[1]), __float_as_uint(a[2]), __float_as_uint(a[3])));
            sts128(xa + 2048, make_uint4(__float_as_uint(a[4]), __float_as_uint(a[5]), __float_as_uint(a[6]), __float_as_uint(a[7])));
            bar_arrive_p(6, 320, !pass);
        }
        mbar_wait_long(bEPI + 8 * (LSEG & 3), ((LSEG - 4) >> 2) & 1);
        #pragma unroll
        for (int j = 0; j < 4; j++) st_relaxed128(dst + (LSEG % PART_SLOTS) * (4 * 8 * 32) + 256 * j, make_uint4(((LSEG / PART_SLOTS) & 1) ^ 1, 0, 0, 0));
    } else {
        asm volatile("setmaxnreg.dec.sync.aligned.u32 %0;" :: "n"(504 - 2 * SD_REG));
        const int w = warp - 8, n = tid - 256;
        bf16 p_la = log_A_real[d0 * NS + n], p_ai = A_imag[d0 * NS + n], p_cr = C_real[d0 * NS + n], p_ci = C_imag[d0 * NS + n], p_dt = log_dt[d0];
        const uint32_t ef = sb + SD_EF + w * 8192;
        const uint32_t efl = ef + lane * 4;
        uint32_t goff[8];
        #pragma unroll
        for (int i = 0; i < 16; i++) {
            const int l = 64 * lane + 8 * (w + 4 * (i >> 3)) + (i & 7);
            const int p = (int)rbf((float)l);
            const int a = p >> 7, b = (p >> 3) & 15, c = p & 7;
            const int row = p < 256 ? 8 * a + c : (p < 512 ? 16 + 4 * (a - 2) + (c >> 1) : (p < 1024 ? 24 + 2 * (a - 4) + (c >> 2) : 24 + a));
            const uint32_t off = row * 72 + b * 4;
            if (i & 1) goff[i >> 1] |= off << 16; else goff[i >> 1] = off;
        }
        for (int c = 0; c < 16; c++) {
            const float dt = rbf(expf(bf(p_dt)));
            const float xr = -rbf(expf(bf(p_la))) * dt, xi = bf(p_ai) * dt;
            cplx C; C.r = 2.f * bf(p_cr) * dt; C.i = 2.f * bf(p_ci) * dt;
            if (c + 1 < 16) {
                const int o = (d0 + c + 1) * NS + n;
                p_la = log_A_real[o]; p_ai = A_imag[o]; p_cr = C_real[o]; p_ci = C_imag[o]; p_dt = log_dt[d0 + c + 1];
            }
            const uint32_t mexp = min(max(__reduce_max_sync(0xffffffffu, __float_as_uint(fmaxf(fabsf(C.r), fabsf(C.i)))) & 0x7f800000u, 0x01000000u), 0x7e000000u);
            const float unsc = __uint_as_float(mexp), sc = __uint_as_float(0x7f000000u - mexp);
            C.r *= sc; C.i *= sc;
            #define EADDR(r) ((efl ^ (((r) & 7) << 4)) + (r) * 128)
            {
                cplx f[16];
                f[1] = cexp_(8.f * xr, -8.f * xi);
                f[2] = cmul(f[1], f[1]); f[3] = cmul(f[2], f[1]); f[4] = cmul(f[2], f[2]); f[5] = cmul(f[4], f[1]); f[6] = cmul(f[4], f[2]); f[7] = cmul(f[4], f[3]);
                f[8] = cmul(f[4], f[4]);
                #pragma unroll
                for (int b = 9; b < 16; b++) f[b] = cmul(f[8], f[b - 8]);
                sts32(EADDR(0) + 6144, 0x00003c00u);
                #pragma unroll
                for (int b = 1; b < 16; b++) sts32(EADDR(b) + 6144, pack_f16(f[b].r, f[b].i));
            }
            {
                cplx G[17], wc[8];
                G[1] = cexp_(128.f * xr, 128.f * xi);
                wc[1] = cexp_(xr, xi);
                G[2] = cmul(G[1], G[1]); G[4] = cmul(G[2], G[2]); G[8] = cmul(G[4], G[4]);
                wc[2] = cmul(wc[1], wc[1]); wc[3] = cmul(wc[2], wc[1]); wc[4] = cmul(wc[2], wc[2]); wc[5] = cmul(wc[4], wc[1]); wc[6] = cmul(wc[4], wc[2]); wc[7] = cmul(wc[4], wc[3]);
                cplx CG[17];
                CG[0] = C; CG[1] = cmul(C, G[1]); CG[2] = cmul(C, G[2]); CG[3] = cmul(CG[1], G[2]);
                #pragma unroll
                for (int a = 0; a < 4; a++) CG[4 + a] = cmul(CG[a], G[4]);
                #pragma unroll
                for (int a = 0; a < 9; a++) CG[8 + a] = cmul(CG[a], G[8]);
                #pragma unroll
                for (int r = 0; r < 41; r++) {
                    const int a = r < 16 ? (r >> 3) : (r < 24 ? 2 + ((r >> 2) & 1) : (r < 32 ? 4 + ((r >> 1) & 3) : r - 24));
                    const int cc = r < 16 ? (r & 7) : (r < 24 ? 2 * (r & 3) : (r < 32 ? 4 * (r & 1) : 0));
                    const cplx e = cc ? cmul(CG[a], wc[cc]) : CG[a];
                    sts32(EADDR(r), pack_f16(e.r, e.i));
                }
            }
            __syncwarp();
            float acc[3][2][4];
            #pragma unroll
            for (int i = 0; i < 3; i++)
                #pragma unroll
                for (int j = 0; j < 2; j++) { acc[i][j][0] = acc[i][j][1] = acc[i][j][2] = acc[i][j][3] = 0.f; }
            #pragma unroll
            for (int ks = 0; ks < 4; ks++) {
                uint32_t bq[4];
                ldsm_x4(bq, ef + 6144 + ((mi >> 1) * 8 + r8) * 128 + (((2 * ks + (mi & 1)) ^ r8) << 4));
                #pragma unroll
                for (int mt = 0; mt < 3; mt++) {
                    uint32_t aq[4];
                    ldsm_x4(aq, ef + (16 * mt + (mi & 1) * 8 + r8) * 128 + (((2 * ks + (mi >> 1)) ^ r8) << 4));
                    mma_f16(acc[mt][0], aq, bq[0], bq[1]);
                    mma_f16(acc[mt][1], aq, bq[2], bq[3]);
                }
            }
            const uint32_t kp = sb + SD_KP;
            #pragma unroll
            for (int mt = 0; mt < 3; mt++)
                #pragma unroll
                for (int nt = 0; nt < 2; nt++) {
                    const uint32_t a = kp + w * 3072 + (16 * mt + g) * 64 + nt * 32 + t * 8;
                    sts64(a, __float_as_uint(acc[mt][nt][0] * unsc), __float_as_uint(acc[mt][nt][1] * unsc));
                    sts64(a + 512, __float_as_uint(acc[mt][nt][2] * unsc), __float_as_uint(acc[mt][nt][3] * unsc));
                }
            bar_sync(4, 128);
            #pragma unroll
            for (int i = 0; i < 3; i++) {
                const uint32_t a = kp + (n + 128 * i) * 8;
                const uint2 v0 = lds64(a), v1 = lds64(a + 3072), v2 = lds64(a + 6144), v3 = lds64(a + 9216);
                sts64(a + 12288 + ((n >> 3) + 16 * i) * 8, __float_as_uint((__uint_as_float(v0.x) + __uint_as_float(v1.x)) + (__uint_as_float(v2.x) + __uint_as_float(v3.x))),
                                 __float_as_uint((__uint_as_float(v0.y) + __uint_as_float(v1.y)) + (__uint_as_float(v2.y) + __uint_as_float(v3.y))));
            }
            bar_sync(4, 128);
            const int slot = c % KSLOTS;
            float kv[16];
            #pragma unroll
            for (int e = 0; e < 8; e++) { kv[2 * e] = __uint_as_float(lds32(kp + 12288 + (goff[e] & 0xffff))); kv[2 * e + 1] = __uint_as_float(lds32(kp + 12288 + (goff[e] >> 16))); }
            if (c >= KSLOTS) mbar_wait_long(bKE + 8 * slot, (c / KSLOTS - 1) & 1);
            #pragma unroll
            for (int it = 0; it < 2; it++) {
                uint32_t hi[4], lo[4];
                #pragma unroll
                for (int e = 0; e < 4; e++) {
                    const float k0 = kv[8 * it + 2 * e], k1 = kv[8 * it + 2 * e + 1];
                    hi[e] = pack_bf16(k0, k1);
                    lo[e] = pack_bf16(k0 - bf_lo(hi[e]), k1 - bf_hi(hi[e]));
                }
                const uint32_t a = sb + SD_BC + slot * BC_BYTES + (w + 4 * it) * BC_LBO + (16 + 2 * lane) * 16;
                sts128(a, make_uint4(hi[0], hi[1], hi[2], hi[3]));
                sts128(a + 16, make_uint4(lo[0], lo[1], lo[2], lo[3]));
            }
            fence_async_smem();
            mbar_arrive(bKF + 8 * slot);
        }
        {
            uint32_t gw[9];
            #pragma unroll
            for (int j = 0; j < 9; j++) gw[j] = __ldg((const uint32_t*)gate_w + lane + 32 * j);
            float z = 0.f;
            #pragma unroll 1
            for (int i0 = 0; i0 < 15; i0 += 5) {
                uint32_t xv[5][9];
                #pragma unroll
                for (int i = 0; i < 5; i++) {
                    const int tk = min(blockIdx.x * 57 + w + 4 * (i0 + i), S_LEN - 1);
                    #pragma unroll
                    for (int j = 0; j < 9; j++) xv[i][j] = __ldg((const uint32_t*)(x + (size_t)tk * DM) + lane + 32 * j);
                }
                #pragma unroll
                for (int i = 0; i < 5; i++) {
                    float acc = 0.f;
                    #pragma unroll
                    for (int j = 0; j < 9; j++) { const uint32_t m = mul_bf2(xv[i][j], gw[j]); acc += bf_lo(m) + bf_hi(m); }
                    #pragma unroll
                    for (int o = 16; o; o >>= 1) acc += __shfl_xor_sync(0xffffffffu, acc, o);
                    if (lane == i0 + i) z = rbf(acc);
                }
            }
            const int li = w + 4 * lane, tk = blockIdx.x * 57 + li;
            if (li < 57 && tk < S_LEN) st_relaxed32(&g_gate[tk], pack_bf16(1.f / (1.f + expf(-z)), 0.f) | (epoch << 16));
        }
        if (tid == 256) GT(blockIdx.x, 67);
        fence_async_smem();
        __syncthreads();
            const uint32_t ost = sb + SD_OST + w * 512;
            const uint4* const pl = &g_part[blockIdx.x][0][0][0][lane];
            bf16* const ol = out + (size_t)(lane >> 1) * DM + d0 + 8 * (lane & 1);
            const uint32_t ga = sb + SD_Q0 + t * 8, bb = sb + SD_BT + g * BT_RS + t * 4, oa = ost + r8 * 32 + (mi & 1) * 16 + (mi >> 1) * 256;
            uint32_t gg[2], mb[2][2];
            auto gates = [&](int u) {
                #pragma unroll
                for (int k = 0; k < 2; k++) {
                    const uint2 gt = lds64(ga + (u + k) * 32);
                    const uint32_t ba = bb + (u >> 3) * 144 + ((u & 7) + k) * 16;
                    gg[k] = __byte_perm(gt.x, gt.y, 0x5410);
                    const uint32_t mm = pack_bf16(1.f - bf_lo(gg[k]), 1.f - bf_hi(gg[k]));
                    mb[k][0] = mul_bf2(mm, lds32(ba)); mb[k][1] = mul_bf2(mm, lds32(ba + 8 * BT_RS));
                }
            };
            auto finish = [&](int u, const uint32_t (&sm)[2][2], uint32_t store) {
                stsm_x4_t(oa, add_bf2(mul_bf2(gg[0], sm[0][0]), mb[0][0]), add_bf2(mul_bf2(gg[0], sm[0][1]), mb[0][1]), add_bf2(mul_bf2(gg[1], sm[1][0]), mb[1][0]), add_bf2(mul_bf2(gg[1], sm[1][1]), mb[1][1]));
                __syncwarp();
                const uint4 o = lds128(ost + lane * 16);
                asm volatile("{\n.reg .pred p;\nsetp.ne.u32 p, %5, 0;\n@p st.global.v4.u32 [%0], {%1,%2,%3,%4};\n}\n" :: "l"(ol + (size_t)u * (8 * DM)), "r"(o.x), "r"(o.y), "r"(o.z), "r"(o.w), "r"(store) : "memory");
                __syncwarp();
            };
            auto units = [&](int u, int end) {
              uint4 v[16];
              auto fetch = [&](int u, bool block) {
                const int s = u >> 2;
                uint32_t early;
                asm volatile("{\n.reg .pred p;\nmbarrier.test_wait.parity.shared::cta.b64 p, [%1], %2;\nselp.u32 %0, 1, 0, p;\n}\n" : "=r"(early) : "r"(bPRT + 8 * (s & 3)), "r"((s >> 2) & 1) : "memory");
                if (!early) {
                    if (!block) return false;
                    mbar_wait_long(bPRT + 8 * (s & 3), (s >> 2) & 1);
                    delay_clk(s < LSEG - 2 ? SD_P1 : SD_P2);
                } else if (SD_P3 && s < SD_RUSH) delay_clk(SD_P3);
                const uint4* p = pl + (u & (4 * PART_SLOTS - 1)) * 256;
                #pragma unroll
                for (int i = 0; i < 16; i++) v[i] = ld_relaxed128(p + 32 * i);
                return true;
              };
              fetch(u, true);
              #pragma unroll 1
              while (true) {
                const int s = u >> 2;
                const uint32_t phm = ((s / PART_SLOTS) & 1) - 1;
                gates(u);
                int it = 0;
                while (true) {
                    uint32_t all = ~0u, any = 0;
                    #pragma unroll
                    for (int i = 0; i < 16; i += 2) { all = lop3_and(all, v[i].x, v[i + 1].x); any = lop3_or(any, v[i].x, v[i + 1].x); }
                    if (!__any_sync(0xffffffffu, ((all ^ phm) | (any ^ phm)) & 1u) || ++it >= SD_SPIN) break;
                    if (it > 1 && s < LSEG - 2) __nanosleep(200);
                    const uint4* p = pl + (u & (4 * PART_SLOTS - 1)) * 256;
                    #pragma unroll
                    for (int i = 0; i < 16; i++) ld_relaxed128_p(v[i], p + 32 * i, (v[i].x ^ phm) & 1u);
                }
                if (lane < 2) mbar_arrive(bEPI + 8 * (s & 3));
                uint32_t sm[2][2];
                #pragma unroll
                for (int k = 0; k < 2; k++) {
                    float a0 = __uint_as_float(v[8 * k].x), a1 = __uint_as_float(v[8 * k].y), a2 = __uint_as_float(v[8 * k].z), a3 = __uint_as_float(v[8 * k].w);
                    #pragma unroll
                    for (int i = 1; i < 8; i++) { a0 += __uint_as_float(v[8 * k + i].x); a1 += __uint_as_float(v[8 * k + i].y); a2 += __uint_as_float(v[8 * k + i].z); a3 += __uint_as_float(v[8 * k + i].w); }
                    sm[k][0] = pack_bf16(a0, a1); sm[k][1] = pack_bf16(a2, a3);
                }
                const int nu = u + 6;
                const bool pre = nu < end && fetch(nu, false);
                finish(u, sm, 1u);
                if (lane == 0 && (u & 2)) GT(blockIdx.x, 1 + s);
                if (nu >= end) break;
                if (!pre) fetch(nu, true);
                u = nu;
              }
            };
        #pragma unroll 1
        for (int pass = w & 1 ? 0 : 1; pass < npass; pass++) {
        if (pass) {
        if (w == 0) {
            if (lane == 0) {
                mbar_expect_tx(bWO, 131072);
                #pragma unroll 1
                for (int q = 0; q < 16; q++) {
                    tma2d(sb + SD_STG + q * 8192, &tmw, bWO, sh ? 128 * (blockIdx.x >> 3) + 64 * (q >> 3) : 512, sh ? 512 * (blockIdx.x & 7) + 64 * (q & 7) : 1024 * (blockIdx.x - 32) + 64 * q);
                    if (SD_WOP) delay_clk(SD_WOP);
                }
            }
            bar_sync(5, 128);
            const int ke0 = sh ? blockIdx.x & 7 : 2 * (blockIdx.x - 32);
            const unsigned int* f = &g_prog[12 * ke0 + (lane < (sh ? 12 : 24) ? lane : 0)];
            int avail = 0;
            #pragma unroll 1
            for (int s = 0; s < LSEG; s++) {
                if (s >= avail) {
                    int it = 0;
                    while (true) {
                        uint32_t v;
                        asm volatile("ld.acquire.gpu.global.u32 %0, [%1];" : "=r"(v) : "l"(f) : "memory");
                        avail = __reduce_min_sync(0xffffffffu, (v >> 8) == (epoch & 0xffffffu) ? v & 255u : 0u);
                        if (avail > s || ++it >= SD_SPIN) break;
                        if (s < LSEG - 1) __nanosleep(64);
                    }
                    asm volatile("fence.proxy.async.global;" ::: "memory");
                    if (lane == 0 && s == LSEG - 1) GT(blockIdx.x, 70);
                }
                if (lane == 0 && s == 2 && blockIdx.x == 0) st_relaxed32(&g_epoch, epoch + 1);
                const int b0 = sh ? s & 3 : s & 1, bp = (sh ? s >> 2 : s >> 1) & 1;
                const bf16* src = g_otok + (size_t)s * (SEG * NH * DH) + ke0 * 16384;
                mbar_wait_long(bEMPTY + 8 * b0, bp);
                if (!sh) mbar_wait_long(bEMPTY + 16 + 8 * b0, bp);
                #pragma unroll
                for (int hc = 0; hc < 2; hc++)
                    asm volatile("{\n.reg .pred p, q;\nelect.sync _|p, 0xffffffff;\nsetp.eq.and.u32 q, %6, 0, p;\n"
                                 "@p mbarrier.arrive.expect_tx.shared.b64 _, [%2], 16384;\n"
                                 "@p cp.async.bulk.shared::cluster.global.mbarrier::complete_tx::bytes [%0], [%1], 16384, [%2];\n"
                                 "@q mbarrier.arrive.expect_tx.shared.b64 _, [%5], 16384;\n"
                                 "@q cp.async.bulk.shared::cluster.global.mbarrier::complete_tx::bytes [%3], [%4], 16384, [%5];\n}\n"
                        :: "r"(sb + SD_STG + b0 * 32768 + hc * 16384), "l"(src + hc * 8192), "r"(bCH + 32 * b0 + 8 * hc),
                           "r"(sb + SD_STG + (b0 + 2) * 32768 + hc * 16384), "l"(src + 16384 + hc * 8192), "r"(bCH + 32 * (b0 + 2) + 8 * hc), "r"((uint32_t)sh) : "memory");
            }
        } else {
            if (w == 3) {
                for (int i = 0; i < 16; i += 8) {
                    uint4 v[8]; uint32_t miss = 0xffu; int it = 0;
                    const uint32_t tag = epoch & 0xffffu;
                    #pragma unroll
                    for (int j = 0; j < 8; j++) v[j] = make_uint4(0, 0, 0, 0);
                    do {
                        #pragma unroll
                        for (int j = 0; j < 8; j++) ld_relaxed128_p(v[j], (const uint4*)g_gate + (i + j) * 32 + lane, miss & (1u << j));
                        miss = 0;
                        #pragma unroll
                        for (int j = 0; j < 8; j++) miss |= (uint32_t)((v[j].x >> 16) != tag || (v[j].y >> 16) != tag || (v[j].z >> 16) != tag || (v[j].w >> 16) != tag) << j;
                    } while (__any_sync(0xffffffffu, miss) && ++it < SD_SPIN);
                    #pragma unroll
                    for (int j = 0; j < 8; j++) sts128(sb + SD_Q0 + ((i + j) * 32 + lane) * 16, v[j]);
                }
            }
            bar_sync(5, 128);
        }
        if (w) units(2 * (w - 1), 4 * LSEG);
        }
        if (w < 2) {
            gates(4 * LSEG + 2 * w);
            bar_sync_p(6, 320, !pass);
            uint32_t sm[2][2];
            #pragma unroll
            for (int k = 0; k < 2; k++) {
                float a0 = 0.f, a1 = 0.f, a2 = 0.f, a3 = 0.f;
                #pragma unroll
                for (int i = 0; i < 4; i++) { const uint4 v = lds128(sb + SD_XCH + w * 4096 + k * 2048 + i * 512 + lane * 16); a0 += __uint_as_float(v.x); a1 += __uint_as_float(v.y); a2 += __uint_as_float(v.z); a3 += __uint_as_float(v.w); }
                sm[k][0] = pack_bf16(a0, a1); sm[k][1] = pack_bf16(a2, a3);
            }
            finish(4 * LSEG + 2 * w, sm, pass);
            if (lane == 0 && w == 1) GT(blockIdx.x, 1 + LSEG);
        }
        }
    }
    if (tid == 256) GT(blockIdx.x, 72);
}

extern "C" void kernel_launch(void* const* d_in, const int* in_sizes, int n_in, void* d_out, int out_size) {
    const bf16* x = (const bf16*)d_in[0];
    const bf16* mem0 = (const bf16*)d_in[1];
    const bf16* Wq = (const bf16*)d_in[2];
    const bf16* Wk = (const bf16*)d_in[3];
    const bf16* Wv = (const bf16*)d_in[4];
    const bf16* Wo = (const bf16*)d_in[5];
    const bf16* log_A_real = (const bf16*)d_in[8];
    const bf16* A_imag = (const bf16*)d_in[9];
    const bf16* C_real = (const bf16*)d_in[10];
    const bf16* C_imag = (const bf16*)d_in[11];
    const bf16* log_dt = (const bf16*)d_in[12];
    const bf16* D_skip = (const bf16*)d_in[13];
    const bf16* gate_w = (const bf16*)d_in[14];
    bf16* out = (bf16*)d_out;
    typedef CUresult (*EncFn)(CUtensorMap*, CUtensorMapDataType, cuuint32_t, void*, const cuuint64_t*, const cuuint64_t*, const cuuint32_t*, const cuuint32_t*,
                              CUtensorMapInterleave, CUtensorMapSwizzle, CUtensorMapL2promotion, CUtensorMapFloatOOBfill);
    static EncFn enc = nullptr;
    if (!enc) { void* fn = nullptr; cudaDriverEntryPointQueryResult qr; cudaGetDriverEntryPoint("cuTensorMapEncodeTiled", &fn, cudaEnableDefault, &qr); enc = (EncFn)fn; }
    auto mk = [&](CUtensorMap* tm, const void* ptr, uint64_t cols, uint64_t rows, uint32_t bc, uint32_t br) {
        cuuint64_t gdim[2] = {cols, rows}; cuuint64_t gstr[1] = {cols * 2}; cuuint32_t box[2] = {bc, br}; cuuint32_t estr[2] = {1, 1};
        enc(tm, CU_TENSOR_MAP_DATA_TYPE_BFLOAT16, 2, (void*)ptr, gdim, gstr, box, estr, CU_TENSOR_MAP_INTERLEAVE_NONE, bc == 64 ? CU_TENSOR_MAP_SWIZZLE_128B : CU_TENSOR_MAP_SWIZZLE_64B,
            CU_TENSOR_MAP_L2_PROMOTION_L2_256B, CU_TENSOR_MAP_FLOAT_OOB_FILL_NONE);
    };
    static bool attr_done = false;
    if (!attr_done) {
        cudaFuncSetAttribute(chain_kernel, cudaFuncAttributeMaxDynamicSharedMemorySize, SM_TOTAL);
        cudaFuncSetAttribute(side_kernel, cudaFuncAttributeMaxDynamicSharedMemorySize, SD_TOTAL);
        attr_done = true;
    }
    CUtensorMap tmx, tma, tmb, tmw, tmq, tmk, tmv, tmo;
    {
        cuuint64_t gdim[3] = {64, S_LEN, DM / 64}; cuuint64_t gstr[2] = {DM * 2, 128}; cuuint32_t box[3] = {64, SEG, 3}; cuuint32_t estr[3] = {1, 1, 1};
        enc(&tmx, CU_TENSOR_MAP_DATA_TYPE_BFLOAT16, 3, (void*)x, gdim, gstr, box, estr, CU_TENSOR_MAP_INTERLEAVE_NONE, CU_TENSOR_MAP_SWIZZLE_128B,
            CU_TENSOR_MAP_L2_PROMOTION_L2_256B, CU_TENSOR_MAP_FLOAT_OOB_FILL_NONE);
    }
    static void* acc = nullptr;
    if (!acc) cudaGetSymbolAddress(&acc, g_acc);
    for (int w = 0; w < 2; w++) {
        cuuint64_t gdim[3] = {64, 4, 64}; cuuint64_t gstr[2] = {256, 1024}; cuuint32_t box[3] = {w ? 8u : 32u, 2, w ? 6u : 12u}; cuuint32_t estr[3] = {1, 1, 1};
        enc(w ? &tmb : &tma, CU_TENSOR_MAP_DATA_TYPE_UINT32, 3, acc, gdim, gstr, box, estr, CU_TENSOR_MAP_INTERLEAVE_NONE, CU_TENSOR_MAP_SWIZZLE_NONE,
            CU_TENSOR_MAP_L2_PROMOTION_NONE, CU_TENSOR_MAP_FLOAT_OOB_FILL_NONE);
    }
    mk(&tmw, Wo, DM, NH * DH, 64, 64);
    mk(&tmo, Wo, DM, NH * DH, 32, 128);
    mk(&tmq, Wq, NH * DH, DM, 32, 144); mk(&tmk, Wk, NH * DH, DM, 32, 144); mk(&tmv, Wv, NH * DH, DM, 32, 144);
    chain_kernel<<<96, CH_THREADS, SM_TOTAL>>>(tmx, tmq, tmk, tmv, tmo, tma, tmb, mem0, 0u);
    cudaLaunchConfig_t cfg = {};
    cfg.gridDim = dim3(SD_CTAS); cfg.blockDim = dim3(SD_THREADS); cfg.dynamicSmemBytes = SD_TOTAL; cfg.stream = cudaStreamPerThread;
    cudaLaunchAttribute at[1];
    at[0].id = cudaLaunchAttributeProgrammaticStreamSerialization; at[0].val.programmaticStreamSerializationAllowed = 1;
    cfg.attrs = at; cfg.numAttrs = 1;
    cudaLaunchKernelEx(&cfg, side_kernel, tmw, x, log_A_real, A_imag, C_real, C_imag, log_dt, D_skip, gate_w, out, 2);
}
```

```cpp
#include <cuda_runtime.h>
#include <cuda.h>
#include <cuda_bf16.h>
#include <stdint.h>

#define S_LEN 2048
#define DM 576
#define NH 32
#define DH 128
#define NMEM 8
#define SEG 32
#define NSEG 64
#define LQ 40
#define NS 128

typedef __nv_bfloat16 bf16;

__device__ __forceinline__ float bf(bf16 v) { return __bfloat162float(v); }
__device__ __forceinline__ bf16 tobf(float v) { return __float2bfloat16_rn(v); }
__device__ __forceinline__ float rbf(float v) { return __bfloat162float(__float2bfloat16_rn(v)); }

#define CH_THREADS 384
#define SPIN_LIMIT (1 << 17)
#define SM_X     0
#define XBUF     36864
#define SM_TOK   73728
#define TOKBUF   24576
#define SM_STASH 139264
#define SM_TS    (SM_STASH + 3072)
#define SM_WO    147456
#define SM_MEM   196608
#define SM_EX    205824
#define EXBUF    6144
#define SM_P     218112
#define SM_OST   131072
#define SM_MEM2(a) ((a) == 2 ? 142848 : 122880 + (a) * 3456)
#define SM_PARK  219136
#define SM_O     223232
#define SM_XT    225280
#define SM_BAR   228352
#define SM_IL    (SM_BAR + 128)
#define SM_TG    (SM_IL + 256)
#define SM_TOTAL (SM_TG + 64)

#define ACC_X    36864
#define ACC_FULL 0x0020u
#define SLOT_OFF(sl) ((((sl) & 1) << 7) | (((sl) & 2) << 8))
__device__ __align__(65536) unsigned char g_acc[65536];
__device__ unsigned int g_init[96];
__device__ __align__(1024) uint4 g_last[36][2][32][32];
__device__ unsigned int g_epoch = 1;
__device__ __align__(128) unsigned int g_ts[128];
__device__ __align__(1024) bf16 g_otok[S_LEN * NH * DH];
__device__ __align__(1024) unsigned char g_tokx[96][8192];
__device__ __align__(128) unsigned int g_prog[96];
#define STAMP(i)
#define STAMPV(i, v)
#define GT(b, i)
#define PT(i)
#define STAMPB(i)

__device__ __forceinline__ uint32_t smem_u32(const void* p) { return (uint32_t)__cvta_generic_to_shared(p); }
__device__ __forceinline__ void ldsm_x4(uint32_t (&r)[4], uint32_t addr) {
    asm volatile("ldmatrix.sync.aligned.m8n8.x4.shared.b16 {%0,%1,%2,%3}, [%4];" : "=r"(r[0]), "=r"(r[1]), "=r"(r[2]), "=r"(r[3]) : "r"(addr) : "memory");
}
__device__ __forceinline__ void ldsm_x4_p(uint32_t (&r)[4], uint32_t addr, uint32_t skip) {
    asm volatile("{\n.reg .pred p;\nsetp.eq.u32 p, %5, 0;\n@p ldmatrix.sync.aligned.m8n8.x4.shared.b16 {%0,%1,%2,%3}, [%4];\n}\n" : "+r"(r[0]), "+r"(r[1]), "+r"(r[2]), "+r"(r[3]) : "r"(addr), "r"(skip) : "memory");
}
__device__ __forceinline__ void ldsm_x4_t(uint32_t (&r)[4], uint32_t addr) {
    asm volatile("ldmatrix.sync.aligned.m8n8.x4.trans.shared.b16 {%0,%1,%2,%3}, [%4];" : "=r"(r[0]), "=r"(r[1]), "=r"(r[2]), "=r"(r[3]) : "r"(addr) : "memory");
}
__device__ __forceinline__ uint32_t ldsm_x1_t(uint32_t addr) {
    uint32_t r; asm volatile("ldmatrix.sync.aligned.m8n8.x1.trans.shared.b16 {%0}, [%1];" : "=r"(r) : "r"(addr) : "memory"); return r;
}
__device__ __forceinline__ void ldsm_x2_t(uint32_t& r0, uint32_t& r1, uint32_t addr) {
    asm volatile("ldmatrix.sync.aligned.m8n8.x2.trans.shared.b16 {%0,%1}, [%2];" : "=r"(r0), "=r"(r1) : "r"(addr) : "memory");
}
__device__ __forceinline__ void stsm_x4(uint32_t addr, uint32_t r0, uint32_t r1, uint32_t r2, uint32_t r3) {
    asm volatile("stmatrix.sync.aligned.m8n8.x4.shared.b16 [%0], {%1,%2,%3,%4};" :: "r"(addr), "r"(r0), "r"(r1), "r"(r2), "r"(r3) : "memory");
}
__device__ __forceinline__ void stsm_x4_t(uint32_t addr, uint32_t r0, uint32_t r1, uint32_t r2, uint32_t r3) {
    asm volatile("stmatrix.sync.aligned.m8n8.x4.trans.shared.b16 [%0], {%1,%2,%3,%4};" :: "r"(addr), "r"(r0), "r"(r1), "r"(r2), "r"(r3) : "memory");
}
__device__ __forceinline__ void mma16816(float (&c)[4], const uint32_t (&a)[4], uint32_t b0, uint32_t b1) {
    asm("mma.sync.aligned.m16n8k16.row.col.f32.bf16.bf16.f32 {%0,%1,%2,%3}, {%4,%5,%6,%7}, {%8,%9}, {%0,%1,%2,%3};"
        : "+f"(c[0]), "+f"(c[1]), "+f"(c[2]), "+f"(c[3]) : "r"(a[0]), "r"(a[1]), "r"(a[2]), "r"(a[3]), "r"(b0), "r"(b1));
}
__device__ __forceinline__ void mma16816r(float (&c)[4], uint32_t a0, uint32_t a1, uint32_t a2, uint32_t a3, uint32_t b0, uint32_t b1) {
    asm("mma.sync.aligned.m16n8k16.row.col.f32.bf16.bf16.f32 {%0,%1,%2,%3}, {%4,%5,%6,%7}, {%8,%9}, {%0,%1,%2,%3};"
        : "+f"(c[0]), "+f"(c[1]), "+f"(c[2]), "+f"(c[3]) : "r"(a0), "r"(a1), "r"(a2), "r"(a3), "r"(b0), "r"(b1));
}
__device__ __forceinline__ void mma1688(float (&c)[4], uint32_t a0, uint32_t a1, uint32_t b0) {
    asm("mma.sync.aligned.m16n8k8.row.col.f32.bf16.bf16.f32 {%0,%1,%2,%3}, {%4,%5}, {%6}, {%0,%1,%2,%3};"
        : "+f"(c[0]), "+f"(c[1]), "+f"(c[2]), "+f"(c[3]) : "r"(a0), "r"(a1), "r"(b0));
}
__device__ __forceinline__ uint32_t pack_bf16(float lo, float hi) {
    uint32_t r; asm("cvt.rn.bf16x2.f32 %0, %1, %2;" : "=r"(r) : "f"(hi), "f"(lo)); return r;
}
__device__ __forceinline__ float bf_lo(uint32_t v) { return __uint_as_float(v << 16); }
__device__ __forceinline__ float bf_hi(uint32_t v) { return __uint_as_float(v & 0xffff0000u); }
__device__ __forceinline__ uint32_t max_bf2(uint32_t a, uint32_t b) { uint32_t r; asm("max.bf16x2 %0, %1, %2;" : "=r"(r) : "r"(a), "r"(b)); return r; }
__device__ __forceinline__ uint32_t maxabs_bf2(uint32_t a, uint32_t b) { uint32_t r; asm("max.NaN.xorsign.abs.bf16x2 %0, %1, %2;" : "=r"(r) : "r"(a), "r"(b)); return r; }
__device__ __forceinline__ float ex2(float x) { float r; asm("ex2.approx.ftz.f32 %0, %1;" : "=f"(r) : "f"(x)); return r; }
__device__ __forceinline__ void ld_relaxed128_p(uint4& v, const uint4* p, uint32_t pred) {
    asm volatile("{\n.reg .pred p;\nsetp.ne.u32 p, %5, 0;\n@p ld.relaxed.gpu.global.v4.u32 {%0,%1,%2,%3}, [%4];\n}\n" : "+r"(v.x), "+r"(v.y), "+r"(v.z), "+r"(v.w) : "l"(p), "r"(pred) : "memory");
}
__device__ __forceinline__ uint4 ld_relaxed128(const uint4* p) { uint4 v; asm volatile("ld.relaxed.gpu.global.v4.u32 {%0,%1,%2,%3}, [%4];" : "=r"(v.x), "=r"(v.y), "=r"(v.z), "=r"(v.w) : "l"(p) : "memory"); return v; }
__device__ __forceinline__ uint32_t ld_relaxed32(const uint32_t* p) { uint32_t v; asm volatile("ld.relaxed.gpu.global.u32 %0, [%1];" : "=r"(v) : "l"(p) : "memory"); return v; }
__device__ __forceinline__ void st_relaxed128(uint4* p, uint4 v) { asm volatile("st.relaxed.gpu.global.v4.u32 [%0], {%1,%2,%3,%4};" :: "l"(p), "r"(v.x), "r"(v.y), "r"(v.z), "r"(v.w) : "memory"); }
__device__ __forceinline__ void st_relaxed32(uint32_t* p, uint32_t v) { asm volatile("st.relaxed.gpu.global.u32 [%0], %1;" :: "l"(p), "r"(v) : "memory"); }
__device__ __forceinline__ void st_relaxed128_p(uint4* p, uint4 v, uint32_t skip) {
    asm volatile("{\n.reg .pred p;\nsetp.eq.u32 p, %5, 0;\n@p st.relaxed.gpu.global.v4.u32 [%0], {%1,%2,%3,%4};\n}\n" :: "l"(p), "r"(v.x), "r"(v.y), "r"(v.z), "r"(v.w), "r"(skip) : "memory");
}
__device__ __forceinline__ void st_relaxed64_p(void* p, uint32_t x, uint32_t y, uint32_t skip) {
    asm volatile("{\n.reg .pred p;\n.reg .b64 v;\nsetp.eq.u32 p, %3, 0;\nmov.b64 v, {%1,%2};\n@p st.relaxed.gpu.global.b64 [%0], v;\n}\n" :: "l"(p), "r"(x), "r"(y), "r"(skip) : "memory");
}
__device__ __forceinline__ void ld_relaxed64_p(uint2& v, const void* p, uint32_t pred) {
    asm volatile("{\n.reg .pred p;\n.reg .b64 v;\nsetp.ne.u32 p, %3, 0;\nmov.b64 v, {%0,%1};\n@p ld.relaxed.gpu.global.b64 v, [%2];\nmov.b64 {%0,%1}, v;\n}\n" : "+r"(v.x), "+r"(v.y) : "l"(p), "r"(pred) : "memory");
}
__device__ __forceinline__ uint2 ld_relaxed64(const void* p) {
    uint2 v; asm volatile("{\n.reg .b64 v;\nld.relaxed.gpu.global.b64 v, [%2];\nmov.b64 {%0,%1}, v;\n}\n" : "=r"(v.x), "=r"(v.y) : "l"(p) : "memory"); return v;
}
__device__ __forceinline__ void st_relaxed32_p(void* p, uint32_t v, uint32_t skip) {
    asm volatile("{\n.reg .pred p;\nsetp.eq.u32 p, %2, 0;\n@p st.relaxed.gpu.global.u32 [%0], %1;\n}\n" :: "l"(p), "r"(v), "r"(skip) : "memory");
}
__device__ __forceinline__ void bar_arrive_p(int id, int n, uint32_t skip) {
    asm volatile("{\n.reg .pred p;\nsetp.eq.u32 p, %2, 0;\n@p bar.arrive %0, %1;\n}\n" :: "r"(id), "r"(n), "r"(skip) : "memory");
}
__device__ __forceinline__ void bar_sync_p(int id, int n, uint32_t skip) {
    asm volatile("{\n.reg .pred p;\nsetp.eq.u32 p, %2, 0;\n@p bar.sync %0, %1;\n}\n" :: "r"(id), "r"(n), "r"(skip) : "memory");
}
__device__ __forceinline__ uint32_t movm(uint32_t x) { uint32_t r; asm volatile("movmatrix.sync.aligned.m8n8.trans.b16 %0, %1;" : "=r"(r) : "r"(x)); return r; }
__device__ __forceinline__ void sts32_p(uint32_t a, uint32_t v, uint32_t doit) {
    asm volatile("{\n.reg .pred p;\nsetp.ne.u32 p, %2, 0;\n@p st.shared.u32 [%0], %1;\n}\n" :: "r"(a), "r"(v), "r"(doit) : "memory");
}
__device__ __forceinline__ uint32_t pin(uint32_t x) { return __shfl_sync(0xffffffffu, x, threadIdx.x & 31); }
__device__ __forceinline__ void ldsm16_t(uint32_t (&b)[4][4], uint32_t a) {
    asm volatile("ldmatrix.sync.aligned.m8n8.x4.trans.shared.b16 {%0,%1,%2,%3}, [%16];\n"
                 "ldmatrix.sync.aligned.m8n8.x4.trans.shared.b16 {%4,%5,%6,%7}, [%16+512];\n"
                 "ldmatrix.sync.aligned.m8n8.x4.trans.shared.b16 {%8,%9,%10,%11}, [%16+1024];\n"
                 "ldmatrix.sync.aligned.m8n8.x4.trans.shared.b16 {%12,%13,%14,%15}, [%16+1536];\n"
        : "=r"(b[0][0]), "=r"(b[0][1]), "=r"(b[0][2]), "=r"(b[0][3]), "=r"(b[1][0]), "=r"(b[1][1]), "=r"(b[1][2]), "=r"(b[1][3]),
          "=r"(b[2][0]), "=r"(b[2][1]), "=r"(b[2][2]), "=r"(b[2][3]), "=r"(b[3][0]), "=r"(b[3][1]), "=r"(b[3][2]), "=r"(b[3][3]) : "r"(a) : "memory");
}
template<int ID> __device__ __forceinline__ void sched_fence(uint32_t never) { while (never == 0x7fffff00u + ID) { asm volatile("nanosleep.u32 64;" ::: "memory"); } }
__device__ __forceinline__ uint32_t opaque_u() { uint32_t v; asm volatile("mov.u32 %0, %%nsmid;" : "=r"(v)); return v; }
__device__ __forceinline__ uint32_t bar_red_or(int id, int n, uint32_t v) {
    uint32_t r; asm volatile("{\n.reg .pred p, q;\nsetp.ne.u32 p, %3, 0;\nbar.red.or.pred q, %1, %2, p;\nselp.u32 %0, 1, 0, q;\n}\n" : "=r"(r) : "r"(id), "r"(n), "r"(v) : "memory"); return r;
}
template<class T> __device__ __forceinline__ T* launder_p(T* p) { asm volatile("" : "+l"(p)); return p; }
__device__ __forceinline__ uint32_t mapa_u32(uint32_t addr, uint32_t rank) { uint32_t d; asm("mapa.shared::cluster.u32 %0, %1, %2;" : "=r"(d) : "r"(addr), "r"(rank)); return d; }
__device__ __forceinline__ uint32_t mapa_v(uint32_t addr, uint32_t rank) { uint32_t d; asm volatile("mapa.shared::cluster.u32 %0, %1, %2;" : "=r"(d) : "r"(addr), "r"(rank)); return d; }
__device__ __forceinline__ void st_async32(uint32_t addr, uint32_t v, uint32_t mbar) { asm volatile("st.async.shared::cluster.mbarrier::complete_tx::bytes.u32 [%0], %1, [%2];" :: "r"(addr), "r"(v), "r"(mbar) : "memory"); }
__device__ __forceinline__ void cluster_arrive() { asm volatile("barrier.cluster.arrive.release.aligned;" ::: "memory"); }
__device__ __forceinline__ void cluster_wait() { asm volatile("barrier.cluster.wait.acquire.aligned;" ::: "memory"); }
__device__ __forceinline__ void cp_async16(uint32_t dst, const void* src) { asm volatile("cp.async.cg.shared.global [%0], [%1], 16;" :: "r"(dst), "l"(src) : "memory"); }
__device__ __forceinline__ void cp_async_commit() { asm volatile("cp.async.commit_group;" ::: "memory"); }
template<int N> __device__ __forceinline__ void cp_async_wait() { asm volatile("cp.async.wait_group %0;" :: "n"(N) : "memory"); }
__device__ __forceinline__ void cp_async_wait0() { asm volatile("cp.async.wait_group 0;" ::: "memory"); }
__device__ __forceinline__ void mbar_init(uint32_t a, uint32_t cnt) { asm volatile("mbarrier.init.shared.b64 [%0], %1;" :: "r"(a), "r"(cnt) : "memory"); }
__device__ __forceinline__ void mbar_expect_tx(uint32_t a, uint32_t bytes) { asm volatile("mbarrier.arrive.expect_tx.shared.b64 _, [%0], %1;" :: "r"(a), "r"(bytes) : "memory"); }
__device__ __forceinline__ bool mbar_try(uint32_t a, uint32_t parity) {
    uint32_t ok; asm volatile("{\n.reg .pred p;\nmbarrier.try_wait.parity.shared::cta.b64 p, [%1], %2;\nselp.u32 %0, 1, 0, p;\n}\n" : "=r"(ok) : "r"(a), "r"(parity) : "memory"); return ok;
}
__device__ __forceinline__ void mbar_wait(uint32_t a, uint32_t parity) { int it = 0; bool more; do { more = ++it < SPIN_LIMIT; } while (!mbar_try(a, parity) && more); }
__device__ __forceinline__ void bar_sync(int id, int n) { asm volatile("bar.sync %0, %1;" :: "r"(id), "r"(n) : "memory"); }
__device__ __forceinline__ void bar_arrive(int id, int n) { asm volatile("bar.arrive %0, %1;" :: "r"(id), "r"(n) : "memory"); }
__device__ __forceinline__ void fence_async_smem() { asm volatile("fence.proxy.async.shared::cta;" ::: "memory"); }
__device__ __forceinline__ void sts32(uint32_t a, uint32_t v) { asm volatile("st.shared.u32 [%0], %1;" :: "r"(a), "r"(v) : "memory"); }
__device__ __forceinline__ void sts128(uint32_t a, uint4 v) { asm volatile("st.shared.v4.u32 [%0], {%1,%2,%3,%4};" :: "r"(a), "r"(v.x), "r"(v.y), "r"(v.z), "r"(v.w) : "memory"); }
__device__ __forceinline__ uint4 lds128(uint32_t a) { uint4 v; asm volatile("ld.shared.v4.u32 {%0,%1,%2,%3}, [%4];" : "=r"(v.x), "=r"(v.y), "=r"(v.z), "=r"(v.w) : "r"(a) : "memory"); return v; }
__device__ __forceinline__ uint32_t lds32(uint32_t a) { uint32_t v; asm volatile("ld.shared.u32 %0, [%1];" : "=r"(v) : "r"(a) : "memory"); return v; }
__device__ __forceinline__ uint32_t gtime_lo() { uint32_t t; asm volatile("mov.u32 %0, %globaltimer_lo;" : "=r"(t)); return t; }
__device__ __forceinline__ void wait_gtime(uint32_t tg) {
    asm volatile("{\n.reg .pred p, q;\n.reg .b64 t;\n.reg .b32 lo, hi, d, n;\nmov.b32 n, 300;\n"
                 "WG_%=:\nmov.u64 t, %%globaltimer;\nmov.b64 {lo, hi}, t;\nsub.s32 d, lo, %0;\nsub.s32 n, n, 1;\n"
                 "setp.gt.s32 q, n, 0;\nsetp.lt.and.s32 p, d, 0, q;\n@p bra.uni WG_%=;\n}\n" :: "r"(tg) : "memory");
}
__device__ __forceinline__ void delay_clk(int d) { uint32_t t0 = clock(); while ((int)(clock() - t0) < d) {} }

__device__ __forceinline__ uint64_t desc128(uint32_t addr) {
    return (uint64_t)((addr & 0x3FFFF) >> 4) | ((uint64_t)1 << 16) | ((uint64_t)64 << 32) | ((uint64_t)1 << 62);
}
template<int accum> __device__ __forceinline__ void wgmma_n32(float (&d)[16], const uint32_t (&a)[4], uint64_t desc) {
    if (accum) {
        asm volatile("{\n.reg .pred p;\nsetp.ne.b32 p, 1, 0;\n"
            "wgmma.mma_async.sync.aligned.m64n32k16.f32.bf16.bf16 {%0,%1,%2,%3,%4,%5,%6,%7,%8,%9,%10,%11,%12,%13,%14,%15}, {%16,%17,%18,%19}, %20, p, 1, 1, 0;\n}\n"
            : "+f"(d[0]), "+f"(d[1]), "+f"(d[2]), "+f"(d[3]), "+f"(d[4]), "+f"(d[5]), "+f"(d[6]), "+f"(d[7]),
              "+f"(d[8]), "+f"(d[9]), "+f"(d[10]), "+f"(d[11]), "+f"(d[12]), "+f"(d[13]), "+f"(d[14]), "+f"(d[15])
            : "r"(a[0]), "r"(a[1]), "r"(a[2]), "r"(a[3]), "l"(desc));
    } else {
        asm volatile("{\n.reg .pred p;\nsetp.ne.b32 p, 0, 0;\n"
            "wgmma.mma_async.sync.aligned.m64n32k16.f32.bf16.bf16 {%0,%1,%2,%3,%4,%5,%6,%7,%8,%9,%10,%11,%12,%13,%14,%15}, {%16,%17,%18,%19}, %20, p, 1, 1, 0;\n}\n"
            : "=f"(d[0]), "=f"(d[1]), "=f"(d[2]), "=f"(d[3]), "=f"(d[4]), "=f"(d[5]), "=f"(d[6]), "=f"(d[7]),
              "=f"(d[8]), "=f"(d[9]), "=f"(d[10]), "=f"(d[11]), "=f"(d[12]), "=f"(d[13]), "=f"(d[14]), "=f"(d[15])
            : "r"(a[0]), "r"(a[1]), "r"(a[2]), "r"(a[3]), "l"(desc));
    }
}
__device__ __forceinline__ float rcp_approx(float x) { float r; asm("rcp.approx.ftz.f32 %0, %1;" : "=f"(r) : "f"(x)); return r; }
__device__ __forceinline__ void wg_fence() { asm volatile("wgmma.fence.sync.aligned;" ::: "memory"); }
__device__ __forceinline__ void wg_commit() { asm volatile("wgmma.commit_group.sync.aligned;" ::: "memory"); }
__device__ __forceinline__ void wg_wait0() { asm volatile("wgmma.wait_group.sync.aligned 0;" ::: "memory"); }

#define SCALE_HI 0x3db53db5u
#define SCALE_LO 0x371e371eu
#define LOG2E 1.4426950408889634f
#define NEG_BIG2 0xce6ece6eu
__device__ __forceinline__ uint32_t scale_bf2(uint32_t x) {
    uint32_t t, r;
    asm("mul.rn.bf16x2 %0, %1, %2;" : "=r"(t) : "r"(x), "r"(SCALE_LO));
    asm("fma.rn.bf16x2 %0, %1, %2, %3;" : "=r"(r) : "r"(x), "r"(SCALE_HI), "r"(t));
    return r;
}
__device__ __forceinline__ void cluster_arrive_rx() { asm volatile("barrier.cluster.arrive.relaxed.aligned;" ::: "memory"); }
__device__ __forceinline__ uint32_t launder(uint32_t x) { asm volatile("" : "+r"(x)); return x; }
__device__ __forceinline__ void mbar_arrive(uint32_t a) { asm volatile("mbarrier.arrive.shared.b64 _, [%0];" :: "r"(a) : "memory"); }
__device__ __forceinline__ void mbar_wait_cl(uint32_t a, uint32_t parity) {
    int it = 0; uint32_t ok;
    do { asm volatile("{\n.reg .pred p;\nmbarrier.try_wait.parity.acquire.cluster.shared::cta.b64 p, [%1], %2;\nselp.u32 %0, 1, 0, p;\n}\n" : "=r"(ok) : "r"(a), "r"(parity) : "memory"); } while (!ok && ++it < SPIN_LIMIT);
}
__device__ __forceinline__ uint64_t desc_from(uint32_t lo) { return (uint64_t)lo | ((uint64_t)0x40000040u << 32); }
#define SB_OFF 1024u
#define DESC_LO(off) ((((SB_OFF + (uint32_t)(off)) & 0x3FFFFu) >> 4) | 0x10000u)
template<int N> struct ic { static constexpr int value = N; };
__device__ __forceinline__ uint32_t uni(uint32_t x) { return __shfl_sync(0xffffffffu, x, 0); }

__device__ __forceinline__ uint32_t pack_f16(float lo, float hi) { uint32_t r; asm("cvt.rn.f16x2.f32 %0, %1, %2;" : "=r"(r) : "f"(hi), "f"(lo)); return r; }
__device__ __forceinline__ void sts16(uint32_t a, uint16_t v) { asm volatile("st.shared.u16 [%0], %1;" :: "r"(a), "h"(v) : "memory"); }
__device__ __forceinline__ void sts64(uint32_t a, uint32_t x, uint32_t y) { asm volatile("st.shared.v2.u32 [%0], {%1,%2};" :: "r"(a), "r"(x), "r"(y) : "memory"); }
__device__ __forceinline__ void ld_relaxed32_p(uint32_t& v, const void* p, uint32_t pred) {
    asm volatile("{\n.reg .pred p;\nsetp.ne.u32 p, %2, 0;\n@p ld.relaxed.gpu.global.u32 %0, [%1];\n}\n" : "+r"(v) : "l"(p), "r"(pred) : "memory");
}
__device__ __forceinline__ uint2 lds64(uint32_t a) { uint2 v; asm volatile("ld.shared.v2.u32 {%0,%1}, [%2];" : "=r"(v.x), "=r"(v.y) : "r"(a) : "memory"); return v; }
__device__ __forceinline__ void mbar_wait2(uint32_t a, uint32_t pa, uint32_t b, uint32_t pb) {
    int it = 0; uint32_t ok;
    do { asm volatile("{\n.reg .pred p, q;\nmbarrier.try_wait.parity.shared::cta.b64 p, [%1], %2;\nmbarrier.try_wait.parity.shared::cta.b64 q, [%3], %4;\nand.pred p, p, q;\nselp.u32 %0, 1, 0, p;\n}\n"
                      : "=r"(ok) : "r"(a), "r"(pa), "r"(b), "r"(pb) : "memory"); } while (!ok && ++it < SPIN_LIMIT);
}
__device__ __forceinline__ float exd(float s, float m) { return ex2(__fmul_rn(__fsub_rn(s, m), LOG2E)); }
__device__ __forceinline__ uint32_t gtime_after(uint32_t z) {
    uint32_t t = 0; asm volatile("{\n.reg .pred p;\nsetp.eq.u32 p, %1, 0;\n@p mov.u32 %0, %%globaltimer_lo;\n}\n" : "+r"(t) : "r"(z)); return t;
}
__device__ __forceinline__ uint32_t ld_acquire32(const uint32_t* p) { uint32_t v; asm volatile("ld.acquire.gpu.global.u32 %0, [%1];" : "=r"(v) : "l"(p) : "memory"); return v; }
#define T_MMAK 4
#define T_KPRE 3
#define BLK_Q(p) (((p) < 3 ? (p) : 8) * 2048)
#define BLK_K(p) (((p) < 3 ? 4 + (p) : 9) * 2048)
#define BLK_V(p) (((p) < 2 ? 3 + 4 * (p) : 8 + (p)) * 2048)
__device__ __forceinline__ uint32_t exp_bf2(uint32_t s) { return pack_bf16(ex2(bf_lo(s) * LOG2E), ex2(bf_hi(s) * LOG2E)); }
template<int MT, int LO, int HI>
__device__ __forceinline__ void tok_loadv(uint32_t tok, int eh, int lane, uint32_t (&bv)[8][4]) {
    const int r8 = lane & 7;
    const uint32_t va = MT ? tok + lane * 64 + ((r8 >> 1) << 4) : tok + (lane & 15) * 64 + (((lane >> 4) ^ (r8 >> 1)) << 4);
    const uint32_t o0 = eh ? BLK_V(2) : BLK_V(0), o1 = eh ? BLK_V(3) : BLK_V(1);
    #pragma unroll
    for (int n = LO; n < HI; n++) { if (MT) ldsm_x4_t(bv[n], (va ^ ((n & 3) << 4)) + (n < 4 ? o0 : o1)); else ldsm_x4_t(bv[n], (va ^ ((n & 1) << 5)) + BLK_V(n >> 1)); }
}
#define T_VPRE 4
template<int MT, class F>
__device__ __forceinline__ void tok_part1(uint32_t tok, int eh, int lane, uint32_t (&q)[8][4], uint32_t (&sp)[5][2], uint32_t (&pa)[5][2], uint32_t (&bv)[8][4], uint32_t& rng, F&& hold) {
    float e[5][4];
    constexpr int NK = MT ? 5 : 3;
    const int g = lane >> 2, t = lane & 3, mi = lane >> 3, r8 = lane & 7;
    #pragma unroll
    for (int nt = 1; nt < NK; nt++) { e[nt][0] = e[nt][1] = e[nt][2] = e[nt][3] = 0.f; }
    const uint32_t qa = tok + (16 * MT + (mi & 1) * 8 + r8) * 64 + (((mi >> 1) ^ (r8 >> 1)) << 4);
    const uint32_t ka = tok + r8 * 64 + ((mi ^ (r8 >> 1)) << 4);
    uint32_t b[4][NK][4];
    constexpr int PRE = MT ? T_KPRE : 4;
    #pragma unroll
    for (int k2 = 0; k2 < 4; k2++) {
        ldsm_x4(q[2 * k2], qa + BLK_Q(k2)); ldsm_x4(q[2 * k2 + 1], (qa ^ 32) + BLK_Q(k2));
        if (k2 < PRE) {
            #pragma unroll
            for (int nt = 1; nt < NK; nt++) ldsm_x4(b[k2][nt], ka + BLK_K(k2) + (nt - 1) * 512);
        }
    }
    hold();
    #pragma unroll
    for (int k2 = 0; k2 < 4; k2++) {
        if (k2 >= PRE) {
            #pragma unroll
            for (int nt = 1; nt < NK; nt++) ldsm_x4(b[k2][nt], ka + BLK_K(k2) + (nt - 1) * 512);
        }
        #pragma unroll
        for (int nt = 1; nt < NK; nt++) if (k2 < T_MMAK) mma16816(e[nt], q[2 * k2], b[k2][nt][0], b[k2][nt][1]);
        #pragma unroll
        for (int nt = 1; nt < NK; nt++) if (k2 < T_MMAK) mma16816(e[nt], q[2 * k2 + 1], b[k2][nt][2], b[k2][nt][3]);
    }
    #pragma unroll
    for (int nt = 1; nt < NK; nt++) asm volatile("" : "+f"(e[nt][0]), "+f"(e[nt][1]), "+f"(e[nt][2]), "+f"(e[nt][3]));
    #pragma unroll
    for (int nt = 1; nt < NK; nt++) {
        sp[nt][0] = nt < NK - 1 ? scale_bf2(pack_bf16(e[nt][0], e[nt][1])) : NEG_BIG2; sp[nt][1] = scale_bf2(pack_bf16(e[nt][2], e[nt][3]));
        rng = maxabs_bf2(nt == 1 ? sp[1][0] : (nt < NK - 1 ? maxabs_bf2(rng, sp[nt][0]) : rng), sp[nt][1]);
    }
    const uint32_t keep = (2 * t <= g ? 0x0000ffffu : 0u) | (2 * t + 1 <= g ? 0xffff0000u : 0u);
    sp[NK - 2][0] = (sp[NK - 2][0] & keep) | (NEG_BIG2 & ~keep);
    sp[NK - 1][1] = (sp[NK - 1][1] & keep) | (NEG_BIG2 & ~keep);
    #pragma unroll
    for (int nt = 1; nt < NK; nt++) { pa[nt][0] = nt < NK - 1 ? exp_bf2(sp[nt][0]) : 0u; pa[nt][1] = exp_bf2(sp[nt][1]); }
    tok_loadv<MT, 0, MT ? T_VPRE : 8>(tok, eh, lane, bv);
}
template<int MT, class F, class G, class H, class I>
__device__ __forceinline__ void tok_part2(uint32_t tok, uint32_t exl, uint32_t ost, int eh, int lane, const uint32_t (&q)[8][4], uint32_t (&sp)[5][2], uint32_t (&pa)[5][2], uint32_t (&bv)[8][4], uint32_t rng, bool vb,
                                          F&& wait_v, G&& duty, H&& pace, I&& wait_x) {
    constexpr int NK = MT ? 5 : 3;
    const int mi = lane >> 3, r8 = lane & 7;
    {
        float c[4][4];
        uint32_t b[4][4];
        ldsm16_t(b, exl + 2048);
        duty();
        #pragma unroll
        for (int j = 0; j < 4; j++) { c[j][0] = c[j][1] = c[j][2] = c[j][3] = 0.f; }
        #pragma unroll
        for (int k2 = 0; k2 < 4; k2++) { mma16816(c[(2 * k2) & 3], q[2 * k2], b[k2][0], b[k2][1]); mma16816(c[(2 * k2 + 1) & 3], q[2 * k2 + 1], b[k2][2], b[k2][3]); }
        sp[0][0] = scale_bf2(pack_bf16((c[0][0] + c[1][0]) + (c[2][0] + c[3][0]), (c[0][1] + c[1][1]) + (c[2][1] + c[3][1])));
        sp[0][1] = scale_bf2(pack_bf16((c[0][2] + c[1][2]) + (c[2][2] + c[3][2]), (c[0][3] + c[1][3]) + (c[2][3] + c[3][3])));
    }
    pa[0][0] = exp_bf2(sp[0][0]); pa[0][1] = exp_bf2(sp[0][1]);
    rng = maxabs_bf2(maxabs_bf2(rng, sp[0][0]), sp[0][1]);
    if (__builtin_expect(__any_sync(0xffffffffu, ((rng & 0x7fff7fffu) + 0x3ddf3ddfu) & 0x80008000u), 0)) {
        uint32_t m0 = sp[0][0], m1 = sp[0][1];
        #pragma unroll
        for (int nt = 1; nt < NK; nt++) { if (nt < NK - 1) m0 = max_bf2(m0, sp[nt][0]); m1 = max_bf2(m1, sp[nt][1]); }
        uint32_t mm = max_bf2(__byte_perm(m0, m1, 0x5410), __byte_perm(m0, m1, 0x7632));
        mm = max_bf2(mm, __shfl_xor_sync(0xffffffffu, mm, 1));
        mm = max_bf2(mm, __shfl_xor_sync(0xffffffffu, mm, 2));
        #pragma unroll
        for (int nt = 0; nt < NK; nt++) {
            if (nt < NK - 1) pa[nt][0] = pack_bf16(exd(bf_lo(sp[nt][0]), bf_lo(mm)), exd(bf_hi(sp[nt][0]), bf_lo(mm)));
            pa[nt][1] = pack_bf16(exd(bf_lo(sp[nt][1]), bf_hi(mm)), exd(bf_hi(sp[nt][1]), bf_hi(mm)));
        }
    }
    tok_loadv<MT, MT ? T_VPRE : 8, 8>(tok, eh, lane, bv);
    wait_v();
    constexpr int NQ = MT ? 2 : 4;
    float o[NQ][4][4], l[4] = {0.f, 0.f, 0.f, 0.f};
    const uint32_t ONE = 0x3F803F80u;
    mma16816r(l, pa[1][0], pa[1][1], pa[2][0], pa[2][1], ONE, ONE);
    if (MT) mma16816r(l, pa[3 % NK][0], pa[3 % NK][1], pa[4 % NK][0], pa[4 % NK][1], ONE, ONE);
    mma1688(l, pa[0][0], pa[0][1], ONE);
    #pragma unroll
    for (int j = 0; j < NQ; j++) {
        uint32_t bm[4];
        ldsm_x4(bm, exl + 4096 + (MT ? eh * 1024 : 0) + 512 * j);
        #pragma unroll
        for (int n = 0; n < 4; n++) {
            o[j][n][0] = o[j][n][1] = o[j][n][2] = o[j][n][3] = 0.f;
            if (MT) mma16816r(o[j][n], pa[1][0], pa[1][1], pa[2][0], pa[2][1], bv[4 * j + n][0], bv[4 * j + n][1]);
            else mma16816r(o[j][n], pa[1][0], pa[1][1], pa[2][0], pa[2][1], bv[2 * j + (n >> 1)][2 * (n & 1)], bv[2 * j + (n >> 1)][2 * (n & 1) + 1]);
        }
        if (MT) {
            #pragma unroll
            for (int n = 0; n < 4; n++) mma16816r(o[j][n], pa[3 % NK][0], pa[3 % NK][1], pa[4 % NK][0], pa[4 % NK][1], bv[4 * j + n][2], bv[4 * j + n][3]);
        }
        #pragma unroll
        for (int n = 0; n < 4; n++) mma1688(o[j][n], pa[0][0], pa[0][1], bm[n]);
    }
    #pragma unroll
    for (int j = 0; j < NQ; j++) asm volatile("" : "+f"(o[j][0][0]), "+f"(o[j][1][0]), "+f"(o[j][2][0]), "+f"(o[j][3][0]));
    asm volatile("" : "+f"(l[0]), "+f"(l[2]));
    wait_x();
    bar_arrive_p(12, 384, !vb);
    pace();
    const float i0 = rcp_approx(l[0]), i1 = rcp_approx(l[2]);
    const uint32_t oa = ost + ((mi & 1) * 8 + r8) * 128 + (((mi >> 1) ^ r8) << 4);
    #pragma unroll
    for (int j = 0; j < NQ; j++) {
        stsm_x4((oa ^ ((j & 1) << 6)) + (j >> 1) * 4096, pack_bf16(o[j][0][0] * i0, o[j][0][1] * i0), pack_bf16(o[j][0][2] * i1, o[j][0][3] * i1), pack_bf16(o[j][1][0] * i0, o[j][1][1] * i0), pack_bf16(o[j][1][2] * i1, o[j][1][3] * i1));
        stsm_x4((oa ^ (((j & 1) << 6) | 32)) + (j >> 1) * 4096, pack_bf16(o[j][2][0] * i0, o[j][2][1] * i0), pack_bf16(o[j][2][2] * i1, o[j][2][3] * i1), pack_bf16(o[j][3][0] * i0, o[j][3][1] * i0), pack_bf16(o[j][3][2] * i1, o[j][3][3] * i1));
    }
}

template<int OA>
__device__ __forceinline__ uint32_t send_main(float c0, float c1, float c2, float c3, uint32_t a, uint32_t l16) {
    uint32_t w2;
    asm volatile("{\n.reg .pred q, pl, ph;\n.reg .b64 pa;\n.reg .b32 t, w0, w1;\n.reg .f32 x, y, z;\n"
                 "and.b32 t, %7, 0x30;\nsetp.eq.u32 q, t, 0;\nand.b32 t, %7, 0x70;\nsetp.eq.u32 ph, t, 0;\nxor.pred pl, q, ph;\n"
                 "selp.f32 x, 0f00010000, %4, pl;\nselp.f32 y, 0f00010000, %6, ph;\nselp.f32 z, %6, %4, ph;\n"
                 "cvt.rn.bf16x2.f32 w0, x, %3;\ncvt.rn.bf16x2.f32 w1, y, %5;\ncvt.rn.bf16x2.f32 %0, 0f00010000, z;\n"
                 "mov.b64 pa, {%1, %2};\n"
                 "red.relaxed.gpu.global.add.noftz.bf16x2 [pa+%8], w0;\nred.relaxed.gpu.global.add.noftz.bf16x2 [pa+%9], w1;\n}\n"
        : "=r"(w2) : "r"(a), "r"((uint32_t)((uint64_t)g_acc >> 32)), "f"(c0), "f"(c1), "f"(c2), "f"(c3), "r"(l16), "n"(OA), "n"(OA + 256) : "memory");
    return w2;
}
template<int OB>
__device__ __forceinline__ void send_extra(uint32_t w2, uint32_t b, uint32_t l16) {
    asm volatile("{\n.reg .pred q;\n.reg .b64 pb;\n.reg .b32 t;\nand.b32 t, %3, 0x30;\nsetp.eq.u32 q, t, 0;\nmov.b64 pb, {%0, %1};\n"
                 "@q red.relaxed.gpu.global.add.noftz.bf16x2 [pb+%4], %2;\n}\n"
        :: "r"(b), "r"((uint32_t)((uint64_t)g_acc >> 32)), "r"(w2), "r"(l16), "n"(OB) : "memory");
}
#define X_AT 0
__device__ __forceinline__ uint32_t send_ua(uint32_t tile) { return (uint32_t)(uint64_t)g_acc + tile * 1024; }
__device__ __forceinline__ uint32_t send_ub(uint32_t tile) { return (uint32_t)(uint64_t)g_acc + ACC_X + (tile >> 1) * 1024 + (tile & 1) * 256; }
__device__ __forceinline__ void lds_il(float& il, float& ih, uint32_t a) {
    uint32_t x, y; asm volatile("ldmatrix.sync.aligned.m8n8.x2.shared.b16 {%0,%1}, [%2];" : "=r"(x), "=r"(y) : "r"(a) : "memory");
    il = __uint_as_float(x); ih = __uint_as_float(y);
}
template<bool AUX>
__device__ __forceinline__ uint32_t stage_w(const uint32_t (&wo)[8][4], uint32_t ol, uint32_t tile, uint32_t so, uint32_t l16, uint32_t nv, uint32_t ila, uint32_t& sx) {
    float il, ih;
    uint32_t b[4][4], sa;
    float c[2][4];
    auto addr = [&] {
        const uint32_t ll = AUX ? l16 : l16 | (__float_as_uint(c[0][0]) & nv);
        sa = (ll >> 2) + (send_ua(tile) + so); sx = (ll >> 4) + (send_ub(tile) + so);
    };
    ldsm16_t(b, ol);
    lds_il(il, ih, ila);
    if (AUX) addr(); else sched_fence<0>(nv);
    #pragma unroll
    for (int i = 0; i < 2; i++) c[i][0] = c[i][1] = c[i][2] = c[i][3] = 0.f;
    #pragma unroll
    for (int j = 0; j < 4; j++) {
        if (!AUX && j == 3) addr();
        mma16816(c[0], wo[2 * j], b[j][0], b[j][1]); mma16816(c[1], wo[2 * j + 1], b[j][2], b[j][3]);
    }
    if (AUX) { asm volatile("" : "+f"(c[0][0]), "+f"(c[1][0])); sched_fence<4>(nv); bar_arrive(12, 384); }
    return send_main<0>((c[0][0] + c[1][0]) * il, (c[0][1] + c[1][1]) * ih, (c[0][2] + c[1][2]) * il, (c[0][3] + c[1][3]) * ih, sa, l16);
}
__device__ __forceinline__ void wgmma_n16(float (&d)[8], const uint32_t (&a)[4], uint64_t desc) {
    asm volatile("{\n.reg .pred p;\nsetp.ne.b32 p, 1, 0;\n"
        "wgmma.mma_async.sync.aligned.m64n16k16.f32.bf16.bf16 {%0,%1,%2,%3,%4,%5,%6,%7}, {%8,%9,%10,%11}, %12, p, 1, 1, 0;\n}\n"
        : "+f"(d[0]), "+f"(d[1]), "+f"(d[2]), "+f"(d[3]), "+f"(d[4]), "+f"(d[5]), "+f"(d[6]), "+f"(d[7])
        : "r"(a[0]), "r"(a[1]), "r"(a[2]), "r"(a[3]), "l"(desc));
}

template<int N> __device__ __forceinline__ void code_pad(uint32_t nv) {
    if (N && nv == 0x7fffffe0u + N % 16) {
        float v = __uint_as_float(nv);
        #pragma unroll
        for (int i = 0; i < N; i++) asm volatile("fma.rn.f32 %0, %0, %0, %0;" : "+f"(v));
        sts32_p(0u, __float_as_uint(v), nv);
    }
}
#define PAD_T0 0
#define PAD_T1 0
#define PAD_S 0
#define PAD_P 0
#define BAR_PRO 1
#define BAR_MEM 2
#define BAR_P   3
#define BAR_PRJ 4
#define BAR_VGO 7
#define BAR_X0  7
#define BAR_S   9
#define BAR_P2  10
#define BAR_O   11
#define BAR_V   12
#define VGO_AT 9
#define TP_N 36
#define REG_P 200
#define WO_PRE 3
#define WO_REP 2
#define X_FIRST 0
#define VF0 1
#define X_PF 0
#define EXA 0
#define TG2 1
#define TG_D 0
#define ISS 2
#define DUAL 0
#define WO_LATE 0
#define TM_PF2 0
#ifndef M_RES
#define M_RES 5
#endif
#ifndef M_LAG
#define M_LAG 2
#endif
#ifndef M_ARR
#define M_ARR -1
#endif
#define G1_0 128
#define G1_NS 1184

__global__ void __cluster_dims__(3, 1, 1) __launch_bounds__(CH_THREADS, 1)
chain_kernel(const __grid_constant__ CUtensorMap tmx, const __grid_constant__ CUtensorMap tmq, const __grid_constant__ CUtensorMap tmk,
             const __grid_constant__ CUtensorMap tmv, const __grid_constant__ CUtensorMap tmo,
             const __grid_constant__ CUtensorMap tma, const __grid_constant__ CUtensorMap tmb, const bf16* __restrict__ mem0, const uint32_t nv_) {
    extern __shared__ __align__(1024) unsigned char smem[];
    const uint32_t sb = smem_u32(smem);
    const int tid = threadIdx.x, lane = tid & 31;
    const int warp = __shfl_sync(0xffffffffu, tid >> 5, 0);
    const uint32_t nv = __shfl_sync(0xffffffffu, nv_ * tid, 0);
    const int h = blockIdx.x / 3, r = blockIdx.x % 3;
    const int mi = lane >> 3, r8 = lane & 7;
    const uint32_t bX = sb + SM_BAR, bTOK = bX + 16, bEX = bX + 40, bW = bX + 64, bEV = bX + 104, bFREE = bX + 32, bMEM = bX + 56, bWA = bX + 120, bM2 = sb + SM_TG + 8;
    const int nqk = r < 2 ? 6 : 4;
    if (lane == 0 && warp < 7) asm volatile("prefetch.param.tensormap [%0];" :: "l"(__cvta_generic_to_grid_constant(&tmx) + 128 * warp) : "memory");
    if ((sb & 0xFFFFFFu) != SB_OFF) __trap();
    asm volatile("griddepcontrol.launch_dependents;");
    if (tid == 0 && blockIdx.x == 0) GT(40, 0);
    if (tid == 0) PT(0);

    #define W_STG(g, j) ((g) == 2 && (j) == 3 ? SM_EX : SM_TOK + ((g) % 3) * 36864 + (j) * 9216)
    auto load_w = [&](int g) {
        #pragma unroll
        for (int j = 0; j < 4; j++) {
            const int m = r < 2 ? (j < 3 ? r : 2) : (j < 2 ? j : 2), p = r < 2 ? (j < 3 ? j : r) : (j < 2 ? 3 : j);
            asm volatile("cp.async.bulk.tensor.2d.shared::cluster.global.mbarrier::complete_tx::bytes [%0], [%1, {%3, %4}], [%2];"
                :: "r"(sb + W_STG(g, j)), "l"(m == 0 ? &tmq : (m == 1 ? &tmk : &tmv)), "r"(bW + 8 * g), "r"(h * DH + p * 32), "r"(g * 144) : "memory");
        }
    };
    auto load_wo = [&](int lo, int hi, uint32_t bar) {
        #pragma unroll
        for (int i = lo; i < hi; i++)
            asm volatile("cp.async.bulk.tensor.2d.shared::cluster.global.mbarrier::complete_tx::bytes [%0], [%1, {%3, %4}], [%2];"
                :: "r"(sb + SM_WO + i * 8192), "l"(&tmo), "r"(bar), "r"(192 * r + 32 * i), "r"(h * DH) : "memory");
    };
    if (warp == 11) {
        if (lane == 0) {
            #pragma unroll
            for (int g = 0; g < 3; g++) mbar_init(bW + 8 * g, 1);
            mbar_init(bX, 1); mbar_init(bX + 8, 1);
            asm volatile("fence.mbarrier_init.release.cluster;" ::: "memory");
        }
        __syncwarp();
        bar_arrive(0, 384);
        if (lane == 0) {
            #pragma unroll 1
            for (int g = 0; g < 3; g++) {
                PT(1 + g);
                mbar_expect_tx(bW + 8 * g, 36864);
                if (X_FIRST == 0) load_w(g);
                if (g < 2) {
                    mbar_expect_tx(bX + 8 * g, XBUF);
                    #pragma unroll
                    for (int c = 0; c < 3; c++)
                        asm volatile("cp.async.bulk.tensor.3d.shared::cluster.global.mbarrier::complete_tx::bytes [%0], [%1, {%3, %4, %5}], [%2];"
                            :: "r"(sb + SM_X + g * XBUF + c * 12288), "l"(&tmx), "r"(bX + 8 * g), "r"(0), "r"(g * SEG), "r"(3 * c) : "memory");
                }
                if (X_FIRST) load_w(g);
            }
            PT(4);
        }
        __syncwarp();
    }
    const uint32_t zs = 3 * blockIdx.x + (r8 >> 1);
    const uint32_t zoff = (r8 < 6 ? (zs >> 3) * 1024 + ((zs >> 2) & 1) * 256 + (zs & 3) * 32 : ACC_X + (blockIdx.x >> 1) * 1024 + (blockIdx.x & 1) * 256) + (lane & 1) * 16;
    const uint32_t zskip = r8 >= 6 && blockIdx.x >= 36;
    if (warp == 9) {
        bar_arrive(0, 384);
        const unsigned ep = ld_relaxed32(&g_epoch);
        unsigned long long o0 = 0, o1 = 0;
        if (!zskip) {
            asm volatile("atom.relaxed.gpu.global.exch.b64 %0, [%1], 0;" : "=l"(o0) : "l"(g_acc + zoff + SLOT_OFF(mi)) : "memory");
            asm volatile("atom.relaxed.gpu.global.exch.b64 %0, [%1], 0;" : "=l"(o1) : "l"(g_acc + zoff + SLOT_OFF(mi) + 8) : "memory");
        }
        const uint32_t done = __reduce_or_sync(0xffffffffu, (uint32_t)(o0 | o1) & nv);
        if (lane == 0) asm volatile("st.relaxed.gpu.global.u32 [%0], %1;" :: "l"(&g_init[blockIdx.x]), "r"(ep + done) : "memory");
    }
    if (tid == 320) {
        #pragma unroll
        for (int i = 2; i < 16; i++) if (i < 8 || i > 10) mbar_init(bX + 8 * i, (i == 5 || i == 6) ? 1 + nqk : (i == 13 || i == 14 ? 9 - nqk : 1));
        mbar_init(bM2, 1);
        asm volatile("fence.mbarrier_init.release.cluster;" ::: "memory");
        mbar_expect_tx(bW + 24, 36864); mbar_expect_tx(bW + 32, 32768); mbar_expect_tx(bWA, 16384);
        sts32(sb + SM_TG, 0u);
    }
    if (warp != 11 && warp != 9) bar_sync(0, 384);
    const uint32_t pw0 = ((mi >> 1) * 8 + r8) * 64 + (((2 * (warp & 1) + (mi & 1)) ^ (r8 >> 1)) << 4);
    auto tok_publish = [&](int tb, int k) {
        const uint32_t src = sb + SM_TOK + tb * TOKBUF + r * 8192, bar = bTOK + 8 * tb;
        if (k == 1) asm volatile("{\n.reg .pred p;\nelect.sync _|p, 0xffffffff;\n@p mbarrier.arrive.expect_tx.shared.b64 _, [%0], 16384;\n}\n" :: "r"(bar) : "memory");
        asm volatile("{\n.reg .pred p;\nelect.sync _|p, 0xffffffff;\n"
                     "@p cp.async.bulk.shared::cluster.shared::cta.mbarrier::complete_tx::bytes [%0], [%1], 8192, [%2];\n}\n"
            :: "r"(mapa_u32(src, (r + k) % 3)), "r"(src), "r"(mapa_u32(bar, (r + k) % 3)) : "memory");
    };
    if (warp < 8) {
        asm volatile("setmaxnreg.inc.sync.aligned.u32 %0;" :: "n"(REG_P));
        uint32_t wf[36][4];
        float ta0[16], ta1[16];
        auto group = [&](auto gg) {
            constexpr int g = gg.value;
            const uint32_t wl = sb + pw0 + W_STG(g, warp >> 1);
            mbar_wait(bW + 8 * g, 0);
            if (tid == 0) PT(5 + g);
            if (g) wg_wait0();
            if (g == 1) sts128(sb + SM_PARK + tid * 16, make_uint4(wf[0][0], wf[0][1], wf[0][2], wf[0][3]));
            #pragma unroll
            for (int i = 0; i < 9; i++) ldsm_x4_t(wf[9 * g + i], wl + i * 1024);
            if (g != 1) fence_async_smem();
            if (g == 0) { bar_arrive(BAR_X0, 288); mbar_wait(bX, 0); mbar_wait(bX + 8, 0); if (tid == 0) PT(9); }
            if (g == 2) bar_arrive(BAR_X0 + 1, 288);
            if (g == 3) cluster_arrive_rx();
            wg_fence();
            #pragma unroll
            for (int i = 9 * g; i < 9 * g + 9; i++) {
                if (i == 0) wgmma_n32<0>(ta0, wf[0], desc_from(DESC_LO(SM_X))); else wgmma_n32<1>(ta0, wf[i], desc_from(DESC_LO(SM_X) + (i >> 2) * 256 + (i & 3) * 2));
            }
            if (g == 3) wg_commit();
            #pragma unroll
            for (int i = 9 * g; i < 9 * g + 9; i++) {
                if (i == 0) wgmma_n32<0>(ta1, wf[0], desc_from(DESC_LO(SM_X + XBUF))); else wgmma_n32<1>(ta1, wf[i], desc_from(DESC_LO(SM_X + XBUF) + (i >> 2) * 256 + (i & 3) * 2));
            }
            wg_commit();
        };
        if (tid == 0) PT(10);
        code_pad<PAD_P>(nv);
        group(ic<0>()); group(ic<1>()); group(ic<2>()); group(ic<3>());
        if (tid == 0) PT(11);
        const uint32_t pw = pin(pw0);
        auto tp_store = [&](const float (&acc)[16], uint32_t off) {
            const uint32_t ta = pw + launder(sb + off + (warp >> 1) * 2048);
            stsm_x4_t(ta, pack_bf16(acc[0], acc[1]), pack_bf16(acc[2], acc[3]), pack_bf16(acc[4], acc[5]), pack_bf16(acc[6], acc[7]));
            stsm_x4_t(ta + 1024, pack_bf16(acc[8], acc[9]), pack_bf16(acc[10], acc[11]), pack_bf16(acc[12], acc[13]), pack_bf16(acc[14], acc[15]));
        };
        cluster_wait();
        asm volatile("wgmma.wait_group.sync.aligned 1;" ::: "memory");
        #pragma unroll
        for (int i = 0; i < 16; i++) asm volatile("" : "+f"(ta0[i]) :: "memory");
        tp_store(ta0, SM_TOK + r * 8192);
        if (warp == 0) { bar_sync(BAR_PRJ, 256); fence_async_smem(); tok_publish(0, 1); tok_publish(0, 2); } else bar_arrive(BAR_PRJ, 256);
        wg_wait0();
        { const uint4 v = lds128(sb + SM_PARK + tid * 16); wf[0][0] = v.x; wf[0][1] = v.y; wf[0][2] = v.z; wf[0][3] = v.w; sts32_p(v.x, v.y, nv); }
        if (tid == 0) PT(12);
        const uint32_t l16 = pin(lane * 16), sbl = sb + l16, sw = sb + warp * 256;
        uint32_t wo[8][4];
        const int exo = r < 2 ? (warp < 6 ? r * 2048 : 4096 + (2 * r - 6) * 256) : (warp < 2 ? 6 * 256 : (warp < 4 ? 2048 + 4 * 256 : 4096));
        const bool isqk = warp < nqk;
        const uint32_t exbar = isqk ? bEX : bEV;
        uint32_t vf[2][4];
        auto prep = [&](int s) {
            const uint32_t va = pw + launder(sb + SM_TOK + (s & 1) * TOKBUF + BLK_V(warp >> 1));
            mbar_wait(bTOK + 8 * (s & 1), (s >> 1) & 1);
            ldsm_x4_t(vf[0], va); ldsm_x4_t(vf[1], va + 1024);
            sts32_p(vf[0][0], vf[1][0], nv);
        };
        if (VF0) { vf[0][0] = vf[0][1] = vf[0][2] = vf[0][3] = vf[1][0] = vf[1][1] = vf[1][2] = vf[1][3] = nv; } else prep(0);
        if (tid == 0) PT(13);
        for (int s = 0; ; s++) {
            const int par = s & 1;
            const uint32_t wa = pw + launder(sb + SM_WO + (warp >> 1) * 8192);
            const uint32_t exu = launder(SM_EX + par * EXBUF);
            wg_wait0();
            #pragma unroll
            for (int i = 0; i < 16; i++) asm volatile("" : "+f"(ta1[i]) :: "memory");
            tp_store(ta1, SM_TOK + (par ^ 1) * TOKBUF + r * 8192);
            { const int s_ = s; const int s = s_ - 1; (void)s; STAMP(13 + (warp >> 2)); }
            bar_sync(BAR_MEM, 352);
            {
                float acc[4][4];
                #pragma unroll
                for (int i = 0; i < 4; i++) { acc[i][0] = acc[i][1] = acc[i][2] = acc[i][3] = 0.f; }
                bar_sync_p(BAR_VGO, 256, isqk);
                #pragma unroll
                for (int i2 = 0; i2 < 18; i2++) {
                    uint32_t b[4];
                    ldsm_x4_t(b, sbl + SM_MEM + i2 * 512);
                    if (i2 == VGO_AT) bar_arrive_p(BAR_VGO, 256, !isqk);
                    mma16816(acc[(2 * i2) & 3], wf[2 * i2], b[0], b[1]);
                    mma16816(acc[(2 * i2 + 1) & 3], wf[2 * i2 + 1], b[2], b[3]);
                }
                float q[4];
                #pragma unroll
                for (int i = 0; i < 4; i++) q[i] = (acc[0][i] + acc[1][i]) + (acc[2][i] + acc[3][i]);
                const uint32_t lo = pack_bf16(q[0], q[1]), hi = pack_bf16(q[2], q[3]);
                const uint32_t eu = launder(sw + exu + exo), exl = (launder(l16) >> 2) + eu, bar = launder(exbar + par * 8);
                #pragma unroll
                for (int k = 1; k < 3; k++) {
                    const uint32_t ed = mapa_u32(eu, (r + k) % 3), exb = mapa_u32(bar, (r + k) % 3);
                    if (EXA) { st_async32((l16 >> 2) + ed, lo, exb); st_async32((l16 >> 2) + launder(ed + 128), hi, exb); }
                    else { const uint32_t exd = mapa_u32(exl, (r + k) % 3); st_async32(exd, lo, exb); st_async32(exd + 128, hi, exb); }
                }
                sts32(exl, lo); sts32(exl + 128, hi);
                __syncwarp();
                asm volatile("{\n.reg .pred p;\nelect.sync _|p, 0xffffffff;\n@p mbarrier.arrive.shared.b64 _, [%0];\n}\n" :: "r"(bar) : "memory");
                if (s < NSEG - 1) bar_sync_p(BAR_PRO, 32 * nqk, !isqk);
            }
            if (__builtin_expect(s == NSEG - 1, 0)) break;
            if (__builtin_expect(s == 0, 0)) { if (VF0) prep(0); mbar_wait(bW + 32, 0); }
            #pragma unroll
            for (int i = 0; i < WO_PRE; i++) ldsm_x4_t(wo[i], wa + i * 1024);
            #pragma unroll
            for (int k = 0; k < WO_REP; k++) mbar_wait(bEX + 8 * par, (s >> 1) & 1);
            #pragma unroll
            for (int i = WO_PRE; i < 8; i++) ldsm_x4_t(wo[i], wa + i * 1024);
            mbar_wait(bEV + 8 * par, (s >> 1) & 1);
            const uint32_t l4 = launder(l16) >> 2;
            const uint32_t vm0 = lds32(l4 + (sw + exu + 4096)), vm1 = lds32(l4 + (sw + exu + 4096 + 128));
            const uint32_t big = bar_red_or(BAR_P, 352, 0u);
            uint32_t pb[4]; ldsm_x4_t(pb, sbl + SM_P);
            uint32_t pm = ldsm_x1_t(sbl + SM_P + 512);
            float o0[4] = {0.f, 0.f, 0.f, 0.f}, o1[4] = {0.f, 0.f, 0.f, 0.f}, o2[4] = {0.f, 0.f, 0.f, 0.f};
            if (__builtin_expect(big, 0)) {
                bar_sync(BAR_P2, 352);
                ldsm_x4_t(pb, sbl + SM_P); pm = ldsm_x1_t(sbl + SM_P + 512);
            }
            mma16816(o0, vf[0], pb[0], pb[1]);
            mma16816(o1, vf[1], pb[2], pb[3]);
            mma1688(o2, vm0, vm1, pm);
            uint32_t oa = pm;
            #pragma unroll
            for (int i = 0; i < 8; i++) oa ^= wo[i][0];
            oa = (l4 | (oa & nv)) + sw;
            sts32(oa + SM_O, pack_bf16((o0[0] + o1[0]) + o2[0], (o0[1] + o1[1]) + o2[1]));
            sts32(oa + SM_O + 128, pack_bf16((o0[2] + o1[2]) + o2[2], (o0[3] + o1[3]) + o2[3]));
            const uint32_t xd = uni(DESC_LO(SM_X) + par * (XBUF >> 4));
            bar_sync(BAR_O, 352);
            uint32_t sx;
            const uint32_t w2 = stage_w<false>(wo, sbl + SM_O, 12 * r + warp, SLOT_OFF(s + 1), l16, nv, sbl + SM_IL, sx);
            if (X_AT == 0) send_extra<0>(w2, sx, l16);
            STAMP(warp);
            bar_sync(BAR_V, 384);
            wg_fence();
            STAMP(12);
            #pragma unroll
            for (int i = 0; i < TP_N; i++) {
                if (X_AT && i == X_AT) send_extra<0>(w2, sx, l16);
                if (i == 0) wgmma_n32<0>(ta1, wf[0], desc_from(xd));
                else wgmma_n32<1>(ta1, wf[i], desc_from(xd + (i >> 2) * 256 + (i & 3) * 2));
            }
            wg_commit();
            prep(s + 1);
        }
        {
            const uint32_t tag = ld_relaxed32(&g_init[blockIdx.x]) & 1u, lq = l16 | (tag & nv), pq = pw | (tag & nv);
            uint4* d0 = &g_last[12 * r + warp][0][h][lq >> 4];
            uint4* d1 = &g_last[12 * r + 8 + (warp & 3)][warp >> 2][h][lq >> 4];
            st_relaxed128(d0, make_uint4(tag ^ 1, 0, 0, 0)); st_relaxed128(d0 + 1024, make_uint4(tag ^ 1, 0, 0, 0)); st_relaxed128(d1, make_uint4(tag ^ 1, 0, 0, 0));
            uint32_t wx[8][4];
            #pragma unroll
            for (int i = 0; i < 8; i++) { ldsm_x4_t(wo[i], pq + sb + SM_WO + (warp >> 1) * 8192 + i * 1024); ldsm_x4_t(wx[i], pq + sb + SM_WO + (4 + ((warp >> 1) & 1)) * 8192 + i * 1024); }
            float c2[8];
            #pragma unroll
            for (int i = 0; i < 8; i++) c2[i] = 0.f;
            const uint32_t od = uni(DESC_LO(SM_OST) + (warp >> 2) * 128);
            mbar_wait(bMEM, 1);
            wg_fence();
            #pragma unroll
            for (int i = 0; i < 8; i++) {
                if (i == 0) wgmma_n32<0>(ta1, wo[0], desc_from(DESC_LO(SM_OST)));
                else wgmma_n32<1>(ta1, wo[i], desc_from(DESC_LO(SM_OST) + (i >> 2) * 256 + (i & 3) * 2));
            }
            wg_commit();
            #pragma unroll
            for (int i = 0; i < 8; i++) wgmma_n16(c2, wx[i], desc_from(od + (i >> 2) * 256 + (i & 3) * 2));
            wg_commit();
            auto put = [&](uint4* d, const float* c) { st_relaxed128(d, make_uint4((pack_bf16(c[0], c[1]) & ~1u) | tag, pack_bf16(c[2], c[3]), pack_bf16(c[4], c[5]), pack_bf16(c[6], c[7]))); };
            asm volatile("wgmma.wait_group.sync.aligned 1;" ::: "memory");
            #pragma unroll
            for (int i = 0; i < 16; i++) asm volatile("" : "+f"(ta1[i]) :: "memory");
            put(d0, ta1); put(d0 + 1024, ta1 + 8);
            wg_wait0();
            #pragma unroll
            for (int i = 0; i < 8; i++) asm volatile("" : "+f"(c2[i]) :: "memory");
            put(d1, c2);
            if (tid == 0 && blockIdx.x == 0) GT(40, NSEG);
        }
        cluster_arrive(); cluster_wait();
    } else {
        asm volatile("setmaxnreg.dec.sync.aligned.u32 %0;" :: "n"(504 - 2 * REG_P));
        const int a = warp - 8;
        const unsigned epoch = ld_relaxed32(&g_epoch);
        const uint32_t sbl = sb + lane * 16;
        if (a < 3) {
            cluster_arrive_rx();
            {
                uint32_t v[3][8];
                #pragma unroll
                for (int k = 0; k < 3; k++)
                    #pragma unroll
                    for (int i = 0; i < 8; i++) v[k][i] = __ldg((const uint32_t*)mem0 + (tid - 256 + 96 * k) + i * (DM / 2));
                #pragma unroll
                for (int k = 0; k < 3; k++) {
                    const uint32_t d = sb + SM_MEM + (tid - 256 + 96 * k) * 32;
                    sts128(d, make_uint4(__byte_perm(v[k][0], v[k][1], 0x5410), __byte_perm(v[k][2], v[k][3], 0x5410), __byte_perm(v[k][4], v[k][5], 0x5410), __byte_perm(v[k][6], v[k][7], 0x5410)));
                    sts128(d + 16, make_uint4(__byte_perm(v[k][0], v[k][1], 0x7632), __byte_perm(v[k][2], v[k][3], 0x7632), __byte_perm(v[k][4], v[k][5], 0x7632), __byte_perm(v[k][6], v[k][7], 0x7632)));
                }
            }
            { int it = 0; while (__any_sync(0xffffffffu, ld_acquire32(&g_init[a * 32 + lane]) != epoch) && ++it < SPIN_LIMIT) {} }
            const uint32_t kl0 = (a < 2 ? SM_TOK + (16 * a + (mi & 1) * 8 + r8) * 64 + (((mi >> 1) ^ (r8 >> 1)) << 4) : SM_EX + 2048 + ((((mi & 1) << 1) | (mi >> 1)) * 8 + r8) * 16);
            const uint32_t l16 = pin(lane * 16);
            uint32_t kf[8][4], wo[8][4];
            auto load_k = [&](int tb, uint32_t kl) {
                const uint32_t ka = kl + launder(sb + tb * TOKBUF);
                #pragma unroll
                for (int kk = 0; kk < 8; kk++) ldsm_x4(kf[kk], (ka ^ ((kk & 1) << 5)) + BLK_K(kk >> 1));
            };
            code_pad<PAD_S>(nv);
            if (tid == 288) PT(14);
            cluster_wait();
            if (a == 0 && lane == 0) { mbar_expect_tx(bEX, 4096 - 256 * nqk); mbar_expect_tx(bEV, 256 * nqk); }
            if (a < 2) bar_arrive(BAR_MEM, 352); else bar_sync(BAR_MEM, 352);
            if (TM_PF2 && lane < 2 && a == 2) asm volatile("prefetch.param.tensormap [%0];" :: "l"(__cvta_generic_to_grid_constant(&tma) + 128 * lane) : "memory");
            mbar_wait(bWA, 0);
            #pragma unroll
            for (int i = 0; i < 8; i++) ldsm_x4_t(wo[i], pw0 + sb + SM_WO + (warp >> 1) * 8192 + i * 1024);
            sts128(sbl + SM_STASH + a * 1024 + 512, make_uint4(kl0, (pw0 ^ 32) + sb + SM_WO + 5 * 8192, zoff | ((zskip || lane >= 8) << 31), 0u));
            sts128(sbl + SM_STASH + a * 1024, make_uint4(a * 12288 + (lane >> 4) * 1024 + (mi & 1) * 256 + r8 * 16, ACC_X + a * 6144 + (lane >> 4) * 1024 + (mi & 1) * 256 + r8 * 4,
                                                         ((lane ^ mi) & 1) ? 0u : ~0u, sb + SM_MEM + a * 3072 + mi * 256 + r8 * 16 + (r8 & 1 ? 2 : 130)));
            const uint32_t stash = l16 + uni(sb + SM_STASH + a * 1024);
            #pragma unroll
            for (int i = 0; i < 8; i++) ldsm_x4_t(kf[i], (pw0 ^ 32) + sb + SM_WO + 5 * 8192 + i * 1024);
            if (a < 2) { mbar_wait(bTOK, 0); load_k(0, kl0); }
            __syncwarp();
            int sn = 0;
            #pragma unroll 1
            while (sn < NSEG - 1) {
              uint32_t bad;
              #pragma unroll 1
              do {
                const int s = sn, par = s & 1;
                const uint32_t exu = launder(sb + par * EXBUF);
                const uint32_t exl = l16 + exu + SM_EX;
                const uint32_t t0 = gtime_lo();
                STAMP(15); STAMPV(31, t0);
                if (a == 2) st_relaxed32_p(&g_ts[blockIdx.x], (t0 & ~31u) | (s & 31), l16);
                if (a == 1) {
                    const uint32_t z = lds32(stash + 520);
                    st_relaxed128_p((uint4*)(g_acc + (z + SLOT_OFF(s + 3))), make_uint4(0, 0, 0, 0), z >> 31);
                }
                if (a == 0 && l16 == 0) { mbar_expect_tx(bEX + 8 * (par ^ 1), 4096 - 256 * nqk); mbar_expect_tx(bEV + 8 * (par ^ 1), 256 * nqk); }
                auto first_half = [&](auto role) {
                constexpr bool M = role.value;
                uint32_t sl, sh, kl = 0;
                if (M) {
                    fence_async_smem();
                    if (l16 == 0) {
                        asm volatile("cp.async.bulk.global.shared::cta.bulk_group [%0], [%1], 8192;\ncp.async.bulk.commit_group;"
                            :: "l"(g_tokx[blockIdx.x]), "r"(sb + SM_TOK + (par ^ 1) * TOKBUF + r * 8192) : "memory");
                        mbar_expect_tx(bTOK + 8 * (par ^ 1), 16384); mbar_expect_tx(bMEM, 10368);
                        if (s == 0) mbar_expect_tx(bX, XBUF);
                        if (s + 3 < NSEG) mbar_expect_tx(bX + 8 * (par ^ 1), XBUF);
                    }
                    __syncwarp();
                    if (s > 0 && s + 2 < NSEG) mbar_wait(bX + 8 * par, ((s >> 1) & 1) ^ 1);
                    asm volatile("cp.async.bulk.wait_group 0;" ::: "memory");
                    kl = lds32(stash + 512);
                }
                const uint32_t pst = (launder(l16) >> 2) + launder(sb + SM_P + a * 256);
                if (!M) {
                    uint32_t x = kf[0][0];
                    #pragma unroll
                    for (int i = 1; i < 8; i++) x ^= kf[i][0];
                    sts32_p(pst, x, nv);
                }
                mbar_wait(bEX + 8 * par, (s >> 1) & 1);
                float c[4][4];
                #pragma unroll
                for (int j = 0; j < 4; j++) { c[j][0] = c[j][1] = c[j][2] = c[j][3] = 0.f; }
                if (!M) {
                    uint32_t b[4][4];
                    ldsm16_t(b, exl);
                    #pragma unroll
                    for (int j = 0; j < 4; j++) { mma16816(c[(2 * j) & 3], kf[2 * j], b[j][0], b[j][1]); mma16816(c[(2 * j + 1) & 3], kf[2 * j + 1], b[j][2], b[j][3]); }
                    sl = scale_bf2(pack_bf16((c[0][0] + c[1][0]) + (c[2][0] + c[3][0]), (c[0][1] + c[1][1]) + (c[2][1] + c[3][1])));
                    sh = scale_bf2(pack_bf16((c[0][2] + c[1][2]) + (c[2][2] + c[3][2]), (c[0][3] + c[1][3]) + (c[2][3] + c[3][3])));
                } else {
                    uint32_t k[4][4], b[4][4];
                    #pragma unroll
                    for (int j = 0; j < 4; j++) { ldsm_x4_t(k[j], kl + exu + 512 * j); ldsm_x4_t(b[j], exl + 512 * j); }
                    #pragma unroll
                    for (int j = 0; j < 4; j++) { mma16816(c[2 * (j & 1)], k[j], b[j][0], b[j][1]); mma16816(c[2 * (j & 1) + 1], k[j], b[j][2], b[j][3]); }
                    asm volatile("{\n.reg .pred p;\nelect.sync _|p, 0xffffffff;\n"
                                 "@p cp.async.bulk.shared::cluster.global.mbarrier::complete_tx::bytes.multicast::cluster [%0], [%1], 8192, [%2], %3;\n}\n"
                        :: "r"(sb + SM_TOK + (par ^ 1) * TOKBUF + r * 8192), "l"(g_tokx[blockIdx.x]), "r"(bTOK + 8 * (par ^ 1)), "h"((unsigned short)(7 ^ (1 << r))) : "memory");
                    sh = sl = scale_bf2(pack_bf16((c[0][0] + c[1][2]) + (c[2][0] + c[3][2]), (c[0][1] + c[1][3]) + (c[2][1] + c[3][3])));
                }
                sts32(pst, exp_bf2(sl));
                if (!M) sts32(pst + 128, exp_bf2(sh));
                const uint32_t big = bar_red_or(BAR_P, 352, ((maxabs_bf2(sl, sh) & 0x7fff7fffu) + 0x3ddf3ddfu) & 0x80008000u);
                auto denom = [&] {
                    uint32_t pb[4]; ldsm_x4_t(pb, l16 + sb + SM_P);
                    const uint32_t pm = ldsm_x1_t(l16 + sb + SM_P + 512), ONE = 0x3F803F80u;
                    float l0[4] = {0.f, 0.f, 0.f, 0.f}, l1[4] = {0.f, 0.f, 0.f, 0.f}, l2[4] = {0.f, 0.f, 0.f, 0.f};
                    mma16816r(l0, ONE, ONE, ONE, ONE, pb[0], pb[1]);
                    mma16816r(l1, ONE, ONE, ONE, ONE, pb[2], pb[3]);
                    mma1688(l2, ONE, ONE, pm);
                    const float dl = (l0[0] + l1[0]) + l2[0], dh = (l0[1] + l1[1]) + l2[1];
                    sts32(pst + (SM_IL - SM_P) - a * 128, __float_as_uint(rcp_approx(a ? dh : dl)));
                };
                if (!M) { denom(); bar_sync_p(BAR_O, 352, big); }
                if (__builtin_expect(big, 0)) {
                    uint32_t m2 = max_bf2(sl, sh);
                    m2 = max_bf2(m2, __shfl_xor_sync(0xffffffffu, m2, 4));
                    m2 = max_bf2(m2, __shfl_xor_sync(0xffffffffu, m2, 8));
                    m2 = max_bf2(m2, __shfl_xor_sync(0xffffffffu, m2, 16));
                    const uint32_t lq = l16 | (m2 & nv);
                    if (lq < 64) sts32(lq + sb + SM_P + 768 + a * 4, m2);
                    bar_sync(BAR_S, 96);
                    const uint4 m = lds128(sb + SM_P + 768 + (lq & 0x30));
                    m2 = max_bf2(max_bf2(m.x, m.y), m.z);
                    const float ml = bf_lo(m2), mh = bf_hi(m2);
                    sts32(pst, pack_bf16(exd(bf_lo(sl), ml), exd(bf_hi(sl), mh)));
                    if (!M) sts32(pst + 128, pack_bf16(exd(bf_lo(sh), ml), exd(bf_hi(sh), mh)));
                    bar_sync(BAR_P2, 352);
                    if (!M) { denom(); bar_sync(BAR_O, 352); }
                }
                const uint32_t ll = launder(l16), so = SLOT_OFF(launder(s) + 1);
                if (!M) { uint32_t sx; const uint32_t w2 = stage_w<true>(wo, l16 + sb + SM_O, 12 * r + warp, so, ll, nv, l16 + sb + SM_IL, sx); send_extra<0>(w2, sx, ll); }
                else {
                    const uint32_t w2 = lds32(stash + 516);
                    #pragma unroll
                    for (int i = M_RES; i < 8; i++) ldsm_x4_t(kf[i], w2 + i * 1024);
                    const uint32_t sa = launder((ll >> 2) + (send_ua(12 * r + 10) + so)), sx = launder((ll >> 4) + (send_ub(12 * r + 10) + so));
                    bar_sync_p(BAR_O, 352, (kf[5][0] ^ kf[6][0] ^ kf[7][0] ^ sa ^ sx) & nv);
                    #pragma unroll
                    for (int k = 0; k < M_LAG; k++) mbar_wait(bEX + 8 * par, (s >> 1) & 1);
                    float il, ih;
                    #pragma unroll
                    for (int i = 0; i < 4; i++) c[i][0] = c[i][1] = c[i][2] = c[i][3] = 0.f;
                    uint32_t b[4][4];
                    #pragma unroll
                    for (int j = 0; j < 4; j++) ldsm_x4_t(b[j], l16 + sb + SM_O + 512 * (3 - j));
                    lds_il(il, ih, l16 + sb + SM_IL);
                    sched_fence<11>(nv);
                    #pragma unroll
                    for (int j = 0; j < 4; j++) {
                        mma16816(c[0], wo[6 - 2 * j], b[j][0], b[j][1]); mma16816(c[2], kf[6 - 2 * j], b[j][0], b[j][1]);
                        mma16816(c[1], wo[7 - 2 * j], b[j][2], b[j][3]); mma16816(c[3], kf[7 - 2 * j], b[j][2], b[j][3]);
                        if (j == M_ARR) { asm volatile("" : "+f"(c[0][0]), "+f"(c[1][0]), "+f"(c[2][0]), "+f"(c[3][0])); sched_fence<10>(nv); bar_arrive(BAR_V, 384); }
                        if (j == 3 && M_ARR < 0) bar_arrive(BAR_V, 384);
                    }
                    const uint32_t x0 = send_main<0>((c[0][0] + c[1][0]) * il, (c[0][1] + c[1][1]) * ih, (c[0][2] + c[1][2]) * il, (c[0][3] + c[1][3]) * ih, sa, ll);
                    const uint32_t x1 = send_main<1024>((c[2][0] + c[3][0]) * il, (c[2][1] + c[3][1]) * ih, (c[2][2] + c[3][2]) * il, (c[2][3] + c[3][3]) * ih, sa, ll);
                    send_extra<0>(x0, sx, ll); send_extra<256>(x1, sx, ll);
                }
                };
                if (a < 2) first_half(ic<0>()); else first_half(ic<1>());
                STAMP(warp);
                {
                    const uint32_t cd = lds32(stash + 12), xa = (launder(l16) >> 2) + launder(sb + SM_XT + a * 384);
                    if (ISS == 2 && a < 2) { const uint32_t kl = lds32(stash + 512); mbar_wait(bTOK + 8 * (par ^ 1), ((s + 1) >> 1) & 1); load_k(par ^ 1, kl); }
                    else if (a == ISS) {
                        STAMP(16 + a);
                        uint32_t tg;
                        asm volatile("{\n.reg .pred p, q;\n.reg .b64 w;\n.reg .b32 t, u, d, n;\nmov.b32 n, 100000;\n"
                                     "WA_%=:\nld.volatile.shared.u32 %0, [%1];\nsub.s32 n, n, 1;\nsetp.gt.s32 q, n, 0;\nxor.b32 d, %0, %2;\nand.b32 d, d, 1;\nsetp.eq.and.u32 p, d, 0, q;\n@p bra.uni WA_%=;\n"
                                     "sub.s32 d, %0, 2;\n"
                                     "WB_%=:\nmov.u64 w, %%globaltimer;\nmov.b64 {t, u}, w;\nsub.s32 n, n, 1;\nsetp.gt.s32 q, n, 0;\nsub.s32 t, d, t;\nsetp.gt.and.s32 p, t, 0, q;\n@p bra.uni WB_%=;\n}\n"
                                     : "=r"(tg) : "r"(sb + SM_TG + (l16 >> 16)), "r"(par + (l16 >> 16)) : "memory");
                        if (TG_D) delay_clk(TG_D);
                        asm volatile("{\n.reg .pred p;\nelect.sync _|p, 0xffffffff;\n"
                                     "@p cp.async.bulk.tensor.3d.shared::cluster.global.mbarrier::complete_tx::bytes.multicast::cluster [%0], [%1, {%3, %4, %5}], [%2], %9;\n"
                                     "@p cp.async.bulk.tensor.3d.shared::cluster.global.mbarrier::complete_tx::bytes.multicast::cluster [%6], [%7, {%3, %4, %8}], [%2], %9;\n}\n"
                            :: "r"(sb + SM_MEM + r * 3072), "l"(&tma), "r"(bMEM), "r"((par ^ 1) * 32), "r"((s + 1) & 2), "r"(12 * r), "r"(sb + SM_XT + r * 384), "l"(&tmb), "r"(ACC_X / 1024 + 6 * r), "h"((unsigned short)7) : "memory");
                        if (DUAL) {
                            wait_gtime(tg + DUAL - 2);
                            asm volatile("{\n.reg .pred p;\nelect.sync _|p, 0xffffffff;\n"
                                         "@p cp.async.bulk.tensor.3d.shared::cluster.global.mbarrier::complete_tx::bytes.multicast::cluster [%0], [%1, {%3, %4, %5}], [%2], %9;\n"
                                         "@p cp.async.bulk.tensor.3d.shared::cluster.global.mbarrier::complete_tx::bytes.multicast::cluster [%6], [%7, {%3, %4, %8}], [%2], %9;\n"
                                         "@p mbarrier.arrive.expect_tx.shared.b64 _, [%2], 10368;\n}\n"
                                :: "r"(sb + SM_MEM2(r)), "l"(&tma), "r"(bM2), "r"((par ^ 1) * 32), "r"((s + 1) & 2), "r"(12 * r), "r"(sb + SM_MEM2(r) + 3072), "l"(&tmb), "r"(ACC_X / 1024 + 6 * r), "h"((unsigned short)7) : "memory");
                        }
                        STAMPV(30, tg);
                    }
                    if (ISS != 2 && a < 2) { const uint32_t kl = lds32(stash + 512); mbar_wait(bTOK + 8 * (par ^ 1), ((s + 1) >> 1) & 1); load_k(par ^ 1, kl); }
                    STAMP(19 + a);
                    mbar_wait(bMEM, par);
                    uint32_t x[3], k[3];
                    #pragma unroll
                    for (int j = 0; j < 3; j++) { x[j] = lds32(xa + 128 * j); k[j] = lds32(cd - 2 + 1024 * j); }
                    #pragma unroll
                    for (int j = 0; j < 3; j++) sts16(cd + 1024 * j, (uint16_t)x[j]);
                    bad = __any_sync(0xffffffffu, !((x[0] & x[1] & x[2]) & (k[0] & k[1] & k[2]) & (ACC_FULL << 16)));
                    STAMP(22 + a); STAMPV(27 + a, bad);
                    bar_sync_p(BAR_MEM, 352, bad);
                }
              } while (++sn < NSEG - 1 && !bad);
                {
                    if (bad) {
                        uint32_t c = nv, cx;
                        const uint32_t lq = l16 | (lds32(stash + 524) & nv), so = SLOT_OFF(sn);
                        const uint4 ad = lds128(stash);
                        cx = nv;
                        if (DUAL) {
                            mbar_wait(bM2, (sn - 1) & 1);
                            uint32_t x[3];
                            c = ~0u;
                            #pragma unroll
                            for (int j = 0; j < 3; j++) x[j] = lds32((lq >> 2) + sb + SM_MEM2(a) + 3072 + 128 * j);
                            #pragma unroll
                            for (int j = 0; j < 6; j++) { const uint4 u = lds128(lq + sb + SM_MEM2(a) + 512 * j); sts128(lq + sb + SM_MEM + a * 3072 + 512 * j, u); c &= u.x; }
                            __syncwarp();
                            #pragma unroll
                            for (int j = 0; j < 3; j++) sts16(ad.w + 1024 * j, (uint16_t)x[j]);
                            c |= ad.z; cx = x[0] & x[1] & x[2];
                        }
                        const unsigned char* pm = launder_p(g_acc + (ad.x + so));
                        const unsigned char* px = launder_p(g_acc + (ad.y + so));
                        int it = 0;
                        while (__any_sync(0xffffffffu, !(c & cx & (ACC_FULL << 16))) && ++it < SPIN_LIMIT) {
                            const uint32_t again = ~(c & __shfl_xor_sync(0xffffffffu, c, 1)) & (ACC_FULL << 16);
                            uint4 u[6]; uint32_t x[3];
                            #pragma unroll
                            for (int j = 0; j < 6; j++) { u[j] = make_uint4(~0u, ~0u, ~0u, ~0u); ld_relaxed128_p(u[j], (const uint4*)(pm + 2048 * j), again); }
                            #pragma unroll
                            for (int j = 0; j < 3; j++) x[j] = ld_relaxed32((const uint32_t*)(px + 2048 * j));
                            c = ~0u;
                            #pragma unroll
                            for (int j = 0; j < 6; j++) {
                                if (again) sts128(lq + sb + SM_MEM + a * 3072 + 512 * j, u[j]);
                                c &= u[j].x;
                            }
                            __syncwarp();
                            #pragma unroll
                            for (int j = 0; j < 3; j++) sts16(ad.w + 1024 * j, (uint16_t)x[j]);
                            c |= ad.z;
                            cx = x[0] & x[1] & x[2];
                        }
                        bar_sync(BAR_MEM, 352);
                    }
                }
            }
            if (DUAL) mbar_wait(bM2, (NSEG - 2) & 1);
        } else {
            cluster_arrive_rx();
            const uint32_t l16 = pin(lane * 16);
            bf16* dst = g_otok + h * 4096 + (r ? 1024 : 0) + (r == 2 ? 2048 : 0);
            {
                bar_sync(BAR_X0, 288);
                if (lane == 0) {
                    load_w(3); load_wo(4, 6, bWA);
                    if (h < X_PF) asm volatile("cp.async.bulk.prefetch.tensor.3d.L2.global [%0, {%1, %2, %3}];" :: "l"(&tmx), "r"(0), "r"((2 + h) * SEG), "r"(3 * r) : "memory");
                }
                __syncwarp();
                bar_sync(BAR_X0 + 1, 288);
                if (WO_LATE) mbar_wait(bW + 24, 0);
                if (lane == 0) { load_wo(0, 4, bW + 32);
 }
                __syncwarp();
                cluster_wait();
            }
            __syncwarp();
            auto t_loop = [&](auto mtile) {
            constexpr int MT = mtile.value;
            uint32_t q[8][4], sp[5][2], pa[5][2], bv[8][4], rng;
            const uint32_t ost = sb + SM_OST + (MT ? 4096 * r - 2048 : 0);
            code_pad<MT ? PAD_T1 : PAD_T0>(nv);
            auto issue_x = [&](int sg) {
                asm volatile("{\n.reg .pred p, q;\nelect.sync _|p, 0xffffffff;\nsetp.eq.and.u32 q, %5, 3, p;\n"
                             "@p cp.async.bulk.tensor.3d.shared::cluster.global.mbarrier::complete_tx::bytes.multicast::cluster [%0], [%1, {%3, %4, %5}], [%2], %6;\n"
                             "@q cp.async.bulk.tensor.3d.shared::cluster.global.mbarrier::complete_tx::bytes.multicast::cluster [%7], [%1, {%3, %4, %3}], [%2], %6;\n}\n"
                    :: "r"(sb + SM_X + (sg & 1) * XBUF + r * 12288), "l"(&tmx), "r"(bX + 8 * (sg & 1)), "r"(0), "r"(sg * SEG), "r"(3 * r), "h"((unsigned short)7), "r"(sb + SM_X + (sg & 1) * XBUF) : "memory");
            };
            mbar_wait(bTOK, 0);
            if (MT) issue_x(2);
            #pragma unroll 1
            for (int s = 0; ; s++) {
                const int par = s & 1;
                mbar_wait(bTOK + 8 * par, (s >> 1) & 1);
                const uint32_t tok = launder(sb + SM_TOK + par * TOKBUF), exl = l16 + launder(sb + SM_EX + par * EXBUF);
                tok_part1<MT>(tok, MT ? r - 1 : 0, launder(l16) >> 4, q, sp, pa, bv, rng, [&] {
                    if (s > 0) {
                        if (lane == 0) {
                            asm volatile("cp.async.bulk.wait_group 0;" ::: "memory");
                            st_relaxed32(&g_prog[blockIdx.x], epoch << 8 | s);
                        }
                        __syncwarp();
                        if (lane == 0 && blockIdx.x == 0) GT(40, s);
                    }
                    sched_fence<6 + MT>(nv); });
                STAMP(25);
                mbar_wait(bEX + 8 * par, (s >> 1) & 1);
                STAMP(26);
                auto duty = [&] { if (s + 1 < NSEG) {
                    asm volatile("{\n.reg .pred p;\nelect.sync _|p, 0xffffffff;\n"
                                 "@p cp.async.bulk.shared::cluster.global.mbarrier::complete_tx::bytes [%0], [%1], 384, [%2];\n"
                                 "@p mbarrier.arrive.expect_tx.shared.b64 _, [%2], 384;\n}\n"
                        :: "r"(sb + SM_TS), "l"(g_ts), "r"(bFREE) : "memory");
                    if (MT && s + 3 < NSEG) issue_x(s + 3);
                } };
                auto pace = [&] { if (s + 1 < NSEG) {
                    const uint32_t lo = min(launder(l16), 368u), b = (gtime_lo() & ~31u) - 0x01000000u + s + (lo >> 16);
                    const uint32_t c = (b & ~31u) + (G1_NS + (s == 0 ? G1_0 : 0)) + (par ^ 1);
                    mbar_wait(bFREE, par);
                    uint4 ts = lds128(sb + SM_TS + lo);
                    int it = 0; uint32_t m;
                    while (true) {
                        m = __reduce_max_sync(0xffffffffu, max(max(__funnelshift_r(ts.x - b, ts.x - b, 5), __funnelshift_r(ts.y - b, ts.y - b, 5)), max(__funnelshift_r(ts.z - b, ts.z - b, 5), __funnelshift_r(ts.w - b, ts.w - b, 5))));
                        if (__builtin_expect(m < 0x00100000u, 1) || ++it >= 64) break;
                        ts = ld_relaxed128((const uint4*)((const char*)g_ts + lo));
                    }
                    asm volatile("st.volatile.shared.u32 [%0], %1;" :: "r"(sb + SM_TG), "r"(c + (min(m, 0x00080000u) << 5)) : "memory");
                } };
                auto wait_v = [&] { mbar_wait(bEV + 8 * par, (s >> 1) & 1); };
                auto wait_x = [&] { if (__builtin_expect(s == 0, 0)) mbar_wait(bX, 1); };
                tok_part2<MT>(tok, exl, ost, MT ? r - 1 : 0, launder(l16) >> 4, q, sp, pa, bv, rng, s < NSEG - 1, wait_v, duty, pace, wait_x);
                STAMP(11);
                fence_async_smem();
                __syncwarp();
                if (s == NSEG - 1) break;
                if (lane == 0) {
                    asm volatile("cp.async.bulk.global.shared::cta.bulk_group [%0], [%1], 2048;" :: "l"(dst), "r"(ost) : "memory");
                    if (!MT) asm volatile("cp.async.bulk.global.shared::cta.bulk_group [%0], [%1], 2048;" :: "l"(dst + 2048), "r"(ost + 4096) : "memory");
                    asm volatile("cp.async.bulk.commit_group;" ::: "memory");
                }
                __syncwarp();
                dst += SEG * NH * DH;
            }
            if (lane == 0) {
                #pragma unroll
                for (int k = 0; k < (MT ? 2 : 4); k++) {
                    const uint32_t src = ost + (k >> 1) * 4096, rk = (r + 1 + (k & 1)) % 3;
                    asm volatile("cp.async.bulk.shared::cluster.shared::cta.mbarrier::complete_tx::bytes [%0], [%1], 2048, [%2];" :: "r"(mapa_u32(src, rk)), "r"(src), "r"(mapa_u32(bMEM, rk)) : "memory");
                }
                mbar_expect_tx(bMEM, MT ? 6144 : 4096);
            }
            __syncwarp();
            };
            if (r == 0) t_loop(ic<0>()); else t_loop(ic<1>());
        }
        cluster_arrive(); cluster_wait();
    }
}
#define SD_THREADS 384
#define SD_CTAS  36
#define BT_RS    4624
#define SD_BT    0
#define SD_STG   74752
#define SD_EF    (SD_STG + 57344)
#define SD_BC    (SD_STG)
#define KSLOTS   5
#define BC_BYTES 10240
#define BC_LBO   1280
#define SD_KP    (SD_STG + 90112)
#define SD_Q0    205824
#define SD_Q1    (SD_STG + 111616)
#define SD_OST   (SD_Q0 + 8192)
#define SD_XCH   (SD_Q0 + 10240)
#define LSEG     (NSEG - 1)
#define SD_BAR   224256
#define SD_TOTAL 224768
#define SD_SPIN  (1 << 22)
#define PART_SLOTS 8
#define SD_WOP 300
#define SD_GO 0
#define SD_REG 200
#define SD_WAIT 6000
#define SD_P2 150
#define SD_P3 600
#define SD_GAP 0
#define SD_RUSH 44
#define SD_P1 300

__device__ uint4 g_part[SD_CTAS][PART_SLOTS][4][8][32];
__device__ __align__(16) unsigned int g_gate[S_LEN];

struct cplx { float r, i; };
__device__ __forceinline__ cplx cmul(cplx a, cplx b) { cplx c; c.r = fmaf(a.r, b.r, -a.i * b.i); c.i = fmaf(a.r, b.i, a.i * b.r); return c; }
__device__ __forceinline__ cplx cexp_(float xr, float xi) {
    const float m = ex2(xr * 1.4426950408889634f);
    const float k = rintf(xi * 0.15915494309189535f);
    const float r = fmaf(k, 1.7484555314695172e-7f, fmaf(k, -6.2831854820251465f, xi));
    cplx o; o.r = m * __cosf(r); o.i = m * __sinf(r); return o;
}
__device__ __forceinline__ void mma_f16(float (&c)[4], const uint32_t (&a)[4], uint32_t b0, uint32_t b1) {
    asm("mma.sync.aligned.m16n8k16.row.col.f32.f16.f16.f32 {%0,%1,%2,%3}, {%4,%5,%6,%7}, {%8,%9}, {%0,%1,%2,%3};"
        : "+f"(c[0]), "+f"(c[1]), "+f"(c[2]), "+f"(c[3]) : "r"(a[0]), "r"(a[1]), "r"(a[2]), "r"(a[3]), "r"(b0), "r"(b1));
}
__device__ __forceinline__ uint32_t mul_bf2(uint32_t a, uint32_t b) { uint32_t r; asm("mul.rn.bf16x2 %0, %1, %2;" : "=r"(r) : "r"(a), "r"(b)); return r; }
__device__ __forceinline__ void mbar_wait_long(uint32_t a, uint32_t parity) { int it = 0; bool more; do { more = ++it < SD_SPIN; } while (!mbar_try(a, parity) && more); }
__device__ __forceinline__ uint32_t lop3_and(uint32_t a, uint32_t b, uint32_t c) { uint32_t r; asm("lop3.b32 %0, %1, %2, %3, 0x80;" : "=r"(r) : "r"(a), "r"(b), "r"(c)); return r; }
__device__ __forceinline__ uint32_t lop3_or(uint32_t a, uint32_t b, uint32_t c) { uint32_t r; asm("lop3.b32 %0, %1, %2, %3, 0xfe;" : "=r"(r) : "r"(a), "r"(b), "r"(c)); return r; }
__device__ __forceinline__ uint16_t lds16(uint32_t a) { uint16_t v; asm volatile("ld.shared.u16 %0, [%1];" : "=h"(v) : "r"(a) : "memory"); return v; }
__device__ __forceinline__ void wg_wait1() { asm volatile("wgmma.wait_group.sync.aligned 1;" ::: "memory"); }
__device__ __forceinline__ void tma2d(uint32_t dst, const CUtensorMap* tm, uint32_t bar, int c0, int c1) {
    asm volatile("cp.async.bulk.tensor.2d.shared::cluster.global.mbarrier::complete_tx::bytes [%0], [%1, {%3, %4}], [%2];"
        :: "r"(dst), "l"(tm), "r"(bar), "r"(c0), "r"(c1) : "memory");
}
__device__ __forceinline__ uint32_t add_bf2(uint32_t a, uint32_t b) { uint32_t r; asm("add.rn.bf16x2 %0, %1, %2;" : "=r"(r) : "r"(a), "r"(b)); return r; }
__device__ __forceinline__ void wgmma_conv(float (&d)[32], uint32_t a0, uint32_t a1, uint32_t a2, uint32_t a3, uint64_t desc) {
    asm volatile("{\n.reg .pred p;\nsetp.ne.b32 p, 1, 0;\n"
        "wgmma.mma_async.sync.aligned.m64n64k16.f32.bf16.bf16 {%0,%1,%2,%3,%4,%5,%6,%7,%8,%9,%10,%11,%12,%13,%14,%15,%16,%17,%18,%19,%20,%21,%22,%23,%24,%25,%26,%27,%28,%29,%30,%31}, {%32,%33,%34,%35}, %36, p, 1, 1, 0;\n}\n"
        : "+f"(d[0]), "+f"(d[1]), "+f"(d[2]), "+f"(d[3]), "+f"(d[4]), "+f"(d[5]), "+f"(d[6]), "+f"(d[7]), "+f"(d[8]), "+f"(d[9]), "+f"(d[10]), "+f"(d[11]), "+f"(d[12]), "+f"(d[13]), "+f"(d[14]), "+f"(d[15]), "+f"(d[16]), "+f"(d[17]), "+f"(d[18]), "+f"(d[19]), "+f"(d[20]), "+f"(d[21]), "+f"(d[22]), "+f"(d[23]), "+f"(d[24]), "+f"(d[25]), "+f"(d[26]), "+f"(d[27]), "+f"(d[28]), "+f"(d[29]), "+f"(d[30]), "+f"(d[31])
        : "r"(a0), "r"(a1), "r"(a2), "r"(a3), "l"(desc));
}
__device__ __forceinline__ void wgmma_conv(float (&d)[24], uint32_t a0, uint32_t a1, uint32_t a2, uint32_t a3, uint64_t desc) {
    asm volatile("{\n.reg .pred p;\nsetp.ne.b32 p, 1, 0;\n"
        "wgmma.mma_async.sync.aligned.m64n48k16.f32.bf16.bf16 {%0,%1,%2,%3,%4,%5,%6,%7,%8,%9,%10,%11,%12,%13,%14,%15,%16,%17,%18,%19,%20,%21,%22,%23}, {%24,%25,%26,%27}, %28, p, 1, 1, 0;\n}\n"
        : "+f"(d[0]), "+f"(d[1]), "+f"(d[2]), "+f"(d[3]), "+f"(d[4]), "+f"(d[5]), "+f"(d[6]), "+f"(d[7]), "+f"(d[8]), "+f"(d[9]), "+f"(d[10]), "+f"(d[11]), "+f"(d[12]), "+f"(d[13]), "+f"(d[14]), "+f"(d[15]), "+f"(d[16]), "+f"(d[17]), "+f"(d[18]), "+f"(d[19]), "+f"(d[20]), "+f"(d[21]), "+f"(d[22]), "+f"(d[23])
        : "r"(a0), "r"(a1), "r"(a2), "r"(a3), "l"(desc));
}
__device__ __forceinline__ void wgmma_conv(float (&d)[16], uint32_t a0, uint32_t a1, uint32_t a2, uint32_t a3, uint64_t desc) {
    asm volatile("{\n.reg .pred p;\nsetp.ne.b32 p, 1, 0;\n"
        "wgmma.mma_async.sync.aligned.m64n32k16.f32.bf16.bf16 {%0,%1,%2,%3,%4,%5,%6,%7,%8,%9,%10,%11,%12,%13,%14,%15}, {%16,%17,%18,%19}, %20, p, 1, 1, 0;\n}\n"
        : "+f"(d[0]), "+f"(d[1]), "+f"(d[2]), "+f"(d[3]), "+f"(d[4]), "+f"(d[5]), "+f"(d[6]), "+f"(d[7]), "+f"(d[8]), "+f"(d[9]), "+f"(d[10]), "+f"(d[11]), "+f"(d[12]), "+f"(d[13]), "+f"(d[14]), "+f"(d[15])
        : "r"(a0), "r"(a1), "r"(a2), "r"(a3), "l"(desc));
}
__device__ __forceinline__ void wgmma_conv(float (&d)[8], uint32_t a0, uint32_t a1, uint32_t a2, uint32_t a3, uint64_t desc) {
    asm volatile("{\n.reg .pred p;\nsetp.ne.b32 p, 1, 0;\n"
        "wgmma.mma_async.sync.aligned.m64n16k16.f32.bf16.bf16 {%0,%1,%2,%3,%4,%5,%6,%7}, {%8,%9,%10,%11}, %12, p, 1, 1, 0;\n}\n"
        : "+f"(d[0]), "+f"(d[1]), "+f"(d[2]), "+f"(d[3]), "+f"(d[4]), "+f"(d[5]), "+f"(d[6]), "+f"(d[7])
        : "r"(a0), "r"(a1), "r"(a2), "r"(a3), "l"(desc));
}
template<int NR> __device__ __forceinline__ void conv_mma(float (&acc)[NR], const uint32_t (&R)[16], uint32_t dlo) {
    #pragma unroll
    for (int q = 0; q < 4; q++)
        wgmma_conv(acc, R[4 * q], R[4 * q + 1], R[4 * q + 2], R[4 * q + 3], (uint64_t)(dlo + (2 * (3 - q)) * (BC_LBO >> 4)) | ((uint64_t)8 << 32));
}
__device__ __forceinline__ void conv_ld(uint32_t (&R)[16], uint32_t a) {
    #pragma unroll
    for (int q = 0; q < 4; q++) { const uint2 u = lds64(a + 64 * (2 * q + 1)); R[4 * q] = u.x; R[4 * q + 1] = u.y; }
}
__device__ __forceinline__ void conv_fix(uint32_t (&R)[16], uint32_t& carry) {
    #pragma unroll
    for (int q = 0; q < 4; q++) {
        asm volatile("mov.b32 %0, %1;" : "=r"(R[4 * q + 2]) : "r"(q ? R[4 * q - 3] : carry));
        asm volatile("mov.b32 %0, %1;" : "=r"(R[4 * q + 3]) : "r"(R[4 * q]));
    }
    asm volatile("mov.b32 %0, %1;" : "=r"(carry) : "r"(R[13]));
}
template<int A> __device__ __forceinline__ void conv_group(float (&acc)[32 - 8 * A], uint32_t (&R)[4][16], uint32_t& carry, uint32_t pb, uint32_t dlo) {
    #pragma unroll
    for (int e = 0; e < 8; e += 2) {
        const int dl = 8 * A + e;
        conv_fix(R[dl & 3], carry); conv_fix(R[(dl + 1) & 3], carry);
        wg_fence(); conv_mma(acc, R[dl & 3], dlo + 16 - 2 * e); conv_mma(acc, R[(dl + 1) & 3], dlo + 14 - 2 * e); wg_commit();
        wg_wait1();
        if (dl + 2 < 32) { conv_ld(R[(dl + 2) & 3], pb + (dl + 2) * 512); conv_ld(R[(dl + 3) & 3], pb + (dl + 3) * 512); }
    }
}

__global__ void __launch_bounds__(SD_THREADS, 1)
side_kernel(const __grid_constant__ CUtensorMap tmw, const bf16* __restrict__ x,
            const bf16* __restrict__ log_A_real, const bf16* __restrict__ A_imag, const bf16* __restrict__ C_real, const bf16* __restrict__ C_imag,
            const bf16* __restrict__ log_dt, const bf16* __restrict__ D_skip, const bf16* __restrict__ gate_w, bf16* __restrict__ out, const int npass) {
    extern __shared__ __align__(1024) unsigned char smem[];
    const uint32_t sb = smem_u32(smem);
    const int tid = threadIdx.x, lane = tid & 31;
    const int warp = __shfl_sync(0xffffffffu, tid >> 5, 0);
    const int g = lane >> 2, t = lane & 3, mi = lane >> 3, r8 = lane & 7;
    const bool sh = blockIdx.x < 32;
    const int d0 = blockIdx.x * 16;
    const uint32_t b0_ = sb + SD_BAR, bKF = b0_ + 384, bKE = bKF + 8 * KSLOTS, bWO = b0_ + 48, bFULL = b0_ + 56, bEMPTY = b0_ + 88, bEPI = b0_ + 120, bPRT = b0_ + 152, bGO = b0_ + 184, bCH = b0_ + 256;
    const unsigned epoch = ld_relaxed32(&g_epoch);
    if (tid == 0) GT(blockIdx.x, 0);
    if (tid == 0) {
        for (int i = 0; i < 2 * KSLOTS; i++) mbar_init(bKF + 8 * i, 128);
        mbar_init(bWO, 1);
        for (int i = 0; i < 16; i++) mbar_init(bCH + 8 * i, 1);
        for (int i = 0; i < 4; i++) { mbar_init(bFULL + 8 * i, 1); mbar_init(bEMPTY + 8 * i, sh ? 8 : 4); mbar_init(bEPI + 8 * i, 4); mbar_init(bPRT + 8 * i, 8); }
        sts32(bGO, epoch);
        asm volatile("fence.mbarrier_init.release.cluster;" ::: "memory");
    }
    for (int i = tid; i < KSLOTS * 8 * 16; i += SD_THREADS) sts128(sb + SD_BC + (i >> 4) * BC_LBO + (i & 15) * 16, make_uint4(0, 0, 0, 0));
    if (tid < 128) sts64(sb + ((tid & 64) ? SD_Q1 : SD_Q0) + (tid & 63) * 8, 0u, 0u);
    fence_async_smem();
    __syncthreads();

    if (warp < 8) {
        asm volatile("setmaxnreg.inc.sync.aligned.u32 %0;" :: "n"(SD_REG));
        const int wg = warp >> 2, w = warp & 3, t128 = tid & 127;
        if (SD_WAIT) __nanosleep(SD_WAIT);
        {
            #pragma unroll 1
            for (int i = 0; i < 4; i++) {
                const int tp = tid + 256 * i;
                const bf16* xp = x + (size_t)(2 * tp) * DM + d0;
                const uint4 v0 = __ldg((const uint4*)xp), v1 = __ldg((const uint4*)(xp + 8)), v2 = __ldg((const uint4*)(xp + DM)), v3 = __ldg((const uint4*)(xp + DM + 8));
                const uint32_t a = sb + SD_BT + (tp >> 5) * 144 + (tp & 31) * 4;
                const uint32_t lo[8] = {v0.x, v0.y, v0.z, v0.w, v1.x, v1.y, v1.z, v1.w};
                const uint32_t hi[8] = {v2.x, v2.y, v2.z, v2.w, v3.x, v3.y, v3.z, v3.w};
                #pragma unroll
                for (int j = 0; j < 8; j++) { sts32(a + (2 * j) * BT_RS, __byte_perm(lo[j], hi[j], 0x5410)); sts32(a + (2 * j + 1) * BT_RS, __byte_perm(lo[j], hi[j], 0x7632)); }
                if (SD_GAP) __nanosleep(SD_GAP);
            }
        }
        bar_sync(1, 256);
        if (tid == 0) GT(blockIdx.x, 65);
        const uint32_t pa = sb + (wg ? SD_Q1 : SD_Q0);
        const uint32_t pb = pa + (72 + 16 * w - 56 + g - 2 * t) * 8;
        for (int c = wg; c < 16; c += 2) {
            const uint32_t bt = sb + SD_BT + c * BT_RS;
            bar_sync(2 + wg, 128);
            #pragma unroll
            for (int it = 0; it < 9; it++) {
                const int k = it < 8 ? t128 + 128 * it : t128 - 4;
                if (it < 8 || t128 < 4) {
                    auto word = [&](int j) { return j >= 0 ? lds32(bt + (j >> 5) * 144 + (j & 31) * 4) : 0u; };
                    const uint32_t c0 = word(k), p0 = word(k - 1), c1 = word(k + 4), p1 = word(k + 3);
                    sts128(pa + (72 + 2 * k) * 8, make_uint4(__byte_perm(c0, p0, 0x7610), __byte_perm(c1, p1, 0x7610), __byte_perm(c0, c0, 0x1032), __byte_perm(c1, c1, 0x1032)));
                }
            }
            bar_sync(2 + wg, 128);
            const int slot = c % KSLOTS;
            float acc[32];
            #pragma unroll
            for (int i = 0; i < 32; i++) acc[i] = 0.f;
            uint32_t R[4][16];
            uint32_t carry = lds32(pb);
            conv_ld(R[0], pb); conv_ld(R[1], pb + 512);
            const uint32_t dlo = (((sb + SD_BC + slot * BC_BYTES) & 0x3FFFF) >> 4) | ((BC_LBO >> 4) << 16);
            mbar_wait_long(bKF + 8 * slot, (c / KSLOTS) & 1);
            const float ds = bf(D_skip[d0 + c]);
            auto fin = [&](const float* a8, int q0) {
                #pragma unroll
                for (int q = 0; q < 2; q++)
                    #pragma unroll
                    for (int hh = 0; hh < 2; hh++) {
                        const uint32_t a = bt + (4 * (q0 + q) + t) * 144 + (16 * w + g + 8 * hh) * 2;
                        const float u = __uint_as_float((uint32_t)lds16(a) << 16);
                        const float y = rbf(a8[4 * q + 2 * hh] + a8[4 * q + 2 * hh + 1]);
                        sts16(a, (uint16_t)(pack_bf16(y + rbf(u * ds), 0.f) & 0xffff));
                    }
            };
            float a1[24], a2[16], a3[8];
            conv_group<0>(acc, R, carry, pb, dlo);
            wg_wait0();
            #pragma unroll
            for (int i = 0; i < 24; i++) asm volatile("mov.b32 %0, %1;" : "=f"(a1[i]) : "f"(acc[8 + i]));
            fin(acc, 0);
            conv_group<1>(a1, R, carry, pb, dlo);
            wg_wait0();
            #pragma unroll
            for (int i = 0; i < 16; i++) asm volatile("mov.b32 %0, %1;" : "=f"(a2[i]) : "f"(a1[8 + i]));
            fin(a1, 2);
            conv_group<2>(a2, R, carry, pb, dlo);
            wg_wait0();
            #pragma unroll
            for (int i = 0; i < 8; i++) asm volatile("mov.b32 %0, %1;" : "=f"(a3[i]) : "f"(a2[8 + i]));
            fin(a2, 4);
            conv_group<3>(a3, R, carry, pb, dlo);
            wg_wait0();
            mbar_arrive(bKE + 8 * slot);
            fin(a3, 6);
        }
        fence_async_smem();
        __syncthreads();
        const uint32_t stg = sb + SD_STG + wg * 65536;
        uint32_t wf[32][4];
        if (tid == 0) GT(blockIdx.x, 66);
        mbar_wait_long(bWO, 0);
        #pragma unroll
        for (int i = 0; i < 32; i++)
            ldsm_x4_t(wf[i], stg + (i * 16 + (mi >> 1) * 8 + r8) * 128 + (((2 * w + (mi & 1)) ^ r8) << 4));
        { uint32_t x = 0;
          #pragma unroll
          for (int i = 0; i < 32; i++) x |= wf[i][0];
          asm volatile("" :: "r"(x) : "memory"); }
        __syncwarp();
        if (lane == 0) {
            mbar_arrive(bEMPTY + 16 * wg); mbar_arrive(bEMPTY + 16 * wg + 8);
            if (sh) { mbar_arrive(bEMPTY + 16 * (wg ^ 1)); mbar_arrive(bEMPTY + 16 * (wg ^ 1) + 8); }
        }
        uint4* dst = sh ? &g_part[(blockIdx.x & ~7) + 4 * wg + w][0][0][blockIdx.x & 7][lane] : &g_part[32 + w][0][0][2 * (blockIdx.x - 32) + wg][lane];
        const uint32_t dl0 = (((sb + SD_STG) & 0x3FFFF) >> 4) | 0x10000u;
        const uint32_t bu = uni(b0_), shu = uni(sh), wgu = uni(wg), dlu = uni(dl0);
        auto seg = [&](int s, float (&acc)[16]) {
            const uint32_t bi = shu ? s & 3 : 2 * wgu + (s & 1), bp = (shu ? s >> 2 : s >> 1) & 1;
            const uint32_t xd = dlu + bi * 2048;
            #pragma unroll
            for (int i = 0; i < 32; i++) {
                if ((i & 15) == 0) { mbar_wait_long(bu + 256 + 32 * bi + (i >> 1), bp); wg_fence(); }
                if (i == 0) wgmma_n32<0>(acc, wf[i], desc_from(xd));
                else wgmma_n32<1>(acc, wf[i], desc_from(xd + (i >> 2) * 256 + (i & 3) * 2));
            }
            wg_commit();
            if (s >= PART_SLOTS / 2) mbar_wait_long(bu + 120 + 8 * (s & 3), ((s - 4) >> 2) & 1);
            const uint32_t ph = ((s / PART_SLOTS) & 1) ^ 1;
            uint4* p = dst + (s % PART_SLOTS) * (4 * 8 * 32);
            wg_wait0();
            #pragma unroll
            for (int j = 0; j < 4; j++)
                st_relaxed128(p + 256 * j, make_uint4((__float_as_uint(acc[4 * j]) & ~1u) | ph, __float_as_uint(acc[4 * j + 1]), __float_as_uint(acc[4 * j + 2]), __float_as_uint(acc[4 * j + 3])));
            if (tid == 0 && s == LSEG - 1) GT(blockIdx.x, 71);
            asm volatile("{\n.reg .pred p;\nelect.sync _|p, 0xffffffff;\n@p mbarrier.arrive.shared.b64 _, [%0];\n@p mbarrier.arrive.shared.b64 _, [%1];\n}\n" :: "r"(bu + 88 + 8 * bi), "r"(bu + 152 + 8 * (s & 3)) : "memory");
        };
        #pragma unroll 1
        for (int pass = 0; pass < npass; pass++) {
            if (pass) {
                float acc0[16], acc1[16];
                #pragma unroll 1
                for (int s = 0; ; s += 2) { seg(s, acc0); if (s + 1 >= LSEG) break; seg(s + 1, acc1); }
            }
            uint32_t tq; asm volatile("mov.u32 %0, %%tid.x;" : "=r"(tq));
            const uint4* p = &g_last[blockIdx.x][0][0][0] + (tq >> 5) * 256 + (tq & 31);
            const uint32_t tag = lds32(bGO) & 1u;
            uint4 v[8]; int it = 0;
            #pragma unroll
            for (int i = 0; i < 8; i++) v[i] = make_uint4(tag ^ pass, 0, 0, 0);
            while (true) {
                #pragma unroll
                for (int i = 0; i < 8; i++) ld_relaxed128_p(v[i], p + 32 * i, (v[i].x ^ tag) & 1u);
                uint32_t any = 0;
                #pragma unroll
                for (int i = 0; i < 8; i++) any |= v[i].x ^ tag;
                if (!__any_sync(0xffffffffu, any & 1u) || ++it >= SD_SPIN) break;
            }
            float a[8];
            #pragma unroll
            for (int i = 0; i < 8; i++) a[i] = 0.f;
            #pragma unroll
            for (int i = 0; i < 8; i++) { a[0] += bf_lo(v[i].x); a[1] += bf_hi(v[i].x); a[2] += bf_lo(v[i].y); a[3] += bf_hi(v[i].y); a[4] += bf_lo(v[i].z); a[5] += bf_hi(v[i].z); a[6] += bf_lo(v[i].w); a[7] += bf_hi(v[i].w); }
            const uint32_t xa = sb + SD_XCH + (tq >> 7) * 4096 + (tq & 127) * 16;
            sts128(xa, make_uint4(__float_as_uint(a[0]), __float_as_uint(a[1]), __float_as_uint(a[2]), __float_as_uint(a[3])));
            sts128(xa + 2048, make_uint4(__float_as_uint(a[4]), __float_as_uint(a[5]), __float_as_uint(a[6]), __float_as_uint(a[7])));
            bar_arrive_p(6, 320, !pass);
        }
        mbar_wait_long(bEPI + 8 * (LSEG & 3), ((LSEG - 4) >> 2) & 1);
        #pragma unroll
        for (int j = 0; j < 4; j++) st_relaxed128(dst + (LSEG % PART_SLOTS) * (4 * 8 * 32) + 256 * j, make_uint4(((LSEG / PART_SLOTS) & 1) ^ 1, 0, 0, 0));
    } else {
        asm volatile("setmaxnreg.dec.sync.aligned.u32 %0;" :: "n"(504 - 2 * SD_REG));
        const int w = warp - 8, n = tid - 256;
        bf16 p_la = log_A_real[d0 * NS + n], p_ai = A_imag[d0 * NS + n], p_cr = C_real[d0 * NS + n], p_ci = C_imag[d0 * NS + n], p_dt = log_dt[d0];
        const uint32_t ef = sb + SD_EF + w * 8192;
        const uint32_t efl = ef + lane * 4;
        uint32_t goff[8];
        #pragma unroll
        for (int i = 0; i < 16; i++) {
            const int l = 64 * lane + 8 * (w + 4 * (i >> 3)) + (i & 7);
            const int p = (int)rbf((float)l);
            const int a = p >> 7, b = (p >> 3) & 15, c = p & 7;
            const int row = p < 256 ? 8 * a + c : (p < 512 ? 16 + 4 * (a - 2) + (c >> 1) : (p < 1024 ? 24 + 2 * (a - 4) + (c >> 2) : 24 + a));
            const uint32_t off = row * 72 + b * 4;
            if (i & 1) goff[i >> 1] |= off << 16; else goff[i >> 1] = off;
        }
        for (int c = 0; c < 16; c++) {
            const float dt = rbf(expf(bf(p_dt)));
            const float xr = -rbf(expf(bf(p_la))) * dt, xi = bf(p_ai) * dt;
            cplx C; C.r = 2.f * bf(p_cr) * dt; C.i = 2.f * bf(p_ci) * dt;
            if (c + 1 < 16) {
                const int o = (d0 + c + 1) * NS + n;
                p_la = log_A_real[o]; p_ai = A_imag[o]; p_cr = C_real[o]; p_ci = C_imag[o]; p_dt = log_dt[d0 + c + 1];
            }
            const uint32_t mexp = min(max(__reduce_max_sync(0xffffffffu, __float_as_uint(fmaxf(fabsf(C.r), fabsf(C.i)))) & 0x7f800000u, 0x01000000u), 0x7e000000u);
            const float unsc = __uint_as_float(mexp), sc = __uint_as_float(0x7f000000u - mexp);
            C.r *= sc; C.i *= sc;
            #define EADDR(r) ((efl ^ (((r) & 7) << 4)) + (r) * 128)
            {
                cplx f[16];
                f[1] = cexp_(8.f * xr, -8.f * xi);
                f[2] = cmul(f[1], f[1]); f[3] = cmul(f[2], f[1]); f[4] = cmul(f[2], f[2]); f[5] = cmul(f[4], f[1]); f[6] = cmul(f[4], f[2]); f[7] = cmul(f[4], f[3]);
                f[8] = cmul(f[4], f[4]);
                #pragma unroll
                for (int b = 9; b < 16; b++) f[b] = cmul(f[8], f[b - 8]);
                sts32(EADDR(0) + 6144, 0x00003c00u);
                #pragma unroll
                for (int b = 1; b < 16; b++) sts32(EADDR(b) + 6144, pack_f16(f[b].r, f[b].i));
            }
            {
                cplx G[17], wc[8];
                G[1] = cexp_(128.f * xr, 128.f * xi);
                wc[1] = cexp_(xr, xi);
                G[2] = cmul(G[1], G[1]); G[4] = cmul(G[2], G[2]); G[8] = cmul(G[4], G[4]);
                wc[2] = cmul(wc[1], wc[1]); wc[3] = cmul(wc[2], wc[1]); wc[4] = cmul(wc[2], wc[2]); wc[5] = cmul(wc[4], wc[1]); wc[6] = cmul(wc[4], wc[2]); wc[7] = cmul(wc[4], wc[3]);
                cplx CG[17];
                CG[0] = C; CG[1] = cmul(C, G[1]); CG[2] = cmul(C, G[2]); CG[3] = cmul(CG[1], G[2]);
                #pragma unroll
                for (int a = 0; a < 4; a++) CG[4 + a] = cmul(CG[a], G[4]);
                #pragma unroll
                for (int a = 0; a < 9; a++) CG[8 + a] = cmul(CG[a], G[8]);
                #pragma unroll
                for (int r = 0; r < 41; r++) {
                    const int a = r < 16 ? (r >> 3) : (r < 24 ? 2 + ((r >> 2) & 1) : (r < 32 ? 4 + ((r >> 1) & 3) : r - 24));
                    const int cc = r < 16 ? (r & 7) : (r < 24 ? 2 * (r & 3) : (r < 32 ? 4 * (r & 1) : 0));
                    const cplx e = cc ? cmul(CG[a], wc[cc]) : CG[a];
                    sts32(EADDR(r), pack_f16(e.r, e.i));
                }
            }
            __syncwarp();
            float acc[3][2][4];
            #pragma unroll
            for (int i = 0; i < 3; i++)
                #pragma unroll
                for (int j = 0; j < 2; j++) { acc[i][j][0] = acc[i][j][1] = acc[i][j][2] = acc[i][j][3] = 0.f; }
            #pragma unroll
            for (int ks = 0; ks < 4; ks++) {
                uint32_t bq[4];
                ldsm_x4(bq, ef + 6144 + ((mi >> 1) * 8 + r8) * 128 + (((2 * ks + (mi & 1)) ^ r8) << 4));
                #pragma unroll
                for (int mt = 0; mt < 3; mt++) {
                    uint32_t aq[4];
                    ldsm_x4(aq, ef + (16 * mt + (mi & 1) * 8 + r8) * 128 + (((2 * ks + (mi >> 1)) ^ r8) << 4));
                    mma_f16(acc[mt][0], aq, bq[0], bq[1]);
                    mma_f16(acc[mt][1], aq, bq[2], bq[3]);
                }
            }
            const uint32_t kp = sb + SD_KP;
            #pragma unroll
            for (int mt = 0; mt < 3; mt++)
                #pragma unroll
                for (int nt = 0; nt < 2; nt++) {
                    const uint32_t a = kp + w * 3072 + (16 * mt + g) * 64 + nt * 32 + t * 8;
                    sts64(a, __float_as_uint(acc[mt][nt][0] * unsc), __float_as_uint(acc[mt][nt][1] * unsc));
                    sts64(a + 512, __float_as_uint(acc[mt][nt][2] * unsc), __float_as_uint(acc[mt][nt][3] * unsc));
                }
            bar_sync(4, 128);
            #pragma unroll
            for (int i = 0; i < 3; i++) {
                const uint32_t a = kp + (n + 128 * i) * 8;
                const uint2 v0 = lds64(a), v1 = lds64(a + 3072), v2 = lds64(a + 6144), v3 = lds64(a + 9216);
                sts64(a + 12288 + ((n >> 3) + 16 * i) * 8, __float_as_uint((__uint_as_float(v0.x) + __uint_as_float(v1.x)) + (__uint_as_float(v2.x) + __uint_as_float(v3.x))),
                                 __float_as_uint((__uint_as_float(v0.y) + __uint_as_float(v1.y)) + (__uint_as_float(v2.y) + __uint_as_float(v3.y))));
            }
            bar_sync(4, 128);
            const int slot = c % KSLOTS;
            float kv[16];
            #pragma unroll
            for (int e = 0; e < 8; e++) { kv[2 * e] = __uint_as_float(lds32(kp + 12288 + (goff[e] & 0xffff))); kv[2 * e + 1] = __uint_as_float(lds32(kp + 12288 + (goff[e] >> 16))); }
            if (c >= KSLOTS) mbar_wait_long(bKE + 8 * slot, (c / KSLOTS - 1) & 1);
            #pragma unroll
            for (int it = 0; it < 2; it++) {
                uint32_t hi[4], lo[4];
                #pragma unroll
                for (int e = 0; e < 4; e++) {
                    const float k0 = kv[8 * it + 2 * e], k1 = kv[8 * it + 2 * e + 1];
                    hi[e] = pack_bf16(k0, k1);
                    lo[e] = pack_bf16(k0 - bf_lo(hi[e]), k1 - bf_hi(hi[e]));
                }
                const uint32_t a = sb + SD_BC + slot * BC_BYTES + (w + 4 * it) * BC_LBO + (16 + 2 * lane) * 16;
                sts128(a, make_uint4(hi[0], hi[1], hi[2], hi[3]));
                sts128(a + 16, make_uint4(lo[0], lo[1], lo[2], lo[3]));
            }
            fence_async_smem();
            mbar_arrive(bKF + 8 * slot);
        }
        {
            uint32_t gw[9];
            #pragma unroll
            for (int j = 0; j < 9; j++) gw[j] = __ldg((const uint32_t*)gate_w + lane + 32 * j);
            float z = 0.f;
            #pragma unroll 1
            for (int i0 = 0; i0 < 15; i0 += 5) {
                uint32_t xv[5][9];
                #pragma unroll
                for (int i = 0; i < 5; i++) {
                    const int tk = min(blockIdx.x * 57 + w + 4 * (i0 + i), S_LEN - 1);
                    #pragma unroll
                    for (int j = 0; j < 9; j++) xv[i][j] = __ldg((const uint32_t*)(x + (size_t)tk * DM) + lane + 32 * j);
                }
                #pragma unroll
                for (int i = 0; i < 5; i++) {
                    float acc = 0.f;
                    #pragma unroll
                    for (int j = 0; j < 9; j++) { const uint32_t m = mul_bf2(xv[i][j], gw[j]); acc += bf_lo(m) + bf_hi(m); }
                    #pragma unroll
                    for (int o = 16; o; o >>= 1) acc += __shfl_xor_sync(0xffffffffu, acc, o);
                    if (lane == i0 + i) z = rbf(acc);
                }
            }
            const int li = w + 4 * lane, tk = blockIdx.x * 57 + li;
            if (li < 57 && tk < S_LEN) st_relaxed32(&g_gate[tk], pack_bf16(1.f / (1.f + expf(-z)), 0.f) | (epoch << 16));
        }
        if (tid == 256) GT(blockIdx.x, 67);
        fence_async_smem();
        __syncthreads();
            const uint32_t ost = sb + SD_OST + w * 512;
            const uint4* const pl = &g_part[blockIdx.x][0][0][0][lane];
            bf16* const ol = out + (size_t)(lane >> 1) * DM + d0 + 8 * (lane & 1);
            const uint32_t ga = sb + SD_Q0 + t * 8, bb = sb + SD_BT + g * BT_RS + t * 4, oa = ost + r8 * 32 + (mi & 1) * 16 + (mi >> 1) * 256;
            uint32_t gg[2], mb[2][2];
            auto gates = [&](int u) {
                #pragma unroll
                for (int k = 0; k < 2; k++) {
                    const uint2 gt = lds64(ga + (u + k) * 32);
                    const uint32_t ba = bb + (u >> 3) * 144 + ((u & 7) + k) * 16;
                    gg[k] = __byte_perm(gt.x, gt.y, 0x5410);
                    const uint32_t mm = pack_bf16(1.f - bf_lo(gg[k]), 1.f - bf_hi(gg[k]));
                    mb[k][0] = mul_bf2(mm, lds32(ba)); mb[k][1] = mul_bf2(mm, lds32(ba + 8 * BT_RS));
                }
            };
            auto finish = [&](int u, const uint32_t (&sm)[2][2], uint32_t store) {
                stsm_x4_t(oa, add_bf2(mul_bf2(gg[0], sm[0][0]), mb[0][0]), add_bf2(mul_bf2(gg[0], sm[0][1]), mb[0][1]), add_bf2(mul_bf2(gg[1], sm[1][0]), mb[1][0]), add_bf2(mul_bf2(gg[1], sm[1][1]), mb[1][1]));
                __syncwarp();
                const uint4 o = lds128(ost + lane * 16);
                asm volatile("{\n.reg .pred p;\nsetp.ne.u32 p, %5, 0;\n@p st.global.v4.u32 [%0], {%1,%2,%3,%4};\n}\n" :: "l"(ol + (size_t)u * (8 * DM)), "r"(o.x), "r"(o.y), "r"(o.z), "r"(o.w), "r"(store) : "memory");
                __syncwarp();
            };
            auto units = [&](int u, int end) {
              uint4 v[16];
              auto fetch = [&](int u, bool block) {
                const int s = u >> 2;
                uint32_t early;
                asm volatile("{\n.reg .pred p;\nmbarrier.test_wait.parity.shared::cta.b64 p, [%1], %2;\nselp.u32 %0, 1, 0, p;\n}\n" : "=r"(early) : "r"(bPRT + 8 * (s & 3)), "r"((s >> 2) & 1) : "memory");
                if (!early) {
                    if (!block) return false;
                    mbar_wait_long(bPRT + 8 * (s & 3), (s >> 2) & 1);
                    delay_clk(s < LSEG - 2 ? SD_P1 : SD_P2);
                } else if (SD_P3 && s < SD_RUSH) delay_clk(SD_P3);
                const uint4* p = pl + (u & (4 * PART_SLOTS - 1)) * 256;
                #pragma unroll
                for (int i = 0; i < 16; i++) v[i] = ld_relaxed128(p + 32 * i);
                return true;
              };
              fetch(u, true);
              #pragma unroll 1
              while (true) {
                const int s = u >> 2;
                const uint32_t phm = ((s / PART_SLOTS) & 1) - 1;
                gates(u);
                int it = 0;
                while (true) {
                    uint32_t all = ~0u, any = 0;
                    #pragma unroll
                    for (int i = 0; i < 16; i += 2) { all = lop3_and(all, v[i].x, v[i + 1].x); any = lop3_or(any, v[i].x, v[i + 1].x); }
                    if (!__any_sync(0xffffffffu, ((all ^ phm) | (any ^ phm)) & 1u) || ++it >= SD_SPIN) break;
                    if (it > 1 && s < LSEG - 2) __nanosleep(200);
                    const uint4* p = pl + (u & (4 * PART_SLOTS - 1)) * 256;
                    #pragma unroll
                    for (int i = 0; i < 16; i++) ld_relaxed128_p(v[i], p + 32 * i, (v[i].x ^ phm) & 1u);
                }
                if (lane < 2) mbar_arrive(bEPI + 8 * (s & 3));
                uint32_t sm[2][2];
                #pragma unroll
                for (int k = 0; k < 2; k++) {
                    float a0 = __uint_as_float(v[8 * k].x), a1 = __uint_as_float(v[8 * k].y), a2 = __uint_as_float(v[8 * k].z), a3 = __uint_as_float(v[8 * k].w);
                    #pragma unroll
                    for (int i = 1; i < 8; i++) { a0 += __uint_as_float(v[8 * k + i].x); a1 += __uint_as_float(v[8 * k + i].y); a2 += __uint_as_float(v[8 * k + i].z); a3 += __uint_as_float(v[8 * k + i].w); }
                    sm[k][0] = pack_bf16(a0, a1); sm[k][1] = pack_bf16(a2, a3);
                }
                const int nu = u + 6;
                const bool pre = nu < end && fetch(nu, false);
                finish(u, sm, 1u);
                if (lane == 0 && (u & 2)) GT(blockIdx.x, 1 + s);
                if (nu >= end) break;
                if (!pre) fetch(nu, true);
                u = nu;
              }
            };
        #pragma unroll 1
        for (int pass = w & 1 ? 0 : 1; pass < npass; pass++) {
        if (pass) {
        if (w == 0) {
            if (lane == 0) {
                mbar_expect_tx(bWO, 131072);
                #pragma unroll 1
                for (int q = 0; q < 16; q++) {
                    tma2d(sb + SD_STG + q * 8192, &tmw, bWO, sh ? 128 * (blockIdx.x >> 3) + 64 * (q >> 3) : 512, sh ? 512 * (blockIdx.x & 7) + 64 * (q & 7) : 1024 * (blockIdx.x - 32) + 64 * q);
                    if (SD_WOP) delay_clk(SD_WOP);
                }
            }
            bar_sync(5, 128);
            const int ke0 = sh ? blockIdx.x & 7 : 2 * (blockIdx.x - 32);
            const unsigned int* f = &g_prog[12 * ke0 + (lane < (sh ? 12 : 24) ? lane : 0)];
            int avail = 0;
            #pragma unroll 1
            for (int s = 0; s < LSEG; s++) {
                if (s >= avail) {
                    int it = 0;
                    while (true) {
                        uint32_t v;
                        asm volatile("ld.acquire.gpu.global.u32 %0, [%1];" : "=r"(v) : "l"(f) : "memory");
                        avail = __reduce_min_sync(0xffffffffu, (v >> 8) == (epoch & 0xffffffu) ? v & 255u : 0u);
                        if (avail > s || ++it >= SD_SPIN) break;
                        if (s < LSEG - 1) __nanosleep(64);
                    }
                    asm volatile("fence.proxy.async.global;" ::: "memory");
                    if (lane == 0 && s == LSEG - 1) GT(blockIdx.x, 70);
                }
                if (lane == 0 && s == 2 && blockIdx.x == 0) st_relaxed32(&g_epoch, epoch + 1);
                const int b0 = sh ? s & 3 : s & 1, bp = (sh ? s >> 2 : s >> 1) & 1;
                const bf16* src = g_otok + (size_t)s * (SEG * NH * DH) + ke0 * 16384;
                mbar_wait_long(bEMPTY + 8 * b0, bp);
                if (!sh) mbar_wait_long(bEMPTY + 16 + 8 * b0, bp);
                #pragma unroll
                for (int hc = 0; hc < 2; hc++)
                    asm volatile("{\n.reg .pred p, q;\nelect.sync _|p, 0xffffffff;\nsetp.eq.and.u32 q, %6, 0, p;\n"
                                 "@p mbarrier.arrive.expect_tx.shared.b64 _, [%2], 16384;\n"
                                 "@p cp.async.bulk.shared::cluster.global.mbarrier::complete_tx::bytes [%0], [%1], 16384, [%2];\n"
                                 "@q mbarrier.arrive.expect_tx.shared.b64 _, [%5], 16384;\n"
                                 "@q cp.async.bulk.shared::cluster.global.mbarrier::complete_tx::bytes [%3], [%4], 16384, [%5];\n}\n"
                        :: "r"(sb + SD_STG + b0 * 32768 + hc * 16384), "l"(src + hc * 8192), "r"(bCH + 32 * b0 + 8 * hc),
                           "r"(sb + SD_STG + (b0 + 2) * 32768 + hc * 16384), "l"(src + 16384 + hc * 8192), "r"(bCH + 32 * (b0 + 2) + 8 * hc), "r"((uint32_t)sh) : "memory");
            }
        } else {
            if (w == 3) {
                for (int i = 0; i < 16; i += 8) {
                    uint4 v[8]; uint32_t miss = 0xffu; int it = 0;
                    const uint32_t tag = epoch & 0xffffu;
                    #pragma unroll
                    for (int j = 0; j < 8; j++) v[j] = make_uint4(0, 0, 0, 0);
                    do {
                        #pragma unroll
                        for (int j = 0; j < 8; j++) ld_relaxed128_p(v[j], (const uint4*)g_gate + (i + j) * 32 + lane, miss & (1u << j));
                        miss = 0;
                        #pragma unroll
                        for (int j = 0; j < 8; j++) miss |= (uint32_t)((v[j].x >> 16) != tag || (v[j].y >> 16) != tag || (v[j].z >> 16) != tag || (v[j].w >> 16) != tag) << j;
                    } while (__any_sync(0xffffffffu, miss) && ++it < SD_SPIN);
                    #pragma unroll
                    for (int j = 0; j < 8; j++) sts128(sb + SD_Q0 + ((i + j) * 32 + lane) * 16, v[j]);
                }
            }
            bar_sync(5, 128);
        }
        if (w) units(2 * (w - 1), 4 * LSEG);
        }
        if (w < 2) {
            gates(4 * LSEG + 2 * w);
            bar_sync_p(6, 320, !pass);
            uint32_t sm[2][2];
            #pragma unroll
            for (int k = 0; k < 2; k++) {
                float a0 = 0.f, a1 = 0.f, a2 = 0.f, a3 = 0.f;
                #pragma unroll
                for (int i = 0; i < 4; i++) { const uint4 v = lds128(sb + SD_XCH + w * 4096 + k * 2048 + i * 512 + lane * 16); a0 += __uint_as_float(v.x); a1 += __uint_as_float(v.y); a2 += __uint_as_float(v.z); a3 += __uint_as_float(v.w); }
                sm[k][0] = pack_bf16(a0, a1); sm[k][1] = pack_bf16(a2, a3);
            }
            finish(4 * LSEG + 2 * w, sm, pass);
            if (lane == 0 && w == 1) GT(blockIdx.x, 1 + LSEG);
        }
        }
    }
    if (tid == 256) GT(blockIdx.x, 72);
}

extern "C" void kernel_launch(void* const* d_in, const int* in_sizes, int n_in, void* d_out, int out_size) {
    const bf16* x = (const bf16*)d_in[0];
    const bf16* mem0 = (const bf16*)d_in[1];
    const bf16* Wq = (const bf16*)d_in[2];
    const bf16* Wk = (const bf16*)d_in[3];
    const bf16* Wv = (const bf16*)d_in[4];
    const bf16* Wo = (const bf16*)d_in[5];
    const bf16* log_A_real = (const bf16*)d_in[8];
    const bf16* A_imag = (const bf16*)d_in[9];
    const bf16* C_real = (const bf16*)d_in[10];
    const bf16* C_imag = (const bf16*)d_in[11];
    const bf16* log_dt = (const bf16*)d_in[12];
    const bf16* D_skip = (const bf16*)d_in[13];
    const bf16* gate_w = (const bf16*)d_in[14];
    bf16* out = (bf16*)d_out;
    typedef CUresult (*EncFn)(CUtensorMap*, CUtensorMapDataType, cuuint32_t, void*, const cuuint64_t*, const cuuint64_t*, const cuuint32_t*, const cuuint32_t*,
                              CUtensorMapInterleave, CUtensorMapSwizzle, CUtensorMapL2promotion, CUtensorMapFloatOOBfill);
    static EncFn enc = nullptr;
    if (!enc) { void* fn = nullptr; cudaDriverEntryPointQueryResult qr; cudaGetDriverEntryPoint("cuTensorMapEncodeTiled", &fn, cudaEnableDefault, &qr); enc = (EncFn)fn; }
    auto mk = [&](CUtensorMap* tm, const void* ptr, uint64_t cols, uint64_t rows, uint32_t bc, uint32_t br) {
        cuuint64_t gdim[2] = {cols, rows}; cuuint64_t gstr[1] = {cols * 2}; cuuint32_t box[2] = {bc, br}; cuuint32_t estr[2] = {1, 1};
        enc(tm, CU_TENSOR_MAP_DATA_TYPE_BFLOAT16, 2, (void*)ptr, gdim, gstr, box, estr, CU_TENSOR_MAP_INTERLEAVE_NONE, bc == 64 ? CU_TENSOR_MAP_SWIZZLE_128B : CU_TENSOR_MAP_SWIZZLE_64B,
            CU_TENSOR_MAP_L2_PROMOTION_L2_256B, CU_TENSOR_MAP_FLOAT_OOB_FILL_NONE);
    };
    static bool attr_done = false;
    if (!attr_done) {
        cudaFuncSetAttribute(chain_kernel, cudaFuncAttributeMaxDynamicSharedMemorySize, SM_TOTAL);
        cudaFuncSetAttribute(side_kernel, cudaFuncAttributeMaxDynamicSharedMemorySize, SD_TOTAL);
        attr_done = true;
    }
    CUtensorMap tmx, tma, tmb, tmw, tmq, tmk, tmv, tmo;
    {
        cuuint64_t gdim[3] = {64, S_LEN, DM / 64}; cuuint64_t gstr[2] = {DM * 2, 128}; cuuint32_t box[3] = {64, SEG, 3}; cuuint32_t estr[3] = {1, 1, 1};
        enc(&tmx, CU_TENSOR_MAP_DATA_TYPE_BFLOAT16, 3, (void*)x, gdim, gstr, box, estr, CU_TENSOR_MAP_INTERLEAVE_NONE, CU_TENSOR_MAP_SWIZZLE_128B,
            CU_TENSOR_MAP_L2_PROMOTION_L2_256B, CU_TENSOR_MAP_FLOAT_OOB_FILL_NONE);
    }
    static void* acc = nullptr;
    if (!acc) cudaGetSymbolAddress(&acc, g_acc);
    for (int w = 0; w < 2; w++) {
        cuuint64_t gdim[3] = {64, 4, 64}; cuuint64_t gstr[2] = {256, 1024}; cuuint32_t box[3] = {w ? 8u : 32u, 2, w ? 6u : 12u}; cuuint32_t estr[3] = {1, 1, 1};
        enc(w ? &tmb : &tma, CU_TENSOR_MAP_DATA_TYPE_UINT32, 3, acc, gdim, gstr, box, estr, CU_TENSOR_MAP_INTERLEAVE_NONE, CU_TENSOR_MAP_SWIZZLE_NONE,
            CU_TENSOR_MAP_L2_PROMOTION_NONE, CU_TENSOR_MAP_FLOAT_OOB_FILL_NONE);
    }
    mk(&tmw, Wo, DM, NH * DH, 64, 64);
    mk(&tmo, Wo, DM, NH * DH, 32, 128);
    mk(&tmq, Wq, NH * DH, DM, 32, 144); mk(&tmk, Wk, NH * DH, DM, 32, 144); mk(&tmv, Wv, NH * DH, DM, 32, 144);
    chain_kernel<<<96, CH_THREADS, SM_TOTAL>>>(tmx, tmq, tmk, tmv, tmo, tma, tmb, mem0, 0u);
    cudaLaunchConfig_t cfg = {};
    cfg.gridDim = dim3(SD_CTAS); cfg.blockDim = dim3(SD_THREADS); cfg.dynamicSmemBytes = SD_TOTAL; cfg.stream = cudaStreamPerThread;
    cudaLaunchAttribute at[1];
    at[0].id = cudaLaunchAttributeProgrammaticStreamSerialization; at[0].val.programmaticStreamSerializationAllowed = 1;
    cfg.attrs = at; cfg.numAttrs = 1;
    cudaLaunchKernelEx(&cfg, side_kernel, tmw, x, log_A_real, A_imag, C_real, C_imag, log_dt, D_skip, gate_w, out, 2);
}
```
